```python
import torch

def _softmax(x, axis=-1):
    return torch.softmax(x, dim=axis)
def _gelu(x):
    return torch.nn.functional.gelu(x, approximate="tanh")
def _silu(x):
    return torch.nn.functional.silu(x)
def _sigmoid(x):
    return torch.sigmoid(x)
def _layernorm(x, axis=-1, eps=1e-5):
    m = x.mean(dim=axis, keepdim=True)
    v = x.var(dim=axis, keepdim=True, unbiased=False)
    return (x - m) / torch.sqrt(v + eps)
def _scatter_add(tgt, idx, src, axis=0):
    return tgt.clone().index_add_(axis, idx, src)
def _segment_sum(src, seg, n):
    out = torch.zeros((n,) + src.shape[1:], dtype=src.dtype)
    return out.index_add_(0, seg, src)
def _pad(x, pw):
    flat = tuple(v for pair in reversed(pw) for v in pair)
    return torch.nn.functional.pad(x, flat)

kernel_name = 'parallel_sum__ssm_conv_s4d__moe_arch_mod__prompt'

def setup_inputs():

    _w = (lambda a: (lambda t: t.to(torch.bfloat16) if t.is_floating_point() else t)(torch.as_tensor(a)))
    def _A_setup():
        Bsz, L, D, N = 1, 2048, 1024, 128
        return {
            "u": _w((lambda *s: torch.randn(*s, dtype=torch.bfloat16) * 0.05)(Bsz, L, D)),
            "log_A_real": _w((lambda *s: torch.randn(*s, dtype=torch.bfloat16) * 3.2)(D, N) * 0.5),
            "A_imag": _w((lambda *s: torch.randn(*s, dtype=torch.bfloat16) * 0.2)(D, N) * 3.14),
            "C_real": _w((lambda *s: torch.randn(*s, dtype=torch.bfloat16) * 3.2)(D, N) / N ** 0.5),
            "C_imag": _w((lambda *s: torch.randn(*s, dtype=torch.bfloat16) * 3.2)(D, N) / N ** 0.5),
            "log_dt": _w((lambda *s: torch.randn(*s, dtype=torch.bfloat16) * 0.2)(D) * 0.5 - 4.0),
            "D_skip": _w((lambda *s: torch.randn(*s, dtype=torch.bfloat16) * 0.4)(D)),
        }
    _A_in = _A_setup()

    def _B_setup():
        B, S, D, F, C = 1, 2048, 1024, 3584, 8
        return {
            "x": _w((lambda *s: torch.randn(*s, dtype=torch.bfloat16) * 0.05)(B, S, D)),
            "w_r": _w((lambda *s: torch.randn(*s, dtype=torch.bfloat16) * 0.05)(D)),
            "w_gate": _w((lambda *s: torch.randn(*s, dtype=torch.bfloat16) * 0.05)(D, F)),
            "w_up": _w((lambda *s: torch.randn(*s, dtype=torch.bfloat16) * 0.05)(D, F)),
            "w_down": _w((lambda *s: torch.randn(*s, dtype=torch.bfloat16) * 0.05)(F, D)),
        }
    _B_in = _B_setup()

    return {
        "A_u": _A_in["u"],
        "A_log_A_real": _A_in["log_A_real"],
        "A_A_imag": _A_in["A_imag"],
        "A_C_real": _A_in["C_real"],
        "A_C_imag": _A_in["C_imag"],
        "A_log_dt": _A_in["log_dt"],
        "A_D_skip": _A_in["D_skip"],
        "B_x": _B_in["x"],
        "B_w_r": _B_in["w_r"],
        "B_w_gate": _B_in["w_gate"],
        "B_w_up": _B_in["w_up"],
        "B_w_down": _B_in["w_down"],
    }

def reference(A_u, A_log_A_real, A_A_imag, A_C_real, A_C_imag, A_log_dt, A_D_skip, B_x, B_w_r, B_w_gate, B_w_up, B_w_down):
    def _A_ref(u, log_A_real, A_imag, C_real, C_imag, log_dt, D_skip):
        L = u.shape[1]
        dt = torch.exp(log_dt)
        A = -torch.exp(log_A_real) + 1j * A_imag
        C = (C_real + 1j * C_imag) * dt[:, None]
        pos = (lambda x, dt: x.to(dt))(torch.arange(L), log_dt.dtype)
        P = torch.exp((A * dt[:, None])[:, :, None] * pos[None, None, :])
        K = 2.0 * torch.einsum("dn,dnl->dl", C, P).real
        L2 = 2 * L
        u_t = (lambda x, *d: x.permute(*d))(u, 0, 2, 1)
        Kf = (lambda x, *a, **k: torch.fft.rfft(x.float(), *a, **k))(K, L2)
        Uf = (lambda x, *a, **k: torch.fft.rfft(x.float(), *a, **k))(u_t, L2)
        y = (lambda x, *a, **k: torch.fft.irfft(x, *a, **k).to(torch.bfloat16))(Uf * Kf[None, :, :], L2)[:, :, :L]
        y = (lambda x, *d: x.permute(*d))(y, 0, 2, 1)
        return y + u * D_skip[None, None, :]

    def _B_ref(x, w_r, w_gate, w_up, w_down):
        B, S, D = x.shape
        C = 8
        r = x @ w_r
        idx = torch.argsort(-r, axis=-1)[:, :C]
        idx_e = (lambda x, n, axis: torch.repeat_interleave(x, n, dim=axis))(idx.reshape(B, C, 1), D, axis=2)
        x_sel = (lambda x, i, axis: torch.take_along_dim(x, i, dim=axis))(x, idx_e, axis=1)
        g = _silu(x_sel @ w_gate)
        u = x_sel @ w_up
        y = (g * u) @ w_down
        r_sel = _sigmoid((lambda x, i, axis: torch.take_along_dim(x, i, dim=axis))(r, idx, axis=1))
        y = y * r_sel.reshape(B, C, 1)
        b_off = (torch.arange(B) * S).reshape(B, 1)
        flat_idx = (idx + b_off).reshape(B * C)
        zero = (x * 0.0).reshape(B * S, D)
        upd = _scatter_add(zero, flat_idx, y.reshape(B * C, D), axis=0)
        return x + upd.reshape(B, S, D)

    x = A_u
    xn = _layernorm(x, axis=-1)
    return x + _A_ref(xn, A_log_A_real, A_A_imag, A_C_real, A_C_imag, A_log_dt, A_D_skip) + _B_ref(xn, B_w_r, B_w_gate, B_w_up, B_w_down)
```

```cpp
#include <cuda_runtime.h>
#include <cuda_bf16.h>
#include <cuda_fp16.h>
#include <cuda.h>
#include <stdint.h>

namespace {

constexpr int SEQ = 2048, DM = 1024, NMODE = 128, FF = 3584;
constexpr int NCTA = 128, NTHR = 416;
constexpr int GU_CTAS = 112;

constexpr int OFF_XT = 0;
constexpr int OFF_RING = 65536;
constexpr int OFF_PRIV = OFF_RING + 65536;
constexpr int OFF_VT = OFF_PRIV + 65536;
constexpr int VT_PAD = 240, VT_PITCH = VT_PAD + 4096, ROW_PITCH = 2064;
constexpr int OFF_BAR = OFF_VT + 8 * VT_PITCH;
constexpr int OFF_MISC = OFF_BAR + 224;
constexpr int OFF_RED = OFF_MISC + 48;
constexpr int OFF_STAMP = OFF_RED + 512;
constexpr int SMEM_BYTES = OFF_STAMP + 256;
constexpr int OFF_LN = OFF_RING + 7 * 8192;
static_assert(SMEM_BYTES <= 232448, "shared memory");

constexpr int B_ROW = 0, B_XT = 4, B_LN = 5, B_KG = 6, B_SFREE = 7, B_RECV = 8, B_RED = 10, B_UPD = 11, B_FREE = 12, B_FULL = 15, NBAR = 27;

constexpr int T_DENSE = 0;
constexpr int T_PATCH = 2240;
constexpr int T_R2 = 2432;
constexpr int T_R3 = 3200;

constexpr uint32_t SPIN_LIMIT = 1u << 20;
#define KG_UNROLL 4
constexpr int kKgUnroll = KG_UNROLL;
#define WIN0 3
#define WIN1 4
#define WIN_SW 6

struct Ptrs {
    const __nv_bfloat16 *logA, *Aim, *Cre, *Cim, *ldt, *dsk, *u, *wr;
    __nv_bfloat16* out;
    uint32_t zero;
};
struct Maps {
    CUtensorMap u, out, wg, wu, wd;
};

__device__ unsigned int g_epoch;
__device__ unsigned int g_rdy;
__device__ __align__(16) unsigned int g_clr[GU_CTAS];
__device__ __align__(128) uint2 g_stat[SEQ];
__device__ __align__(128) uint2 g_sel[8];
__device__ __align__(128) uint4 g_xs[1024];
__device__ __align__(128) uint32_t g_h[GU_CTAS * 128];

#define STAMP(i) do { } while (0)
#define GSTAMP(i) do { } while (0)

__device__ __forceinline__ uint32_t s_u32(const void* p) { return (uint32_t)__cvta_generic_to_shared(p); }
__device__ __forceinline__ void mbar_init(uint32_t b, uint32_t n) {
    asm volatile("mbarrier.init.shared::cta.b64 [%0], %1;" ::"r"(b), "r"(n) : "memory");
}
__device__ __forceinline__ void mbar_expect_tx(uint32_t b, uint32_t bytes) {
    asm volatile("mbarrier.arrive.expect_tx.shared::cta.b64 _, [%0], %1;" ::"r"(b), "r"(bytes) : "memory");
}
__device__ __forceinline__ void mbar_arrive(uint32_t b) {
    asm volatile("mbarrier.arrive.shared::cta.b64 _, [%0];" ::"r"(b) : "memory");
}
__device__ __forceinline__ void mbar_arrive_peer(uint32_t b_cluster) {
    asm volatile("mbarrier.arrive.relaxed.cluster.shared::cluster.b64 _, [%0];" ::"r"(b_cluster) : "memory");
}
__device__ __forceinline__ void mbar_wait(uint32_t b, uint32_t parity) {
    asm volatile("{\n\t.reg .pred p;\n\t.reg .u32 c;\n\tmov.u32 c, 0;\n"
                 "W:\n\tmbarrier.try_wait.parity.shared::cta.b64 p, [%0], %1, 4000;\n\t@p bra D;\n\t"
                 "add.u32 c, c, 1;\n\tsetp.lt.u32 p, c, 1048576;\n\t@p bra W;\n\ttrap;\nD:\n\t}"
                 ::"r"(b), "r"(parity) : "memory");
}
__device__ __forceinline__ bool mbar_test(uint32_t b, uint32_t parity) {
    uint32_t ok;
    asm volatile("{ .reg .pred p; mbarrier.test_wait.parity.shared::cta.b64 p, [%1], %2; selp.u32 %0, 1, 0, p; }" : "=r"(ok) : "r"(b), "r"(parity) : "memory");
    return __all_sync(0xffffffffu, ok != 0);
}
__device__ __forceinline__ bool elect_one() {
    uint32_t p;
    asm volatile("{ .reg .pred P; elect.sync _|P, 0xffffffff; selp.u32 %0, 1, 0, P; }" : "=r"(p));
    return p != 0;
}
__device__ __forceinline__ uint32_t mapa(uint32_t a, uint32_t rank) {
    uint32_t r;
    asm("mapa.shared::cluster.u32 %0, %1, %2;" : "=r"(r) : "r"(a), "r"(rank));
    return r;
}
__device__ __forceinline__ void cluster_arrive() { asm volatile("barrier.cluster.arrive.relaxed.aligned;" ::: "memory"); }
__device__ __forceinline__ void cluster_wait() { asm volatile("barrier.cluster.wait.acquire.aligned;" ::: "memory"); }
__device__ __forceinline__ void tma_load_2d(uint32_t dst, const CUtensorMap* m, int c0, int c1, uint32_t bar) {
    asm volatile("cp.async.bulk.tensor.2d.shared::cluster.global.mbarrier::complete_tx::bytes [%0], [%1, {%3, %4}], [%2];"
                 ::"r"(dst), "l"(m), "r"(bar), "r"(c0), "r"(c1) : "memory");
}
__device__ __forceinline__ void tma_load_tile(uint32_t dst, const CUtensorMap* m, int c0, int c2, int c3, uint32_t bar) {
    asm volatile("cp.async.bulk.tensor.4d.shared::cluster.global.mbarrier::complete_tx::bytes.multicast::cluster [%0], [%1, {%3, %4, %5, %6}], [%2], %7;"
                 ::"r"(dst), "l"(m), "r"(bar), "r"(c0), "r"(0), "r"(c2), "r"(c3), "h"((uint16_t)3) : "memory");
}
__device__ __forceinline__ void tma_store_tile(const CUtensorMap* m, uint32_t src, int c0, int c2, int c3) {
    asm volatile("cp.async.bulk.tensor.4d.global.shared::cta.bulk_group [%0, {%2, %3, %4, %5}], [%1];"
                 ::"l"(m), "r"(src), "r"(c0), "r"(0), "r"(c2), "r"(c3) : "memory");
    asm volatile("cp.async.bulk.commit_group;" ::: "memory");
}
__device__ __forceinline__ void bulk_g2s(uint32_t dst, const void* src, uint32_t bytes, uint32_t bar) {
    asm volatile("cp.async.bulk.shared::cluster.global.mbarrier::complete_tx::bytes [%0], [%1], %2, [%3];"
                 ::"r"(dst), "l"(src), "r"(bytes), "r"(bar) : "memory");
}
__device__ __forceinline__ void st_async128(uint32_t dst_cluster, uint32_t x, uint32_t y, uint32_t z, uint32_t w, uint32_t bar_cluster) {
    asm volatile("st.async.weak.shared::cluster.mbarrier::complete_tx::bytes.v4.b32 [%0], {%1,%2,%3,%4}, [%5];"
                 ::"r"(dst_cluster), "r"(x), "r"(y), "r"(z), "r"(w), "r"(bar_cluster) : "memory");
}
__device__ __forceinline__ void fence_async() { asm volatile("fence.proxy.async.shared::cta;" ::: "memory"); }
__device__ __forceinline__ void named_sync(int id, int n) { asm volatile("bar.sync %0, %1;" ::"r"(id), "r"(n) : "memory"); }

__device__ __forceinline__ void ldsm4(uint32_t* r, uint32_t a) {
    asm volatile("ldmatrix.sync.aligned.m8n8.x4.shared.b16 {%0,%1,%2,%3}, [%4];"
                 : "=r"(r[0]), "=r"(r[1]), "=r"(r[2]), "=r"(r[3]) : "r"(a));
}
__device__ __forceinline__ void ldsm4t(uint32_t* r, uint32_t a) {
    asm volatile("ldmatrix.sync.aligned.m8n8.x4.trans.shared.b16 {%0,%1,%2,%3}, [%4];"
                 : "=r"(r[0]), "=r"(r[1]), "=r"(r[2]), "=r"(r[3]) : "r"(a));
}
__device__ __forceinline__ void stsm4t(uint32_t a, uint32_t x, uint32_t y, uint32_t z, uint32_t w) {
    asm volatile("stmatrix.sync.aligned.m8n8.x4.trans.shared.b16 [%0], {%1,%2,%3,%4};"
                 ::"r"(a), "r"(x), "r"(y), "r"(z), "r"(w) : "memory");
}
__device__ __forceinline__ uint32_t lds32(uint32_t a) { uint32_t v; asm volatile("ld.shared.u32 %0, [%1];" : "=r"(v) : "r"(a)); return v; }
__device__ __forceinline__ float lds32f(uint32_t a) { float v; asm volatile("ld.shared.f32 %0, [%1];" : "=f"(v) : "r"(a)); return v; }
__device__ __forceinline__ uint2 lds64(uint32_t a) { uint2 v; asm volatile("ld.shared.v2.u32 {%0,%1}, [%2];" : "=r"(v.x), "=r"(v.y) : "r"(a)); return v; }
__device__ __forceinline__ uint4 lds128(uint32_t a) {
    uint4 v; asm volatile("ld.shared.v4.u32 {%0,%1,%2,%3}, [%4];" : "=r"(v.x), "=r"(v.y), "=r"(v.z), "=r"(v.w) : "r"(a)); return v;
}
__device__ __forceinline__ float4 lds128f(uint32_t a) {
    float4 v; asm volatile("ld.shared.v4.f32 {%0,%1,%2,%3}, [%4];" : "=f"(v.x), "=f"(v.y), "=f"(v.z), "=f"(v.w) : "r"(a)); return v;
}
__device__ __forceinline__ void sts32(uint32_t a, uint32_t v) { asm volatile("st.shared.u32 [%0], %1;" ::"r"(a), "r"(v) : "memory"); }
__device__ __forceinline__ void sts32f(uint32_t a, float v) { asm volatile("st.shared.f32 [%0], %1;" ::"r"(a), "f"(v) : "memory"); }
__device__ __forceinline__ void sts64(uint32_t a, uint32_t x, uint32_t y) { asm volatile("st.shared.v2.u32 [%0], {%1,%2};" ::"r"(a), "r"(x), "r"(y) : "memory"); }
__device__ __forceinline__ void sts64f(uint32_t a, float x, float y) { asm volatile("st.shared.v2.f32 [%0], {%1,%2};" ::"r"(a), "f"(x), "f"(y) : "memory"); }
__device__ __forceinline__ void sts128(uint32_t a, uint32_t x, uint32_t y, uint32_t z, uint32_t w) {
    asm volatile("st.shared.v4.u32 [%0], {%1,%2,%3,%4};" ::"r"(a), "r"(x), "r"(y), "r"(z), "r"(w) : "memory");
}
__device__ __forceinline__ void sts128f(uint32_t a, const float* v) {
    asm volatile("st.shared.v4.f32 [%0], {%1,%2,%3,%4};" ::"r"(a), "f"(v[0]), "f"(v[1]), "f"(v[2]), "f"(v[3]) : "memory");
}
__device__ __forceinline__ uint4 ldg128(const void* p) {
    uint4 v; asm volatile("ld.global.nc.L1::no_allocate.v4.u32 {%0,%1,%2,%3}, [%4];" : "=r"(v.x), "=r"(v.y), "=r"(v.z), "=r"(v.w) : "l"(p)); return v;
}
__device__ __forceinline__ uint2 ldg64(const void* p) {
    uint2 v; asm volatile("ld.global.nc.L1::no_allocate.v2.u32 {%0,%1}, [%2];" : "=r"(v.x), "=r"(v.y) : "l"(p)); return v;
}
__device__ __forceinline__ uint32_t ldg32(const void* p) {
    uint32_t v; asm volatile("ld.global.nc.u32 %0, [%1];" : "=r"(v) : "l"(p)); return v;
}
__device__ __forceinline__ uint32_t ldg16(const void* p) {
    uint32_t v; asm volatile("ld.global.nc.u16 %0, [%1];" : "=r"(v) : "l"(p)); return v;
}
__device__ __forceinline__ uint4 ld_relaxed_128(const void* p) {
    uint4 v; asm volatile("ld.relaxed.gpu.global.v4.u32 {%0,%1,%2,%3}, [%4];" : "=r"(v.x), "=r"(v.y), "=r"(v.z), "=r"(v.w) : "l"(p) : "memory"); return v;
}
__device__ __forceinline__ void ld_relaxed_128_unless(uint4& q, const void* p, bool have) {
    asm volatile("{ .reg .pred p; setp.eq.u32 p, %5, 0; @p ld.relaxed.gpu.global.v4.u32 {%0,%1,%2,%3}, [%4]; }"
                 : "+r"(q.x), "+r"(q.y), "+r"(q.z), "+r"(q.w) : "l"(p), "r"((uint32_t)have) : "memory");
}
__device__ __forceinline__ uint2 ld_relaxed_64(const void* p) {
    uint2 v; asm volatile("ld.relaxed.gpu.global.v2.u32 {%0,%1}, [%2];" : "=r"(v.x), "=r"(v.y) : "l"(p) : "memory"); return v;
}
__device__ __forceinline__ uint32_t ld_relaxed_32(const void* p) {
    uint32_t v; asm volatile("ld.relaxed.gpu.global.u32 %0, [%1];" : "=r"(v) : "l"(p) : "memory"); return v;
}
__device__ __forceinline__ void st_relaxed_128(void* p, uint32_t x, uint32_t y, uint32_t z, uint32_t w) {
    asm volatile("st.relaxed.gpu.global.v4.u32 [%0], {%1,%2,%3,%4};" ::"l"(p), "r"(x), "r"(y), "r"(z), "r"(w) : "memory");
}
__device__ __forceinline__ void st_relaxed_64(void* p, uint32_t x, uint32_t y) {
    asm volatile("st.relaxed.gpu.global.v2.u32 [%0], {%1,%2};" ::"l"(p), "r"(x), "r"(y) : "memory");
}
__device__ __forceinline__ void st_relaxed_32(void* p, uint32_t v) {
    asm volatile("st.relaxed.gpu.global.u32 [%0], %1;" ::"l"(p), "r"(v) : "memory");
}
__device__ __forceinline__ void spin_guard(uint32_t& it) { if (++it > SPIN_LIMIT) __trap(); }
__device__ __forceinline__ void mma_bf16(float* c, uint32_t a0, uint32_t a1, uint32_t a2, uint32_t a3, uint32_t b0, uint32_t b1) {
    asm("mma.sync.aligned.m16n8k16.row.col.f32.bf16.bf16.f32 {%0,%1,%2,%3}, {%4,%5,%6,%7}, {%8,%9}, {%0,%1,%2,%3};"
                 : "+f"(c[0]), "+f"(c[1]), "+f"(c[2]), "+f"(c[3]) : "r"(a0), "r"(a1), "r"(a2), "r"(a3), "r"(b0), "r"(b1));
}
__device__ __forceinline__ void mma_bf16_k8(float* c, uint32_t a0, uint32_t a1, uint32_t b0) {
    asm("mma.sync.aligned.m16n8k8.row.col.f32.bf16.bf16.f32 {%0,%1,%2,%3}, {%4,%5}, {%6}, {%0,%1,%2,%3};"
                 : "+f"(c[0]), "+f"(c[1]), "+f"(c[2]), "+f"(c[3]) : "r"(a0), "r"(a1), "r"(b0));
}
__device__ __forceinline__ void mma_bf16_z(float* c, uint32_t a0, uint32_t a1, uint32_t a2, uint32_t a3, uint32_t b0, uint32_t b1) {
    asm("mma.sync.aligned.m16n8k16.row.col.f32.bf16.bf16.f32 {%0,%1,%2,%3}, {%4,%5,%6,%7}, {%8,%9}, {%10,%10,%10,%10};"
        : "=f"(c[0]), "=f"(c[1]), "=f"(c[2]), "=f"(c[3]) : "r"(a0), "r"(a1), "r"(a2), "r"(a3), "r"(b0), "r"(b1), "f"(0.f));
}
__device__ __forceinline__ void mma_f16(float* c, uint32_t a0, uint32_t a1, uint32_t a2, uint32_t a3, uint32_t b0, uint32_t b1) {
    asm("mma.sync.aligned.m16n8k16.row.col.f32.f16.f16.f32 {%0,%1,%2,%3}, {%4,%5,%6,%7}, {%8,%9}, {%0,%1,%2,%3};"
                 : "+f"(c[0]), "+f"(c[1]), "+f"(c[2]), "+f"(c[3]) : "r"(a0), "r"(a1), "r"(a2), "r"(a3), "r"(b0), "r"(b1));
}
__device__ __forceinline__ uint32_t pack_bf16(float lo, float hi) {
    uint32_t r; asm("cvt.rn.bf16x2.f32 %0, %1, %2;" : "=r"(r) : "f"(hi), "f"(lo)); return r;
}
__device__ __forceinline__ uint32_t pack_f16(float lo, float hi) {
    uint32_t r; asm("cvt.rn.f16x2.f32 %0, %1, %2;" : "=r"(r) : "f"(hi), "f"(lo)); return r;
}
__device__ __forceinline__ float bf_lo(uint32_t v) { return __uint_as_float(v << 16); }
__device__ __forceinline__ float bf_hi(uint32_t v) { return __uint_as_float(v & 0xffff0000u); }
__device__ __forceinline__ float bf_round(float x) { return __uint_as_float(pack_bf16(0.f, x)); }
__device__ __forceinline__ uint32_t badd2(uint32_t a, uint32_t b) { uint32_t r; asm("add.rn.bf16x2 %0, %1, %2;" : "=r"(r) : "r"(a), "r"(b)); return r; }
__device__ __forceinline__ uint32_t bmax2(uint32_t a, uint32_t b) { uint32_t r; asm("max.bf16x2 %0, %1, %2;" : "=r"(r) : "r"(a), "r"(b)); return r; }
__device__ __forceinline__ uint32_t normalize2(uint32_t x, uint32_t s0, uint32_t s1) {
    uint32_t r;
    asm("{ .reg .b16 m, h, l, k; .reg .b32 m2, h2, l2, d, t;\n\t"
        "mov.b32 {m, h}, %2; mov.b32 {l, k}, %3; mov.b32 m2, {m, m}; mov.b32 h2, {h, h}; mov.b32 l2, {l, l};\n\t"
        "sub.rn.bf16x2 d, %1, m2; mul.rn.bf16x2 t, d, l2; fma.rn.bf16x2 %0, d, h2, t; }" : "=r"(r) : "r"(x), "r"(s0), "r"(s1));
    return r;
}
__device__ __forceinline__ float rcpf(float x) { float r; asm("rcp.approx.ftz.f32 %0, %1;" : "=f"(r) : "f"(x)); return r; }
__device__ __forceinline__ float sqrtaf(float x) { float r; asm("sqrt.approx.ftz.f32 %0, %1;" : "=f"(r) : "f"(x)); return r; }
__device__ __forceinline__ float ex2f(float x) { float r; asm("ex2.approx.ftz.f32 %0, %1;" : "=f"(r) : "f"(x)); return r; }

__device__ __forceinline__ int tok_off(int t) { return (t >> 4) * 32 + ((((t >> 3) ^ (t >> 6)) & 1) << 4); }

__device__ __forceinline__ uint32_t order_key(uint32_t b16) { return b16 ^ ((b16 & 0x8000u) ? 0xffffu : 0x8000u); }
__device__ __forceinline__ uint32_t unorder_key(uint32_t k16) { return k16 ^ ((k16 & 0x8000u) ? 0x8000u : 0xffffu); }

struct cplx { float r, i; };
struct hc { uint32_t r, i; };
template <bool CONJ> __device__ __forceinline__ cplx csq(cplx a) {
    float im;
    asm("{ .reg .f32 t; mul.ftz.f32 t, %1, %2; mul.ftz.f32 %0, t, 0f40000000; }" : "=f"(im) : "f"(CONJ ? -a.r : a.r), "f"(a.i));
    return {fmaf(a.r, a.r, -(a.i * a.i)), im};
}
__device__ __forceinline__ cplx cexpp(float a2, float ai) {
    float m = ex2f(a2), s, c;
    __sincosf(ai, &s, &c);
    return {m * c, m * s};
}
__device__ __forceinline__ __half2 as_h2(uint32_t x) { return *reinterpret_cast<__half2*>(&x); }
__device__ __forceinline__ uint32_t as_u(__half2 x) { return *reinterpret_cast<uint32_t*>(&x); }
__device__ __forceinline__ hc hmul(hc a, hc b) {
    return {as_u(__hfma2(__hneg2(as_h2(a.i)), as_h2(b.i), __hmul2(as_h2(a.r), as_h2(b.r)))),
            as_u(__hfma2(as_h2(a.i), as_h2(b.r), __hmul2(as_h2(a.r), as_h2(b.i))))};
}
__device__ __forceinline__ hc hpack(cplx a, cplx b) { return {pack_f16(a.r, b.r), pack_f16(a.i, b.i)}; }
__device__ __forceinline__ void sts16(uint32_t a, uint32_t v) { asm volatile("st.shared.u16 [%0], %1;" ::"r"(a), "r"(v) : "memory"); }

template <class Hook>
__device__ __forceinline__ void kgen(uint32_t tab, int lane, uint2 la, uint2 aim, uint2 cre, uint2 cim, float dt, float skip, int dch, Hook main_done) {
    const int g = lane >> 2, t = lane & 3;
    const float dt2 = 2.f * dt;
    const uint32_t am = bmax2(bmax2(cre.x & 0x7fff7fffu, cre.y & 0x7fff7fffu), bmax2(cim.x & 0x7fff7fffu, cim.y & 0x7fff7fffu));
    const float mx = dt2 * fmaxf(bf_lo(am), bf_hi(am));
    const uint32_t eb = min(max(__reduce_max_sync(0xffffffffu, __float_as_uint(mx)) >> 23, 1u), 252u);
    const float cscale = dt2 * __uint_as_float((253u - eb) << 23);
    const float scale_inv = __uint_as_float((eb + 1u) << 23);
    float k0 = (bf_lo(cre.x) + bf_hi(cre.x)) + (bf_lo(cre.y) + bf_hi(cre.y));
#pragma unroll
    for (int o = 16; o; o >>= 1) k0 += __shfl_xor_sync(0xffffffffu, k0, o);
    const float ndt = -1.4426950408889634f * dt;

    float acc[5][4];
#pragma unroll
    for (int i = 0; i < 5; i++) { acc[i][0] = acc[i][1] = acc[i][2] = acc[i][3] = 0.f; }

    const uint32_t rec = tab + t * 512, sw = (uint32_t)t << 5;
    const uint32_t ad_l = rec + (((uint32_t)g << 4) ^ sw), ad_h = rec + 128 + (((uint32_t)g << 3) ^ sw);
    const uint32_t ad_2 = rec + (0xc0u ^ sw) + ((g & 1) << 3), ad_3 = rec + (0xd0u ^ sw) + ((g & 2) << 2);
    const uint32_t ad_4 = rec + (0xe0u ^ sw) + ((g & 4) << 1), ad_z = rec + (0xf0u ^ sw);
    const uint32_t wrec = tab + lane * 256 + ((lane & 7) << 4);

#pragma unroll 1
    for (int bb = 0; bb < 2; bb++) {
        cplx z[2][11], cz[2];
#pragma unroll
        for (int e = 0; e < 2; e++) {
            const float lg = e ? bf_hi(la.x) : bf_lo(la.x), ai = (e ? bf_hi(aim.x) : bf_lo(aim.x)) * dt;
            const float cr = (e ? bf_hi(cre.x) : bf_lo(cre.x)) * cscale, ci = (e ? bf_hi(cim.x) : bf_lo(cim.x)) * cscale;
            const float a2 = bf_round(ex2f(lg * 1.4426950408889634f)) * ndt;
            z[e][0] = cexpp(a2, ai);
            z[e][5] = cexpp(a2 * 32.f, ai * -32.f);
#pragma unroll
            for (int i = 1; i < 11; i++) if (i != 5) z[e][i] = (i == 3 || i == 7) ? csq<true>(z[e][i - 1]) : csq<false>(z[e][i - 1]);
            cz[e] = {fmaf(cr, z[e][0].r, -(ci * z[e][0].i)), fmaf(cr, z[e][0].i, ci * z[e][0].r)};
        }
        la.x = la.y; aim.x = aim.y; cre.x = cre.y; cim.x = cim.y;
        const hc z1 = hpack(z[0][0], z[1][0]), z2 = hpack(z[0][1], z[1][1]), z4 = hpack(z[0][2], z[1][2]);
        hc L[8], H[8];
        L[1] = hpack(z[0][3], z[1][3]); L[2] = hpack(z[0][4], z[1][4]); L[4] = hpack(z[0][5], z[1][5]);
        const hc y64 = hpack(z[0][6], z[1][6]), z128 = hpack(z[0][7], z[1][7]), z256 = hpack(z[0][8], z[1][8]);
        const hc z512 = hpack(z[0][9], z[1][9]), z1024 = hpack(z[0][10], z[1][10]);
        H[0] = hpack(cz[0], cz[1]);
        H[1] = hmul(H[0], z1); H[2] = hmul(H[0], z2); H[3] = hmul(H[1], z2);
        L[3] = hmul(L[1], L[2]);
#pragma unroll
        for (int i = 0; i < 4; i++) { H[4 + i] = hmul(H[i], z4); if (i) L[4 + i] = hmul(L[i], L[4]); }
        __syncwarp();
        sts128(wrec, 0x3c003c00u, y64.r, 0u, y64.i);
#pragma unroll
        for (int i = 1; i < 8; i++) { const hc q = hmul(L[i], y64); sts128(wrec ^ (i << 4), L[i].r, q.r, L[i].i, q.i); }
#pragma unroll
        for (int i = 0; i < 4; i++) sts128((wrec ^ (i << 4)) + 128, H[2 * i].r, H[2 * i].i, H[2 * i + 1].r, H[2 * i + 1].i);
        {
            const hc a = hmul(z256, z1), b = hmul(z256, z128), c = hmul(z256, z2), d = hmul(z512, z4);
            sts128((wrec ^ 0x40) + 128, a.r, a.i, b.r, b.i);
            sts128((wrec ^ 0x50) + 128, c.r, c.i, z512.r, z512.i);
            sts128((wrec ^ 0x60) + 128, d.r, d.i, z1024.r, z1024.i);
            sts64((wrec ^ 0x70) + 128, z128.r, z128.i);
        }
        __syncwarp();
#pragma unroll kKgUnroll
        for (int k2 = 0; k2 < 4; k2++) {
#pragma unroll
            for (uint32_t s = 0; s < 2; s++) {
                const uint32_t o = k2 * 2048 + s * 256, x = s << 4;
                const uint4 l = lds128((ad_l ^ x) + o);
                const uint2 h0 = lds64((ad_h ^ x) + o), m2 = lds64((ad_2 ^ x) + o), m3 = lds64((ad_3 ^ x) + o);
                const uint2 m4 = lds64((ad_4 ^ x) + o), mz = lds64((ad_z ^ x) + o);
                const hc H0 = {h0.x, h0.y};
                const hc H1 = hmul(H0, {mz.x, mz.y}), H2 = hmul(H0, {m2.x, m2.y}), H3 = hmul(H2, {m3.x, m3.y}), H4 = hmul(H3, {m4.x, m4.y});
                mma_f16(acc[0], l.x, l.y, l.z, l.w, H0.r, H0.i);
                mma_f16(acc[1], l.x, l.y, l.z, l.w, H1.r, H1.i);
                mma_f16(acc[2], l.x, l.y, l.z, l.w, H2.r, H2.i);
                mma_f16(acc[3], l.x, l.y, l.z, l.w, H3.r, H3.i);
                mma_f16(acc[4], l.x, l.y, l.z, l.w, H4.r, H4.i);
            }
        }
    }
    __syncwarp();
    main_done();
#pragma unroll
    for (int i = 0; i < 4; i++) sts128(tab + 2048 + 512 * i + 16 * lane, 0, 0, 0, 0);
    sts32(tab + 4 * lane, 0);
    __syncwarp();
    const uint32_t d0 = tab + T_DENSE + 4 * 17 + 8 * lane;
    const uint32_t d2a = d0 + 4 * 257 - 4 * (lane & 1), d2b = d0 + 4 * 258 + 2 + 4 * (lane & 1);
    const uint32_t d3 = tab + T_R2 + (g & 1) * 384 + (6 + 16 * (t & 1) + (g >> 1)) * 8 + (t >> 1) * 4;
    const uint32_t d4 = tab + T_R3 + (6 + 16 * t + (g >> 1)) * 8 + (g & 1) * 4;
    uint32_t last[3];
#pragma unroll
    for (int hf = 0; hf < 2; hf++) {
#pragma unroll
        for (int G = 0; G < 2; G++) {
            const uint32_t pk = pack_bf16(acc[G][2 * hf + 1] * scale_inv, acc[G][2 * hf] * scale_inv), a = d0 + 512 * G + 256 * hf;
            sts32(a + 4, pk);
            sts16(a + 10, pk);
            sts16(a, pk >> 16);
            last[0] = pk;
        }
#pragma unroll
        for (int e = 0; e < 2; e++) {
            const float v2 = acc[2][2 * hf + e] * scale_inv, v3 = acc[3][2 * hf + e] * scale_inv, v4 = acc[4][2 * hf + e] * scale_inv;
            const uint32_t p2 = pack_bf16(v2, v2), p3 = pack_bf16(v3, v3), p4 = pack_bf16(v4, v4), o = 256 * hf + 512 * e;
            sts16(d2a + o, p2);
            sts16(d2b + o, p2);
            if (lane & 1) sts64(d2a + o + 4, p2, p2);
            sts16(d3 + 32 * hf + 64 * e, p3);
            sts16(d3 + 32 * hf + 64 * e + 10, p3);
            sts16(d4 + 32 * hf + 64 * e, p4);
            sts16(d4 + 32 * hf + 64 * e + 10, p4);
            last[1] = p2; last[2] = p3;
        }
    }
    if (lane == 31) {
        const uint32_t p0 = pack_bf16(fmaf(k0, dt2, skip), 0.f), d = tab + T_DENSE + 4 * 16;
        sts16(d, p0); sts16(d + 6, p0);
        sts16(d + 4 * 257, last[0]); sts16(d + 4 * 258 + 2, last[0]);
        sts16(d + 4 * 514, last[1]); sts16(d + 4 * 515 + 2, last[1]);
        sts16(tab + T_PATCH + 4 * 17, last[2]); sts32(tab + T_PATCH + 4 * 18, last[2]); sts16(tab + T_PATCH + 4 * 19 + 2, last[2]);
    }
    __syncwarp();
}

__device__ __forceinline__ void dense_phase(float (&acc)[16][4], uint32_t vrow, uint32_t tab, uint32_t zero, int lane) {
    const int m = lane >> 3, r = lane & 7;
    const int off = (lane >> 2) - 2 * (lane & 3);
#pragma unroll 1
    for (int rho = 0; rho < 8; rho++) {
        const int lam = 8 * (lane >> 4) - rho + r;
        const uint32_t a = vrow + lam * 32 + (((m & 1) ^ ((lam >> 2) & 1)) << 4);
        uint32_t R[32];
#pragma unroll
        for (int i = 0; i < 8; i++) ldsm4(&R[4 * i], a + i * 512);
        const uint32_t pb = tab + T_DENSE + (off + 16 + 16 * rho) * 4;
#pragma unroll
        for (int ka = 0; ka < 4; ka++) {
            const uint32_t a0 = lds32(pb + ka * 512), a1 = lds32(pb + ka * 512 + 32), a2 = lds32(pb + ka * 512 - 32), a3 = lds32(pb + zero + ka * 512);
#pragma unroll
            for (int nu = ka; nu < 16; nu++) mma_bf16(acc[nu], a0, a1, a2, a3, R[2 * (nu - ka)], R[2 * (nu - ka) + 1]);
        }
        if (rho <= 1) {
            uint32_t a0 = lds32(pb + 2048), a1 = lds32(pb + 2048 + 32), a2 = lds32(pb + 2048 - 32), a3 = lds32(pb + zero + 2048);
#pragma unroll
            for (int nu = 4; nu < 16; nu++) mma_bf16(acc[nu], a0, a1, a2, a3, R[2 * (nu - 4)], R[2 * (nu - 4) + 1]);
            const uint32_t pp = pb + (T_PATCH - T_DENSE - 8);
            a0 = lds32(pp); a1 = lds32(pp + 32); a2 = lds32(pp - 32); a3 = lds32(pp + zero);
#pragma unroll
            for (int nu = 8; nu < 16; nu++) mma_bf16(acc[nu], a0, a1, a2, a3, R[2 * (nu - 8)], R[2 * (nu - 8) + 1]);
        }
    }
}
__device__ __forceinline__ uint32_t ones2(int c, int lo, int hi) {
    return (((uint32_t)(c - lo) <= (uint32_t)(hi - lo)) ? 0x3f80u : 0u) | (((uint32_t)(c + 1 - lo) <= (uint32_t)(hi - lo)) ? 0x3f800000u : 0u);
}
struct Boxes {
    uint32_t q[4], ha[4], hz[2];
    __device__ __forceinline__ Boxes(uint32_t vrow, uint32_t zero, int lane, int O, int L1, int H1, int L2, int H2) {
        const int g = lane >> 2, t = lane & 3, d = 2 * t - g;
        q[0] = ones2(d, L1, H1); q[1] = ones2(d, L2, H2); q[2] = ones2(d + 8, L1, H1); q[3] = ones2(d + 8, L2, H2);
#pragma unroll
        for (int i = 0; i < 4; i++) {
            const int T = 16 * g + O + 8 * i + 2 * t;
            ha[i] = vrow + tok_off(T & ~7) + (T & 7) * 2;
        }
        hz[0] = ha[1] + zero; hz[1] = ha[2] + zero;
    }
    __device__ __forceinline__ void run(int j, float* Z, float* X, float* Y) const {
        const uint32_t o = j * 256;
        mma_bf16_z(Z, q[0], q[1], q[2], q[3], lds32(ha[0] + o), lds32(hz[0] + o));
        mma_bf16_z(X, q[0], q[1], q[2], q[3], lds32(ha[1] + o), lds32(hz[1] + o));
        mma_bf16_z(Y, q[0], q[1], q[2], q[3], lds32(ha[2] + o), lds32(ha[3] + o));
    }
};
template <int J0, int J1>
__device__ __forceinline__ void tail2(float (&acc)[16][4], const Boxes& bx, const uint2 (&tp)[10]) {
#pragma unroll
    for (int j = J0; j < J1; j++) {
        float Z[4], X[4], Y[4];
        bx.run(j, Z, X, Y);
        const uint32_t x0 = pack_bf16(X[0], X[1]), x1 = pack_bf16(X[2], X[3]);
        const uint32_t y0 = pack_bf16(Y[0], Y[1]), y1 = pack_bf16(Y[2], Y[3]), z0 = pack_bf16(Z[0], Z[1]), z1 = pack_bf16(Z[2], Z[3]);
#pragma unroll
        for (int b = 0; b < 5; b++) if (j + 4 + b < 16) mma_bf16(acc[j + 4 + b], z0, x0, z1, x1, tp[5 + b].x, tp[5 + b].y);
#pragma unroll
        for (int b = 0; b < 5; b++) if (j + 4 + b < 16) mma_bf16(acc[j + 4 + b], x0, y0, x1, y1, tp[b].x, tp[b].y);
    }
}
__device__ __forceinline__ void tail3(float (&acc)[16][4], const Boxes& bx, uint32_t tp3) {
    uint2 tp[8];
#pragma unroll
    for (int b = 0; b < 8; b++) tp[b] = lds64(tp3 + 64 * b);
#pragma unroll
    for (int j = 0; j < 8; j++) {
        float Z[4], X[4], Y[4];
        bx.run(j, Z, X, Y);
        const uint32_t a0 = pack_bf16(X[0], X[1]), a1 = pack_bf16(Y[0], Y[1]), a2 = pack_bf16(Z[2], Z[3]), a3 = pack_bf16(X[2], X[3]);
#pragma unroll
        for (int b = 0; b < 8; b++) if (j + 8 + b < 16) mma_bf16(acc[j + 8 + b], a0, a1, a2, a3, tp[b].x, tp[b].y);
    }
}
template <int G>
__device__ __forceinline__ void emit(const float (&acc)[16][4], uint32_t dst0, uint32_t dst1, uint32_t bar0, uint32_t bar1) {
#pragma unroll
    for (int o = 0; o < 2; o++)
#pragma unroll
        for (int hf = 0; hf < 2; hf++) {
            const int n = 8 * G + 4 * o;
            st_async128((o ? dst1 : dst0) + G * 16384 + hf * 512, pack_bf16(acc[n][2 * hf], acc[n][2 * hf + 1]), pack_bf16(acc[n + 1][2 * hf], acc[n + 1][2 * hf + 1]),
                        pack_bf16(acc[n + 2][2 * hf], acc[n + 2][2 * hf + 1]), pack_bf16(acc[n + 3][2 * hf], acc[n + 3][2 * hf + 1]), (o ? bar1 : bar0) + 8 * G);
        }
}
__device__ __forceinline__ void finish(uint32_t src, uint32_t xa) {
    uint32_t s[4][4];
    uint4 x[4];
#pragma unroll
    for (int i = 0; i < 4; i++) {
        ldsm4t(s[i], (src ^ ((i & 1) << 5)) + (i >> 1) * 8192);
        x[i] = lds128((xa ^ ((i >> 1) << 4)) + (i & 1) * 256);
    }
#pragma unroll
    for (int i = 0; i < 4; i++)
        sts128((xa ^ ((i >> 1) << 4)) + (i & 1) * 256, badd2(x[i].x, s[i][0]), badd2(x[i].y, s[i][1]), badd2(x[i].z, s[i][2]), badd2(x[i].w, s[i][3]));
}

__device__ __noinline__ float centred_var(uint32_t rows, float mu, int lane) {
    float var = 0.f;
#pragma unroll 1
    for (int rr = 0; rr < 16; rr++) {
        const float c0 = __shfl_sync(0xffffffffu, mu, rr);
        float c = 0.f;
#pragma unroll 1
        for (int k = 0; k < 16; k++) {
            const uint32_t q = lds32(rows + rr * ROW_PITCH + k * 128 + lane * 4);
            const float d0 = bf_lo(q) - c0, d1 = bf_hi(q) - c0;
            c = fmaf(d0, d0, fmaf(d1, d1, c));
        }
#pragma unroll 1
        for (int o = 16; o; o >>= 1) c += __shfl_xor_sync(0xffffffffu, c, o);
        if ((lane & 15) == rr) var = c * (1.f / DM);
    }
    return var;
}
__device__ __noinline__ float centred_score(uint32_t rows, uint32_t wbuf, uint32_t s0, uint32_t s1, int lane) {
    float sc = 0.f;
#pragma unroll 1
    for (int rr = 0; rr < 16; rr++) {
        const uint32_t t0 = __shfl_sync(0xffffffffu, s0, rr), t1 = __shfl_sync(0xffffffffu, s1, rr);
        float c = 0.f;
#pragma unroll 1
        for (int k = 0; k < 16; k++) {
            const uint32_t xn = normalize2(lds32(rows + rr * ROW_PITCH + k * 128 + lane * 4), t0, t1);
            const uint32_t wq = lds32(wbuf + (k >> 2) * 1024 + (k & 3) * 128 + lane * 4);
            c = fmaf(bf_lo(xn), bf_lo(wq), fmaf(bf_hi(xn), bf_hi(wq), c));
        }
#pragma unroll 1
        for (int o = 16; o; o >>= 1) c += __shfl_xor_sync(0xffffffffu, c, o);
        if ((lane & 15) == rr) sc = c;
    }
    return sc;
}

__device__ __noinline__ void router_cta(const __nv_bfloat16* u, uint32_t sb, int tid) {
    const int lane = tid & 31, warp = tid >> 5;
    const uint32_t misc = sb, sel = sb + 64, cand = sb + 256, cst = cand + 8192 + 64;
    const uint32_t epoch = ld_relaxed_32(&g_epoch);
#pragma unroll
    for (int i = 0; i < 4; i++) st_relaxed_128(&g_xs[tid + 256 * i], 0u, 0u, 0u, 0u);
    if (tid < 8) st_relaxed_64(g_sel + tid, 0u, epoch);
    if (tid == 0) sts32(misc + 32, 0);
#pragma unroll
    for (int i = 0; i < 2; i++) sts128(cand + 16 * tid + 4096 * i, 0, 0, 0, 0);
    if (tid < 4) sts128(cand + 8192 + 16 * tid, 0, 0, 0, 0);
    asm volatile("fence.acq_rel.gpu;" ::: "memory");
    const uint32_t tag = epoch + 1u;
    named_sync(1, 256);
    if (tid == 0) st_relaxed_32(&g_rdy, tag);
    STAMP(0); GSTAMP(24);
    uint4 q[4];
#pragma unroll
    for (int j = 0; j < 4; j++) q[j] = make_uint4(0, epoch, 0, 0);
#pragma unroll 1
    for (uint32_t it = 0;; spin_guard(it)) {
        uint32_t bad = 0;
#pragma unroll
        for (int j = 0; j < 4; j++) ld_relaxed_128_unless(q[j], g_stat + 2 * (256 * j + tid), ((q[j].y ^ tag) & 3) == 0);
#pragma unroll
        for (int j = 0; j < 4; j++) bad |= q[j].y ^ tag;
        if (__all_sync(0xffffffffu, (bad & 3) == 0)) break;
    }
    uint32_t key[8], mx = 0;
#pragma unroll
    for (int j = 0; j < 4; j++) {
        const uint32_t inv = 0xffffu - (512 * j + 16 * (tid >> 3) + (tid & 7));
        key[2 * j] = (q[j].y & 0xffff0000u) | inv;
        key[2 * j + 1] = (q[j].w & 0xffff0000u) | (inv - 8);
        mx = max(mx, max(key[2 * j], key[2 * j + 1]));
    }
    const uint32_t gm = __reduce_max_sync(0xffffffffu, mx);
    if (lane == 0) sts32(misc + 4 * warp, gm);
    STAMP(10); GSTAMP(26);
    named_sync(1, 256);
    if (tid == 0) st_relaxed_32(&g_epoch, tag);
    const uint4 t0 = lds128(misc), t1 = lds128(misc + 16);
    const uint32_t tau = min(min(min(t0.x, t0.y), min(t0.z, t0.w)), min(min(t1.x, t1.y), min(t1.z, t1.w)));
    if (mx >= tau) {
#pragma unroll
        for (int j = 0; j < 8; j++)
            if (key[j] >= tau) {
                uint32_t pos;
                asm volatile("atom.shared.add.u32 %0, [%1], 1;" : "=r"(pos) : "r"(misc + 32) : "memory");
                sts32(cand + 4 * pos, key[j]);
                sts64(cst + 8 * pos, (j & 1) ? q[j >> 1].z : q[j >> 1].x, (j & 1) ? q[j >> 1].w : q[j >> 1].y);
            }
    }
    named_sync(1, 256);
    const int n = (int)lds32(misc + 32);
#pragma unroll 1
    for (int i = lane; i < n; i += 32) {
        const uint32_t k = lds32(cand + 4 * i);
        const uint2 st = lds64(cst + 8 * i);
        int rk = 0;
#pragma unroll 1
        for (int j = 0; j < n; j += 16) {
#pragma unroll
            for (int jj = 0; jj < 4; jj++) {
                const uint4 c = lds128(cand + 4 * j + 16 * jj);
                rk += (c.x > k) + (c.y > k) + (c.z > k) + (c.w > k);
            }
        }
        if (rk < 8) sts128(sel + 16 * rk, k, st.x, st.y, 0);
    }
    __syncwarp();
    STAMP(11);
    const uint4 s = lds128(sel + 16 * (lane >> 2));
    const __nv_bfloat16* src = u + (size_t)(0xffffu - (s.x & 0xffffu)) * DM + 128 * warp + 2 * (lane & 3);
    uint32_t w[16];
#pragma unroll
    for (int j = 0; j < 16; j++) w[j] = ldg32(src + 8 * j);
#pragma unroll
    for (int j = 0; j < 16; j++) w[j] = normalize2(w[j], s.y, s.z);
#pragma unroll
    for (int j = 0; j < 4; j++)
        st_relaxed_128(&g_xs[128 * warp + 32 * j + lane], w[4 * j], w[4 * j + 1], w[4 * j + 2], w[4 * j + 3] ? w[4 * j + 3] : 0x80008000u);
    STAMP(12); GSTAMP(29);
    if (warp == 0) {
#pragma unroll 1
        for (uint32_t it = 0;; spin_guard(it)) {
            const uint4 c = lane < GU_CTAS / 4 ? ld_relaxed_128(&g_clr[4 * lane]) : make_uint4(tag, tag, tag, tag);
            if (__all_sync(0xffffffffu, c.x == tag && c.y == tag && c.z == tag && c.w == tag)) break;
        }
        if ((lane & 3) == 0) st_relaxed_64(g_sel + (lane >> 2), s.x, tag);
    }
}

__global__ void __cluster_dims__(2, 1, 1) __launch_bounds__(NTHR, 1)
fused_kernel(const __grid_constant__ Ptrs p, const __grid_constant__ Maps maps) {
    extern __shared__ __align__(1024) unsigned char smem[];
    const int tid = threadIdx.x, lane = tid & 31, b = blockIdx.x;
    const int dch = (8 * b + (tid >> 5) - 4) & (DM - 1);
    uint2 la, aim, cre, cim;
    uint32_t ldt16, dsk16;
    if ((uint32_t)(tid - 128) < 256u) {
        la = ldg64(p.logA + dch * NMODE + 4 * lane); aim = ldg64(p.Aim + dch * NMODE + 4 * lane);
        cre = ldg64(p.Cre + dch * NMODE + 4 * lane); cim = ldg64(p.Cim + dch * NMODE + 4 * lane);
        ldt16 = ldg16(p.ldt + dch); dsk16 = ldg16(p.dsk + dch);
    }
    const uint32_t sb = s_u32(smem);
    const int warp = __shfl_sync(0xffffffffu, tid >> 5, 0);
    const int h = b & 1, cl = b >> 1;
    const uint32_t bar0 = sb + OFF_BAR;
    const int m = lane >> 3, r = lane & 7, g = lane >> 2, t = lane & 3;
    const bool has_gu = b < GU_CTAS;
    if (b >= NCTA) {
        if (b == NCTA && tid < 256) router_cta(p.u, sb, tid);
        return;
    }
    if (warp == 4) { STAMP(0); GSTAMP(24); }

    if (warp == 12) {
        const bool el = elect_one();
        if (el) {
#pragma unroll
            for (int j = 0; j < 4; j++) mbar_init(bar0 + 8 * (B_ROW + j), 1);
            asm volatile("fence.mbarrier_init.release.cluster;" ::: "memory");
            fence_async();
#pragma unroll 1
            for (int j = 0; j < 4; j++) {
                mbar_expect_tx(bar0 + 8 * (B_ROW + j), 8192);
#pragma unroll
                for (int i = 0; i < 4; i++)
                    bulk_g2s(sb + OFF_VT + (4 * j + i) * ROW_PITCH, p.u + (size_t)(16 * b + 4 * j + i) * DM, 2048, bar0 + 8 * (B_ROW + j));
            }
        }
        __syncwarp();
        cluster_arrive();
        cluster_wait();
        STAMP(18);
        if (el) {
#pragma unroll 1
            for (int i = 0; i < 16; i++) {
                if ((i & 3) == 0) mbar_wait(bar0 + 8 * B_ROW + 2 * i, 0);
                tma_load_tile(sb + OFF_XT + h * 32768 + (i & 1) * 16384 + (i >> 1) * 2048, &maps.u, 16 * cl, i & 14, 16 * (i & 1) + 8 * h, bar0 + 8 * B_XT);
            }
            mbar_wait(bar0 + 8 * B_LN, 0);
            const int i0 = has_gu ? 0 : 16;
#pragma unroll 1
            for (int i = i0; i < 24; i++) {
                const int j = i - (i < WIN_SW ? WIN0 : WIN1), s = i < 12 ? i : i - 12;
                if (j >= i0) mbar_wait(bar0 + 8 * (B_FULL + (j < 12 ? j : j - 12)), has_gu && j >= 12);
                if (s == 8) mbar_wait(bar0 + 8 * B_KG, 0);
                if (i >= 12 && has_gu) mbar_wait(bar0 + 8 * (B_FREE + (s >> 2)), 0);
                const uint32_t dst = sb + OFF_RING + (s < 8 ? s * 8192 : (2 * s - 8) * 8192 + 4096), bar = bar0 + 8 * (B_FULL + s);
                const bool gu = i < 16;
                const int c0 = gu ? 32 * b : 16 * cl, c1 = gu ? 64 * i : 1792 * h + 448 * (i & 3) + 56 * (i & 4);
                mbar_expect_tx(bar, gu ? 8192 : 7168);
                tma_load_2d(dst, gu ? &maps.wg : &maps.wd, c0, c1, bar);
                tma_load_2d(dst + (s < 8 ? 4096 : 8192), gu ? &maps.wu : &maps.wd, c0, c1 + (gu ? 0 : 112), bar);
            }
            STAMP(19);
        }
    } else if (warp >= 4) {
        const int w = warp - 4;
        cluster_arrive();
        const uint32_t vrow = sb + OFF_VT + w * VT_PITCH + VT_PAD, tab = sb + OFF_PRIV + w * 8192;
        kgen(tab, lane, la, aim, cre, cim, bf_round(ex2f(bf_lo(ldt16) * 1.4426950408889634f)), 1.f + bf_lo(dsk16), dch, [&]() {
            STAMP(21);
            cluster_wait();
            fence_async();
            __syncwarp();
            if (elect_one()) mbar_arrive(bar0 + 8 * B_KG);
        });
        STAMP(1);
        {
            mbar_wait(bar0 + 8 * B_LN, 0);
            const uint32_t tag = lds32(sb + OFF_MISC);
            if (lane < 15) sts128(vrow - VT_PAD + lane * 16, 0, 0, 0, 0);
            const uint2* sp = g_stat + 256 * w + 16 * t + 2 * g;
            uint4 q[4];
#pragma unroll
            for (int n = 0; n < 4; n++) q[n] = make_uint4(0, tag + 1, 0, 0);
#pragma unroll 1
            for (uint32_t it = 0;; spin_guard(it)) {
                uint32_t bad = 0;
#pragma unroll
                for (int n = 0; n < 4; n++) ld_relaxed_128_unless(q[n], sp + 64 * n, ((q[n].y ^ tag) & 3) == 0);
#pragma unroll
                for (int n = 0; n < 4; n++) bad |= q[n].y ^ tag;
                if (__all_sync(0xffffffffu, (bad & 3) == 0)) break;
            }
            STAMP(2); GSTAMP(28);
            mbar_wait(bar0 + 8 * B_XT, 0);
            STAMP(8);
            const uint32_t xa = sb + OFF_XT + (w & 2) * 16384 + (w >> 2) * 16384 + (w & 1) * 1024 + (g >> 1) * 2048 + (g & 1) * 128 + t * 32 + ((h ^ (g & 1)) << 4);
            const uint32_t va = sb + OFF_VT + (2 * m + (r & 1)) * VT_PITCH + VT_PAD + (16 * w + (r >> 1)) * 32;
            uint4 x[8];
#pragma unroll
            for (int i = 0; i < 8; i++) x[i] = lds128(xa + (i & 1) * 8192 + (i >> 1) * 256);
#pragma unroll
            for (int i = 0; i < 8; i++) {
                const uint32_t s0 = (i & 1) ? q[i >> 1].z : q[i >> 1].x, s1 = (i & 1) ? q[i >> 1].w : q[i >> 1].y;
                stsm4t(va + (i >> 1) * 128 + (((i ^ (i >> 1)) & 1) << 4), normalize2(x[i].x, s0, s1), normalize2(x[i].y, s0, s1),
                       normalize2(x[i].z, s0, s1), normalize2(x[i].w, s0, s1));
            }
            named_sync(2, 256);
            if (tid == 128) mbar_arrive_peer(mapa(bar0 + 8 * B_SFREE, h ^ 1));
        }
        STAMP(3);
        float acc[16][4];
#pragma unroll
        for (int i = 0; i < 16; i++) { acc[i][0] = acc[i][1] = acc[i][2] = acc[i][3] = 0.f; }
        dense_phase(acc, vrow, tab, p.zero, lane);
        STAMP(4);
        const uint32_t so = sb + OFF_XT + (8 * h + w) * 1024 + ((lane ^ ((w & 1) << 1)) << 4);
        const uint32_t dst0 = mapa(so + 32768, 0), dst1 = mapa(so, 1), rb0 = mapa(bar0 + 8 * B_RECV, 0), rb1 = mapa(bar0 + 8 * B_RECV, 1);
        const uint32_t box = sb + OFF_XT + h * 32768 + w * 2048;
        const uint32_t fs = sb + OFF_XT + (h ^ 1) * 32768 + (2 * m + (r & 1)) * 1024 + (w >> 2) * 512 + (((8 * (w & 3) + (r & 4) + ((r >> 1) & 1)) ^ ((r & 1) << 1)) << 4);
        const uint32_t fx = box + (g >> 1) * 512 + (t >> 1) * 144 + (2 * (t & 1) + (g & 1)) * 32;
        const uint32_t tpo = tab + (g - 2 * t + 6) * 8;
        {
            const Boxes bx(vrow, p.zero, lane, -18, 5, 7, 0, 4);
            uint2 tp[10];
#pragma unroll
            for (int i = 0; i < 10; i++) tp[i] = lds64(tpo + T_R2 + (i / 5) * 384 + (i % 5) * 64);
            tail2<0, 4>(acc, bx, tp);
            mbar_wait(bar0 + 8 * B_SFREE, 0);
            emit<0>(acc, dst0, dst1, rb0, rb1);
            STAMP(5);
            tail2<4, 8>(acc, bx, tp);
            mbar_wait(bar0 + 8 * B_RECV, 0);
            finish(fs, fx);
            fence_async();
            __syncwarp();
            if (elect_one()) tma_store_tile(&maps.out, box, 16 * cl, 2 * w, 8 * h);
            STAMP(20);
            tail2<8, 12>(acc, bx, tp);
        }
        tail3(acc, Boxes(vrow, p.zero, lane, -20, 1, 7, 0, 8), tpo + T_R3);
        emit<1>(acc, dst0, dst1, rb0, rb1);
        STAMP(30);
        mbar_wait(bar0 + 8 * (B_RECV + 1), 0);
        STAMP(6);
        finish(fs + 16384, fx + 16384);
        const bool ready = mbar_test(bar0 + 8 * B_UPD, 0);
        const bool el = elect_one();
#pragma unroll 1
        for (int pass = 0; pass < 2; pass++) {
            if ((pass != 0) == ready) {
                fence_async();
                __syncwarp();
                if (el) tma_store_tile(&maps.out, box + 16384, 16 * cl, 2 * w, 16 + 8 * h);
            } else {
                if (el) asm volatile("cp.async.bulk.wait_group 0;" ::: "memory");
                __syncwarp();
                mbar_wait(bar0 + 8 * B_UPD, 0);
                const int tok = (int)lds32(sb + OFF_MISC + 16 + 4 * g);
                if (tok >= 0 && ((tok >> 1) & 7) == w) {
                    const uint32_t xa = box + (tok >> 10) * 16384 + ((tok >> 6) & 7) * 256 + (tok & 1) * 128 + ((tok >> 4) & 3) * 32 + (((t >> 1) ^ (tok & 1)) << 4) + (t & 1) * 8;
                    const uint2 o0 = lds64(xa);
                    const float4 up = lds128f(sb + OFF_RED + 16 * lane);
                    const uint2 o1 = make_uint2(badd2(o0.x, pack_bf16(up.x, up.y)), badd2(o0.y, pack_bf16(up.z, up.w)));
                    if (ready && tok >= 1024) sts64(xa, o1.x, o1.y);
                    else *reinterpret_cast<uint2*>(p.out + (size_t)tok * DM + 16 * cl + 4 * t) = o1;
                }
            }
        }
        if (el) asm volatile("cp.async.bulk.wait_group.read 0;" ::: "memory");
        STAMP(7);
    } else {
        const int a = warp;
        if (tid == 0) {
#pragma unroll
            for (int i = B_XT; i < NBAR; i++) mbar_init(bar0 + 8 * i, i == B_KG ? 8 : (i >= B_UPD && i < B_FULL) ? 4 : 1);
            asm volatile("fence.mbarrier_init.release.cluster;" ::: "memory");
            fence_async();
            mbar_expect_tx(bar0 + 8 * B_XT, 65536);
            mbar_expect_tx(bar0 + 8 * B_RECV, 16384);
            mbar_expect_tx(bar0 + 8 * B_RECV + 8, 16384);
            mbar_expect_tx(bar0 + 8 * B_RED, 512);
        }
        __syncwarp();
        cluster_arrive();
        const uint4 wq = ldg128(p.wr + 8 * tid);
        uint32_t epoch = 0;
        if (a == 0) epoch = ld_relaxed_32(&g_epoch);
        if (tid == 32) {
#pragma unroll
            for (int i = 0; i < 5; i++) asm volatile("prefetch.tensormap [%0];" ::"l"(&maps.u + i) : "memory");
        }
        if (has_gu && a == 1) st_relaxed_128(&g_h[b * 128 + 4 * lane], 0u, 0u, 0u, 0u);
        if (tid < 16) st_relaxed_64(g_stat + 16 * b + 2 * r + m, 0u, epoch);
        if (tid == 0) sts32(sb + OFF_MISC, epoch + 1u);
        const uint32_t wbuf = sb + OFF_LN + a * 1024, part = sb + OFF_LN + 4096;
        {
            sts128(wbuf + 16 * lane, wq.x, wq.y, wq.z, wq.w);
            sts128(wbuf + 512 + 16 * lane, 0x3f803f80u, 0x3f803f80u, 0x3f803f80u, 0x3f803f80u);
            float wsum = ((bf_lo(wq.x) + bf_hi(wq.x)) + (bf_lo(wq.y) + bf_hi(wq.y))) + ((bf_lo(wq.z) + bf_hi(wq.z)) + (bf_lo(wq.w) + bf_hi(wq.w)));
#pragma unroll
            for (int o = 16; o; o >>= 1) wsum += __shfl_xor_sync(0xffffffffu, wsum, o);
            if (lane < 16) sts32f(part + a * 256 + lane * 16 + 12, wsum);
            const uint32_t wa = wbuf + (r == 1 ? 0 : 512) + m * 16;
            const uint32_t ra = sb + OFF_VT + (8 * (m & 1) + r) * ROW_PITCH + 512 * a + (m >> 1) * 16;
            const uint32_t rz = sb + OFF_VT + (8 * (m >> 1) + r) * ROW_PITCH + 512 * a + (m & 1) * 16;
            float cs[4] = {0, 0, 0, 0}, q1[4] = {0, 0, 0, 0}, q2[4] = {0, 0, 0, 0};
            cluster_wait();
            STAMP(22);
#pragma unroll 1
            for (int j = 0; j < 4; j++) mbar_wait(bar0 + 8 * (B_ROW + j), 0);
            STAMP(23);
#pragma unroll 1
            for (int k4 = 0; k4 < 2; k4++) {
                uint32_t x[8][4], z[8][4], wf[4][4];
#pragma unroll
                for (int k = 0; k < 8; k++) {
                    ldsm4(x[k], ra + k4 * 256 + k * 32);
                    ldsm4(z[k], rz + k4 * 256 + k * 32);
                    if ((k & 1) == 0) ldsm4(wf[k >> 1], wa + k4 * 256 + k * 32);
                }
#pragma unroll
                for (int k = 0; k < 8; k++) {
                    mma_bf16(q1, x[k][0], x[k][1], x[k][2], x[k][3], z[k][0], z[k][1]);
                    mma_bf16(q2, x[k][0], x[k][1], x[k][2], x[k][3], z[k][2], z[k][3]);
                    mma_bf16(cs, x[k][0], x[k][1], x[k][2], x[k][3], wf[k >> 1][2 * (k & 1)], wf[k >> 1][2 * (k & 1) + 1]);
                }
            }
            const uint32_t pa = part + a * 256 + g * 16;
            if (t == 0) { sts64f(pa, cs[0], cs[1]); sts64f(pa + 128, cs[2], cs[3]); }
            if (t == (g >> 1)) { sts32f(pa + 8, (g & 1) ? q1[1] : q1[0]); sts32f(pa + 136, (g & 1) ? q2[3] : q2[2]); }
        }
        named_sync(1, 128);
        const uint32_t tag = lds32(sb + OFF_MISC);
        if (a == 0) {
            const uint32_t pa = part + (lane & 15) * 16;
            const float4 p0 = lds128f(pa), p1 = lds128f(pa + 256), p2 = lds128f(pa + 512), p3 = lds128f(pa + 768);
            const float mu = ((p0.x + p1.x) + (p2.x + p3.x)) * (1.f / DM);
            float var = ((p0.z + p1.z) + (p2.z + p3.z)) * (1.f / DM) - mu * mu;
            const bool centred = __any_sync(0xffffffffu, !(mu * mu <= 4.f * var));
            if (centred) var = centred_var(sb + OFF_VT, mu, lane);
            const float ri = rcpf(bf_round(sqrtaf(bf_round(bf_round(var) + 1e-5f))));
            const uint32_t s0 = pack_bf16(mu, ri), s1 = (pack_bf16(ri - bf_hi(s0), 0.f) & 0xfffcu) | (tag & 3);
            float sc = (((p0.y + p1.y) + (p2.y + p3.y)) - bf_lo(s0) * ((p0.w + p1.w) + (p2.w + p3.w))) * ri;
            if (centred) sc = centred_score(sb + OFF_VT, sb + OFF_LN, s0, s1, lane);
            if (lane < 16) st_relaxed_64(g_stat + 16 * b + 2 * r + m, s0, s1 | (order_key(pack_bf16(sc, 0.f)) << 16));
            fence_async();
            __syncwarp();
            if (elect_one()) mbar_arrive(bar0 + 8 * B_LN);
            STAMP(9); GSTAMP(25);
        }
        const uint32_t slot0 = sb + OFF_RING + a * 8192, slot2 = sb + OFF_PRIV + a * 16384 + 4096, fbar = bar0 + 8 * (B_FULL + a);
        if (has_gu) {
            uint4 xq[8];
            const uint4* xp = g_xs + 64 * a + lane;
            if (a == 1) {
                asm volatile("fence.acq_rel.gpu;" ::: "memory");
                __syncwarp();
                if (lane == 0) st_relaxed_32(&g_clr[b], tag);
            }
#pragma unroll 1
            for (uint32_t it = 0; ld_relaxed_32(&g_rdy) != tag; spin_guard(it)) { }
#pragma unroll 1
            for (uint32_t it = 0; ld_relaxed_32(&g_xs[64 * a].w) == 0; spin_guard(it)) { }
#pragma unroll 1
            for (uint32_t it = 0;; spin_guard(it)) {
#pragma unroll
                for (int j = 0; j < 8; j++) xq[j] = ld_relaxed_128(xp + (j >> 1) * 256 + (j & 1) * 32);
                const uint32_t mn = min(min(min(xq[0].w, xq[1].w), min(xq[2].w, xq[3].w)), min(min(xq[4].w, xq[5].w), min(xq[6].w, xq[7].w)));
                if (__all_sync(0xffffffffu, mn != 0u)) break;
            }
            STAMP(12);
            float gacc[4][4];
#pragma unroll
            for (int i = 0; i < 4; i++) { gacc[i][0] = gacc[i][1] = gacc[i][2] = gacc[i][3] = 0.f; }
            const uint32_t ko = (r + ((m >> 1) << 3)) * 64 + (((r >> 1) & 3) << 4);
#pragma unroll
            for (int c = 0; c < 4; c++) {
                mbar_wait(fbar + 32 * (c % 3), c / 3);
                const uint32_t rowa = (c == 2 ? slot2 + (m & 1) * 8192 : slot0 + (c == 1) * 32768 + (m & 1) * 4096) + ko;
                uint32_t af[16][4];
#pragma unroll
                for (int ks = 0; ks < 4; ks++)
#pragma unroll
                    for (int mt = 0; mt < 4; mt++) ldsm4t(af[4 * ks + mt], (rowa ^ (mt << 4)) + ks * 1024);
                __syncwarp();
                if (c < 3 && elect_one()) mbar_arrive(bar0 + 8 * (B_FREE + c) + (af[15][3] & p.zero));
#pragma unroll
                for (int ks = 0; ks < 4; ks++) {
                    const uint4 q = xq[2 * c + (ks >> 1)];
#pragma unroll
                    for (int mt = 0; mt < 4; mt++)
                        mma_bf16(gacc[mt], af[4 * ks + mt][0], af[4 * ks + mt][1], af[4 * ks + mt][2], af[4 * ks + mt][3],
                                 (ks & 1) ? q.z : q.x, (ks & 1) ? q.w : q.y);
                }
            }
            STAMP(13);
#pragma unroll
            for (int mt = 0; mt < 4; mt++) sts128f(slot0 + mt * 512 + lane * 16, gacc[mt]);
            named_sync(1, 128);
            const int tk = tid >> 4, tt = (tid >> 2) & 3;
            const uint32_t base = sb + OFF_RING + t * 512 + (8 * tt + (tk >> 1)) * 16 + (tk & 1) * 4;
            float hv[2];
#pragma unroll
            for (int e = 0; e < 2; e++) {
                float pg[4], pu[4];
#pragma unroll
                for (int wq = 0; wq < 4; wq++) { pg[wq] = lds32f(base + wq * 8192 + e * 64); pu[wq] = lds32f(base + wq * 8192 + e * 64 + 8); }
                const float gb = bf_round((pg[0] + pg[1]) + (pg[2] + pg[3]));
                hv[e] = bf_round(gb * rcpf(1.f + ex2f(-1.4426950408889634f * gb))) * bf_round((pu[0] + pu[1]) + (pu[2] + pu[3]));
            }
            const uint32_t hw = pack_bf16(hv[0], hv[1]);
            st_relaxed_32(&g_h[b * 128 + tid], hw ? hw : 0x80008000u);
            STAMP(14);
        }
        uint2 sel;
#pragma unroll 1
        for (uint32_t it = 0;; spin_guard(it)) {
            sel = ld_relaxed_64(g_sel + (tid >> 4));
            if (__all_sync(0xffffffffu, sel.y == tag)) break;
        }
        if ((tid & 15) == 0) {
            const int tok = 0xffff - (int)(sel.x & 0xffffu);
            sts32(sb + OFF_MISC + 16 + (tid >> 2), (((tok >> 9) & 1) == h) ? (uint32_t)tok : 0xffffffffu);
        }
        float dacc[4] = {0, 0, 0, 0};
        {
            const uint32_t* hp = &g_h[(56 * h + 14 * a) * 128];
            uint32_t hf = lane >= 14;
#pragma unroll 1
            for (uint32_t it = 0;; spin_guard(it)) {
                if (hf == 0) hf = ld_relaxed_32(hp + lane * 128 + 127);
                if (__all_sync(0xffffffffu, hf != 0)) break;
            }
            uint4 hq[14];
#pragma unroll 1
            for (uint32_t it = 0;; spin_guard(it)) {
                uint32_t mn = 0xffffffffu;
#pragma unroll
                for (int j = 0; j < 14; j++) hq[j] = ld_relaxed_128(hp + 4 * lane + j * 128);
#pragma unroll
                for (int j = 0; j < 14; j += 2) mn = min(mn, min(hq[j].w, hq[j + 1].w));
                if (__all_sync(0xffffffffu, mn != 0)) break;
            }
            STAMP(15);
            const uint32_t wo = (r + ((m >> 1) << 3)) * 32 + (((m & 1) ^ (r >> 2)) << 4);
            float dacc2[4] = {0, 0, 0, 0};
#pragma unroll
            for (int s = 0; s < 2; s++) {
                mbar_wait(fbar + 32 * (s + 1), has_gu);
                uint32_t af[14][4];
#pragma unroll
                for (int j = 0; j < 14; j++) ldsm4t(af[j], (s ? slot2 : slot0 + 32768) + wo + (j / 7) * (s ? 8192 : 4096) + (j % 7) * 512);
#pragma unroll
                for (int j = 0; j < 7; j++) {
                    const uint4 q = hq[7 * s + j];
                    mma_bf16(dacc, af[2 * j][0], af[2 * j][1], af[2 * j][2], af[2 * j][3], q.x, q.y);
                    mma_bf16(dacc2, af[2 * j + 1][0], af[2 * j + 1][1], af[2 * j + 1][2], af[2 * j + 1][3], q.z, q.w);
                }
            }
#pragma unroll
            for (int j = 0; j < 4; j++) dacc[j] += dacc2[j];
        }
        STAMP(16);
        {
            sts128f(slot0 + 4096 + lane * 16, dacc);
            named_sync(1, 128);
            const int tk = tid >> 4, col = tid & 15;
            const uint32_t base = sb + OFF_RING + 4096 + ((col & 7) * 4 + (tk >> 1)) * 16 + (((col >> 3) << 1) + (tk & 1)) * 4;
            const float y0 = (lds32f(base) + lds32f(base + 8192)) + (lds32f(base + 16384) + lds32f(base + 24576));
            const uint32_t red = sb + OFF_RED + 4 * tid;
            asm volatile("st.async.weak.shared::cluster.mbarrier::complete_tx::bytes.f32 [%0], %1, [%2];"
                         ::"r"(mapa(red, h ^ 1)), "f"(y0), "r"(mapa(bar0 + 8 * B_RED, h ^ 1)) : "memory");
            const float rv = __uint_as_float(unorder_key(sel.x >> 16) << 16);
            const float sg = bf_round(rcpf(1.f + ex2f(-1.4426950408889634f * rv)));
            mbar_wait(bar0 + 8 * B_RED, 0);
            sts32f(red, bf_round(y0 + lds32f(red)) * sg);
            __syncwarp();
            if (elect_one()) mbar_arrive(bar0 + 8 * B_UPD);
        }
        STAMP(17); GSTAMP(29);
    }
}

typedef CUresult (*EncodeFn)(CUtensorMap*, CUtensorMapDataType, cuuint32_t, void*, const cuuint64_t*, const cuuint64_t*,
                             const cuuint32_t*, const cuuint32_t*, CUtensorMapInterleave, CUtensorMapSwizzle,
                             CUtensorMapL2promotion, CUtensorMapFloatOOBfill);

void make_map(EncodeFn enc, CUtensorMap* m, const void* ptr, uint64_t cols, uint64_t rows, uint32_t bc, uint32_t br,
              CUtensorMapSwizzle sw, CUtensorMapL2promotion pr) {
    cuuint64_t dims[2] = {cols, rows};
    cuuint64_t str[1] = {cols * 2};
    cuuint32_t box[2] = {bc, br};
    cuuint32_t es[2] = {1, 1};
    enc(m, CU_TENSOR_MAP_DATA_TYPE_BFLOAT16, 2, const_cast<void*>(ptr), dims, str, box, es, CU_TENSOR_MAP_INTERLEAVE_NONE, sw, pr,
        CU_TENSOR_MAP_FLOAT_OOB_FILL_NONE);
}
void make_tile_map(EncodeFn enc, CUtensorMap* m, const void* ptr) {
    cuuint64_t dims[4] = {DM, 4, 16, SEQ / 64};
    cuuint64_t str[3] = {16 * DM * 2, DM * 2, 64 * DM * 2};
    cuuint32_t box[4] = {16, 4, 2, 8};
    cuuint32_t es[4] = {1, 1, 1, 1};
    enc(m, CU_TENSOR_MAP_DATA_TYPE_BFLOAT16, 4, const_cast<void*>(ptr), dims, str, box, es, CU_TENSOR_MAP_INTERLEAVE_NONE,
        CU_TENSOR_MAP_SWIZZLE_32B, CU_TENSOR_MAP_L2_PROMOTION_NONE, CU_TENSOR_MAP_FLOAT_OOB_FILL_NONE);
}

}

#define WD_PROMO CU_TENSOR_MAP_L2_PROMOTION_L2_128B
extern "C" void kernel_launch(void* const* d_in, const int* in_sizes, int n_in, void* d_out, int out_size) {
    (void)in_sizes; (void)n_in; (void)out_size;
    static EncodeFn enc = nullptr;
    if (!enc) {
        void* fn = nullptr;
        cudaDriverEntryPointQueryResult q;
        cudaGetDriverEntryPoint("cuTensorMapEncodeTiled", &fn, cudaEnableDefault, &q);
        enc = (EncodeFn)fn;
        cudaFuncSetAttribute(fused_kernel, cudaFuncAttributeMaxDynamicSharedMemorySize, SMEM_BYTES);
    }
    Maps maps;
    make_tile_map(enc, &maps.u, d_in[0]);
    make_tile_map(enc, &maps.out, d_out);
    make_map(enc, &maps.wg, d_in[9], FF, DM, 32, 64, CU_TENSOR_MAP_SWIZZLE_64B, CU_TENSOR_MAP_L2_PROMOTION_L2_128B);
    make_map(enc, &maps.wu, d_in[10], FF, DM, 32, 64, CU_TENSOR_MAP_SWIZZLE_64B, CU_TENSOR_MAP_L2_PROMOTION_L2_128B);
    make_map(enc, &maps.wd, d_in[11], DM, FF, 16, 112, CU_TENSOR_MAP_SWIZZLE_32B, WD_PROMO);
    Ptrs p;
    p.u = (const __nv_bfloat16*)d_in[0];
    p.logA = (const __nv_bfloat16*)d_in[1];
    p.Aim = (const __nv_bfloat16*)d_in[2];
    p.Cre = (const __nv_bfloat16*)d_in[3];
    p.Cim = (const __nv_bfloat16*)d_in[4];
    p.ldt = (const __nv_bfloat16*)d_in[5];
    p.dsk = (const __nv_bfloat16*)d_in[6];
    p.wr = (const __nv_bfloat16*)d_in[8];
    p.out = (__nv_bfloat16*)d_out;
    p.zero = 0;
    fused_kernel<<<NCTA + 2, NTHR, SMEM_BYTES, cudaStreamPerThread>>>(p, maps);
}
```

```cpp
#include <cuda_runtime.h>
#include <cuda_bf16.h>
#include <cuda_fp16.h>
#include <cuda.h>
#include <stdint.h>

namespace {

constexpr int SEQ = 2048, DM = 1024, NMODE = 128, FF = 3584;
constexpr int NCTA = 128, NTHR = 512;
constexpr int GU_CTAS = 112;

constexpr int OFF_XT = 0;
constexpr int OFF_RING = 65536;
constexpr int OFF_PRIV = OFF_RING + 65536;
constexpr int OFF_VT = OFF_PRIV + 65536;
constexpr int VT_PAD = 240, VT_PITCH = VT_PAD + 4096, ROW_PITCH = 2064;
constexpr int OFF_BAR = OFF_VT + 8 * VT_PITCH;
constexpr int OFF_MISC = OFF_BAR + 224;
constexpr int OFF_RED = OFF_MISC + 48;
constexpr int OFF_STAMP = OFF_RED + 512;
constexpr int SMEM_BYTES = OFF_STAMP + 256;
constexpr int OFF_LN = OFF_RING + 7 * 8192;
static_assert(SMEM_BYTES <= 232448, "shared memory");

constexpr int B_ROW = 0, B_XT = 4, B_LN = 5, B_KG = 6, B_SFREE = 7, B_RECV = 8, B_RED = 10, B_UPD = 11, B_FREE = 12, B_FULL = 15, NBAR = 27;

constexpr int T_DENSE = 0;
constexpr int T_PATCH = 2240;
constexpr int T_R2 = 2432;
constexpr int T_R3 = 3200;

constexpr uint32_t SPIN_LIMIT = 1u << 20;
#define KG_UNROLL 4
constexpr int kKgUnroll = KG_UNROLL;
#define WIN0 3
#define WIN1 4
#define WIN_SW 6

struct Ptrs {
    const __nv_bfloat16 *logA, *Aim, *Cre, *Cim, *ldt, *dsk, *u, *wr;
    __nv_bfloat16* out;
    uint32_t zero;
};
struct Maps {
    CUtensorMap u, out, wg, wu, wd;
};

__device__ unsigned int g_epoch;
__device__ unsigned int g_rdy;
__device__ __align__(16) unsigned int g_clr[GU_CTAS];
__device__ __align__(128) uint2 g_stat[SEQ];
__device__ __align__(128) uint2 g_sel[8];
__device__ __align__(128) uint4 g_xs[1024];
__device__ __align__(128) uint32_t g_h[GU_CTAS * 128];

#define STAMP(i) do { } while (0)
#define GSTAMP(i) do { } while (0)

__device__ __forceinline__ uint32_t s_u32(const void* p) { return (uint32_t)__cvta_generic_to_shared(p); }
__device__ __forceinline__ void mbar_init(uint32_t b, uint32_t n) {
    asm volatile("mbarrier.init.shared::cta.b64 [%0], %1;" ::"r"(b), "r"(n) : "memory");
}
__device__ __forceinline__ void mbar_expect_tx(uint32_t b, uint32_t bytes) {
    asm volatile("mbarrier.arrive.expect_tx.shared::cta.b64 _, [%0], %1;" ::"r"(b), "r"(bytes) : "memory");
}
__device__ __forceinline__ void mbar_arrive(uint32_t b) {
    asm volatile("mbarrier.arrive.shared::cta.b64 _, [%0];" ::"r"(b) : "memory");
}
__device__ __forceinline__ void mbar_arrive_peer(uint32_t b_cluster) {
    asm volatile("mbarrier.arrive.relaxed.cluster.shared::cluster.b64 _, [%0];" ::"r"(b_cluster) : "memory");
}
__device__ __forceinline__ void mbar_wait(uint32_t b, uint32_t parity) {
    asm volatile("{\n\t.reg .pred p;\n\t.reg .u32 c;\n\tmov.u32 c, 0;\n"
                 "W:\n\tmbarrier.try_wait.parity.shared::cta.b64 p, [%0], %1, 4000;\n\t@p bra D;\n\t"
                 "add.u32 c, c, 1;\n\tsetp.lt.u32 p, c, 1048576;\n\t@p bra W;\n\ttrap;\nD:\n\t}"
                 ::"r"(b), "r"(parity) : "memory");
}
__device__ __forceinline__ bool mbar_test(uint32_t b, uint32_t parity) {
    uint32_t ok;
    asm volatile("{ .reg .pred p; mbarrier.test_wait.parity.shared::cta.b64 p, [%1], %2; selp.u32 %0, 1, 0, p; }" : "=r"(ok) : "r"(b), "r"(parity) : "memory");
    return __all_sync(0xffffffffu, ok != 0);
}
__device__ __forceinline__ bool elect_one() {
    uint32_t p;
    asm volatile("{ .reg .pred P; elect.sync _|P, 0xffffffff; selp.u32 %0, 1, 0, P; }" : "=r"(p));
    return p != 0;
}
__device__ __forceinline__ uint32_t mapa(uint32_t a, uint32_t rank) {
    uint32_t r;
    asm("mapa.shared::cluster.u32 %0, %1, %2;" : "=r"(r) : "r"(a), "r"(rank));
    return r;
}
__device__ __forceinline__ void cluster_arrive() { asm volatile("barrier.cluster.arrive.relaxed.aligned;" ::: "memory"); }
__device__ __forceinline__ void cluster_wait() { asm volatile("barrier.cluster.wait.acquire.aligned;" ::: "memory"); }
__device__ __forceinline__ void tma_load_2d(uint32_t dst, const CUtensorMap* m, int c0, int c1, uint32_t bar) {
    asm volatile("cp.async.bulk.tensor.2d.shared::cluster.global.mbarrier::complete_tx::bytes [%0], [%1, {%3, %4}], [%2];"
                 ::"r"(dst), "l"(m), "r"(bar), "r"(c0), "r"(c1) : "memory");
}
__device__ __forceinline__ void tma_load_tile(uint32_t dst, const CUtensorMap* m, int c0, int c2, int c3, uint32_t bar) {
    asm volatile("cp.async.bulk.tensor.4d.shared::cluster.global.mbarrier::complete_tx::bytes.multicast::cluster [%0], [%1, {%3, %4, %5, %6}], [%2], %7;"
                 ::"r"(dst), "l"(m), "r"(bar), "r"(c0), "r"(0), "r"(c2), "r"(c3), "h"((uint16_t)3) : "memory");
}
__device__ __forceinline__ void tma_store_tile(const CUtensorMap* m, uint32_t src, int c0, int c2, int c3) {
    asm volatile("cp.async.bulk.tensor.4d.global.shared::cta.bulk_group [%0, {%2, %3, %4, %5}], [%1];"
                 ::"l"(m), "r"(src), "r"(c0), "r"(0), "r"(c2), "r"(c3) : "memory");
    asm volatile("cp.async.bulk.commit_group;" ::: "memory");
}
__device__ __forceinline__ void bulk_g2s(uint32_t dst, const void* src, uint32_t bytes, uint32_t bar) {
    asm volatile("cp.async.bulk.shared::cluster.global.mbarrier::complete_tx::bytes [%0], [%1], %2, [%3];"
                 ::"r"(dst), "l"(src), "r"(bytes), "r"(bar) : "memory");
}
__device__ __forceinline__ void st_async128(uint32_t dst_cluster, uint32_t x, uint32_t y, uint32_t z, uint32_t w, uint32_t bar_cluster) {
    asm volatile("st.async.weak.shared::cluster.mbarrier::complete_tx::bytes.v4.b32 [%0], {%1,%2,%3,%4}, [%5];"
                 ::"r"(dst_cluster), "r"(x), "r"(y), "r"(z), "r"(w), "r"(bar_cluster) : "memory");
}
__device__ __forceinline__ void fence_async() { asm volatile("fence.proxy.async.shared::cta;" ::: "memory"); }
__device__ __forceinline__ void named_sync(int id, int n) { asm volatile("bar.sync %0, %1;" ::"r"(id), "r"(n) : "memory"); }

__device__ __forceinline__ void ldsm4(uint32_t* r, uint32_t a) {
    asm volatile("ldmatrix.sync.aligned.m8n8.x4.shared.b16 {%0,%1,%2,%3}, [%4];"
                 : "=r"(r[0]), "=r"(r[1]), "=r"(r[2]), "=r"(r[3]) : "r"(a));
}
__device__ __forceinline__ void ldsm4t(uint32_t* r, uint32_t a) {
    asm volatile("ldmatrix.sync.aligned.m8n8.x4.trans.shared.b16 {%0,%1,%2,%3}, [%4];"
                 : "=r"(r[0]), "=r"(r[1]), "=r"(r[2]), "=r"(r[3]) : "r"(a));
}
__device__ __forceinline__ void stsm4t(uint32_t a, uint32_t x, uint32_t y, uint32_t z, uint32_t w) {
    asm volatile("stmatrix.sync.aligned.m8n8.x4.trans.shared.b16 [%0], {%1,%2,%3,%4};"
                 ::"r"(a), "r"(x), "r"(y), "r"(z), "r"(w) : "memory");
}
__device__ __forceinline__ uint32_t lds32(uint32_t a) { uint32_t v; asm volatile("ld.shared.u32 %0, [%1];" : "=r"(v) : "r"(a)); return v; }
__device__ __forceinline__ float lds32f(uint32_t a) { float v; asm volatile("ld.shared.f32 %0, [%1];" : "=f"(v) : "r"(a)); return v; }
__device__ __forceinline__ uint2 lds64(uint32_t a) { uint2 v; asm volatile("ld.shared.v2.u32 {%0,%1}, [%2];" : "=r"(v.x), "=r"(v.y) : "r"(a)); return v; }
__device__ __forceinline__ uint4 lds128(uint32_t a) {
    uint4 v; asm volatile("ld.shared.v4.u32 {%0,%1,%2,%3}, [%4];" : "=r"(v.x), "=r"(v.y), "=r"(v.z), "=r"(v.w) : "r"(a)); return v;
}
__device__ __forceinline__ float4 lds128f(uint32_t a) {
    float4 v; asm volatile("ld.shared.v4.f32 {%0,%1,%2,%3}, [%4];" : "=f"(v.x), "=f"(v.y), "=f"(v.z), "=f"(v.w) : "r"(a)); return v;
}
__device__ __forceinline__ void sts32(uint32_t a, uint32_t v) { asm volatile("st.shared.u32 [%0], %1;" ::"r"(a), "r"(v) : "memory"); }
__device__ __forceinline__ void sts32f(uint32_t a, float v) { asm volatile("st.shared.f32 [%0], %1;" ::"r"(a), "f"(v) : "memory"); }
__device__ __forceinline__ void sts64(uint32_t a, uint32_t x, uint32_t y) { asm volatile("st.shared.v2.u32 [%0], {%1,%2};" ::"r"(a), "r"(x), "r"(y) : "memory"); }
__device__ __forceinline__ void sts64f(uint32_t a, float x, float y) { asm volatile("st.shared.v2.f32 [%0], {%1,%2};" ::"r"(a), "f"(x), "f"(y) : "memory"); }
__device__ __forceinline__ void sts128(uint32_t a, uint32_t x, uint32_t y, uint32_t z, uint32_t w) {
    asm volatile("st.shared.v4.u32 [%0], {%1,%2,%3,%4};" ::"r"(a), "r"(x), "r"(y), "r"(z), "r"(w) : "memory");
}
__device__ __forceinline__ void sts128f(uint32_t a, const float* v) {
    asm volatile("st.shared.v4.f32 [%0], {%1,%2,%3,%4};" ::"r"(a), "f"(v[0]), "f"(v[1]), "f"(v[2]), "f"(v[3]) : "memory");
}
__device__ __forceinline__ uint4 ldg128(const void* p) {
    uint4 v; asm volatile("ld.global.nc.L1::no_allocate.v4.u32 {%0,%1,%2,%3}, [%4];" : "=r"(v.x), "=r"(v.y), "=r"(v.z), "=r"(v.w) : "l"(p)); return v;
}
__device__ __forceinline__ uint2 ldg64(const void* p) {
    uint2 v; asm volatile("ld.global.nc.L1::no_allocate.v2.u32 {%0,%1}, [%2];" : "=r"(v.x), "=r"(v.y) : "l"(p)); return v;
}
__device__ __forceinline__ uint32_t ldg32(const void* p) {
    uint32_t v; asm volatile("ld.global.nc.u32 %0, [%1];" : "=r"(v) : "l"(p)); return v;
}
__device__ __forceinline__ uint32_t ldg16(const void* p) {
    uint32_t v; asm volatile("ld.global.nc.u16 %0, [%1];" : "=r"(v) : "l"(p)); return v;
}
__device__ __forceinline__ uint4 ld_relaxed_128(const void* p) {
    uint4 v; asm volatile("ld.relaxed.gpu.global.v4.u32 {%0,%1,%2,%3}, [%4];" : "=r"(v.x), "=r"(v.y), "=r"(v.z), "=r"(v.w) : "l"(p) : "memory"); return v;
}
__device__ __forceinline__ void ld_relaxed_128_unless(uint4& q, const void* p, bool have) {
    asm volatile("{ .reg .pred p; setp.eq.u32 p, %5, 0; @p ld.relaxed.gpu.global.v4.u32 {%0,%1,%2,%3}, [%4]; }"
                 : "+r"(q.x), "+r"(q.y), "+r"(q.z), "+r"(q.w) : "l"(p), "r"((uint32_t)have) : "memory");
}
__device__ __forceinline__ uint2 ld_relaxed_64(const void* p) {
    uint2 v; asm volatile("ld.relaxed.gpu.global.v2.u32 {%0,%1}, [%2];" : "=r"(v.x), "=r"(v.y) : "l"(p) : "memory"); return v;
}
__device__ __forceinline__ uint32_t ld_relaxed_32(const void* p) {
    uint32_t v; asm volatile("ld.relaxed.gpu.global.u32 %0, [%1];" : "=r"(v) : "l"(p) : "memory"); return v;
}
__device__ __forceinline__ void st_relaxed_128(void* p, uint32_t x, uint32_t y, uint32_t z, uint32_t w) {
    asm volatile("st.relaxed.gpu.global.v4.u32 [%0], {%1,%2,%3,%4};" ::"l"(p), "r"(x), "r"(y), "r"(z), "r"(w) : "memory");
}
__device__ __forceinline__ void st_relaxed_64(void* p, uint32_t x, uint32_t y) {
    asm volatile("st.relaxed.gpu.global.v2.u32 [%0], {%1,%2};" ::"l"(p), "r"(x), "r"(y) : "memory");
}
__device__ __forceinline__ void st_relaxed_32(void* p, uint32_t v) {
    asm volatile("st.relaxed.gpu.global.u32 [%0], %1;" ::"l"(p), "r"(v) : "memory");
}
__device__ __forceinline__ void spin_guard(uint32_t& it) { if (++it > SPIN_LIMIT) __trap(); }
__device__ __forceinline__ void mma_bf16(float* c, uint32_t a0, uint32_t a1, uint32_t a2, uint32_t a3, uint32_t b0, uint32_t b1) {
    asm("mma.sync.aligned.m16n8k16.row.col.f32.bf16.bf16.f32 {%0,%1,%2,%3}, {%4,%5,%6,%7}, {%8,%9}, {%0,%1,%2,%3};"
                 : "+f"(c[0]), "+f"(c[1]), "+f"(c[2]), "+f"(c[3]) : "r"(a0), "r"(a1), "r"(a2), "r"(a3), "r"(b0), "r"(b1));
}
__device__ __forceinline__ void mma_bf16_k8(float* c, uint32_t a0, uint32_t a1, uint32_t b0) {
    asm("mma.sync.aligned.m16n8k8.row.col.f32.bf16.bf16.f32 {%0,%1,%2,%3}, {%4,%5}, {%6}, {%0,%1,%2,%3};"
                 : "+f"(c[0]), "+f"(c[1]), "+f"(c[2]), "+f"(c[3]) : "r"(a0), "r"(a1), "r"(b0));
}
__device__ __forceinline__ void mma_v(float* c, const uint32_t* a, uint32_t b0, uint32_t b1) {
    asm volatile("mma.sync.aligned.m16n8k16.row.col.f32.bf16.bf16.f32 {%0,%1,%2,%3}, {%4,%5,%6,%7}, {%8,%9}, {%0,%1,%2,%3};"
                 : "+f"(c[0]), "+f"(c[1]), "+f"(c[2]), "+f"(c[3]) : "r"(a[0]), "r"(a[1]), "r"(a[2]), "r"(a[3]), "r"(b0), "r"(b1));
}
__device__ __forceinline__ void mma_bf16_z(float* c, uint32_t a0, uint32_t a1, uint32_t a2, uint32_t a3, uint32_t b0, uint32_t b1) {
    asm volatile("mma.sync.aligned.m16n8k16.row.col.f32.bf16.bf16.f32 {%0,%1,%2,%3}, {%4,%5,%6,%7}, {%8,%9}, {%10,%10,%10,%10};"
        : "=f"(c[0]), "=f"(c[1]), "=f"(c[2]), "=f"(c[3]) : "r"(a0), "r"(a1), "r"(a2), "r"(a3), "r"(b0), "r"(b1), "f"(0.f));
}
__device__ __forceinline__ void mma_f16(float* c, uint32_t a0, uint32_t a1, uint32_t a2, uint32_t a3, uint32_t b0, uint32_t b1) {
    asm("mma.sync.aligned.m16n8k16.row.col.f32.f16.f16.f32 {%0,%1,%2,%3}, {%4,%5,%6,%7}, {%8,%9}, {%0,%1,%2,%3};"
                 : "+f"(c[0]), "+f"(c[1]), "+f"(c[2]), "+f"(c[3]) : "r"(a0), "r"(a1), "r"(a2), "r"(a3), "r"(b0), "r"(b1));
}
__device__ __forceinline__ uint32_t pack_bf16(float lo, float hi) {
    uint32_t r; asm("cvt.rn.bf16x2.f32 %0, %1, %2;" : "=r"(r) : "f"(hi), "f"(lo)); return r;
}
__device__ __forceinline__ uint32_t pack_v(float lo, float hi) {
    uint32_t r; asm volatile("cvt.rn.bf16x2.f32 %0, %1, %2;" : "=r"(r) : "f"(hi), "f"(lo)); return r;
}
__device__ __forceinline__ uint32_t pack_w(float lo, float hi) {
    uint32_t r; asm volatile("cvt.rn.satfinite.bf16x2.f32 %0, %1, %2;" : "=r"(r) : "f"(hi), "f"(lo)); return r;
}
__device__ __forceinline__ void pin(uint32_t& x) { asm volatile("" : "+r"(x)); }
__device__ __forceinline__ uint32_t pack_f16(float lo, float hi) {
    uint32_t r; asm("cvt.rn.f16x2.f32 %0, %1, %2;" : "=r"(r) : "f"(hi), "f"(lo)); return r;
}
__device__ __forceinline__ float bf_lo(uint32_t v) { return __uint_as_float(v << 16); }
__device__ __forceinline__ float bf_hi(uint32_t v) { return __uint_as_float(v & 0xffff0000u); }
__device__ __forceinline__ float bf_round(float x) { return __uint_as_float(pack_bf16(0.f, x)); }
__device__ __forceinline__ uint32_t badd2(uint32_t a, uint32_t b) { uint32_t r; asm("add.rn.bf16x2 %0, %1, %2;" : "=r"(r) : "r"(a), "r"(b)); return r; }
__device__ __forceinline__ uint32_t bmax2(uint32_t a, uint32_t b) { uint32_t r; asm("max.bf16x2 %0, %1, %2;" : "=r"(r) : "r"(a), "r"(b)); return r; }
__device__ __forceinline__ uint32_t normalize2(uint32_t x, uint32_t s0, uint32_t s1) {
    uint32_t r;
    asm("{ .reg .b16 m, h, l, k; .reg .b32 m2, h2, l2, d, t;\n\t"
        "mov.b32 {m, h}, %2; mov.b32 {l, k}, %3; mov.b32 m2, {m, m}; mov.b32 h2, {h, h}; mov.b32 l2, {l, l};\n\t"
        "sub.rn.bf16x2 d, %1, m2; mul.rn.bf16x2 t, d, l2; fma.rn.bf16x2 %0, d, h2, t; }" : "=r"(r) : "r"(x), "r"(s0), "r"(s1));
    return r;
}
__device__ __forceinline__ float rcpf(float x) { float r; asm("rcp.approx.ftz.f32 %0, %1;" : "=f"(r) : "f"(x)); return r; }
__device__ __forceinline__ float sqrtaf(float x) { float r; asm("sqrt.approx.ftz.f32 %0, %1;" : "=f"(r) : "f"(x)); return r; }
__device__ __forceinline__ float ex2f(float x) { float r; asm("ex2.approx.ftz.f32 %0, %1;" : "=f"(r) : "f"(x)); return r; }

__device__ __forceinline__ int tok_off(int t) { return (t >> 4) * 32 + ((((t >> 3) ^ (t >> 6)) & 1) << 4); }

__device__ __forceinline__ uint32_t order_key(uint32_t b16) { return b16 ^ ((b16 & 0x8000u) ? 0xffffu : 0x8000u); }
__device__ __forceinline__ uint32_t unorder_key(uint32_t k16) { return k16 ^ ((k16 & 0x8000u) ? 0x8000u : 0xffffu); }

struct cplx { float r, i; };
struct hc { uint32_t r, i; };
template <bool CONJ> __device__ __forceinline__ cplx csq(cplx a) {
    float im;
    asm("{ .reg .f32 t; mul.ftz.f32 t, %1, %2; mul.ftz.f32 %0, t, 0f40000000; }" : "=f"(im) : "f"(CONJ ? -a.r : a.r), "f"(a.i));
    return {fmaf(a.r, a.r, -(a.i * a.i)), im};
}
__device__ __forceinline__ cplx cexpp(float a2, float ai) {
    float m = ex2f(a2), s, c;
    __sincosf(ai, &s, &c);
    return {m * c, m * s};
}
__device__ __forceinline__ __half2 as_h2(uint32_t x) { return *reinterpret_cast<__half2*>(&x); }
__device__ __forceinline__ uint32_t as_u(__half2 x) { return *reinterpret_cast<uint32_t*>(&x); }
__device__ __forceinline__ hc hmul(hc a, hc b) {
    return {as_u(__hfma2(__hneg2(as_h2(a.i)), as_h2(b.i), __hmul2(as_h2(a.r), as_h2(b.r)))),
            as_u(__hfma2(as_h2(a.i), as_h2(b.r), __hmul2(as_h2(a.r), as_h2(b.i))))};
}
__device__ __forceinline__ hc hpack(cplx a, cplx b) { return {pack_f16(a.r, b.r), pack_f16(a.i, b.i)}; }
__device__ __forceinline__ void sts16(uint32_t a, uint32_t v) { asm volatile("st.shared.u16 [%0], %1;" ::"r"(a), "r"(v) : "memory"); }

template <class Hook>
__device__ __forceinline__ void kgen(uint32_t tab, int lane, uint2 la, uint2 aim, uint2 cre, uint2 cim, float dt, float skip, int dch, Hook main_done) {
    const int g = lane >> 2, t = lane & 3;
    const float dt2 = 2.f * dt;
    const uint32_t am = bmax2(bmax2(cre.x & 0x7fff7fffu, cre.y & 0x7fff7fffu), bmax2(cim.x & 0x7fff7fffu, cim.y & 0x7fff7fffu));
    const float mx = dt2 * fmaxf(bf_lo(am), bf_hi(am));
    const uint32_t eb = min(max(__reduce_max_sync(0xffffffffu, __float_as_uint(mx)) >> 23, 1u), 252u);
    const float cscale = dt2 * __uint_as_float((253u - eb) << 23);
    const float scale_inv = __uint_as_float((eb + 1u) << 23);
    float k0 = (bf_lo(cre.x) + bf_hi(cre.x)) + (bf_lo(cre.y) + bf_hi(cre.y));
#pragma unroll
    for (int o = 16; o; o >>= 1) k0 += __shfl_xor_sync(0xffffffffu, k0, o);
    const float ndt = -1.4426950408889634f * dt;

    float acc[5][4];
#pragma unroll
    for (int i = 0; i < 5; i++) { acc[i][0] = acc[i][1] = acc[i][2] = acc[i][3] = 0.f; }

    const uint32_t rec = tab + t * 512, sw = (uint32_t)t << 5;
    const uint32_t ad_l = rec + (((uint32_t)g << 4) ^ sw), ad_h = rec + 128 + (((uint32_t)g << 3) ^ sw);
    const uint32_t ad_2 = rec + (0xc0u ^ sw) + ((g & 1) << 3), ad_3 = rec + (0xd0u ^ sw) + ((g & 2) << 2);
    const uint32_t ad_4 = rec + (0xe0u ^ sw) + ((g & 4) << 1), ad_z = rec + (0xf0u ^ sw);
    const uint32_t wrec = tab + lane * 256 + ((lane & 7) << 4);

#pragma unroll 1
    for (int bb = 0; bb < 2; bb++) {
        cplx z[2][11], cz[2];
#pragma unroll
        for (int e = 0; e < 2; e++) {
            const float lg = e ? bf_hi(la.x) : bf_lo(la.x), ai = (e ? bf_hi(aim.x) : bf_lo(aim.x)) * dt;
            const float cr = (e ? bf_hi(cre.x) : bf_lo(cre.x)) * cscale, ci = (e ? bf_hi(cim.x) : bf_lo(cim.x)) * cscale;
            const float a2 = bf_round(ex2f(lg * 1.4426950408889634f)) * ndt;
            z[e][0] = cexpp(a2, ai);
            z[e][5] = cexpp(a2 * 32.f, ai * -32.f);
#pragma unroll
            for (int i = 1; i < 11; i++) if (i != 5) z[e][i] = (i == 3 || i == 7) ? csq<true>(z[e][i - 1]) : csq<false>(z[e][i - 1]);
            cz[e] = {fmaf(cr, z[e][0].r, -(ci * z[e][0].i)), fmaf(cr, z[e][0].i, ci * z[e][0].r)};
        }
        la.x = la.y; aim.x = aim.y; cre.x = cre.y; cim.x = cim.y;
        const hc z1 = hpack(z[0][0], z[1][0]), z2 = hpack(z[0][1], z[1][1]), z4 = hpack(z[0][2], z[1][2]);
        hc L[8], H[8];
        L[1] = hpack(z[0][3], z[1][3]); L[2] = hpack(z[0][4], z[1][4]); L[4] = hpack(z[0][5], z[1][5]);
        const hc y64 = hpack(z[0][6], z[1][6]), z128 = hpack(z[0][7], z[1][7]), z256 = hpack(z[0][8], z[1][8]);
        const hc z512 = hpack(z[0][9], z[1][9]), z1024 = hpack(z[0][10], z[1][10]);
        H[0] = hpack(cz[0], cz[1]);
        H[1] = hmul(H[0], z1); H[2] = hmul(H[0], z2); H[3] = hmul(H[1], z2);
        L[3] = hmul(L[1], L[2]);
#pragma unroll
        for (int i = 0; i < 4; i++) { H[4 + i] = hmul(H[i], z4); if (i) L[4 + i] = hmul(L[i], L[4]); }
        __syncwarp();
        sts128(wrec, 0x3c003c00u, y64.r, 0u, y64.i);
#pragma unroll
        for (int i = 1; i < 8; i++) { const hc q = hmul(L[i], y64); sts128(wrec ^ (i << 4), L[i].r, q.r, L[i].i, q.i); }
#pragma unroll
        for (int i = 0; i < 4; i++) sts128((wrec ^ (i << 4)) + 128, H[2 * i].r, H[2 * i].i, H[2 * i + 1].r, H[2 * i + 1].i);
        {
            const hc a = hmul(z256, z1), b = hmul(z256, z128), c = hmul(z256, z2), d = hmul(z512, z4);
            sts128((wrec ^ 0x40) + 128, a.r, a.i, b.r, b.i);
            sts128((wrec ^ 0x50) + 128, c.r, c.i, z512.r, z512.i);
            sts128((wrec ^ 0x60) + 128, d.r, d.i, z1024.r, z1024.i);
            sts64((wrec ^ 0x70) + 128, z128.r, z128.i);
        }
        __syncwarp();
#pragma unroll kKgUnroll
        for (int k2 = 0; k2 < 4; k2++) {
#pragma unroll
            for (uint32_t s = 0; s < 2; s++) {
                const uint32_t o = k2 * 2048 + s * 256, x = s << 4;
                const uint4 l = lds128((ad_l ^ x) + o);
                const uint2 h0 = lds64((ad_h ^ x) + o), m2 = lds64((ad_2 ^ x) + o), m3 = lds64((ad_3 ^ x) + o);
                const uint2 m4 = lds64((ad_4 ^ x) + o), mz = lds64((ad_z ^ x) + o);
                const hc H0 = {h0.x, h0.y};
                const hc H1 = hmul(H0, {mz.x, mz.y}), H2 = hmul(H0, {m2.x, m2.y}), H3 = hmul(H2, {m3.x, m3.y}), H4 = hmul(H3, {m4.x, m4.y});
                mma_f16(acc[0], l.x, l.y, l.z, l.w, H0.r, H0.i);
                mma_f16(acc[1], l.x, l.y, l.z, l.w, H1.r, H1.i);
                mma_f16(acc[2], l.x, l.y, l.z, l.w, H2.r, H2.i);
                mma_f16(acc[3], l.x, l.y, l.z, l.w, H3.r, H3.i);
                mma_f16(acc[4], l.x, l.y, l.z, l.w, H4.r, H4.i);
            }
        }
    }
    __syncwarp();
    main_done();
#pragma unroll
    for (int i = 0; i < 4; i++) sts128(tab + 2048 + 512 * i + 16 * lane, 0, 0, 0, 0);
    sts32(tab + 4 * lane, 0);
    __syncwarp();
    const uint32_t d0 = tab + T_DENSE + 4 * 17 + 8 * lane;
    const uint32_t d2a = d0 + 4 * 257 - 4 * (lane & 1), d2b = d0 + 4 * 258 + 2 + 4 * (lane & 1);
    const uint32_t d3 = tab + T_R2 + (g & 1) * 384 + (6 + 16 * (t & 1) + (g >> 1)) * 8 + (t >> 1) * 4;
    const uint32_t d4 = tab + T_R3 + (6 + 16 * t + (g >> 1)) * 8 + (g & 1) * 4;
    uint32_t last[3];
#pragma unroll
    for (int hf = 0; hf < 2; hf++) {
#pragma unroll
        for (int G = 0; G < 2; G++) {
            const uint32_t pk = pack_bf16(acc[G][2 * hf + 1] * scale_inv, acc[G][2 * hf] * scale_inv), a = d0 + 512 * G + 256 * hf;
            sts32(a + 4, pk);
            sts16(a + 10, pk);
            sts16(a, pk >> 16);
            last[0] = pk;
        }
#pragma unroll
        for (int e = 0; e < 2; e++) {
            const float v2 = acc[2][2 * hf + e] * scale_inv, v3 = acc[3][2 * hf + e] * scale_inv, v4 = acc[4][2 * hf + e] * scale_inv;
            const uint32_t p2 = pack_bf16(v2, v2), p3 = pack_bf16(v3, v3), p4 = pack_bf16(v4, v4), o = 256 * hf + 512 * e;
            sts16(d2a + o, p2);
            sts16(d2b + o, p2);
            if (lane & 1) sts64(d2a + o + 4, p2, p2);
            sts16(d3 + 32 * hf + 64 * e, p3);
            sts16(d3 + 32 * hf + 64 * e + 10, p3);
            sts16(d4 + 32 * hf + 64 * e, p4);
            sts16(d4 + 32 * hf + 64 * e + 10, p4);
            last[1] = p2; last[2] = p3;
        }
    }
    if (lane == 31) {
        const uint32_t p0 = pack_bf16(fmaf(k0, dt2, skip), 0.f), d = tab + T_DENSE + 4 * 16;
        sts16(d, p0); sts16(d + 6, p0);
        sts16(d + 4 * 257, last[0]); sts16(d + 4 * 258 + 2, last[0]);
        sts16(d + 4 * 514, last[1]); sts16(d + 4 * 515 + 2, last[1]);
        sts16(tab + T_PATCH + 4 * 17, last[2]); sts32(tab + T_PATCH + 4 * 18, last[2]); sts16(tab + T_PATCH + 4 * 19 + 2, last[2]);
    }
    __syncwarp();
}

__device__ __forceinline__ void load_toep(uint32_t* a, uint32_t p, uint32_t zero) {
    a[0] = lds32(p); a[1] = lds32(p + 32); a[2] = lds32(p - 32); a[3] = lds32(p + zero);
}
__device__ __forceinline__ uint32_t dense_row(uint32_t vrow, int lane, int rho) {
    const int lam = 8 * (lane >> 4) - rho + (lane & 7);
    return vrow + lam * 32 + ((((lane >> 3) ^ (lam >> 2)) & 1) << 4);
}
__device__ __forceinline__ void dense_phase(float (&acc)[16][4], uint32_t vrow, uint32_t pb, uint32_t (&A0)[4], uint32_t zero, int lane) {
    uint32_t R[32];
    const uint32_t va0 = dense_row(vrow, lane, 0);
#pragma unroll
    for (int i = 0; i < 8; i++) ldsm4(&R[4 * ((i + 7) & 7)], va0 + ((i + 7) & 7) * 512);
#pragma unroll 1
    for (int rho = 0; rho < 8; rho++) {
        uint32_t A1[4], A2[4], A3[4];
        if (rho <= 1) {
            load_toep(A1, pb + 2048, zero);
            load_toep(A2, pb + (T_PATCH - T_DENSE - 8), zero);
#pragma unroll
            for (int nu = 4; nu < 16; nu++) mma_v(acc[nu], A1, R[2 * (nu - 4)], R[2 * (nu - 4) + 1]);
#pragma unroll
            for (int nu = 8; nu < 16; nu++) mma_v(acc[nu], A2, R[2 * (nu - 8)], R[2 * (nu - 8) + 1]);
        }
        load_toep(A1, pb + 512, zero);
#pragma unroll
        for (int i = 0; i < 16; i++) {
            const int nu = i < 8 ? i : i < 12 ? i + 4 : i - 4;
            mma_v(acc[nu], A0, R[2 * nu], R[2 * nu + 1]);
        }
        load_toep(A2, pb + 1024, zero);
        const uint32_t va = dense_row(vrow, lane, rho + 1);
#pragma unroll
        for (int nu = 1; nu < 16; nu++) mma_v(acc[nu], A1, R[2 * (nu - 1)], R[2 * (nu - 1) + 1]);
        load_toep(A3, pb + 1536, zero);
        ldsm4(&R[28], va + 7 * 512);
#pragma unroll
        for (int nu = 2; nu < 16; nu++) mma_v(acc[nu], A2, R[2 * (nu - 2)], R[2 * (nu - 2) + 1]);
        pb += 64;
        load_toep(A0, pb, zero);
#pragma unroll
        for (int i = 0; i < 13; i++) {
            const int k = i < 8 ? i : i == 8 ? 12 : i - 1;
            mma_v(acc[k + 3], A3, R[2 * k], R[2 * k + 1]);
            if ((k & 1) || k == 12) ldsm4(&R[4 * (k >> 1)], va + (k >> 1) * 512);
        }
    }
}
__device__ __forceinline__ uint32_t ones2(int c, int lo, int hi) {
    return (((uint32_t)(c - lo) <= (uint32_t)(hi - lo)) ? 0x3f80u : 0u) | (((uint32_t)(c + 1 - lo) <= (uint32_t)(hi - lo)) ? 0x3f800000u : 0u);
}
struct Boxes {
    uint32_t q[4], ha[4];
    __device__ __forceinline__ Boxes(uint32_t vrow, int lane, int O, int L1, int H1, int L2, int H2) {
        const int g = lane >> 2, t = lane & 3, d = 2 * t - g;
        q[0] = ones2(d, L1, H1); q[1] = ones2(d, L2, H2); q[2] = ones2(d + 8, L1, H1); q[3] = ones2(d + 8, L2, H2);
#pragma unroll
        for (int i = 0; i < 4; i++) {
            const int T = 16 * g + O + 8 * i + 2 * t;
            ha[i] = vrow + tok_off(T & ~7) + (T & 7) * 2;
            pin(q[i]); pin(ha[i]);
        }
    }
    __device__ __forceinline__ void load(int j, uint32_t* v, uint32_t zero) const {
        const uint32_t o = j * 256;
        v[0] = lds32(ha[0] + o); v[1] = lds32(ha[1] + zero + o); v[2] = lds32(ha[1] + o);
        v[3] = lds32(ha[2] + zero + o); v[4] = lds32(ha[2] + o); v[5] = lds32(ha[3] + o);
    }
    __device__ __forceinline__ void sums(const uint32_t* v, float* Z, float* X, float* Y) const {
        mma_bf16_z(Z, q[0], q[1], q[2], q[3], v[0], v[1]);
        mma_bf16_z(X, q[0], q[1], q[2], q[3], v[2], v[3]);
        mma_bf16_z(Y, q[0], q[1], q[2], q[3], v[4], v[5]);
    }
};
template <class After>
__device__ __forceinline__ void tail_phase(float (&acc)[16][4], const Boxes& b2, const Boxes& b3, uint32_t tpo, uint32_t zero, After after) {
    uint2 tp[10];
    uint32_t v[6], a0[4], a1[4];
    float Z[4], X[4], Y[4];
    b2.load(0, v, zero);
#pragma unroll
    for (int i = 0; i < 10; i++) tp[i] = lds64(tpo + T_R2 + (i / 5) * 384 + (i % 5) * 64);
#pragma unroll
    for (int j = -1; j < 20; j++) {
        if (j < 19) {
            (j < 11 ? b2 : b3).sums(v, Z, X, Y);
            if (j < 10) b2.load(j + 2, v, zero); else if (j < 18) b3.load(j - 10, v, zero);
        }
        if (j >= 0 && j < 12) {
#pragma unroll
            for (int b = 0; b < 5; b++) if (j + 4 + b < 16) mma_v(acc[j + 4 + b], a1, tp[5 + b].x, tp[5 + b].y);
        }
        if (j < 11) { a1[0] = pack_v(Z[0], Z[1]); a1[1] = pack_w(X[0], X[1]); a1[2] = pack_v(Z[2], Z[3]); a1[3] = pack_w(X[2], X[3]); }
        if (j >= 0 && j < 12) {
#pragma unroll
            for (int b = 0; b < 5; b++) if (j + 4 + b < 16) mma_v(acc[j + 4 + b], a0, tp[b].x, tp[b].y);
            if (j >= 7 && j < 11) { tp[11 - j] = lds64(tpo + T_R3 + 64 * (10 - j)); tp[16 - j] = lds64(tpo + T_R3 + 64 * (14 - j)); }
        } else if (j >= 12) {
#pragma unroll
            for (int b = 0; b < 8; b++) if (j - 4 + b < 16) mma_v(acc[j - 4 + b], a0, tp[b < 4 ? b + 1 : b + 2].x, tp[b < 4 ? b + 1 : b + 2].y);
        }
        if (j < 11) { a0[0] = pack_v(X[0], X[1]); a0[1] = pack_v(Y[0], Y[1]); a0[2] = pack_v(X[2], X[3]); a0[3] = pack_v(Y[2], Y[3]); }
        else if (j < 19) { a0[0] = pack_v(X[0], X[1]); a0[1] = pack_v(Y[0], Y[1]); a0[2] = pack_v(Z[2], Z[3]); a0[3] = pack_v(X[2], X[3]); }
        after(j);
    }
}
template <int G>
__device__ __forceinline__ void emit(const float (&acc)[16][4], uint32_t dst0, uint32_t dst1, uint32_t bar0, uint32_t bar1) {
#pragma unroll
    for (int o = 0; o < 2; o++)
#pragma unroll
        for (int hf = 0; hf < 2; hf++) {
            const int n = 8 * G + 4 * o;
            st_async128((o ? dst1 : dst0) + G * 16384 + hf * 512, pack_bf16(acc[n][2 * hf], acc[n][2 * hf + 1]), pack_bf16(acc[n + 1][2 * hf], acc[n + 1][2 * hf + 1]),
                        pack_bf16(acc[n + 2][2 * hf], acc[n + 2][2 * hf + 1]), pack_bf16(acc[n + 3][2 * hf], acc[n + 3][2 * hf + 1]), (o ? bar1 : bar0) + 8 * G);
        }
}
__device__ __forceinline__ void finish(uint32_t src, uint32_t xa) {
    uint32_t s[4][4];
    uint4 x[4];
#pragma unroll
    for (int i = 0; i < 4; i++) {
        ldsm4t(s[i], (src ^ ((i & 1) << 5)) + (i >> 1) * 8192);
        x[i] = lds128((xa ^ ((i >> 1) << 4)) + (i & 1) * 256);
    }
#pragma unroll
    for (int i = 0; i < 4; i++)
        sts128((xa ^ ((i >> 1) << 4)) + (i & 1) * 256, badd2(x[i].x, s[i][0]), badd2(x[i].y, s[i][1]), badd2(x[i].z, s[i][2]), badd2(x[i].w, s[i][3]));
}

__device__ __noinline__ float centred_var(uint32_t rows, float mu, int lane) {
    float var = 0.f;
#pragma unroll 1
    for (int rr = 0; rr < 16; rr++) {
        const float c0 = __shfl_sync(0xffffffffu, mu, rr);
        float c = 0.f;
#pragma unroll 1
        for (int k = 0; k < 16; k++) {
            const uint32_t q = lds32(rows + rr * ROW_PITCH + k * 128 + lane * 4);
            const float d0 = bf_lo(q) - c0, d1 = bf_hi(q) - c0;
            c = fmaf(d0, d0, fmaf(d1, d1, c));
        }
#pragma unroll 1
        for (int o = 16; o; o >>= 1) c += __shfl_xor_sync(0xffffffffu, c, o);
        if ((lane & 15) == rr) var = c * (1.f / DM);
    }
    return var;
}
__device__ __noinline__ float centred_score(uint32_t rows, uint32_t wbuf, uint32_t s0, uint32_t s1, int lane) {
    float sc = 0.f;
#pragma unroll 1
    for (int rr = 0; rr < 16; rr++) {
        const uint32_t t0 = __shfl_sync(0xffffffffu, s0, rr), t1 = __shfl_sync(0xffffffffu, s1, rr);
        float c = 0.f;
#pragma unroll 1
        for (int k = 0; k < 16; k++) {
            const uint32_t xn = normalize2(lds32(rows + rr * ROW_PITCH + k * 128 + lane * 4), t0, t1);
            const uint32_t wq = lds32(wbuf + (k >> 2) * 1024 + (k & 3) * 128 + lane * 4);
            c = fmaf(bf_lo(xn), bf_lo(wq), fmaf(bf_hi(xn), bf_hi(wq), c));
        }
#pragma unroll 1
        for (int o = 16; o; o >>= 1) c += __shfl_xor_sync(0xffffffffu, c, o);
        if ((lane & 15) == rr) sc = c;
    }
    return sc;
}

__device__ __noinline__ void router_cta(const __nv_bfloat16* u, uint32_t sb, int tid) {
    const int lane = tid & 31, warp = tid >> 5;
    const uint32_t misc = sb, sel = sb + 64, cand = sb + 256, cst = cand + 8192 + 64;
    const uint32_t epoch = ld_relaxed_32(&g_epoch);
#pragma unroll
    for (int i = 0; i < 4; i++) st_relaxed_128(&g_xs[tid + 256 * i], 0u, 0u, 0u, 0u);
    if (tid < 8) st_relaxed_64(g_sel + tid, 0u, epoch);
    if (tid == 0) sts32(misc + 32, 0);
#pragma unroll
    for (int i = 0; i < 2; i++) sts128(cand + 16 * tid + 4096 * i, 0, 0, 0, 0);
    if (tid < 4) sts128(cand + 8192 + 16 * tid, 0, 0, 0, 0);
    asm volatile("fence.acq_rel.gpu;" ::: "memory");
    const uint32_t tag = epoch + 1u;
    named_sync(1, 256);
    if (tid == 0) st_relaxed_32(&g_rdy, tag);
    STAMP(0); GSTAMP(24);
    uint4 q[4];
#pragma unroll
    for (int j = 0; j < 4; j++) q[j] = make_uint4(0, epoch, 0, 0);
#pragma unroll 1
    for (uint32_t it = 0;; spin_guard(it)) {
        uint32_t bad = 0;
#pragma unroll
        for (int j = 0; j < 4; j++) ld_relaxed_128_unless(q[j], g_stat + 2 * (256 * j + tid), ((q[j].y ^ tag) & 3) == 0);
#pragma unroll
        for (int j = 0; j < 4; j++) bad |= q[j].y ^ tag;
        if (__all_sync(0xffffffffu, (bad & 3) == 0)) break;
    }
    uint32_t key[8], mx = 0;
#pragma unroll
    for (int j = 0; j < 4; j++) {
        const uint32_t inv = 0xffffu - (512 * j + 16 * (tid >> 3) + (tid & 7));
        key[2 * j] = (q[j].y & 0xffff0000u) | inv;
        key[2 * j + 1] = (q[j].w & 0xffff0000u) | (inv - 8);
        mx = max(mx, max(key[2 * j], key[2 * j + 1]));
    }
    const uint32_t gm = __reduce_max_sync(0xffffffffu, mx);
    if (lane == 0) sts32(misc + 4 * warp, gm);
    STAMP(10); GSTAMP(26);
    named_sync(1, 256);
    if (tid == 0) st_relaxed_32(&g_epoch, tag);
    const uint4 t0 = lds128(misc), t1 = lds128(misc + 16);
    const uint32_t tau = min(min(min(t0.x, t0.y), min(t0.z, t0.w)), min(min(t1.x, t1.y), min(t1.z, t1.w)));
    if (mx >= tau) {
#pragma unroll
        for (int j = 0; j < 8; j++)
            if (key[j] >= tau) {
                uint32_t pos;
                asm volatile("atom.shared.add.u32 %0, [%1], 1;" : "=r"(pos) : "r"(misc + 32) : "memory");
                sts32(cand + 4 * pos, key[j]);
                sts64(cst + 8 * pos, (j & 1) ? q[j >> 1].z : q[j >> 1].x, (j & 1) ? q[j >> 1].w : q[j >> 1].y);
            }
    }
    named_sync(1, 256);
    const int n = (int)lds32(misc + 32);
#pragma unroll 1
    for (int i = lane; i < n; i += 32) {
        const uint32_t k = lds32(cand + 4 * i);
        const uint2 st = lds64(cst + 8 * i);
        int rk = 0;
#pragma unroll 1
        for (int j = 0; j < n; j += 16) {
#pragma unroll
            for (int jj = 0; jj < 4; jj++) {
                const uint4 c = lds128(cand + 4 * j + 16 * jj);
                rk += (c.x > k) + (c.y > k) + (c.z > k) + (c.w > k);
            }
        }
        if (rk < 8) sts128(sel + 16 * rk, k, st.x, st.y, 0);
    }
    __syncwarp();
    STAMP(11);
    const uint4 s = lds128(sel + 16 * (lane >> 2));
    const __nv_bfloat16* src = u + (size_t)(0xffffu - (s.x & 0xffffu)) * DM + 128 * warp + 2 * (lane & 3);
    uint32_t w[16];
#pragma unroll
    for (int j = 0; j < 16; j++) w[j] = ldg32(src + 8 * j);
#pragma unroll
    for (int j = 0; j < 16; j++) w[j] = normalize2(w[j], s.y, s.z);
#pragma unroll
    for (int j = 0; j < 4; j++)
        st_relaxed_128(&g_xs[128 * warp + 32 * j + lane], w[4 * j], w[4 * j + 1], w[4 * j + 2], w[4 * j + 3] ? w[4 * j + 3] : 0x80008000u);
    STAMP(12); GSTAMP(29);
    if (warp == 0) {
#pragma unroll 1
        for (uint32_t it = 0;; spin_guard(it)) {
            const uint4 c = lane < GU_CTAS / 4 ? ld_relaxed_128(&g_clr[4 * lane]) : make_uint4(tag, tag, tag, tag);
            if (__all_sync(0xffffffffu, c.x == tag && c.y == tag && c.z == tag && c.w == tag)) break;
        }
        if ((lane & 3) == 0) st_relaxed_64(g_sel + (lane >> 2), s.x, tag);
    }
}

__global__ void __cluster_dims__(2, 1, 1) __launch_bounds__(NTHR, 1)
fused_kernel(const __grid_constant__ Ptrs p, const __grid_constant__ Maps maps) {
    extern __shared__ __align__(1024) unsigned char smem[];
    const int tid = threadIdx.x, lane = tid & 31, b = blockIdx.x;
    const int dch = (8 * b + (tid >> 5) - 4) & (DM - 1);
    uint2 la, aim, cre, cim;
    uint32_t ldt16, dsk16;
    if ((uint32_t)(tid - 128) < 256u) {
        la = ldg64(p.logA + dch * NMODE + 4 * lane); aim = ldg64(p.Aim + dch * NMODE + 4 * lane);
        cre = ldg64(p.Cre + dch * NMODE + 4 * lane); cim = ldg64(p.Cim + dch * NMODE + 4 * lane);
        ldt16 = ldg16(p.ldt + dch); dsk16 = ldg16(p.dsk + dch);
    }
    const uint32_t sb = s_u32(smem);
    const int warp = __shfl_sync(0xffffffffu, tid >> 5, 0);
    const int h = b & 1, cl = b >> 1;
    const uint32_t bar0 = sb + OFF_BAR;
    const int m = lane >> 3, r = lane & 7, g = lane >> 2, t = lane & 3;
    const bool has_gu = b < GU_CTAS;
    if (b >= NCTA) {
        if (b == NCTA && tid < 256) router_cta(p.u, sb, tid);
        return;
    }
    if (warp == 4) { STAMP(0); GSTAMP(24); }

    if (warp >= 12) {
        asm volatile("setmaxnreg.dec.sync.aligned.u32 40;");
        const bool el = warp == 12 && elect_one();
        if (el) {
#pragma unroll
            for (int j = 0; j < 4; j++) mbar_init(bar0 + 8 * (B_ROW + j), 1);
            asm volatile("fence.mbarrier_init.release.cluster;" ::: "memory");
            fence_async();
#pragma unroll 1
            for (int j = 0; j < 4; j++) {
                mbar_expect_tx(bar0 + 8 * (B_ROW + j), 8192);
#pragma unroll
                for (int i = 0; i < 4; i++)
                    bulk_g2s(sb + OFF_VT + (4 * j + i) * ROW_PITCH, p.u + (size_t)(16 * b + 4 * j + i) * DM, 2048, bar0 + 8 * (B_ROW + j));
            }
        }
        __syncwarp();
        cluster_arrive();
        cluster_wait();
        STAMP(18);
        if (el) {
#pragma unroll 1
            for (int i = 0; i < 16; i++) {
                if ((i & 3) == 0) mbar_wait(bar0 + 8 * B_ROW + 2 * i, 0);
                tma_load_tile(sb + OFF_XT + h * 32768 + (i & 1) * 16384 + (i >> 1) * 2048, &maps.u, 16 * cl, i & 14, 16 * (i & 1) + 8 * h, bar0 + 8 * B_XT);
            }
            mbar_wait(bar0 + 8 * B_LN, 0);
            const int i0 = has_gu ? 0 : 16;
#pragma unroll 1
            for (int i = i0; i < 24; i++) {
                const int j = i - (i < WIN_SW ? WIN0 : WIN1), s = i < 12 ? i : i - 12;
                if (j >= i0) mbar_wait(bar0 + 8 * (B_FULL + (j < 12 ? j : j - 12)), has_gu && j >= 12);
                if (s == 8) mbar_wait(bar0 + 8 * B_KG, 0);
                if (i >= 12 && has_gu) mbar_wait(bar0 + 8 * (B_FREE + (s >> 2)), 0);
                const uint32_t dst = sb + OFF_RING + (s < 8 ? s * 8192 : (2 * s - 8) * 8192 + 4096), bar = bar0 + 8 * (B_FULL + s);
                const bool gu = i < 16;
                const int c0 = gu ? 32 * b : 16 * cl, c1 = gu ? 64 * i : 1792 * h + 448 * (i & 3) + 56 * (i & 4);
                mbar_expect_tx(bar, gu ? 8192 : 7168);
                tma_load_2d(dst, gu ? &maps.wg : &maps.wd, c0, c1, bar);
                tma_load_2d(dst + (s < 8 ? 4096 : 8192), gu ? &maps.wu : &maps.wd, c0, c1 + (gu ? 0 : 112), bar);
            }
            STAMP(19);
        }
    } else if (warp >= 4) {
        const int w = warp - 4;
        cluster_arrive();
        asm volatile("setmaxnreg.inc.sync.aligned.u32 168;");
        const uint32_t vrow = sb + OFF_VT + w * VT_PITCH + VT_PAD, tab = sb + OFF_PRIV + w * 8192;
        kgen(tab, lane, la, aim, cre, cim, bf_round(ex2f(bf_lo(ldt16) * 1.4426950408889634f)), 1.f + bf_lo(dsk16), dch, [&]() {
            STAMP(21);
            cluster_wait();
            fence_async();
            __syncwarp();
            if (elect_one()) mbar_arrive(bar0 + 8 * B_KG);
        });
        STAMP(1);
        const uint32_t so = sb + OFF_XT + (8 * h + w) * 1024 + ((lane ^ ((w & 1) << 1)) << 4);
        uint32_t dst0 = mapa(so + 32768, 0), dst1 = mapa(so, 1);
        const uint32_t rb0 = mapa(bar0 + 8 * B_RECV, 0), rb1 = mapa(bar0 + 8 * B_RECV, 1);
        const uint32_t box = sb + OFF_XT + h * 32768 + w * 2048;
        uint32_t fs = sb + OFF_XT + (h ^ 1) * 32768 + (2 * m + (r & 1)) * 1024 + (w >> 2) * 512 + (((8 * (w & 3) + (r & 4) + ((r >> 1) & 1)) ^ ((r & 1) << 1)) << 4);
        uint32_t fx = box + (g >> 1) * 512 + (t >> 1) * 144 + (2 * (t & 1) + (g & 1)) * 32;
        uint32_t tpo = tab + (g - 2 * t + 6) * 8;
        pin(dst0); pin(dst1); pin(fs); pin(fx); pin(tpo);
        const Boxes b2(vrow, lane, -18, 5, 7, 0, 4), b3(vrow, lane, -20, 1, 7, 0, 8);
        const uint32_t pb = tab + T_DENSE + (g - 2 * t + 16) * 4;
        uint32_t A0[4];
        load_toep(A0, pb, p.zero);
        {
            mbar_wait(bar0 + 8 * B_LN, 0);
            const uint32_t tag = lds32(sb + OFF_MISC);
            if (lane < 15) sts128(vrow - VT_PAD + lane * 16, 0, 0, 0, 0);
            const uint2* sp = g_stat + 256 * w + 16 * t + 2 * g;
            uint4 q[4];
#pragma unroll
            for (int n = 0; n < 4; n++) q[n] = make_uint4(0, tag + 1, 0, 0);
#pragma unroll 1
            for (uint32_t it = 0;; spin_guard(it)) {
                uint32_t bad = 0;
#pragma unroll
                for (int n = 0; n < 4; n++) ld_relaxed_128_unless(q[n], sp + 64 * n, ((q[n].y ^ tag) & 3) == 0);
#pragma unroll
                for (int n = 0; n < 4; n++) bad |= q[n].y ^ tag;
                if (__all_sync(0xffffffffu, (bad & 3) == 0)) break;
            }
            STAMP(2); GSTAMP(28);
            mbar_wait(bar0 + 8 * B_XT, 0);
            STAMP(8);
            const uint32_t xa = sb + OFF_XT + (w & 2) * 16384 + (w >> 2) * 16384 + (w & 1) * 1024 + (g >> 1) * 2048 + (g & 1) * 128 + t * 32 + ((h ^ (g & 1)) << 4);
            const uint32_t va = sb + OFF_VT + (2 * m + (r & 1)) * VT_PITCH + VT_PAD + (16 * w + (r >> 1)) * 32;
            uint4 x[8];
#pragma unroll
            for (int i = 0; i < 8; i++) x[i] = lds128(xa + (i & 1) * 8192 + (i >> 1) * 256);
#pragma unroll
            for (int i = 0; i < 8; i++) {
                const uint32_t s0 = (i & 1) ? q[i >> 1].z : q[i >> 1].x, s1 = (i & 1) ? q[i >> 1].w : q[i >> 1].y;
                stsm4t(va + (i >> 1) * 128 + (((i ^ (i >> 1)) & 1) << 4), normalize2(x[i].x, s0, s1), normalize2(x[i].y, s0, s1),
                       normalize2(x[i].z, s0, s1), normalize2(x[i].w, s0, s1));
            }
            named_sync(2, 256);
            if (tid == 128) mbar_arrive_peer(mapa(bar0 + 8 * B_SFREE, h ^ 1));
        }
        STAMP(3);
        float acc[16][4];
#pragma unroll
        for (int i = 0; i < 16; i++) { acc[i][0] = acc[i][1] = acc[i][2] = acc[i][3] = 0.f; }
        dense_phase(acc, vrow, pb, A0, p.zero, lane);
        STAMP(4);
        tail_phase(acc, b2, b3, tpo, p.zero, [&](int j) {
            if (j == 3) {
                mbar_wait(bar0 + 8 * B_SFREE, 0);
                emit<0>(acc, dst0, dst1, rb0, rb1);
                STAMP(5);
            }
            if (j == 7) {
                mbar_wait(bar0 + 8 * B_RECV, 0);
                finish(fs, fx);
                fence_async();
                __syncwarp();
                if (elect_one()) tma_store_tile(&maps.out, box, 16 * cl, 2 * w, 8 * h);
                STAMP(20);
            }
        });
        emit<1>(acc, dst0, dst1, rb0, rb1);
        STAMP(30);
        mbar_wait(bar0 + 8 * (B_RECV + 1), 0);
        STAMP(6);
        finish(fs + 16384, fx + 16384);
        const bool ready = mbar_test(bar0 + 8 * B_UPD, 0);
        const bool el = elect_one();
#pragma unroll 1
        for (int pass = 0; pass < 2; pass++) {
            if ((pass != 0) == ready) {
                fence_async();
                __syncwarp();
                if (el) tma_store_tile(&maps.out, box + 16384, 16 * cl, 2 * w, 16 + 8 * h);
            } else {
                if (el) asm volatile("cp.async.bulk.wait_group 0;" ::: "memory");
                __syncwarp();
                mbar_wait(bar0 + 8 * B_UPD, 0);
                const int tok = (int)lds32(sb + OFF_MISC + 16 + 4 * g);
                if (tok >= 0 && ((tok >> 1) & 7) == w) {
                    const uint32_t xa = box + (tok >> 10) * 16384 + ((tok >> 6) & 7) * 256 + (tok & 1) * 128 + ((tok >> 4) & 3) * 32 + (((t >> 1) ^ (tok & 1)) << 4) + (t & 1) * 8;
                    const uint2 o0 = lds64(xa);
                    const float4 up = lds128f(sb + OFF_RED + 16 * lane);
                    const uint2 o1 = make_uint2(badd2(o0.x, pack_bf16(up.x, up.y)), badd2(o0.y, pack_bf16(up.z, up.w)));
                    if (ready && tok >= 1024) sts64(xa, o1.x, o1.y);
                    else *reinterpret_cast<uint2*>(p.out + (size_t)tok * DM + 16 * cl + 4 * t) = o1;
                }
            }
        }
        if (el) asm volatile("cp.async.bulk.wait_group.read 0;" ::: "memory");
        STAMP(7);
    } else {
        const int a = warp;
        if (tid == 0) {
#pragma unroll
            for (int i = B_XT; i < NBAR; i++) mbar_init(bar0 + 8 * i, i == B_KG ? 8 : (i >= B_UPD && i < B_FULL) ? 4 : 1);
            asm volatile("fence.mbarrier_init.release.cluster;" ::: "memory");
            fence_async();
            mbar_expect_tx(bar0 + 8 * B_XT, 65536);
            mbar_expect_tx(bar0 + 8 * B_RECV, 16384);
            mbar_expect_tx(bar0 + 8 * B_RECV + 8, 16384);
            mbar_expect_tx(bar0 + 8 * B_RED, 512);
        }
        __syncwarp();
        cluster_arrive();
        const uint4 wq = ldg128(p.wr + 8 * tid);
        uint32_t epoch = 0;
        if (a == 0) epoch = ld_relaxed_32(&g_epoch);
        if (tid == 32) {
#pragma unroll
            for (int i = 0; i < 5; i++) asm volatile("prefetch.tensormap [%0];" ::"l"(&maps.u + i) : "memory");
        }
        if (has_gu && a == 1) st_relaxed_128(&g_h[b * 128 + 4 * lane], 0u, 0u, 0u, 0u);
        if (tid < 16) st_relaxed_64(g_stat + 16 * b + 2 * r + m, 0u, epoch);
        if (tid == 0) sts32(sb + OFF_MISC, epoch + 1u);
        const uint32_t wbuf = sb + OFF_LN + a * 1024, part = sb + OFF_LN + 4096;
        {
            sts128(wbuf + 16 * lane, wq.x, wq.y, wq.z, wq.w);
            sts128(wbuf + 512 + 16 * lane, 0x3f803f80u, 0x3f803f80u, 0x3f803f80u, 0x3f803f80u);
            float wsum = ((bf_lo(wq.x) + bf_hi(wq.x)) + (bf_lo(wq.y) + bf_hi(wq.y))) + ((bf_lo(wq.z) + bf_hi(wq.z)) + (bf_lo(wq.w) + bf_hi(wq.w)));
#pragma unroll
            for (int o = 16; o; o >>= 1) wsum += __shfl_xor_sync(0xffffffffu, wsum, o);
            sts32f(part + 1024 + 4 * a, wsum);
            uint32_t wf[4][4];
#pragma unroll
            for (int i = 0; i < 4; i++) ldsm4(wf[i], wbuf + ((uint32_t)(r - 1) < 2u ? 16 * (r - 1) : 512) + 32 * m + 128 * i);
            uint32_t ra = sb + OFF_VT + r * ROW_PITCH + 512 * a + 16 * m, pa = part + a * 256 + g * 16;
            cluster_wait();
            STAMP(22);
#pragma unroll 1
            for (int hf = 0; hf < 2; hf++) {
                mbar_wait(bar0 + 8 * B_ROW + 16 * hf, 0);
                mbar_wait(bar0 + 8 * B_ROW + 16 * hf + 8, 0);
                STAMP(23);
                uint32_t x[8][4];
                float cs[4] = {0, 0, 0, 0}, q[4][4] = {{0, 0, 0, 0}, {0, 0, 0, 0}, {0, 0, 0, 0}, {0, 0, 0, 0}};
#pragma unroll
                for (int k = 0; k < 8; k++) ldsm4(x[k], ra + k * 64);
#pragma unroll
                for (int k = 0; k < 8; k++) {
                    mma_bf16(cs, x[k][0], x[k][1], x[k][2], x[k][3], wf[k >> 1][2 * (k & 1)], wf[k >> 1][2 * (k & 1) + 1]);
#pragma unroll
                    for (int i = 0; i < 4; i++) mma_bf16_k8(q[i], x[k][i & 2], x[k][i | 1], x[k][i]);
                }
                if (t == 0) sts64f(pa, cs[0] + cs[2], cs[1]);
                if (t == 1) sts32f(pa + 12, cs[2]);
                if (t == (g >> 1)) sts32f(pa + 8, (g & 1) ? (q[0][1] + q[2][1]) + (q[1][3] + q[3][3]) : (q[0][0] + q[2][0]) + (q[1][2] + q[3][2]));
                ra += 8 * ROW_PITCH; pa += 128;
            }
        }
        named_sync(1, 128);
        const uint32_t tag = lds32(sb + OFF_MISC);
        if (a == 0) {
            const uint32_t pa = part + (lane & 15) * 16;
            const float4 p0 = lds128f(pa), p1 = lds128f(pa + 256), p2 = lds128f(pa + 512), p3 = lds128f(pa + 768), ws = lds128f(part + 1024);
            const float mu = ((p0.x + p1.x) + (p2.x + p3.x)) * (1.f / DM);
            float var = ((p0.z + p1.z) + (p2.z + p3.z)) * (1.f / DM) - mu * mu;
            const bool centred = __any_sync(0xffffffffu, !(mu * mu <= 4.f * var));
            if (centred) var = centred_var(sb + OFF_VT, mu, lane);
            const float ri = rcpf(bf_round(sqrtaf(bf_round(bf_round(var) + 1e-5f))));
            const uint32_t s0 = pack_bf16(mu, ri), s1 = (pack_bf16(ri - bf_hi(s0), 0.f) & 0xfffcu) | (tag & 3);
            float sc = ((((p0.y + p1.y) + (p2.y + p3.y)) + ((p0.w + p1.w) + (p2.w + p3.w))) - bf_lo(s0) * ((ws.x + ws.y) + (ws.z + ws.w))) * ri;
            if (centred) sc = centred_score(sb + OFF_VT, sb + OFF_LN, s0, s1, lane);
            if (lane < 16) st_relaxed_64(g_stat + 16 * b + 2 * r + m, s0, s1 | (order_key(pack_bf16(sc, 0.f)) << 16));
            fence_async();
            __syncwarp();
            if (elect_one()) mbar_arrive(bar0 + 8 * B_LN);
            STAMP(9); GSTAMP(25);
        }
        const uint32_t slot0 = sb + OFF_RING + a * 8192, slot2 = sb + OFF_PRIV + a * 16384 + 4096, fbar = bar0 + 8 * (B_FULL + a);
        if (has_gu) {
            uint4 xq[8];
            const uint4* xp = g_xs + 64 * a + lane;
            if (a == 1) {
                asm volatile("fence.acq_rel.gpu;" ::: "memory");
                __syncwarp();
                if (lane == 0) st_relaxed_32(&g_clr[b], tag);
            }
#pragma unroll 1
            for (uint32_t it = 0; ld_relaxed_32(&g_rdy) != tag; spin_guard(it)) { }
#pragma unroll 1
            for (uint32_t it = 0; ld_relaxed_32(&g_xs[64 * a].w) == 0; spin_guard(it)) { }
#pragma unroll 1
            for (uint32_t it = 0;; spin_guard(it)) {
#pragma unroll
                for (int j = 0; j < 8; j++) xq[j] = ld_relaxed_128(xp + (j >> 1) * 256 + (j & 1) * 32);
                const uint32_t mn = min(min(min(xq[0].w, xq[1].w), min(xq[2].w, xq[3].w)), min(min(xq[4].w, xq[5].w), min(xq[6].w, xq[7].w)));
                if (__all_sync(0xffffffffu, mn != 0u)) break;
            }
            STAMP(12);
            float gacc[4][4];
#pragma unroll
            for (int i = 0; i < 4; i++) { gacc[i][0] = gacc[i][1] = gacc[i][2] = gacc[i][3] = 0.f; }
            const uint32_t ko = (r + ((m >> 1) << 3)) * 64 + (((r >> 1) & 3) << 4);
#pragma unroll
            for (int c = 0; c < 4; c++) {
                mbar_wait(fbar + 32 * (c % 3), c / 3);
                const uint32_t rowa = (c == 2 ? slot2 + (m & 1) * 8192 : slot0 + (c == 1) * 32768 + (m & 1) * 4096) + ko;
                uint32_t af[16][4];
#pragma unroll
                for (int ks = 0; ks < 4; ks++)
#pragma unroll
                    for (int mt = 0; mt < 4; mt++) ldsm4t(af[4 * ks + mt], (rowa ^ (mt << 4)) + ks * 1024);
                __syncwarp();
                if (c < 3 && elect_one()) mbar_arrive(bar0 + 8 * (B_FREE + c) + (af[15][3] & p.zero));
#pragma unroll
                for (int ks = 0; ks < 4; ks++) {
                    const uint4 q = xq[2 * c + (ks >> 1)];
#pragma unroll
                    for (int mt = 0; mt < 4; mt++)
                        mma_bf16(gacc[mt], af[4 * ks + mt][0], af[4 * ks + mt][1], af[4 * ks + mt][2], af[4 * ks + mt][3],
                                 (ks & 1) ? q.z : q.x, (ks & 1) ? q.w : q.y);
                }
            }
            STAMP(13);
#pragma unroll
            for (int mt = 0; mt < 4; mt++) sts128f(slot0 + mt * 512 + lane * 16, gacc[mt]);
            named_sync(1, 128);
            const uint32_t base = sb + OFF_RING + 16 * tid;
            const float4 p0 = lds128f(base), p1 = lds128f(base + 8192), p2 = lds128f(base + 16384), p3 = lds128f(base + 24576);
            const float g0 = bf_round((p0.x + p1.x) + (p2.x + p3.x)), g1 = bf_round((p0.y + p1.y) + (p2.y + p3.y));
            const float h0 = bf_round(g0 * rcpf(1.f + ex2f(-1.4426950408889634f * g0))) * bf_round((p0.z + p1.z) + (p2.z + p3.z));
            const float h1 = bf_round(g1 * rcpf(1.f + ex2f(-1.4426950408889634f * g1))) * bf_round((p0.w + p1.w) + (p2.w + p3.w));
            uint32_t hw;
            asm volatile("movmatrix.sync.aligned.m8n8.trans.b16 %0, %1;" : "=r"(hw) : "r"(pack_bf16(h0, h1)));
            sts32(sb + OFF_RING + 2048 + 16 * lane + 4 * a, hw);
            named_sync(1, 128);
            if (a == 0) {
                const uint4 q = lds128(base + 2048);
                st_relaxed_128(&g_h[b * 128 + 4 * lane], q.x, q.y, q.z, q.w ? q.w : 0x80008000u);
            }
            STAMP(14);
        }
        uint2 sel;
#pragma unroll 1
        for (uint32_t it = 0;; spin_guard(it)) {
            sel = ld_relaxed_64(g_sel + (tid >> 4));
            if (__all_sync(0xffffffffu, sel.y == tag)) break;
        }
        if ((tid & 15) == 0) {
            const int tok = 0xffff - (int)(sel.x & 0xffffu);
            sts32(sb + OFF_MISC + 16 + (tid >> 2), (((tok >> 9) & 1) == h) ? (uint32_t)tok : 0xffffffffu);
        }
        float dacc[4] = {0, 0, 0, 0};
        {
            const uint32_t* hp = &g_h[(56 * h + 14 * a) * 128];
            uint32_t hf = lane >= 14;
#pragma unroll 1
            for (uint32_t it = 0;; spin_guard(it)) {
                if (hf == 0) hf = ld_relaxed_32(hp + lane * 128 + 127);
                if (__all_sync(0xffffffffu, hf != 0)) break;
            }
            uint4 hq[14];
#pragma unroll 1
            for (uint32_t it = 0;; spin_guard(it)) {
                uint32_t mn = 0xffffffffu;
#pragma unroll
                for (int j = 0; j < 14; j++) hq[j] = ld_relaxed_128(hp + 4 * lane + j * 128);
#pragma unroll
                for (int j = 0; j < 14; j += 2) mn = min(mn, min(hq[j].w, hq[j + 1].w));
                if (__all_sync(0xffffffffu, mn != 0)) break;
            }
            STAMP(15);
            const uint32_t wo = (r + ((m >> 1) << 3)) * 32 + (((m & 1) ^ (r >> 2)) << 4);
            float dacc2[4] = {0, 0, 0, 0};
#pragma unroll
            for (int s = 0; s < 2; s++) {
                mbar_wait(fbar + 32 * (s + 1), has_gu);
                uint32_t af[14][4];
#pragma unroll
                for (int j = 0; j < 14; j++) ldsm4t(af[j], (s ? slot2 : slot0 + 32768) + wo + (j / 7) * (s ? 8192 : 4096) + (j % 7) * 512);
#pragma unroll
                for (int j = 0; j < 7; j++) {
                    const uint4 q = hq[7 * s + j];
                    mma_bf16(dacc, af[2 * j][0], af[2 * j][1], af[2 * j][2], af[2 * j][3], q.x, q.y);
                    mma_bf16(dacc2, af[2 * j + 1][0], af[2 * j + 1][1], af[2 * j + 1][2], af[2 * j + 1][3], q.z, q.w);
                }
            }
#pragma unroll
            for (int j = 0; j < 4; j++) dacc[j] += dacc2[j];
        }
        STAMP(16);
        {
            sts128f(slot0 + 4096 + lane * 16, dacc);
            named_sync(1, 128);
            const int tk = tid >> 4, col = tid & 15;
            const uint32_t base = sb + OFF_RING + 4096 + ((col & 7) * 4 + (tk >> 1)) * 16 + (((col >> 3) << 1) + (tk & 1)) * 4;
            const float y0 = (lds32f(base) + lds32f(base + 8192)) + (lds32f(base + 16384) + lds32f(base + 24576));
            const uint32_t red = sb + OFF_RED + 4 * tid;
            asm volatile("st.async.weak.shared::cluster.mbarrier::complete_tx::bytes.f32 [%0], %1, [%2];"
                         ::"r"(mapa(red, h ^ 1)), "f"(y0), "r"(mapa(bar0 + 8 * B_RED, h ^ 1)) : "memory");
            const float rv = __uint_as_float(unorder_key(sel.x >> 16) << 16);
            const float sg = bf_round(rcpf(1.f + ex2f(-1.4426950408889634f * rv)));
            mbar_wait(bar0 + 8 * B_RED, 0);
            sts32f(red, bf_round(y0 + lds32f(red)) * sg);
            __syncwarp();
            if (elect_one()) mbar_arrive(bar0 + 8 * B_UPD);
        }
        STAMP(17); GSTAMP(29);
    }
}

typedef CUresult (*EncodeFn)(CUtensorMap*, CUtensorMapDataType, cuuint32_t, void*, const cuuint64_t*, const cuuint64_t*,
                             const cuuint32_t*, const cuuint32_t*, CUtensorMapInterleave, CUtensorMapSwizzle,
                             CUtensorMapL2promotion, CUtensorMapFloatOOBfill);

void make_map(EncodeFn enc, CUtensorMap* m, const void* ptr, uint64_t cols, uint64_t rows, uint32_t bc, uint32_t br,
              CUtensorMapSwizzle sw, CUtensorMapL2promotion pr) {
    cuuint64_t dims[2] = {cols, rows};
    cuuint64_t str[1] = {cols * 2};
    cuuint32_t box[2] = {bc, br};
    cuuint32_t es[2] = {1, 1};
    enc(m, CU_TENSOR_MAP_DATA_TYPE_BFLOAT16, 2, const_cast<void*>(ptr), dims, str, box, es, CU_TENSOR_MAP_INTERLEAVE_NONE, sw, pr,
        CU_TENSOR_MAP_FLOAT_OOB_FILL_NONE);
}
void make_tile_map(EncodeFn enc, CUtensorMap* m, const void* ptr) {
    cuuint64_t dims[4] = {DM, 4, 16, SEQ / 64};
    cuuint64_t str[3] = {16 * DM * 2, DM * 2, 64 * DM * 2};
    cuuint32_t box[4] = {16, 4, 2, 8};
    cuuint32_t es[4] = {1, 1, 1, 1};
    enc(m, CU_TENSOR_MAP_DATA_TYPE_BFLOAT16, 4, const_cast<void*>(ptr), dims, str, box, es, CU_TENSOR_MAP_INTERLEAVE_NONE,
        CU_TENSOR_MAP_SWIZZLE_32B, CU_TENSOR_MAP_L2_PROMOTION_NONE, CU_TENSOR_MAP_FLOAT_OOB_FILL_NONE);
}

}

#define WD_PROMO CU_TENSOR_MAP_L2_PROMOTION_L2_128B
extern "C" void kernel_launch(void* const* d_in, const int* in_sizes, int n_in, void* d_out, int out_size) {
    (void)in_sizes; (void)n_in; (void)out_size;
    static EncodeFn enc = nullptr;
    if (!enc) {
        void* fn = nullptr;
        cudaDriverEntryPointQueryResult q;
        cudaGetDriverEntryPoint("cuTensorMapEncodeTiled", &fn, cudaEnableDefault, &q);
        enc = (EncodeFn)fn;
        cudaFuncSetAttribute(fused_kernel, cudaFuncAttributeMaxDynamicSharedMemorySize, SMEM_BYTES);
    }
    Maps maps;
    make_tile_map(enc, &maps.u, d_in[0]);
    make_tile_map(enc, &maps.out, d_out);
    make_map(enc, &maps.wg, d_in[9], FF, DM, 32, 64, CU_TENSOR_MAP_SWIZZLE_64B, CU_TENSOR_MAP_L2_PROMOTION_L2_128B);
    make_map(enc, &maps.wu, d_in[10], FF, DM, 32, 64, CU_TENSOR_MAP_SWIZZLE_64B, CU_TENSOR_MAP_L2_PROMOTION_L2_128B);
    make_map(enc, &maps.wd, d_in[11], DM, FF, 16, 112, CU_TENSOR_MAP_SWIZZLE_32B, WD_PROMO);
    Ptrs p;
    p.u = (const __nv_bfloat16*)d_in[0];
    p.logA = (const __nv_bfloat16*)d_in[1];
    p.Aim = (const __nv_bfloat16*)d_in[2];
    p.Cre = (const __nv_bfloat16*)d_in[3];
    p.Cim = (const __nv_bfloat16*)d_in[4];
    p.ldt = (const __nv_bfloat16*)d_in[5];
    p.dsk = (const __nv_bfloat16*)d_in[6];
    p.wr = (const __nv_bfloat16*)d_in[8];
    p.out = (__nv_bfloat16*)d_out;
    p.zero = 0;
    fused_kernel<<<NCTA + 2, NTHR, SMEM_BYTES, cudaStreamPerThread>>>(p, maps);
}
```

```cpp
#include <cuda_runtime.h>
#include <cuda_bf16.h>
#include <cuda_fp16.h>
#include <cuda.h>
#include <stdint.h>

namespace {

constexpr int SEQ = 2048, DM = 1024, NMODE = 128, FF = 3584;
constexpr int NCTA = 128, NTHR = 512;
constexpr int GU_CTAS = 112;

constexpr int OFF_XT = 0;
constexpr int OFF_RING = 65536;
constexpr int OFF_PRIV = OFF_RING + 65536;
constexpr int OFF_VT = OFF_PRIV + 65536;
constexpr int VT_PAD = 240, VT_PITCH = VT_PAD + 4096, ROW_PITCH = 2064;
constexpr int OFF_BAR = OFF_VT + 8 * VT_PITCH;
constexpr int OFF_MISC = OFF_BAR + 240;
constexpr int OFF_RED = OFF_MISC + 112;
constexpr int OFF_STAMP = OFF_RED + 512;
constexpr int SMEM_BYTES = OFF_STAMP + 192;
constexpr int OFF_LN = OFF_RING + 7 * 8192;
constexpr int OFF_ST = OFF_RING + 5 * 8192;
static_assert(SMEM_BYTES <= 232448, "shared memory");

constexpr int B_ROW = 0, B_XT = 4, B_LN = 5, B_CLR = 6, B_SFREE = 7, B_RECV = 8, B_RED = 10, B_V = 11, B_ST = 12, B_UPD = 13, B_FREE = 14, B_FULL = 17, NBAR = 29;

constexpr int T_DENSE = 60;
constexpr int T_PATCH = 2208;
constexpr int T_R2 = 2368;
constexpr int T_R3 = 3296;

constexpr uint32_t SPIN_LIMIT = 1u << 20;
#define KG_UNROLL 4
constexpr int kKgUnroll = KG_UNROLL;
#define DENSE_UNROLL 1
constexpr int kDenseUnroll = DENSE_UNROLL;
#define PF_T0 1900
#define PF_PER 306
#define PF_FIRST 0
#define GATE B_LN
#define WIN0 3
#define WIN1 4
#define WIN_SW 6

struct Scratch {
    uint2 stat[SEQ];
    uint32_t key[SEQ];
    uint32_t h[GU_CTAS * 128];
    uint32_t clr[128];
    uint32_t epoch;
};
__device__ __align__(128) Scratch g_scratch;

struct Ptrs {
    Scratch* sc;
    const __nv_bfloat16 *logA, *Aim, *Cre, *Cim, *ldt, *dsk, *u, *wr, *wg, *wu, *wd;
    __nv_bfloat16* out;
    uint32_t zero;
};
struct Maps {
    CUtensorMap u, out, wg, wu, wd;
};

#define STAMP(i) do { } while (0)
#define KSTAMP(i) do { } while (0)
#define GSTAMP(i) do { } while (0)

__device__ __forceinline__ uint32_t s_u32(const void* p) { return (uint32_t)__cvta_generic_to_shared(p); }
__device__ __forceinline__ void mbar_init(uint32_t b, uint32_t n) {
    asm volatile("mbarrier.init.shared::cta.b64 [%0], %1;" ::"r"(b), "r"(n) : "memory");
}
__device__ __forceinline__ void mbar_expect_tx(uint32_t b, uint32_t bytes) {
    asm volatile("mbarrier.arrive.expect_tx.shared::cta.b64 _, [%0], %1;" ::"r"(b), "r"(bytes) : "memory");
}
__device__ __forceinline__ void mbar_arrive(uint32_t b) {
    asm volatile("mbarrier.arrive.shared::cta.b64 _, [%0];" ::"r"(b) : "memory");
}
__device__ __forceinline__ void mbar_arrive_peer(uint32_t b_cluster) {
    asm volatile("mbarrier.arrive.relaxed.cluster.shared::cluster.b64 _, [%0];" ::"r"(b_cluster) : "memory");
}
__device__ __forceinline__ void mbar_wait(uint32_t b, uint32_t parity) {
    asm volatile("{\n\t.reg .pred p;\n\t.reg .u32 c;\n\tmov.u32 c, 0;\n"
                 "W:\n\tmbarrier.try_wait.parity.shared::cta.b64 p, [%0], %1, 4000;\n\t@p bra D;\n\t"
                 "add.u32 c, c, 1;\n\tsetp.lt.u32 p, c, 1048576;\n\t@p bra W;\n\ttrap;\nD:\n\t}"
                 ::"r"(b), "r"(parity) : "memory");
}
__device__ __forceinline__ bool mbar_test(uint32_t b, uint32_t parity) {
    uint32_t ok;
    asm volatile("{ .reg .pred p; mbarrier.test_wait.parity.shared::cta.b64 p, [%1], %2; selp.u32 %0, 1, 0, p; }" : "=r"(ok) : "r"(b), "r"(parity) : "memory");
    return __all_sync(0xffffffffu, ok != 0);
}
__device__ __forceinline__ bool elect_one() {
    uint32_t p;
    asm volatile("{ .reg .pred P; elect.sync _|P, 0xffffffff; selp.u32 %0, 1, 0, P; }" : "=r"(p));
    return p != 0;
}
__device__ __forceinline__ uint32_t mapa(uint32_t a, uint32_t rank) {
    uint32_t r;
    asm("mapa.shared::cluster.u32 %0, %1, %2;" : "=r"(r) : "r"(a), "r"(rank));
    return r;
}
__device__ __forceinline__ void cluster_arrive() { asm volatile("barrier.cluster.arrive.relaxed.aligned;" ::: "memory"); }
__device__ __forceinline__ void cluster_wait() { asm volatile("barrier.cluster.wait.acquire.aligned;" ::: "memory"); }
__device__ __forceinline__ void tma_load_2d(uint32_t dst, const CUtensorMap* m, int c0, int c1, uint32_t bar) {
    asm volatile("cp.async.bulk.tensor.2d.shared::cluster.global.mbarrier::complete_tx::bytes [%0], [%1, {%3, %4}], [%2];"
                 ::"r"(dst), "l"(m), "r"(bar), "r"(c0), "r"(c1) : "memory");
}
__device__ __forceinline__ void tma_load_perm(uint32_t dst, const CUtensorMap* m, int c0, int blk, uint32_t bar) {
    asm volatile("cp.async.bulk.tensor.5d.shared::cluster.global.mbarrier::complete_tx::bytes [%0], [%1, {%3, %4, %4, %4, %5}], [%2];"
                 ::"r"(dst), "l"(m), "r"(bar), "r"(c0), "r"(0), "r"(blk) : "memory");
}
__device__ __forceinline__ void tma_load_tile(uint32_t dst, const CUtensorMap* m, int c0, int c2, int c3, uint32_t bar) {
    asm volatile("cp.async.bulk.tensor.4d.shared::cluster.global.mbarrier::complete_tx::bytes.multicast::cluster [%0], [%1, {%3, %4, %5, %6}], [%2], %7;"
                 ::"r"(dst), "l"(m), "r"(bar), "r"(c0), "r"(0), "r"(c2), "r"(c3), "h"((uint16_t)3) : "memory");
}
__device__ __forceinline__ void tma_store_tile(const CUtensorMap* m, uint32_t src, int c0, int c2, int c3) {
    asm volatile("cp.async.bulk.tensor.4d.global.shared::cta.bulk_group [%0, {%2, %3, %4, %5}], [%1];"
                 ::"l"(m), "r"(src), "r"(c0), "r"(0), "r"(c2), "r"(c3) : "memory");
    asm volatile("cp.async.bulk.commit_group;" ::: "memory");
}
__device__ __forceinline__ void bulk_g2s(uint32_t dst, const void* src, uint32_t bytes, uint32_t bar) {
    asm volatile("cp.async.bulk.shared::cluster.global.mbarrier::complete_tx::bytes [%0], [%1], %2, [%3];"
                 ::"r"(dst), "l"(src), "r"(bytes), "r"(bar) : "memory");
}
__device__ __forceinline__ void st_async128(uint32_t dst_cluster, uint32_t x, uint32_t y, uint32_t z, uint32_t w, uint32_t bar_cluster) {
    asm volatile("st.async.weak.shared::cluster.mbarrier::complete_tx::bytes.v4.b32 [%0], {%1,%2,%3,%4}, [%5];"
                 ::"r"(dst_cluster), "r"(x), "r"(y), "r"(z), "r"(w), "r"(bar_cluster) : "memory");
}
__device__ __forceinline__ void fence_async() { asm volatile("fence.proxy.async.shared::cta;" ::: "memory"); }
__device__ __forceinline__ void named_sync(int id, int n) { asm volatile("bar.sync %0, %1;" ::"r"(id), "r"(n) : "memory"); }

__device__ __forceinline__ void ldsm4(uint32_t* r, uint32_t a) {
    asm volatile("ldmatrix.sync.aligned.m8n8.x4.shared.b16 {%0,%1,%2,%3}, [%4];"
                 : "=r"(r[0]), "=r"(r[1]), "=r"(r[2]), "=r"(r[3]) : "r"(a));
}
__device__ __forceinline__ void ldsm4t(uint32_t* r, uint32_t a) {
    asm volatile("ldmatrix.sync.aligned.m8n8.x4.trans.shared.b16 {%0,%1,%2,%3}, [%4];"
                 : "=r"(r[0]), "=r"(r[1]), "=r"(r[2]), "=r"(r[3]) : "r"(a));
}
__device__ __forceinline__ void stsm4t(uint32_t a, uint32_t x, uint32_t y, uint32_t z, uint32_t w) {
    asm volatile("stmatrix.sync.aligned.m8n8.x4.trans.shared.b16 [%0], {%1,%2,%3,%4};"
                 ::"r"(a), "r"(x), "r"(y), "r"(z), "r"(w) : "memory");
}
__device__ __forceinline__ uint32_t lds32(uint32_t a) { uint32_t v; asm volatile("ld.shared.u32 %0, [%1];" : "=r"(v) : "r"(a)); return v; }
__device__ __forceinline__ float lds32f(uint32_t a) { float v; asm volatile("ld.shared.f32 %0, [%1];" : "=f"(v) : "r"(a)); return v; }
__device__ __forceinline__ uint2 lds64(uint32_t a) { uint2 v; asm volatile("ld.shared.v2.u32 {%0,%1}, [%2];" : "=r"(v.x), "=r"(v.y) : "r"(a)); return v; }
__device__ __forceinline__ uint4 lds128(uint32_t a) {
    uint4 v; asm volatile("ld.shared.v4.u32 {%0,%1,%2,%3}, [%4];" : "=r"(v.x), "=r"(v.y), "=r"(v.z), "=r"(v.w) : "r"(a)); return v;
}
__device__ __forceinline__ float4 lds128f(uint32_t a) {
    float4 v; asm volatile("ld.shared.v4.f32 {%0,%1,%2,%3}, [%4];" : "=f"(v.x), "=f"(v.y), "=f"(v.z), "=f"(v.w) : "r"(a)); return v;
}
__device__ __forceinline__ void sts32(uint32_t a, uint32_t v) { asm volatile("st.shared.u32 [%0], %1;" ::"r"(a), "r"(v) : "memory"); }
__device__ __forceinline__ void sts32f(uint32_t a, float v) { asm volatile("st.shared.f32 [%0], %1;" ::"r"(a), "f"(v) : "memory"); }
__device__ __forceinline__ void sts64(uint32_t a, uint32_t x, uint32_t y) { asm volatile("st.shared.v2.u32 [%0], {%1,%2};" ::"r"(a), "r"(x), "r"(y) : "memory"); }
__device__ __forceinline__ void sts64f(uint32_t a, float x, float y) { asm volatile("st.shared.v2.f32 [%0], {%1,%2};" ::"r"(a), "f"(x), "f"(y) : "memory"); }
__device__ __forceinline__ void sts128(uint32_t a, uint32_t x, uint32_t y, uint32_t z, uint32_t w) {
    asm volatile("st.shared.v4.u32 [%0], {%1,%2,%3,%4};" ::"r"(a), "r"(x), "r"(y), "r"(z), "r"(w) : "memory");
}
__device__ __forceinline__ void sts128f(uint32_t a, const float* v) {
    asm volatile("st.shared.v4.f32 [%0], {%1,%2,%3,%4};" ::"r"(a), "f"(v[0]), "f"(v[1]), "f"(v[2]), "f"(v[3]) : "memory");
}
__device__ __forceinline__ uint4 ldg128(const void* p) {
    uint4 v; asm volatile("ld.global.nc.L1::no_allocate.v4.u32 {%0,%1,%2,%3}, [%4];" : "=r"(v.x), "=r"(v.y), "=r"(v.z), "=r"(v.w) : "l"(p)); return v;
}
__device__ __forceinline__ uint2 ldg64(const void* p) {
    uint2 v; asm volatile("ld.global.nc.L1::no_allocate.v2.u32 {%0,%1}, [%2];" : "=r"(v.x), "=r"(v.y) : "l"(p)); return v;
}
__device__ __forceinline__ uint32_t ldg32(const void* p) {
    uint32_t v; asm volatile("ld.global.nc.u32 %0, [%1];" : "=r"(v) : "l"(p)); return v;
}
__device__ __forceinline__ uint32_t ldg16(const void* p) {
    uint32_t v; asm volatile("ld.global.nc.u16 %0, [%1];" : "=r"(v) : "l"(p)); return v;
}
__device__ __forceinline__ uint4 ld_relaxed_128(const void* p) {
    uint4 v; asm volatile("ld.relaxed.gpu.global.v4.u32 {%0,%1,%2,%3}, [%4];" : "=r"(v.x), "=r"(v.y), "=r"(v.z), "=r"(v.w) : "l"(p) : "memory"); return v;
}
__device__ __forceinline__ void ld_relaxed_128_unless(uint4& q, const void* p, bool have) {
    asm volatile("{ .reg .pred p; setp.eq.u32 p, %5, 0; @p ld.relaxed.gpu.global.v4.u32 {%0,%1,%2,%3}, [%4]; }"
                 : "+r"(q.x), "+r"(q.y), "+r"(q.z), "+r"(q.w) : "l"(p), "r"((uint32_t)have) : "memory");
}
__device__ __forceinline__ uint2 ld_relaxed_64(const void* p) {
    uint2 v; asm volatile("ld.relaxed.gpu.global.v2.u32 {%0,%1}, [%2];" : "=r"(v.x), "=r"(v.y) : "l"(p) : "memory"); return v;
}
__device__ __forceinline__ uint32_t ld_relaxed_32(const void* p) {
    uint32_t v; asm volatile("ld.relaxed.gpu.global.u32 %0, [%1];" : "=r"(v) : "l"(p) : "memory"); return v;
}
__device__ __forceinline__ void st_relaxed_128(void* p, uint32_t x, uint32_t y, uint32_t z, uint32_t w) {
    asm volatile("st.relaxed.gpu.global.v4.u32 [%0], {%1,%2,%3,%4};" ::"l"(p), "r"(x), "r"(y), "r"(z), "r"(w) : "memory");
}
__device__ __forceinline__ void st_relaxed_64(void* p, uint32_t x, uint32_t y) {
    asm volatile("st.relaxed.gpu.global.v2.u32 [%0], {%1,%2};" ::"l"(p), "r"(x), "r"(y) : "memory");
}
__device__ __forceinline__ void st_relaxed_32(void* p, uint32_t v) {
    asm volatile("st.relaxed.gpu.global.u32 [%0], %1;" ::"l"(p), "r"(v) : "memory");
}
__device__ __forceinline__ void spin_guard(uint32_t& it) { if (++it > SPIN_LIMIT) __trap(); }
__device__ __forceinline__ void mma_bf16(float* c, uint32_t a0, uint32_t a1, uint32_t a2, uint32_t a3, uint32_t b0, uint32_t b1) {
    asm("mma.sync.aligned.m16n8k16.row.col.f32.bf16.bf16.f32 {%0,%1,%2,%3}, {%4,%5,%6,%7}, {%8,%9}, {%0,%1,%2,%3};"
                 : "+f"(c[0]), "+f"(c[1]), "+f"(c[2]), "+f"(c[3]) : "r"(a0), "r"(a1), "r"(a2), "r"(a3), "r"(b0), "r"(b1));
}
__device__ __forceinline__ void mma_bf16_k8(float* c, uint32_t a0, uint32_t a1, uint32_t b0) {
    asm("mma.sync.aligned.m16n8k8.row.col.f32.bf16.bf16.f32 {%0,%1,%2,%3}, {%4,%5}, {%6}, {%0,%1,%2,%3};"
                 : "+f"(c[0]), "+f"(c[1]), "+f"(c[2]), "+f"(c[3]) : "r"(a0), "r"(a1), "r"(b0));
}
__device__ __forceinline__ void mma_v(float* c, const uint32_t* a, uint32_t b0, uint32_t b1) {
    asm volatile("mma.sync.aligned.m16n8k16.row.col.f32.bf16.bf16.f32 {%0,%1,%2,%3}, {%4,%5,%6,%7}, {%8,%9}, {%0,%1,%2,%3};"
                 : "+f"(c[0]), "+f"(c[1]), "+f"(c[2]), "+f"(c[3]) : "r"(a[0]), "r"(a[1]), "r"(a[2]), "r"(a[3]), "r"(b0), "r"(b1));
}
__device__ __forceinline__ void mma_bf16_z(float* c, uint32_t a0, uint32_t a1, uint32_t a2, uint32_t a3, uint32_t b0, uint32_t b1) {
    asm volatile("mma.sync.aligned.m16n8k16.row.col.f32.bf16.bf16.f32 {%0,%1,%2,%3}, {%4,%5,%6,%7}, {%8,%9}, {%10,%10,%10,%10};"
        : "=f"(c[0]), "=f"(c[1]), "=f"(c[2]), "=f"(c[3]) : "r"(a0), "r"(a1), "r"(a2), "r"(a3), "r"(b0), "r"(b1), "f"(0.f));
}
__device__ __forceinline__ void mma_f16(float* c, uint32_t a0, uint32_t a1, uint32_t a2, uint32_t a3, uint32_t b0, uint32_t b1) {
    asm("mma.sync.aligned.m16n8k16.row.col.f32.f16.f16.f32 {%0,%1,%2,%3}, {%4,%5,%6,%7}, {%8,%9}, {%0,%1,%2,%3};"
                 : "+f"(c[0]), "+f"(c[1]), "+f"(c[2]), "+f"(c[3]) : "r"(a0), "r"(a1), "r"(a2), "r"(a3), "r"(b0), "r"(b1));
}
__device__ __forceinline__ uint32_t pack_bf16(float lo, float hi) {
    uint32_t r; asm("cvt.rn.bf16x2.f32 %0, %1, %2;" : "=r"(r) : "f"(hi), "f"(lo)); return r;
}
__device__ __forceinline__ uint32_t pack_v(float lo, float hi) {
    uint32_t r; asm volatile("cvt.rn.bf16x2.f32 %0, %1, %2;" : "=r"(r) : "f"(hi), "f"(lo)); return r;
}
__device__ __forceinline__ uint32_t pack_w(float lo, float hi) {
    uint32_t r; asm volatile("cvt.rn.satfinite.bf16x2.f32 %0, %1, %2;" : "=r"(r) : "f"(hi), "f"(lo)); return r;
}
__device__ __forceinline__ void pin(uint32_t& x) { asm volatile("" : "+r"(x)); }
__device__ __forceinline__ uint32_t pack_f16(float lo, float hi) {
    uint32_t r; asm("cvt.rn.f16x2.f32 %0, %1, %2;" : "=r"(r) : "f"(hi), "f"(lo)); return r;
}
__device__ __forceinline__ float bf_lo(uint32_t v) { return __uint_as_float(v << 16); }
__device__ __forceinline__ float bf_hi(uint32_t v) { return __uint_as_float(v & 0xffff0000u); }
__device__ __forceinline__ float bf_round(float x) { return __uint_as_float(pack_bf16(0.f, x)); }
__device__ __forceinline__ uint32_t badd2(uint32_t a, uint32_t b) { uint32_t r; asm("add.rn.bf16x2 %0, %1, %2;" : "=r"(r) : "r"(a), "r"(b)); return r; }
__device__ __forceinline__ uint32_t bsub2_lo(uint32_t a, uint32_t b) {
    uint32_t r; asm("{ .reg .b16 m, h; .reg .b32 m2; mov.b32 {m, h}, %2; mov.b32 m2, {m, m}; sub.rn.bf16x2 %0, %1, m2; }" : "=r"(r) : "r"(a), "r"(b)); return r;
}
__device__ __forceinline__ uint32_t bmax2(uint32_t a, uint32_t b) { uint32_t r; asm("max.bf16x2 %0, %1, %2;" : "=r"(r) : "r"(a), "r"(b)); return r; }
__device__ __forceinline__ uint32_t normalize2(uint32_t x, uint32_t s0, uint32_t s1) {
    uint32_t r;
    asm("{ .reg .b16 m, h, l, k; .reg .b32 m2, h2, l2, d, t;\n\t"
        "mov.b32 {m, h}, %2; mov.b32 {l, k}, %3; mov.b32 m2, {m, m}; mov.b32 h2, {h, h}; mov.b32 l2, {l, l};\n\t"
        "sub.rn.bf16x2 d, %1, m2; mul.rn.bf16x2 t, d, l2; fma.rn.bf16x2 %0, d, h2, t; }" : "=r"(r) : "r"(x), "r"(s0), "r"(s1));
    return r;
}
__device__ __forceinline__ float rcpf(float x) { float r; asm("rcp.approx.ftz.f32 %0, %1;" : "=f"(r) : "f"(x)); return r; }
__device__ __forceinline__ float sqrtaf(float x) { float r; asm("sqrt.approx.ftz.f32 %0, %1;" : "=f"(r) : "f"(x)); return r; }
__device__ __forceinline__ float ex2f(float x) { float r; asm("ex2.approx.ftz.f32 %0, %1;" : "=f"(r) : "f"(x)); return r; }

__device__ __forceinline__ int tok_off(int t) { return (t >> 4) * 32 + ((((t >> 3) ^ (t >> 6)) & 1) << 4); }

__device__ __forceinline__ uint32_t order_key(uint32_t b16) { return b16 ^ ((b16 & 0x8000u) ? 0xffffu : 0x8000u); }
__device__ __forceinline__ uint32_t unorder_key(uint32_t k16) { return k16 ^ ((k16 & 0x8000u) ? 0x8000u : 0xffffu); }

struct cplx { float r, i; };
struct hc { uint32_t r, i; };
template <bool CONJ> __device__ __forceinline__ cplx csq(cplx a) {
    float im;
    asm("{ .reg .f32 t; mul.ftz.f32 t, %1, %2; mul.ftz.f32 %0, t, 0f40000000; }" : "=f"(im) : "f"(CONJ ? -a.r : a.r), "f"(a.i));
    return {fmaf(a.r, a.r, -(a.i * a.i)), im};
}
__device__ __forceinline__ cplx cexpp(float a2, float ai) {
    float m = ex2f(a2), s, c;
    __sincosf(ai, &s, &c);
    return {m * c, m * s};
}
__device__ __forceinline__ __half2 as_h2(uint32_t x) { return *reinterpret_cast<__half2*>(&x); }
__device__ __forceinline__ uint32_t as_u(__half2 x) { return *reinterpret_cast<uint32_t*>(&x); }
__device__ __forceinline__ hc hmul(hc a, hc b) {
    return {as_u(__hfma2(__hneg2(as_h2(a.i)), as_h2(b.i), __hmul2(as_h2(a.r), as_h2(b.r)))),
            as_u(__hfma2(as_h2(a.i), as_h2(b.r), __hmul2(as_h2(a.r), as_h2(b.i))))};
}
__device__ __forceinline__ hc hpack(cplx a, cplx b) { return {pack_f16(a.r, b.r), pack_f16(a.i, b.i)}; }
__device__ __forceinline__ void sts16(uint32_t a, uint32_t v) { asm volatile("st.shared.u16 [%0], %1;" ::"r"(a), "r"(v) : "memory"); }

template <class Hook>
__device__ __forceinline__ void kgen(uint32_t tab, int lane, uint2 la, uint2 aim, uint2 cre, uint2 cim, float dt, float skip, int dch, Hook main_done) {
    const int g = lane >> 2, t = lane & 3;
    const float dt2 = 2.f * dt;
    const uint32_t am = bmax2(bmax2(cre.x & 0x7fff7fffu, cre.y & 0x7fff7fffu), bmax2(cim.x & 0x7fff7fffu, cim.y & 0x7fff7fffu));
    const float mx = dt2 * fmaxf(bf_lo(am), bf_hi(am));
    const uint32_t eb = min(max(__reduce_max_sync(0xffffffffu, __float_as_uint(mx)) >> 23, 1u), 252u);
    const float cscale = dt2 * __uint_as_float((253u - eb) << 23);
    const float scale_inv = __uint_as_float((eb + 1u) << 23);
    float k0 = (bf_lo(cre.x) + bf_hi(cre.x)) + (bf_lo(cre.y) + bf_hi(cre.y));
#pragma unroll
    for (int o = 16; o; o >>= 1) k0 += __shfl_xor_sync(0xffffffffu, k0, o);
    const float ndt = -1.4426950408889634f * dt;
    STAMP(40); KSTAMP(0);

    float acc[5][4];
#pragma unroll
    for (int i = 0; i < 5; i++) { acc[i][0] = acc[i][1] = acc[i][2] = acc[i][3] = 0.f; }

    const uint32_t rec = tab + t * 512, sw = (uint32_t)t << 5;
    const uint32_t ad_l = rec + (((uint32_t)g << 4) ^ sw), ad_h = rec + 128 + (((uint32_t)g << 3) ^ sw);
    const uint32_t ad_2 = rec + (0xc0u ^ sw) + ((g & 1) << 3), ad_3 = rec + (0xd0u ^ sw) + ((g & 2) << 2);
    const uint32_t ad_4 = rec + (0xe0u ^ sw) + ((g & 4) << 1), ad_z = rec + (0xf0u ^ sw);
    const uint32_t wrec = tab + lane * 256 + ((lane & 7) << 4);

#pragma unroll 1
    for (int bb = 0; bb < 2; bb++) {
        cplx z[2][11], cz[2];
#pragma unroll
        for (int e = 0; e < 2; e++) {
            const float lg = e ? bf_hi(la.x) : bf_lo(la.x), ai = (e ? bf_hi(aim.x) : bf_lo(aim.x)) * dt;
            const float cr = (e ? bf_hi(cre.x) : bf_lo(cre.x)) * cscale, ci = (e ? bf_hi(cim.x) : bf_lo(cim.x)) * cscale;
            const float a2 = bf_round(ex2f(lg * 1.4426950408889634f)) * ndt;
            z[e][0] = cexpp(a2, ai);
            z[e][5] = cexpp(a2 * 32.f, ai * -32.f);
#pragma unroll
            for (int i = 1; i < 11; i++) if (i != 5) z[e][i] = (i == 3 || i == 7) ? csq<true>(z[e][i - 1]) : csq<false>(z[e][i - 1]);
            cz[e] = {fmaf(cr, z[e][0].r, -(ci * z[e][0].i)), fmaf(cr, z[e][0].i, ci * z[e][0].r)};
        }
        la.x = la.y; aim.x = aim.y; cre.x = cre.y; cim.x = cim.y;
        const hc z1 = hpack(z[0][0], z[1][0]), z2 = hpack(z[0][1], z[1][1]), z4 = hpack(z[0][2], z[1][2]);
        hc L[8], H[8];
        L[1] = hpack(z[0][3], z[1][3]); L[2] = hpack(z[0][4], z[1][4]); L[4] = hpack(z[0][5], z[1][5]);
        const hc y64 = hpack(z[0][6], z[1][6]), z128 = hpack(z[0][7], z[1][7]), z256 = hpack(z[0][8], z[1][8]);
        const hc z512 = hpack(z[0][9], z[1][9]), z1024 = hpack(z[0][10], z[1][10]);
        H[0] = hpack(cz[0], cz[1]);
        H[1] = hmul(H[0], z1); H[2] = hmul(H[0], z2); H[3] = hmul(H[1], z2);
        L[3] = hmul(L[1], L[2]);
#pragma unroll
        for (int i = 0; i < 4; i++) { H[4 + i] = hmul(H[i], z4); if (i) L[4 + i] = hmul(L[i], L[4]); }
        __syncwarp();
        sts128(wrec, 0x3c003c00u, y64.r, 0u, y64.i);
#pragma unroll
        for (int i = 1; i < 8; i++) { const hc q = hmul(L[i], y64); sts128(wrec ^ (i << 4), L[i].r, q.r, L[i].i, q.i); }
#pragma unroll
        for (int i = 0; i < 4; i++) sts128((wrec ^ (i << 4)) + 128, H[2 * i].r, H[2 * i].i, H[2 * i + 1].r, H[2 * i + 1].i);
        {
            const hc a = hmul(z256, z1), b = hmul(z256, z128), c = hmul(z256, z2), d = hmul(z512, z4);
            sts128((wrec ^ 0x40) + 128, a.r, a.i, b.r, b.i);
            sts128((wrec ^ 0x50) + 128, c.r, c.i, z512.r, z512.i);
            sts128((wrec ^ 0x60) + 128, d.r, d.i, z1024.r, z1024.i);
            sts64((wrec ^ 0x70) + 128, z128.r, z128.i);
        }
        __syncwarp();
        KSTAMP(1 + 2 * bb);
#pragma unroll kKgUnroll
        for (int k2 = 0; k2 < 4; k2++) {
#pragma unroll
            for (uint32_t s = 0; s < 2; s++) {
                const uint32_t o = k2 * 2048 + s * 256, x = s << 4;
                const uint4 l = lds128((ad_l ^ x) + o);
                const uint2 h0 = lds64((ad_h ^ x) + o), m2 = lds64((ad_2 ^ x) + o), m3 = lds64((ad_3 ^ x) + o);
                const uint2 m4 = lds64((ad_4 ^ x) + o), mz = lds64((ad_z ^ x) + o);
                const hc H0 = {h0.x, h0.y};
                const hc H1 = hmul(H0, {mz.x, mz.y}), H2 = hmul(H0, {m2.x, m2.y}), H3 = hmul(H2, {m3.x, m3.y}), H4 = hmul(H3, {m4.x, m4.y});
                mma_f16(acc[0], l.x, l.y, l.z, l.w, H0.r, H0.i);
                mma_f16(acc[1], l.x, l.y, l.z, l.w, H1.r, H1.i);
                mma_f16(acc[2], l.x, l.y, l.z, l.w, H2.r, H2.i);
                mma_f16(acc[3], l.x, l.y, l.z, l.w, H3.r, H3.i);
                mma_f16(acc[4], l.x, l.y, l.z, l.w, H4.r, H4.i);
            }
        }
        KSTAMP(2 + 2 * bb);
    }
    __syncwarp();
    main_done();
    KSTAMP(5);
#pragma unroll
    for (int i = 0; i < 4; i++) sts128(tab + 2048 + 512 * i + 16 * lane, 0, 0, 0, 0);
    if (lane < 15) sts32(tab + 4 * lane, 0);
    __syncwarp();
    const uint32_t d0 = tab + T_DENSE + 4 + 8 * lane, src = (lane + 31) & 31;
    const uint32_t p0 = pack_bf16(fmaf(k0, dt2, skip), 0.f);
    uint32_t prev = p0;
#pragma unroll
    for (int i = 0; i < 4; i++) {
        const uint32_t pk = pack_bf16(acc[i >> 1][2 * (i & 1) + 1] * scale_inv, acc[i >> 1][2 * (i & 1)] * scale_inv);
        sts64(d0 + 256 * i, __byte_perm(pk, __shfl_sync(0xffffffffu, lane == 31 ? prev : pk, src), 0x5432), pk);
        prev = pk;
    }
    const uint32_t w0 = pack_bf16(acc[2][0] * scale_inv, acc[2][1] * scale_inv), w1 = pack_bf16(acc[2][2] * scale_inv, acc[2][3] * scale_inv);
    const uint32_t sa = (lane & 1) ? 0x5410u : 0x5454u, sb2 = (lane & 1) ? 0x1010u : 0x5410u;
#pragma unroll
    for (int hf = 0; hf < 2; hf++) {
        const uint32_t w = hf ? w1 : w0;
        const uint32_t pv = __shfl_sync(0xffffffffu, lane != 31 ? w : hf ? w0 : __byte_perm(prev, w1, 0x5410), src);
        sts64(d0 + 1024 + 256 * hf, __byte_perm(w, pv, sa), __byte_perm(w, pv, sb2));
        sts64(d0 + 1536 + 256 * hf, __byte_perm(w, pv, sa + 0x2222u), __byte_perm(w, pv, sb2 + 0x2222u));
    }
    const uint32_t d3 = tab + T_R2 + 160 + 320 * (t & 1) + 16 * (g >> 1) + 8 * (g & 1) + 4 * (t >> 1), d3n = d3 + (g >= 6 ? 32 : 0);
    const uint32_t d4 = tab + T_R3 + 80 + 160 * t + 4 * g, d4n = d4 + (g >= 6 ? 16 : 0);
    uint32_t p3;
#pragma unroll
    for (int hf = 0; hf < 2; hf++)
#pragma unroll
        for (int e = 0; e < 2; e++) {
            const float v3 = acc[3][2 * hf + e] * scale_inv;
            const uint32_t p4 = pack_bf16(acc[4][2 * hf + e] * scale_inv, 0.f);
            p3 = pack_bf16(v3, v3);
            sts16(d3 + 64 * hf + 160 * e, p3);
            sts16((hf ? d3n : d3) + 64 * hf + 160 * e + 18, p3);
            sts16(d4 + 32 * hf + 80 * e, p4);
            sts16((hf ? d4n : d4) + 32 * hf + 80 * e + 10, p4);
        }
    if (lane == 31) {
        const uint32_t k512 = __byte_perm(w1, 0, 0x3232);
        sts32(tab + T_DENSE, p0);
        sts64(tab + T_DENSE + 4 * 513, k512, k512); sts16(tab + T_DENSE + 4 * 515 + 2, k512);
        sts16(tab + T_PATCH + 4 * 17, p3); sts32(tab + T_PATCH + 4 * 18, p3); sts16(tab + T_PATCH + 4 * 19 + 2, p3);
    }
    __syncwarp();
}

__device__ __forceinline__ void load_toep(uint32_t* a, uint32_t p, uint32_t zero) {
    a[0] = lds32(p); a[1] = lds32(p + 32); a[2] = lds32(p - 32); a[3] = lds32(p + zero);
}
__device__ __forceinline__ uint32_t dense_row(uint32_t vrow, int lane, int rho) {
    const int lam = (lane & 7) - rho;
    return vrow + (lane >> 4) * 2048 + lam * 32 + ((((lane >> 3) ^ (lam >> 2)) & 1) << 4);
}
__device__ __forceinline__ void dense_step(float (&acc)[16][4], uint32_t (&R)[8][4], const uint32_t (&A)[4][4], uint32_t (&An)[4][4],
                                           uint32_t va, uint32_t pn, uint32_t zero) {
#pragma unroll
    for (int i = 0; i < 8; i++) {
#pragma unroll
        for (int ka = 0; ka < 4; ka++) {
            mma_v(acc[i + ka], A[ka], R[i][0], R[i][1]);
            if (i + 8 + ka < 16) mma_v(acc[i + 8 + ka], A[ka], R[i][2], R[i][3]);
        }
        ldsm4(R[i], va + i * 256);
        if (i >= 1 && i < 5) load_toep(An[i - 1], pn + (i - 1) * 512, zero);
    }
}
__device__ __forceinline__ void dense_extra(float (&acc)[16][4], const uint32_t (&R)[8][4], uint32_t pb, uint32_t zero) {
    uint32_t E[4], F[4];
    load_toep(E, pb + 2048, zero);
    load_toep(F, pb + (T_PATCH - T_DENSE + 56), zero);
#pragma unroll
    for (int i = 0; i < 12; i++) mma_v(acc[i + 4], E, R[i & 7][2 * (i >> 3)], R[i & 7][2 * (i >> 3) + 1]);
#pragma unroll
    for (int i = 0; i < 8; i++) mma_v(acc[i + 8], F, R[i][0], R[i][1]);
}
__device__ __forceinline__ void dense_extra8(float (&acc)[16][4], const uint32_t (&R)[8][4], uint32_t pb) {
    const uint32_t e2 = lds32(pb + 2048 - 32), e3 = lds32(pb + 2048), f2 = lds32(pb + (T_PATCH - T_DENSE + 56) - 32), f3 = lds32(pb + (T_PATCH - T_DENSE + 56));
#pragma unroll
    for (int i = 0; i < 12; i++) mma_bf16_k8(acc[i + 4], e2, e3, R[i & 7][2 * (i >> 3) + 1]);
#pragma unroll
    for (int i = 0; i < 8; i++) mma_bf16_k8(acc[i + 8], f2, f3, R[i][1]);
}
__device__ __forceinline__ void dense_phase(float (&acc)[16][4], uint32_t vrow, uint32_t pb, uint32_t (&A0)[4][4], uint32_t zero, int lane) {
    uint32_t R[8][4], A1[4][4];
    const uint32_t va0 = dense_row(vrow, lane, 0);
#pragma unroll
    for (int i = 0; i < 8; i++) ldsm4(R[i], va0 + i * 256);
    dense_extra(acc, R, pb, zero);
#pragma unroll kDenseUnroll
    for (int rho = 0; rho < 8; rho += 2) {
        const uint32_t va1 = dense_row(vrow, lane, rho + 1), va2 = dense_row(vrow, lane, rho + 2);
        dense_step(acc, R, A0, A1, va1, pb + 64, zero);
        if (rho == 0) dense_extra8(acc, R, pb + 64);
        pb += 128;
        dense_step(acc, R, A1, A0, va2, pb, zero);
    }
}
__device__ __forceinline__ uint32_t ones2(int c, int lo, int hi) {
    return (((uint32_t)(c - lo) <= (uint32_t)(hi - lo)) ? 0x3f80u : 0u) | (((uint32_t)(c + 1 - lo) <= (uint32_t)(hi - lo)) ? 0x3f800000u : 0u);
}
struct Boxes {
    uint32_t q[4], ha[4];
    __device__ __forceinline__ Boxes(uint32_t vrow, int lane, int O, int L1, int H1, int L2, int H2) {
        const int g = lane >> 2, t = lane & 3, d = 2 * t - g;
        q[0] = ones2(d, L1, H1); q[1] = ones2(d, L2, H2); q[2] = ones2(d + 8, L1, H1); q[3] = ones2(d + 8, L2, H2);
#pragma unroll
        for (int i = 0; i < 4; i++) {
            const int T = 16 * g + O + 8 * i + 2 * t;
            ha[i] = vrow + tok_off(T & ~7) + (T & 7) * 2;
            pin(q[i]); pin(ha[i]);
        }
    }
    __device__ __forceinline__ void load(int j, uint32_t* v, uint32_t zero) const {
        const uint32_t o = j * 256;
        v[0] = lds32(ha[0] + o); v[1] = lds32(ha[1] + zero + o); v[2] = lds32(ha[1] + o);
        v[3] = lds32(ha[2] + zero + o); v[4] = lds32(ha[2] + o); v[5] = lds32(ha[3] + o);
    }
    __device__ __forceinline__ void sums(const uint32_t* v, float* Z, float* X, float* Y) const {
        mma_bf16_z(Z, q[0], q[1], q[2], q[3], v[0], v[1]);
        mma_bf16_z(X, q[0], q[1], q[2], q[3], v[2], v[3]);
        mma_bf16_z(Y, q[0], q[1], q[2], q[3], v[4], v[5]);
    }
};
template <class After>
__device__ __forceinline__ void tail_phase(float (&acc)[16][4], const Boxes& b2, const Boxes& b3, uint32_t tp2, uint32_t tp3, uint32_t zero, After after) {
    uint2 tp[10];
    uint32_t v[6], a0[4], a1[4];
    float Z[4], X[4], Y[4];
    b2.load(0, v, zero);
#pragma unroll
    for (int i = 0; i < 5; i++) { const uint4 c = lds128(tp2 + 160 * i); tp[i] = make_uint2(c.x, c.y); tp[5 + i] = make_uint2(c.z, c.w); }
#pragma unroll
    for (int j = -1; j < 20; j++) {
        if (j < 19) {
            (j < 11 ? b2 : b3).sums(v, Z, X, Y);
            if (j < 10) b2.load(j + 2, v, zero); else if (j < 18) b3.load(j - 10, v, zero);
        }
        if (j >= 0 && j < 12) {
#pragma unroll
            for (int b = 0; b < 5; b++) if (j + 4 + b < 16) mma_v(acc[j + 4 + b], a1, tp[5 + b].x, tp[5 + b].y);
        }
        if (j < 11) { a1[0] = pack_v(Z[0], Z[1]); a1[1] = pack_w(X[0], X[1]); a1[2] = pack_v(Z[2], Z[3]); a1[3] = pack_w(X[2], X[3]); }
        if (j >= 0 && j < 12) {
#pragma unroll
            for (int b = 0; b < 5; b++) if (j + 4 + b < 16) mma_v(acc[j + 4 + b], a0, tp[b].x, tp[b].y);
            if (j >= 7 && j < 11) { tp[11 - j] = lds64(tp3 + 80 * (10 - j)); tp[16 - j] = lds64(tp3 + 80 * (14 - j)); }
        } else if (j >= 12) {
#pragma unroll
            for (int b = 0; b < 8; b++) if (j - 4 + b < 16) mma_v(acc[j - 4 + b], a0, tp[b < 4 ? b + 1 : b + 2].x, tp[b < 4 ? b + 1 : b + 2].y);
        }
        if (j < 11) { a0[0] = pack_v(X[0], X[1]); a0[1] = pack_v(Y[0], Y[1]); a0[2] = pack_v(X[2], X[3]); a0[3] = pack_v(Y[2], Y[3]); }
        else if (j < 19) { a0[0] = pack_v(X[0], X[1]); a0[1] = pack_v(Y[0], Y[1]); a0[2] = pack_v(Z[2], Z[3]); a0[3] = pack_v(X[2], X[3]); }
        after(j);
    }
}
template <int G>
__device__ __forceinline__ void emit(const float (&acc)[16][4], uint32_t dst0, uint32_t dst1, uint32_t bar0, uint32_t bar1) {
#pragma unroll
    for (int o = 0; o < 2; o++)
#pragma unroll
        for (int hf = 0; hf < 2; hf++) {
            const int n = 8 * G + 4 * o;
            st_async128((o ? dst1 : dst0) + G * 16384 + hf * 512, pack_bf16(acc[n][2 * hf], acc[n][2 * hf + 1]), pack_bf16(acc[n + 1][2 * hf], acc[n + 1][2 * hf + 1]),
                        pack_bf16(acc[n + 2][2 * hf], acc[n + 2][2 * hf + 1]), pack_bf16(acc[n + 3][2 * hf], acc[n + 3][2 * hf + 1]), (o ? bar1 : bar0) + 8 * G);
        }
}
__device__ __forceinline__ void finish(uint32_t src, uint32_t xa) {
    uint32_t s[4][4];
    uint4 x[4];
#pragma unroll
    for (int i = 0; i < 4; i++) {
        ldsm4t(s[i], (src ^ ((i & 1) << 5)) + (i >> 1) * 8192);
        x[i] = lds128((xa ^ ((i >> 1) << 4)) + (i & 1) * 256);
    }
#pragma unroll
    for (int i = 0; i < 4; i++)
        sts128((xa ^ ((i >> 1) << 4)) + (i & 1) * 256, badd2(x[i].x, s[i][0]), badd2(x[i].y, s[i][1]), badd2(x[i].z, s[i][2]), badd2(x[i].w, s[i][3]));
}

__device__ __noinline__ float centred_var(uint32_t rows, float mu, int lane) {
    float var = 0.f;
#pragma unroll 1
    for (int rr = 0; rr < 16; rr++) {
        const float c0 = __shfl_sync(0xffffffffu, mu, rr);
        float c = 0.f;
#pragma unroll 1
        for (int k = 0; k < 16; k++) {
            const uint32_t q = lds32(rows + rr * ROW_PITCH + k * 128 + lane * 4);
            const float d0 = bf_lo(q) - c0, d1 = bf_hi(q) - c0;
            c = fmaf(d0, d0, fmaf(d1, d1, c));
        }
#pragma unroll 1
        for (int o = 16; o; o >>= 1) c += __shfl_xor_sync(0xffffffffu, c, o);
        if ((lane & 15) == rr) var = c * (1.f / DM);
    }
    return var;
}
__device__ __noinline__ float centred_score(uint32_t rows, uint32_t wbuf, uint32_t s0, uint32_t s1, int lane) {
    float sc = 0.f;
#pragma unroll 1
    for (int rr = 0; rr < 16; rr++) {
        const uint32_t t0 = __shfl_sync(0xffffffffu, s0, rr), t1 = __shfl_sync(0xffffffffu, s1, rr);
        float c = 0.f;
#pragma unroll 1
        for (int k = 0; k < 16; k++) {
            const uint32_t xn = normalize2(lds32(rows + rr * ROW_PITCH + k * 128 + lane * 4), t0, t1);
            const uint32_t wq = lds32(wbuf + (k >> 2) * 1024 + (k & 3) * 128 + lane * 4);
            c = fmaf(bf_lo(xn), bf_lo(wq), fmaf(bf_hi(xn), bf_hi(wq), c));
        }
#pragma unroll 1
        for (int o = 16; o; o >>= 1) c += __shfl_xor_sync(0xffffffffu, c, o);
        if ((lane & 15) == rr) sc = c;
    }
    return sc;
}

__global__ void __cluster_dims__(2, 1, 1) __launch_bounds__(NTHR, 1)
fused_kernel(const __grid_constant__ Ptrs p, const __grid_constant__ Maps maps) {
    extern __shared__ __align__(1024) unsigned char smem[];
    const int tid = threadIdx.x, lane = tid & 31, b = blockIdx.x;
    const int dch = 8 * b + (tid >> 5) - 4;
    uint2 la, aim, cre, cim;
    uint32_t ldt16, dsk16, epoch;
    uint4 wq;
    if ((uint32_t)(tid - 128) < 256u) {
        la = ldg64(p.logA + dch * NMODE + 4 * lane); aim = ldg64(p.Aim + dch * NMODE + 4 * lane);
        cre = ldg64(p.Cre + dch * NMODE + 4 * lane); cim = ldg64(p.Cim + dch * NMODE + 4 * lane);
        ldt16 = ldg16(p.ldt + dch); dsk16 = ldg16(p.dsk + dch);
    }
    if (tid < 128) { wq = ldg128(p.wr + 8 * tid); epoch = ld_relaxed_32(&p.sc->epoch); }
    const uint32_t sb = s_u32(smem);
    const int warp = __shfl_sync(0xffffffffu, tid >> 5, 0);
    const int h = b & 1, cl = b >> 1;
    const uint32_t bar0 = sb + OFF_BAR;
    const int m = lane >> 3, r = lane & 7, g = lane >> 2, t = lane & 3;
    const bool has_gu = b < GU_CTAS;
    if (warp == 4) { STAMP(0); GSTAMP(24); }

    if (warp >= 12) {
        asm volatile("setmaxnreg.dec.sync.aligned.u32 24;");
        const bool el = warp == 13 && elect_one();
        if (el) {
#pragma unroll
            for (int j = 0; j < 4; j++) mbar_init(bar0 + 8 * (B_ROW + j), 1);
            asm volatile("fence.mbarrier_init.release.cluster;" ::: "memory");
            fence_async();
#pragma unroll 1
            for (int j = 0; j < 4; j++) {
                mbar_expect_tx(bar0 + 8 * (B_ROW + j), 8192);
#pragma unroll
                for (int i = 0; i < 4; i++)
                    bulk_g2s(sb + OFF_VT + (4 * j + i) * ROW_PITCH, p.u + (size_t)(16 * b + 4 * j + i) * DM, 2048, bar0 + 8 * (B_ROW + j));
            }
        }
        if (warp == 14 && elect_one()) {
#pragma unroll
            for (int i = B_XT; i < NBAR; i++) mbar_init(bar0 + 8 * i, i == B_SFREE ? 2 : (i >= B_ST && i < B_FULL) ? 4 : 1);
            asm volatile("fence.mbarrier_init.release.cluster;" ::: "memory");
            fence_async();
            mbar_expect_tx(bar0 + 8 * B_XT, 65536);
            mbar_expect_tx(bar0 + 8 * B_RECV, 16384);
            mbar_expect_tx(bar0 + 8 * B_RECV + 8, 16384);
            mbar_expect_tx(bar0 + 8 * B_RED, 512);
        }
        if (warp == 15 && elect_one()) {
#pragma unroll
            for (int i = 0; i < 5; i++) asm volatile("prefetch.tensormap [%0];" ::"l"(&maps.u + i) : "memory");
        }
        __syncwarp();
        cluster_arrive();
        cluster_wait();
        STAMP(18);
        if (warp == 12 && has_gu) {
            st_relaxed_128(&p.sc->h[b * 128 + 4 * lane], 0u, 0u, 0u, 0u);
            asm volatile("fence.acq_rel.gpu;" ::: "memory");
            __syncwarp();
            mbar_wait(bar0 + 8 * B_LN, 0);
            if (lane == 0) { st_relaxed_32(&p.sc->clr[b], lds32(sb + OFF_MISC)); mbar_arrive(bar0 + 8 * B_CLR); }
        }
        if (el) {
#pragma unroll 1
            for (int i = 0; i < 16; i++) {
                if ((i & 3) == 0) mbar_wait(bar0 + 8 * B_ROW + 2 * i, 0);
                tma_load_tile(sb + OFF_XT + h * 32768 + (i & 1) * 16384 + (i >> 1) * 2048, &maps.u, 16 * cl, i & 14, 16 * (i & 1) + 8 * h, bar0 + 8 * B_XT);
            }
            mbar_wait(bar0 + 8 * GATE, 0);
            const int i0 = has_gu ? 0 : 16;
#pragma unroll 1
            for (int i = i0; i < 24; i++) {
                const int j = i - (i < WIN_SW ? WIN0 : WIN1), s = i < 12 ? i : i - 12;
                if (j >= i0) mbar_wait(bar0 + 8 * (B_FULL + (j < 12 ? j : j - 12)), has_gu && j >= 12);
                if (s == 5) mbar_wait(bar0 + 8 * B_V, 0);
                if (i >= 12 && has_gu) mbar_wait(bar0 + 8 * (B_FREE + (s >> 2)), 0);
                const uint32_t dst = sb + OFF_RING + (s < 8 ? s * 8192 : (2 * s - 8) * 8192 + 4096), bar = bar0 + 8 * (B_FULL + s);
                const uint32_t dst2 = dst + (s < 8 ? 4096 : 8192);
                if (i < 16) {
                    mbar_expect_tx(bar, 8192);
                    tma_load_perm(dst, &maps.wg, 32 * b, 2 * i, bar);
                    tma_load_perm(dst2, &maps.wu, 32 * b, 2 * i, bar);
                } else {
                    const int c1 = 1792 * h + 448 * (i & 3) + 56 * (i & 4);
                    mbar_expect_tx(bar, 7168);
                    tma_load_2d(dst, &maps.wd, 16 * cl, c1, bar);
                    tma_load_2d(dst2, &maps.wd, 16 * cl, c1 + 112, bar);
                }
            }
            STAMP(19);
        }
    } else if (warp >= 4) {
        const int w = warp - 4;
        cluster_arrive();
        asm volatile("setmaxnreg.inc.sync.aligned.u32 168;");
        const uint32_t vrow = sb + OFF_VT + w * VT_PITCH + VT_PAD, tab = sb + OFF_PRIV + w * 8192;
        const uint32_t so = sb + OFF_XT + (8 * h + w) * 1024 + ((lane ^ ((w & 1) << 1)) << 4);
        uint32_t dst0 = mapa(so + 32768, 0), dst1 = mapa(so, 1);
        const uint32_t rb0 = mapa(bar0 + 8 * B_RECV, 0), rb1 = mapa(bar0 + 8 * B_RECV, 1);
        const uint32_t box = sb + OFF_XT + h * 32768 + w * 2048;
        uint32_t fs = sb + OFF_XT + (h ^ 1) * 32768 + (2 * m + (r & 1)) * 1024 + (w >> 2) * 512 + (((8 * (w & 3) + (r & 4) + ((r >> 1) & 1)) ^ ((r & 1) << 1)) << 4);
        uint32_t fx = box + (g >> 1) * 512 + (t >> 1) * 144 + (2 * (t & 1) + (g & 1)) * 32;
        uint32_t tpo = 80 + (g - 2 * t) * 8 - (g < 2 * t ? 16 : 0);
        pin(dst0); pin(dst1); pin(fs); pin(fx); pin(tpo);
        const Boxes b2(vrow, lane, -18, 5, 7, 0, 4), b3(vrow, lane, -20, 1, 7, 0, 8);
        if (__any_sync(0xffffffffu, (((dst0 | dst1 | fs) | (fx | tpo | b2.q[0]) | (b2.q[1] | b2.q[2] | b2.q[3])) | ((b2.ha[0] | b2.ha[1] | b2.ha[2]) | (b2.ha[3] | b3.q[0] | b3.q[1]) |
             (b3.q[2] | b3.q[3] | b3.ha[0])) | (b3.ha[1] | b3.ha[2] | b3.ha[3])) & p.zero)) __trap();
        cluster_wait();
        pin(la.x); pin(la.y); pin(aim.x); pin(aim.y); pin(cre.x); pin(cre.y); pin(cim.x); pin(cim.y); pin(ldt16); pin(dsk16);
        kgen(tab, lane, la, aim, cre, cim, bf_round(ex2f(bf_lo(ldt16) * 1.4426950408889634f)), 1.f + bf_lo(dsk16), dch, [&]() {
            STAMP(21);
        });
        STAMP(1); KSTAMP(6);
        const uint32_t pb = tab + T_DENSE + (g - 2 * t) * 4;
        uint32_t A0[4][4];
#pragma unroll
        for (int i = 0; i < 4; i++) load_toep(A0[i], pb + 512 * i, p.zero);
        {
            uint4 q[4], x[8];
            mbar_wait(bar0 + 8 * B_XT, 0);
            const uint32_t xa = sb + OFF_XT + (w & 2) * 16384 + (w >> 2) * 16384 + (w & 1) * 1024 + (g >> 1) * 2048 + (g & 1) * 128 + t * 32 + ((h ^ (g & 1)) << 4);
            const uint32_t va = sb + OFF_VT + (2 * m + (r & 1)) * VT_PITCH + VT_PAD + (16 * w + (r >> 1)) * 32;
#pragma unroll
            for (int i = 0; i < 8; i++) x[i] = lds128(xa + (i & 1) * 8192 + (i >> 1) * 256);
            mbar_wait(bar0 + 8 * B_ST, 0);
#pragma unroll
            for (int n = 0; n < 4; n++) q[n] = lds128(sb + OFF_ST + 2048 * w + 512 * n + 16 * lane);
            if (lane < 15) sts128(vrow - VT_PAD + lane * 16, 0, 0, 0, 0);
            STAMP(2); GSTAMP(28);
#pragma unroll
            for (int i = 0; i < 8; i++) {
                const uint32_t s0 = (i & 1) ? q[i >> 1].z : q[i >> 1].x, s1 = (i & 1) ? q[i >> 1].w : q[i >> 1].y;
                stsm4t(va + (i >> 1) * 128 + (((i ^ (i >> 1)) & 1) << 4), normalize2(x[i].x, s0, s1), normalize2(x[i].y, s0, s1),
                       normalize2(x[i].z, s0, s1), normalize2(x[i].w, s0, s1));
            }
            named_sync(2, 256);
            if (tid == 128) { mbar_arrive(bar0 + 8 * B_V); mbar_arrive_peer(mapa(bar0 + 8 * B_SFREE, h ^ 1)); }
        }
        STAMP(3); KSTAMP(7);
        float acc[16][4];
#pragma unroll
        for (int i = 0; i < 16; i++) { acc[i][0] = acc[i][1] = acc[i][2] = acc[i][3] = 0.f; }
        dense_phase(acc, vrow, pb, A0, p.zero, lane);
        STAMP(4); KSTAMP(8);
        tail_phase(acc, b2, b3, tab + T_R2 + 2 * tpo, tab + T_R3 + tpo, p.zero, [&](int j) {
            if (j == 3) {
                mbar_wait(bar0 + 8 * B_SFREE, 0);
                emit<0>(acc, dst0, dst1, rb0, rb1);
                STAMP(5);
            }
            if (j == 7) {
                mbar_wait(bar0 + 8 * B_RECV, 0);
                finish(fs, fx);
                fence_async();
                __syncwarp();
                if (elect_one()) tma_store_tile(&maps.out, box, 16 * cl, 2 * w, 8 * h);
                STAMP(20);
            }
        });
        emit<1>(acc, dst0, dst1, rb0, rb1);
        STAMP(30);
        mbar_wait(bar0 + 8 * (B_RECV + 1), 0);
        STAMP(6);
        finish(fs + 16384, fx + 16384);
        const bool ready = mbar_test(bar0 + 8 * B_UPD, 0);
        const bool el = elect_one();
#pragma unroll 1
        for (int pass = 0; pass < 2; pass++) {
            if ((pass != 0) == ready) {
                fence_async();
                __syncwarp();
                if (el) tma_store_tile(&maps.out, box + 16384, 16 * cl, 2 * w, 16 + 8 * h);
            } else {
                if (el) asm volatile("cp.async.bulk.wait_group 0;" ::: "memory");
                __syncwarp();
                mbar_wait(bar0 + 8 * B_UPD, 0);
                const int tok = 2047 - (int)((lds32(sb + OFF_MISC + 48 + 8 * g) >> 2) & 2047);
                if ((((tok >> 6) & 8) | ((tok >> 1) & 7)) == 8 * h + w) {
                    const uint32_t xa = box + (tok >> 10) * 16384 + ((tok >> 6) & 7) * 256 + (tok & 1) * 128 + ((tok >> 4) & 3) * 32 + (((t >> 1) ^ (tok & 1)) << 4) + (t & 1) * 8;
                    const uint2 o0 = lds64(xa);
                    const float4 up = lds128f(sb + OFF_RED + 16 * lane);
                    const uint2 o1 = make_uint2(badd2(o0.x, pack_bf16(up.x, up.y)), badd2(o0.y, pack_bf16(up.z, up.w)));
                    if (ready && tok >= 1024) sts64(xa, o1.x, o1.y);
                    else *reinterpret_cast<uint2*>(p.out + (size_t)tok * DM + 16 * cl + 4 * t) = o1;
                }
            }
        }
        if (el) asm volatile("cp.async.bulk.wait_group.read 0;" ::: "memory");
        STAMP(7);
    } else {
        const int a = warp;
        cluster_arrive();
        asm volatile("setmaxnreg.inc.sync.aligned.u32 152;");
        if (tid < 16) { st_relaxed_64(p.sc->stat + 16 * b + 2 * r + m, 0u, epoch); st_relaxed_32(p.sc->key + 16 * b + tid, epoch); }
        const uint32_t tag = epoch + 1u, misc = sb + OFF_MISC;
        if (tid == 0) sts32(misc, tag);
        if (tid < 64) sts32(sb + OFF_RED + 4 * tid, 0);
        const uint32_t wbuf = sb + OFF_LN + a * 1024, part = sb + OFF_LN + 4096;
        {
            sts128(wbuf + 16 * lane, wq.x, wq.y, wq.z, wq.w);
            sts128(wbuf + 512 + 16 * lane, 0x3f803f80u, 0x3f803f80u, 0x3f803f80u, 0x3f803f80u);
            float wsum = ((bf_lo(wq.x) + bf_hi(wq.x)) + (bf_lo(wq.y) + bf_hi(wq.y))) + ((bf_lo(wq.z) + bf_hi(wq.z)) + (bf_lo(wq.w) + bf_hi(wq.w)));
#pragma unroll
            for (int o = 16; o; o >>= 1) wsum += __shfl_xor_sync(0xffffffffu, wsum, o);
            sts32f(part + 1024 + 4 * a, wsum);
            uint32_t wf[4][4];
#pragma unroll
            for (int i = 0; i < 4; i++) ldsm4(wf[i], wbuf + ((uint32_t)(r - 1) < 2u ? 16 * (r - 1) : 512) + 32 * m + 128 * i);
            uint32_t ra = sb + OFF_VT + r * ROW_PITCH + 512 * a + 16 * m, pa = part + a * 256 + g * 16;
            cluster_wait();
            STAMP(22);
#pragma unroll 1
            for (int hf = 0; hf < 2; hf++) {
                mbar_wait(bar0 + 8 * B_ROW + 16 * hf, 0);
                mbar_wait(bar0 + 8 * B_ROW + 16 * hf + 8, 0);
                STAMP(23);
                uint32_t x[8][4];
                float cs[2][4], q[8][4];
#pragma unroll
                for (int i = 0; i < 40; i++) (i < 8 ? cs[i >> 2 & 1] : q[(i - 8) >> 2 & 7])[i & 3] = 0.f;
#pragma unroll
                for (int k = 0; k < 8; k++) ldsm4(x[k], ra + k * 64);
                const uint32_t dep = (x[6][3] | x[7][3]) & p.zero;
                x[0][0] |= dep; x[0][2] |= dep; x[1][0] |= dep; x[1][2] |= dep;
#pragma unroll
                for (int k = 0; k < 8; k++) {
                    mma_bf16(cs[k & 1], x[k][0], x[k][1], x[k][2], x[k][3], wf[k >> 1][2 * (k & 1)], wf[k >> 1][2 * (k & 1) + 1]);
#pragma unroll
                    for (int i = 0; i < 4; i++) mma_bf16_k8(q[4 * (k & 1) + i], x[k][i & 2], x[k][i | 1], x[k][i]);
                }
                const float c2 = cs[0][2] + cs[1][2];
                if (t == 0) sts64f(pa, (cs[0][0] + cs[1][0]) + c2, cs[0][1] + cs[1][1]);
                if (t == 1) sts32f(pa + 12, c2);
                const float e0 = ((q[0][0] + q[2][0]) + (q[4][0] + q[6][0])) + ((q[1][2] + q[3][2]) + (q[5][2] + q[7][2]));
                const float e1 = ((q[0][1] + q[2][1]) + (q[4][1] + q[6][1])) + ((q[1][3] + q[3][3]) + (q[5][3] + q[7][3]));
                if (t == (g >> 1)) sts32f(pa + 8, (g & 1) ? e1 : e0);
                ra += 8 * ROW_PITCH; pa += 128;
            }
        }
        STAMP(31);
        named_sync(1, 128);
        if (a == 0) {
            const uint32_t pa = part + (lane & 15) * 16;
            const float4 p0 = lds128f(pa), p1 = lds128f(pa + 256), p2 = lds128f(pa + 512), p3 = lds128f(pa + 768), ws = lds128f(part + 1024);
            const float mu = ((p0.x + p1.x) + (p2.x + p3.x)) * (1.f / DM);
            float var = ((p0.z + p1.z) + (p2.z + p3.z)) * (1.f / DM) - mu * mu;
            const bool centred = __any_sync(0xffffffffu, !(mu * mu <= 4.f * var));
            if (centred) var = centred_var(sb + OFF_VT, mu, lane);
            const float ri = rcpf(bf_round(sqrtaf(bf_round(bf_round(var) + 1e-5f))));
            const uint32_t s0 = pack_bf16(mu, ri), s1 = (pack_bf16(ri - bf_hi(s0), 0.f) & 0xfffcu) | (tag & 3);
            if (lane < 16) st_relaxed_64(p.sc->stat + 16 * b + 2 * r + m, s0, s1);
            STAMP(41);
            float sc = ((((p0.y + p1.y) + (p2.y + p3.y)) + ((p0.w + p1.w) + (p2.w + p3.w))) - bf_lo(s0) * ((ws.x + ws.y) + (ws.z + ws.w))) * ri;
            if (centred) sc = centred_score(sb + OFF_VT, sb + OFF_LN, s0, s1, lane);
            if (lane < 16) st_relaxed_32(p.sc->key + 16 * b + lane, (order_key(pack_bf16(sc, 0.f)) << 16) | ((2047 - 16 * b - lane) << 2) | (tag & 3));
            __syncwarp();
            if (elect_one()) mbar_arrive(bar0 + 8 * B_LN);
            STAMP(9); GSTAMP(25);
        }
        const uint32_t slot0 = sb + OFF_RING + a * 8192, slot2 = sb + OFF_PRIV + a * 16384 + 4096, fbar = bar0 + 8 * (B_FULL + a);
        uint32_t mine = 0;
        {
            uint4 q[4], u[8];
            const uint2* sp = p.sc->stat + 512 * a + 16 * t + 2 * g;
            mbar_wait(bar0 + 8 * B_LN, 0);
            uint32_t f = epoch;
#pragma unroll 1
            for (uint32_t it = 0;; spin_guard(it)) {
                if ((f ^ tag) & 3) f = ld_relaxed_32(&p.sc->stat[16 * tid].y);
                if (__all_sync(0xffffffffu, ((f ^ tag) & 3) == 0)) break;
            }
#pragma unroll 1
            for (uint32_t it = 0;; spin_guard(it)) {
                uint32_t bad = 0;
#pragma unroll
                for (int n = 0; n < 8; n++) u[n] = ld_relaxed_128(sp + 64 * n);
#pragma unroll
                for (int n = 0; n < 4; n++) q[n] = ld_relaxed_128(p.sc->key + 512 * a + 128 * n + 4 * lane);
#pragma unroll
                for (int n = 0; n < 8; n++) bad |= u[n].y ^ tag;
                if (__all_sync(0xffffffffu, (bad & 3) == 0)) break;
            }
#pragma unroll
            for (int n = 0; n < 8; n++) sts128(sb + OFF_ST + 4096 * a + 512 * n + 16 * lane, u[n].x, u[n].y, u[n].z, u[n].w);
            __syncwarp();
            if (elect_one()) mbar_arrive(bar0 + 8 * B_ST);
            STAMP(8);
#pragma unroll 1
            for (uint32_t it = 0;; spin_guard(it)) {
                uint32_t bad = 0;
#pragma unroll
                for (int n = 0; n < 4; n++) bad |= q[n].x ^ tag;
                if (__all_sync(0xffffffffu, (bad & 3) == 0)) break;
#pragma unroll
                for (int n = 0; n < 4; n++) ld_relaxed_128_unless(q[n], p.sc->key + 512 * a + 128 * n + 4 * lane, ((q[n].x ^ tag) & 3) == 0);
            }
            STAMP(10);
            auto below = [&](uint32_t x) {
                uint32_t d = 0xffffffffu;
                x -= 1;
#pragma unroll
                for (int n = 0; n < 4; n++) d = min(min(d, min(x - q[n].x, x - q[n].y)), min(x - q[n].z, x - q[n].w));
                return d <= x ? x - d : 0u;
            };
            const uint32_t mx0 = below(0);
            const uint32_t gm = __reduce_max_sync(lane < 16 ? 0xffffu : 0xffff0000u, mx0);
            if ((lane & 15) == 0) sts32(misc + 16 + (tid >> 2), gm);
            named_sync(1, 128);
            if (b == 0 && tid == 0) st_relaxed_32(&p.sc->epoch, tag);
            const uint4 t0 = lds128(misc + 16), t1 = lds128(misc + 32);
            uint32_t tau = min(min(min(t0.x, t0.y), min(t0.z, t0.w)), min(min(t1.x, t1.y), min(t1.z, t1.w)));
            uint32_t mx = mx0, cnt = 0;
            bool slow = false;
#pragma unroll 1
            while (true) {
                if (slow) tau = __reduce_max_sync(0xffffffffu, mx);
                const uint32_t bal = __ballot_sync(0xffffffffu, mx >= tau);
                if (bal == 0 || (slow && cnt == 8)) break;
                if (cnt + __popc(bal) > 16) { slow = true; cnt = 0; mx = mx0; continue; }
                if (mx >= tau) { sts32(sb + OFF_RED + 64 * a + 4 * (cnt + __popc(bal & ((1u << lane) - 1u))), mx); mx = below(mx); }
                cnt += __popc(bal);
            }
            named_sync(1, 128);
            uint2 k = lds64(sb + OFF_RED + 8 * lane);
#pragma unroll
            for (int j = 0; j < 8; j++) {
                const uint32_t top = __reduce_max_sync(0xffffffffu, max(k.x, k.y));
                if (g == j) mine = top;
                if (k.x == top) k.x = 0;
                if (k.y == top) k.y = 0;
            }
        }
        STAMP(11);
        const int tok = 2047 - (int)((mine >> 2) & 2047);
        uint4 xq[8];
        if (has_gu) {
#pragma unroll
            for (int j = 0; j < 8; j++) xq[j] = ldg128(p.u + (size_t)tok * DM + 64 * a + 8 * t + (j >> 1) * 256 + (j & 1) * 32);
        }
        const uint2 st = ld_relaxed_64(p.sc->stat + (tok & ~15) + 2 * (tok & 7) + ((tok >> 3) & 1));
        if (a == 0 && t == 0) sts64(misc + 48 + 8 * g, mine, __float_as_uint(bf_hi(st.x) + bf_lo(st.y)));
        named_sync(1, 128);
        if (tid == 0) mbar_arrive_peer(mapa(bar0 + 8 * B_SFREE, h ^ 1));
        if (has_gu) {
#pragma unroll
            for (int j = 0; j < 8; j++) xq[j] = make_uint4(bsub2_lo(xq[j].x, st.x), bsub2_lo(xq[j].y, st.x), bsub2_lo(xq[j].z, st.x), bsub2_lo(xq[j].w, st.x));
            STAMP(12);
            float gacc[8][4];
#pragma unroll
            for (int i = 0; i < 8; i++) { gacc[i][0] = gacc[i][1] = gacc[i][2] = gacc[i][3] = 0.f; }
            const uint32_t ko = (r + ((m >> 1) << 3)) * 64 + (((r >> 1) & 3) << 4);
#pragma unroll
            for (int c = 0; c < 4; c++) {
                mbar_wait(fbar + 32 * (c % 3), c / 3);
                STAMP(36 + c);
                const uint32_t rowa = (c == 2 ? slot2 + (m & 1) * 8192 : slot0 + (c == 1) * 32768 + (m & 1) * 4096) + ko;
                uint32_t af[16][4];
#pragma unroll
                for (int ks = 0; ks < 4; ks++)
#pragma unroll
                    for (int mt = 0; mt < 4; mt++) ldsm4t(af[4 * ks + mt], (rowa ^ (mt << 4)) + ks * 1024);
                const uint32_t dep = ((af[12][3] | af[13][3]) | (af[14][3] | af[15][3])) & p.zero;
                __syncwarp();
                if (c < 3 && elect_one()) mbar_arrive(bar0 + 8 * (B_FREE + c) + dep);
#pragma unroll
                for (int ks = 0; ks < 4; ks++) {
                    uint4 q = xq[2 * c + (ks >> 1)];
                    if (ks < 2) { q.x |= dep; q.z |= dep; }
#pragma unroll
                    for (int mt = 0; mt < 4; mt++)
                        mma_bf16(gacc[4 * (ks & 1) + mt], af[4 * ks + mt][0], af[4 * ks + mt][1], af[4 * ks + mt][2], af[4 * ks + mt][3],
                                 (ks & 1) ? q.z : q.x, (ks & 1) ? q.w : q.y);
                }
            }
            STAMP(13);
#pragma unroll
            for (int mt = 0; mt < 4; mt++) {
#pragma unroll
                for (int j = 0; j < 4; j++) gacc[mt][j] += gacc[4 + mt][j];
                sts128f(slot0 + mt * 512 + lane * 16, gacc[mt]);
            }
            named_sync(1, 128);
            const uint32_t base = sb + OFF_RING + 16 * tid;
            const float4 p0 = lds128f(base), p1 = lds128f(base + 8192), p2 = lds128f(base + 16384), p3 = lds128f(base + 24576);
            const float r0 = lds32f(misc + 52 + 16 * t), r1 = lds32f(misc + 60 + 16 * t);
            const float g0 = bf_round(((p0.x + p1.x) + (p2.x + p3.x)) * r0), g1 = bf_round(((p0.y + p1.y) + (p2.y + p3.y)) * r1);
            const float h0 = bf_round(g0 * rcpf(1.f + ex2f(-1.4426950408889634f * g0))) * bf_round(((p0.z + p1.z) + (p2.z + p3.z)) * r0);
            const float h1 = bf_round(g1 * rcpf(1.f + ex2f(-1.4426950408889634f * g1))) * bf_round(((p0.w + p1.w) + (p2.w + p3.w)) * r1);
            uint32_t hw;
            asm volatile("movmatrix.sync.aligned.m8n8.trans.b16 %0, %1;" : "=r"(hw) : "r"(pack_bf16(h0, h1)));
            sts32(sb + OFF_RING + 2048 + 16 * lane + 4 * a, hw);
            named_sync(1, 128);
            if (a == 0) {
                const uint4 q = lds128(base + 2048);
                mbar_wait(bar0 + 8 * B_CLR, 0);
                st_relaxed_128(&p.sc->h[b * 128 + 4 * lane], q.x, q.y, q.z, q.w ? q.w : 0x80008000u);
            }
            STAMP(14);
        }
        float dacc[4];
        {
            const uint32_t* hp = &p.sc->h[(56 * h + 14 * a) * 128];
            uint32_t hf = lane >= 14;
#pragma unroll 1
            for (uint32_t it = 0; !__all_sync(0xffffffffu, hf || ld_relaxed_32(&p.sc->clr[56 * h + 14 * a + lane]) == tag); spin_guard(it)) { }
#pragma unroll 1
            for (uint32_t it = 0;; spin_guard(it)) {
                if (hf == 0) hf = ld_relaxed_32(hp + lane * 128 + 127);
                if (__all_sync(0xffffffffu, hf != 0)) break;
            }
            STAMP(33);
            uint4 hq[14];
#pragma unroll 1
            for (uint32_t it = 0;; spin_guard(it)) {
                uint32_t mn = 0xffffffffu;
#pragma unroll
                for (int j = 0; j < 14; j++) hq[j] = ld_relaxed_128(hp + 4 * lane + j * 128);
#pragma unroll
                for (int j = 0; j < 14; j += 2) mn = min(mn, min(hq[j].w, hq[j + 1].w));
                if (__all_sync(0xffffffffu, mn != 0)) break;
            }
            STAMP(15);
            const uint32_t wo = (r + ((m >> 1) << 3)) * 32 + (((m & 1) ^ (r >> 2)) << 4);
            float d[7][4];
#pragma unroll
            for (int i = 0; i < 7; i++) { d[i][0] = d[i][1] = d[i][2] = d[i][3] = 0.f; }
#pragma unroll
            for (int s = 0; s < 2; s++) {
                mbar_wait(fbar + 32 + 32 * s, has_gu);
                uint32_t af[14][4];
#pragma unroll
                for (int j = 0; j < 14; j++) ldsm4t(af[j], (s ? slot2 + (j / 7) * 8192 : slot0 + 32768 + (j / 7) * 4096) + wo + (j % 7) * 512);
                const uint32_t dep = (af[11][3] | af[12][3] | af[13][3]) & p.zero;
#pragma unroll
                for (int j = 0; j < 14; j++) {
                    const uint4 q = hq[7 * s + (j >> 1)];
                    mma_bf16(d[j % 7], af[j][0], af[j][1], af[j][2], af[j][3], ((j & 1) ? q.z : q.x) | (j < 7 ? dep : 0u), (j & 1) ? q.w : q.y);
                }
            }
#pragma unroll
            for (int j = 0; j < 4; j++) dacc[j] = ((d[0][j] + d[1][j]) + (d[2][j] + d[3][j])) + ((d[4][j] + d[5][j]) + d[6][j]);
        }
        STAMP(16);
        {
            sts128f(slot0 + 4096 + lane * 16, dacc);
            named_sync(1, 128);
            const int tk = tid >> 4, col = tid & 15;
            const uint32_t base = sb + OFF_RING + 4096 + ((col & 7) * 4 + (tk >> 1)) * 16 + (((col >> 3) << 1) + (tk & 1)) * 4;
            const float y0 = (lds32f(base) + lds32f(base + 8192)) + (lds32f(base + 16384) + lds32f(base + 24576));
            const uint32_t red = sb + OFF_RED + 4 * tid, key = lds32(misc + 48 + 8 * tk);
            mbar_wait(bar0 + 8 * B_SFREE, 0);
            asm volatile("st.async.weak.shared::cluster.mbarrier::complete_tx::bytes.f32 [%0], %1, [%2];"
                         ::"r"(mapa(red, h ^ 1)), "f"(y0), "r"(mapa(bar0 + 8 * B_RED, h ^ 1)) : "memory");
            const float rv = __uint_as_float(unorder_key(key >> 16) << 16);
            const float sg = bf_round(rcpf(1.f + ex2f(-1.4426950408889634f * rv)));
            mbar_wait(bar0 + 8 * B_RED, 0);
            sts32f(red, bf_round(y0 + lds32f(red)) * sg);
            __syncwarp();
            if (elect_one()) mbar_arrive(bar0 + 8 * B_UPD);
        }
        STAMP(17); GSTAMP(29);
    }
}

typedef CUresult (*EncodeFn)(CUtensorMap*, CUtensorMapDataType, cuuint32_t, void*, const cuuint64_t*, const cuuint64_t*,
                             const cuuint32_t*, const cuuint32_t*, CUtensorMapInterleave, CUtensorMapSwizzle,
                             CUtensorMapL2promotion, CUtensorMapFloatOOBfill);

void make_map(EncodeFn enc, CUtensorMap* m, const void* ptr, uint64_t cols, uint64_t rows, uint32_t bc, uint32_t br,
              CUtensorMapSwizzle sw, CUtensorMapL2promotion pr) {
    cuuint64_t dims[2] = {cols, rows};
    cuuint64_t str[1] = {cols * 2};
    cuuint32_t box[2] = {bc, br};
    cuuint32_t es[2] = {1, 1};
    enc(m, CU_TENSOR_MAP_DATA_TYPE_BFLOAT16, 2, const_cast<void*>(ptr), dims, str, box, es, CU_TENSOR_MAP_INTERLEAVE_NONE, sw, pr,
        CU_TENSOR_MAP_FLOAT_OOB_FILL_NONE);
}
void make_perm_map(EncodeFn enc, CUtensorMap* m, const void* ptr) {
    cuuint64_t dims[5] = {FF, 2, 4, 4, DM / 32};
    cuuint64_t str[4] = {FF * 2, 8 * FF * 2, 2 * FF * 2, 32 * FF * 2};
    cuuint32_t box[5] = {32, 2, 4, 4, 2};
    cuuint32_t es[5] = {1, 1, 1, 1, 1};
    enc(m, CU_TENSOR_MAP_DATA_TYPE_BFLOAT16, 5, const_cast<void*>(ptr), dims, str, box, es, CU_TENSOR_MAP_INTERLEAVE_NONE,
        CU_TENSOR_MAP_SWIZZLE_64B, CU_TENSOR_MAP_L2_PROMOTION_L2_128B, CU_TENSOR_MAP_FLOAT_OOB_FILL_NONE);
}
void make_tile_map(EncodeFn enc, CUtensorMap* m, const void* ptr) {
    cuuint64_t dims[4] = {DM, 4, 16, SEQ / 64};
    cuuint64_t str[3] = {16 * DM * 2, DM * 2, 64 * DM * 2};
    cuuint32_t box[4] = {16, 4, 2, 8};
    cuuint32_t es[4] = {1, 1, 1, 1};
    enc(m, CU_TENSOR_MAP_DATA_TYPE_BFLOAT16, 4, const_cast<void*>(ptr), dims, str, box, es, CU_TENSOR_MAP_INTERLEAVE_NONE,
        CU_TENSOR_MAP_SWIZZLE_32B, CU_TENSOR_MAP_L2_PROMOTION_NONE, CU_TENSOR_MAP_FLOAT_OOB_FILL_NONE);
}

}

#define WD_PROMO CU_TENSOR_MAP_L2_PROMOTION_L2_128B
extern "C" void kernel_launch(void* const* d_in, const int* in_sizes, int n_in, void* d_out, int out_size) {
    (void)in_sizes; (void)n_in; (void)out_size;
    static EncodeFn enc = nullptr;
    static void* scratch = nullptr;
    if (!enc) {
        void* fn = nullptr;
        cudaDriverEntryPointQueryResult q;
        cudaGetDriverEntryPoint("cuTensorMapEncodeTiled", &fn, cudaEnableDefault, &q);
        enc = (EncodeFn)fn;
        cudaGetSymbolAddress(&scratch, g_scratch);
        cudaFuncSetAttribute(fused_kernel, cudaFuncAttributeMaxDynamicSharedMemorySize, SMEM_BYTES);
    }
    Maps maps;
    make_tile_map(enc, &maps.u, d_in[0]);
    make_tile_map(enc, &maps.out, d_out);
    make_perm_map(enc, &maps.wg, d_in[9]);
    make_perm_map(enc, &maps.wu, d_in[10]);
    make_map(enc, &maps.wd, d_in[11], DM, FF, 16, 112, CU_TENSOR_MAP_SWIZZLE_32B, WD_PROMO);
    Ptrs p;
    p.sc = (Scratch*)scratch;
    p.u = (const __nv_bfloat16*)d_in[0];
    p.logA = (const __nv_bfloat16*)d_in[1];
    p.Aim = (const __nv_bfloat16*)d_in[2];
    p.Cre = (const __nv_bfloat16*)d_in[3];
    p.Cim = (const __nv_bfloat16*)d_in[4];
    p.ldt = (const __nv_bfloat16*)d_in[5];
    p.dsk = (const __nv_bfloat16*)d_in[6];
    p.wr = (const __nv_bfloat16*)d_in[8];
    p.wg = (const __nv_bfloat16*)d_in[9];
    p.wu = (const __nv_bfloat16*)d_in[10];
    p.wd = (const __nv_bfloat16*)d_in[11];
    p.out = (__nv_bfloat16*)d_out;
    p.zero = 0;
    fused_kernel<<<NCTA, NTHR, SMEM_BYTES, cudaStreamPerThread>>>(p, maps);
}
```

```cpp
#include <cuda_runtime.h>
#include <cuda_bf16.h>
#include <cuda_fp16.h>
#include <cuda.h>
#include <stdint.h>

namespace {

constexpr int SEQ = 2048, DM = 1024, NMODE = 128, FF = 3584;
constexpr int NCTA = 128, NTHR = 512;
constexpr int GU_CTAS = 112;

constexpr int OFF_XT = 0;
constexpr int OFF_RING = 65536;
constexpr int OFF_PRIV = OFF_RING + 65536;
constexpr int OFF_VT = OFF_PRIV + 65536;
constexpr int VT_PAD = 32, VT_PLANE = VT_PAD + 2048, VT_PITCH = 2 * VT_PLANE, ROW_PITCH = 2064;
constexpr int OFF_BAR = OFF_VT + 8 * VT_PITCH;
constexpr int OFF_MISC = OFF_BAR + 384;
constexpr int OFF_RED = OFF_MISC + 112;
constexpr int OFF_STAMP = OFF_RED + 512;
constexpr int SMEM_BYTES = OFF_STAMP + 256;
constexpr int OFF_LN = OFF_RING + 7 * 8192;
constexpr int OFF_ST = OFF_RING + 6 * 8192;
static_assert(SMEM_BYTES <= 232448, "shared memory");

constexpr int B_ROW = 0, B_XT = 4, B_V = 5, B_SFREE = 7, B_RECV = 8, B_RED = 10, B_UPD = 11, B_ST = 12, B_FREE = 20, B_FULL = 32, B_AUX = 44, NBAR = 48;

constexpr int T_DENSE = 60;
constexpr int T_PATCH = 2208;
constexpr int T_R2 = 2368;
constexpr int T_R3 = 3296;

constexpr uint32_t SPIN_LIMIT = 1u << 20;
#define KG_UNROLL 4
constexpr int kKgUnroll = KG_UNROLL;
#define DENSE_UNROLL 1
constexpr int kDenseUnroll = DENSE_UNROLL;
#define ST_T0 3200
#define FEW_ST 0
#define FEW_H 0
#define ST_GAP 0
#define ST_PER 310
#define ST_PER2 300

struct Scratch {
    uint2 stat[SEQ];
    uint4 h[GU_CTAS * 32];
    uint32_t n_stat[4 * 32];
    uint32_t n_h[8 * 32];
    uint32_t epoch;
};
__device__ __align__(128) Scratch g_scratch;

struct Ptrs {
    Scratch* sc;
    const __nv_bfloat16 *logA, *Aim, *Cre, *Cim, *ldt, *dsk, *u, *wr;
    __nv_bfloat16* out;
    uint32_t zero;
};
struct Maps {
    CUtensorMap u, out, wg, wu, wd;
};

#define STAMP(i) do { } while (0)
#define KSTAMP(i) do { } while (0)
#define GSTAMP(i) do { } while (0)

__device__ __forceinline__ uint32_t s_u32(const void* p) { return (uint32_t)__cvta_generic_to_shared(p); }
__device__ __forceinline__ void mbar_init(uint32_t b, uint32_t n) {
    asm volatile("mbarrier.init.shared::cta.b64 [%0], %1;" ::"r"(b), "r"(n) : "memory");
}
__device__ __forceinline__ void mbar_expect_tx(uint32_t b, uint32_t bytes) {
    asm volatile("mbarrier.arrive.expect_tx.shared::cta.b64 _, [%0], %1;" ::"r"(b), "r"(bytes) : "memory");
}
__device__ __forceinline__ void mbar_arrive(uint32_t b) {
    asm volatile("mbarrier.arrive.shared::cta.b64 _, [%0];" ::"r"(b) : "memory");
}
__device__ __forceinline__ void mbar_arrive2(uint32_t b) {
    asm volatile("mbarrier.arrive.shared::cta.b64 _, [%0], 2;" ::"r"(b) : "memory");
}
__device__ __forceinline__ void mbar_arrive_peer(uint32_t b_cluster) {
    asm volatile("mbarrier.arrive.relaxed.cluster.shared::cluster.b64 _, [%0];" ::"r"(b_cluster) : "memory");
}
__device__ __forceinline__ void mbar_wait(uint32_t b, uint32_t parity) {
    asm volatile("{\n\t.reg .pred p;\n\t.reg .u32 c;\n\tmov.u32 c, 0;\n"
                 "W:\n\tmbarrier.try_wait.parity.shared::cta.b64 p, [%0], %1, 4000;\n\t@p bra D;\n\t"
                 "add.u32 c, c, 1;\n\tsetp.lt.u32 p, c, 1048576;\n\t@p bra W;\n\ttrap;\nD:\n\t}"
                 ::"r"(b), "r"(parity) : "memory");
}
template <int NS>
__device__ __forceinline__ void mbar_wait_lazy(uint32_t b, uint32_t parity) {
    asm volatile("{\n\t.reg .pred p;\n\t.reg .u32 c;\n\tmov.u32 c, 0;\n"
                 "W:\n\tmbarrier.test_wait.parity.shared::cta.b64 p, [%0], %1;\n\t@p bra D;\n\tnanosleep.u32 %2;\n\t"
                 "add.u32 c, c, 1;\n\tsetp.lt.u32 p, c, 4194304;\n\t@p bra W;\n\ttrap;\nD:\n\t}"
                 ::"r"(b), "r"(parity), "n"(NS) : "memory");
}
__device__ __forceinline__ bool mbar_test(uint32_t b, uint32_t parity) {
    uint32_t ok;
    asm volatile("{ .reg .pred p; mbarrier.test_wait.parity.shared::cta.b64 p, [%1], %2; selp.u32 %0, 1, 0, p; }" : "=r"(ok) : "r"(b), "r"(parity) : "memory");
    return __all_sync(0xffffffffu, ok != 0);
}
__device__ __forceinline__ bool elect_one() {
    uint32_t p;
    asm volatile("{ .reg .pred P; elect.sync _|P, 0xffffffff; selp.u32 %0, 1, 0, P; }" : "=r"(p));
    return p != 0;
}
__device__ __forceinline__ uint32_t mapa(uint32_t a, uint32_t rank) {
    uint32_t r;
    asm("mapa.shared::cluster.u32 %0, %1, %2;" : "=r"(r) : "r"(a), "r"(rank));
    return r;
}
__device__ __forceinline__ void cluster_arrive() { asm volatile("barrier.cluster.arrive.relaxed.aligned;" ::: "memory"); }
__device__ __forceinline__ void cluster_wait() { asm volatile("barrier.cluster.wait.acquire.aligned;" ::: "memory"); }
__device__ __forceinline__ void tma_load_2d(uint32_t dst, const CUtensorMap* m, int c0, int c1, uint32_t bar) {
    asm volatile("cp.async.bulk.tensor.2d.shared::cluster.global.mbarrier::complete_tx::bytes [%0], [%1, {%3, %4}], [%2];"
                 ::"r"(dst), "l"(m), "r"(bar), "r"(c0), "r"(c1) : "memory");
}
__device__ __forceinline__ void tma_load_tile(uint32_t dst, const CUtensorMap* m, int c0, int c2, int c3, uint32_t bar) {
    asm volatile("cp.async.bulk.tensor.4d.shared::cluster.global.mbarrier::complete_tx::bytes.multicast::cluster [%0], [%1, {%3, %4, %5, %6}], [%2], %7;"
                 ::"r"(dst), "l"(m), "r"(bar), "r"(c0), "r"(0), "r"(c2), "r"(c3), "h"((uint16_t)3) : "memory");
}
__device__ __forceinline__ void tma_store_tile(const CUtensorMap* m, uint32_t src, int c0, int c2, int c3) {
    asm volatile("cp.async.bulk.tensor.4d.global.shared::cta.bulk_group [%0, {%2, %3, %4, %5}], [%1];"
                 ::"l"(m), "r"(src), "r"(c0), "r"(0), "r"(c2), "r"(c3) : "memory");
    asm volatile("cp.async.bulk.commit_group;" ::: "memory");
}
__device__ __forceinline__ void bulk_g2s(uint32_t dst, const void* src, uint32_t bytes, uint32_t bar) {
    asm volatile("cp.async.bulk.shared::cluster.global.mbarrier::complete_tx::bytes [%0], [%1], %2, [%3];"
                 ::"r"(dst), "l"(src), "r"(bytes), "r"(bar) : "memory");
}
__device__ __forceinline__ void st_async128(uint32_t dst_cluster, uint32_t x, uint32_t y, uint32_t z, uint32_t w, uint32_t bar_cluster) {
    asm volatile("st.async.weak.shared::cluster.mbarrier::complete_tx::bytes.v4.b32 [%0], {%1,%2,%3,%4}, [%5];"
                 ::"r"(dst_cluster), "r"(x), "r"(y), "r"(z), "r"(w), "r"(bar_cluster) : "memory");
}
__device__ __forceinline__ void fence_async() { asm volatile("fence.proxy.async.shared::cta;" ::: "memory"); }
__device__ __forceinline__ void named_sync(int id, int n) { asm volatile("bar.sync %0, %1;" ::"r"(id), "r"(n) : "memory"); }

__device__ __forceinline__ void ldsm4(uint32_t* r, uint32_t a) {
    asm volatile("ldmatrix.sync.aligned.m8n8.x4.shared.b16 {%0,%1,%2,%3}, [%4];"
                 : "=r"(r[0]), "=r"(r[1]), "=r"(r[2]), "=r"(r[3]) : "r"(a));
}
__device__ __forceinline__ void ldsm4t(uint32_t* r, uint32_t a) {
    asm volatile("ldmatrix.sync.aligned.m8n8.x4.trans.shared.b16 {%0,%1,%2,%3}, [%4];"
                 : "=r"(r[0]), "=r"(r[1]), "=r"(r[2]), "=r"(r[3]) : "r"(a));
}
__device__ __forceinline__ void stsm4t(uint32_t a, uint32_t x, uint32_t y, uint32_t z, uint32_t w) {
    asm volatile("stmatrix.sync.aligned.m8n8.x4.trans.shared.b16 [%0], {%1,%2,%3,%4};"
                 ::"r"(a), "r"(x), "r"(y), "r"(z), "r"(w) : "memory");
}
__device__ __forceinline__ uint32_t lds32(uint32_t a) { uint32_t v; asm volatile("ld.shared.u32 %0, [%1];" : "=r"(v) : "r"(a)); return v; }
__device__ __forceinline__ float lds32f(uint32_t a) { float v; asm volatile("ld.shared.f32 %0, [%1];" : "=f"(v) : "r"(a)); return v; }
__device__ __forceinline__ uint2 lds64(uint32_t a) { uint2 v; asm volatile("ld.shared.v2.u32 {%0,%1}, [%2];" : "=r"(v.x), "=r"(v.y) : "r"(a)); return v; }
__device__ __forceinline__ uint4 lds128(uint32_t a) {
    uint4 v; asm volatile("ld.shared.v4.u32 {%0,%1,%2,%3}, [%4];" : "=r"(v.x), "=r"(v.y), "=r"(v.z), "=r"(v.w) : "r"(a)); return v;
}
__device__ __forceinline__ uint4 lds128v(uint32_t a) {
    uint4 v; asm volatile("ld.volatile.shared.v4.u32 {%0,%1,%2,%3}, [%4];" : "=r"(v.x), "=r"(v.y), "=r"(v.z), "=r"(v.w) : "r"(a)); return v;
}
__device__ __forceinline__ uint32_t or_xor(uint32_t a, uint32_t b, uint32_t c) {
    uint32_t r; asm("lop3.b32 %0, %1, %2, %3, 0xf6;" : "=r"(r) : "r"(a), "r"(b), "r"(c)); return r;
}
__device__ __forceinline__ float4 lds128f(uint32_t a) {
    float4 v; asm volatile("ld.shared.v4.f32 {%0,%1,%2,%3}, [%4];" : "=f"(v.x), "=f"(v.y), "=f"(v.z), "=f"(v.w) : "r"(a)); return v;
}
__device__ __forceinline__ void sts32(uint32_t a, uint32_t v) { asm volatile("st.shared.u32 [%0], %1;" ::"r"(a), "r"(v) : "memory"); }
__device__ __forceinline__ void sts32f(uint32_t a, float v) { asm volatile("st.shared.f32 [%0], %1;" ::"r"(a), "f"(v) : "memory"); }
__device__ __forceinline__ void sts64(uint32_t a, uint32_t x, uint32_t y) { asm volatile("st.shared.v2.u32 [%0], {%1,%2};" ::"r"(a), "r"(x), "r"(y) : "memory"); }
__device__ __forceinline__ void sts64f(uint32_t a, float x, float y) { asm volatile("st.shared.v2.f32 [%0], {%1,%2};" ::"r"(a), "f"(x), "f"(y) : "memory"); }
__device__ __forceinline__ void sts128(uint32_t a, uint32_t x, uint32_t y, uint32_t z, uint32_t w) {
    asm volatile("st.shared.v4.u32 [%0], {%1,%2,%3,%4};" ::"r"(a), "r"(x), "r"(y), "r"(z), "r"(w) : "memory");
}
__device__ __forceinline__ void sts128f(uint32_t a, const float* v) {
    asm volatile("st.shared.v4.f32 [%0], {%1,%2,%3,%4};" ::"r"(a), "f"(v[0]), "f"(v[1]), "f"(v[2]), "f"(v[3]) : "memory");
}
__device__ __forceinline__ uint4 ldg128(const void* p) {
    uint4 v; asm volatile("ld.global.nc.L1::no_allocate.v4.u32 {%0,%1,%2,%3}, [%4];" : "=r"(v.x), "=r"(v.y), "=r"(v.z), "=r"(v.w) : "l"(p)); return v;
}
__device__ __forceinline__ uint2 ldg64(const void* p) {
    uint2 v; asm volatile("ld.global.nc.L1::no_allocate.v2.u32 {%0,%1}, [%2];" : "=r"(v.x), "=r"(v.y) : "l"(p)); return v;
}
__device__ __forceinline__ uint32_t ldg32(const void* p) {
    uint32_t v; asm volatile("ld.global.nc.u32 %0, [%1];" : "=r"(v) : "l"(p)); return v;
}
__device__ __forceinline__ uint32_t ldg16(const void* p) {
    uint32_t v; asm volatile("ld.global.nc.u16 %0, [%1];" : "=r"(v) : "l"(p)); return v;
}
__device__ __forceinline__ uint4 ld_relaxed_128(const void* p) {
    uint4 v; asm volatile("ld.relaxed.gpu.global.v4.u32 {%0,%1,%2,%3}, [%4];" : "=r"(v.x), "=r"(v.y), "=r"(v.z), "=r"(v.w) : "l"(p) : "memory"); return v;
}
__device__ __forceinline__ void ld_relaxed_128_unless(uint4& q, const void* p, bool have) {
    asm volatile("{ .reg .pred p; setp.eq.u32 p, %5, 0; @p ld.relaxed.gpu.global.v4.u32 {%0,%1,%2,%3}, [%4]; }"
                 : "+r"(q.x), "+r"(q.y), "+r"(q.z), "+r"(q.w) : "l"(p), "r"((uint32_t)have) : "memory");
}
__device__ __forceinline__ uint2 ld_relaxed_64(const void* p) {
    uint2 v; asm volatile("ld.relaxed.gpu.global.v2.u32 {%0,%1}, [%2];" : "=r"(v.x), "=r"(v.y) : "l"(p) : "memory"); return v;
}
__device__ __forceinline__ uint32_t ld_relaxed_32(const void* p) {
    uint32_t v; asm volatile("ld.relaxed.gpu.global.u32 %0, [%1];" : "=r"(v) : "l"(p) : "memory"); return v;
}
__device__ __forceinline__ void st_relaxed_128(void* p, uint32_t x, uint32_t y, uint32_t z, uint32_t w) {
    asm volatile("st.relaxed.gpu.global.v4.u32 [%0], {%1,%2,%3,%4};" ::"l"(p), "r"(x), "r"(y), "r"(z), "r"(w) : "memory");
}
__device__ __forceinline__ void st_relaxed_64(void* p, uint32_t x, uint32_t y) {
    asm volatile("st.relaxed.gpu.global.v2.u32 [%0], {%1,%2};" ::"l"(p), "r"(x), "r"(y) : "memory");
}
__device__ __forceinline__ void st_relaxed_32(void* p, uint32_t v) {
    asm volatile("st.relaxed.gpu.global.u32 [%0], %1;" ::"l"(p), "r"(v) : "memory");
}
__device__ __forceinline__ void red_add(void* p, uint32_t v) { asm volatile("red.relaxed.gpu.global.add.u32 [%0], %1;" ::"l"(p), "r"(v) : "memory"); }
__device__ __forceinline__ uint32_t now_ns() { uint32_t t; asm volatile("mov.u32 %0, %%globaltimer_lo;" : "=r"(t) :: "memory"); return t; }
__device__ __forceinline__ void spin_guard(uint32_t& it) { if (++it > SPIN_LIMIT) __trap(); }
__device__ __forceinline__ void wait_count(const uint32_t* p, uint32_t target) {
#pragma unroll 1
    for (uint32_t it = 0; __any_sync(0xffffffffu, (int)(ld_relaxed_32(p) - target) < 0); spin_guard(it)) { }
}
__device__ __forceinline__ void mma_bf16(float* c, uint32_t a0, uint32_t a1, uint32_t a2, uint32_t a3, uint32_t b0, uint32_t b1) {
    asm("mma.sync.aligned.m16n8k16.row.col.f32.bf16.bf16.f32 {%0,%1,%2,%3}, {%4,%5,%6,%7}, {%8,%9}, {%0,%1,%2,%3};"
                 : "+f"(c[0]), "+f"(c[1]), "+f"(c[2]), "+f"(c[3]) : "r"(a0), "r"(a1), "r"(a2), "r"(a3), "r"(b0), "r"(b1));
}
__device__ __forceinline__ void mma_bf16_k8(float* c, uint32_t a0, uint32_t a1, uint32_t b0) {
    asm("mma.sync.aligned.m16n8k8.row.col.f32.bf16.bf16.f32 {%0,%1,%2,%3}, {%4,%5}, {%6}, {%0,%1,%2,%3};"
                 : "+f"(c[0]), "+f"(c[1]), "+f"(c[2]), "+f"(c[3]) : "r"(a0), "r"(a1), "r"(b0));
}
__device__ __forceinline__ void mma_v(float* c, const uint32_t* a, uint32_t b0, uint32_t b1) {
    asm volatile("mma.sync.aligned.m16n8k16.row.col.f32.bf16.bf16.f32 {%0,%1,%2,%3}, {%4,%5,%6,%7}, {%8,%9}, {%0,%1,%2,%3};"
                 : "+f"(c[0]), "+f"(c[1]), "+f"(c[2]), "+f"(c[3]) : "r"(a[0]), "r"(a[1]), "r"(a[2]), "r"(a[3]), "r"(b0), "r"(b1));
}
__device__ __forceinline__ void mma_bf16_z(float* c, uint32_t a0, uint32_t a1, uint32_t a2, uint32_t a3, uint32_t b0, uint32_t b1) {
    asm volatile("mma.sync.aligned.m16n8k16.row.col.f32.bf16.bf16.f32 {%0,%1,%2,%3}, {%4,%5,%6,%7}, {%8,%9}, {%10,%10,%10,%10};"
        : "=f"(c[0]), "=f"(c[1]), "=f"(c[2]), "=f"(c[3]) : "r"(a0), "r"(a1), "r"(a2), "r"(a3), "r"(b0), "r"(b1), "f"(0.f));
}
__device__ __forceinline__ void mma_f16(float* c, uint32_t a0, uint32_t a1, uint32_t a2, uint32_t a3, uint32_t b0, uint32_t b1) {
    asm("mma.sync.aligned.m16n8k16.row.col.f32.f16.f16.f32 {%0,%1,%2,%3}, {%4,%5,%6,%7}, {%8,%9}, {%0,%1,%2,%3};"
                 : "+f"(c[0]), "+f"(c[1]), "+f"(c[2]), "+f"(c[3]) : "r"(a0), "r"(a1), "r"(a2), "r"(a3), "r"(b0), "r"(b1));
}
__device__ __forceinline__ uint32_t pack_bf16(float lo, float hi) {
    uint32_t r; asm("cvt.rn.bf16x2.f32 %0, %1, %2;" : "=r"(r) : "f"(hi), "f"(lo)); return r;
}
__device__ __forceinline__ uint32_t pack_v(float lo, float hi) {
    uint32_t r; asm volatile("cvt.rn.bf16x2.f32 %0, %1, %2;" : "=r"(r) : "f"(hi), "f"(lo)); return r;
}
__device__ __forceinline__ uint32_t pack_w(float lo, float hi) {
    uint32_t r; asm volatile("cvt.rn.satfinite.bf16x2.f32 %0, %1, %2;" : "=r"(r) : "f"(hi), "f"(lo)); return r;
}
__device__ __forceinline__ void pin(uint32_t& x) { asm volatile("" : "+r"(x)); }
template <class T> __device__ __forceinline__ void pin(T*& x) { asm volatile("" : "+l"(x)); }
__device__ __forceinline__ uint32_t pack_f16(float lo, float hi) {
    uint32_t r; asm("cvt.rn.f16x2.f32 %0, %1, %2;" : "=r"(r) : "f"(hi), "f"(lo)); return r;
}
__device__ __forceinline__ float bf_lo(uint32_t v) { return __uint_as_float(v << 16); }
__device__ __forceinline__ float bf_hi(uint32_t v) { return __uint_as_float(v & 0xffff0000u); }
__device__ __forceinline__ float bf_round(float x) { return __uint_as_float(pack_bf16(0.f, x)); }
__device__ __forceinline__ uint32_t badd2(uint32_t a, uint32_t b) { uint32_t r; asm("add.rn.bf16x2 %0, %1, %2;" : "=r"(r) : "r"(a), "r"(b)); return r; }
__device__ __forceinline__ uint32_t bsub2_lo(uint32_t a, uint32_t b) {
    uint32_t r; asm("{ .reg .b16 m, h; .reg .b32 m2; mov.b32 {m, h}, %2; mov.b32 m2, {m, m}; sub.rn.bf16x2 %0, %1, m2; }" : "=r"(r) : "r"(a), "r"(b)); return r;
}
__device__ __forceinline__ uint32_t bmax2(uint32_t a, uint32_t b) { uint32_t r; asm("max.bf16x2 %0, %1, %2;" : "=r"(r) : "r"(a), "r"(b)); return r; }
__device__ __forceinline__ uint32_t normalize2(uint32_t x, uint32_t s0, uint32_t s1) {
    uint32_t r;
    asm("{ .reg .b16 m, h, l, k; .reg .b32 m2, h2, l2, d, t;\n\t"
        "mov.b32 {m, h}, %2; mov.b32 {l, k}, %3; mov.b32 m2, {m, m}; mov.b32 h2, {h, h}; mov.b32 l2, {l, l};\n\t"
        "sub.rn.bf16x2 d, %1, m2; mul.rn.bf16x2 t, d, l2; fma.rn.bf16x2 %0, d, h2, t; }" : "=r"(r) : "r"(x), "r"(s0), "r"(s1));
    return r;
}
__device__ __forceinline__ float rcpf(float x) { float r; asm("rcp.approx.ftz.f32 %0, %1;" : "=f"(r) : "f"(x)); return r; }
__device__ __forceinline__ float sqrtaf(float x) { float r; asm("sqrt.approx.ftz.f32 %0, %1;" : "=f"(r) : "f"(x)); return r; }
__device__ __forceinline__ float ex2f(float x) { float r; asm("ex2.approx.ftz.f32 %0, %1;" : "=f"(r) : "f"(x)); return r; }

__device__ __forceinline__ int tok_off(int t) { return ((t >> 3) & 1) * VT_PLANE + (t >> 4) * 16 + (t & 7) * 2; }

__device__ __forceinline__ uint32_t order_key(uint32_t b16) { return b16 ^ ((b16 & 0x8000u) ? 0xffffu : 0x8000u); }
__device__ __forceinline__ uint32_t unorder_key(uint32_t k16) { return k16 ^ ((k16 & 0x8000u) ? 0x8000u : 0xffffu); }

struct cplx { float r, i; };
struct hc { uint32_t r, i; };
template <bool CONJ> __device__ __forceinline__ cplx csq(cplx a) {
    float im;
    asm("{ .reg .f32 t; mul.ftz.f32 t, %1, %2; mul.ftz.f32 %0, t, 0f40000000; }" : "=f"(im) : "f"(CONJ ? -a.r : a.r), "f"(a.i));
    return {fmaf(a.r, a.r, -(a.i * a.i)), im};
}
__device__ __forceinline__ cplx cexpp(float a2, float ai) {
    float m = ex2f(a2), s, c;
    __sincosf(ai, &s, &c);
    return {m * c, m * s};
}
__device__ __forceinline__ __half2 as_h2(uint32_t x) { return *reinterpret_cast<__half2*>(&x); }
__device__ __forceinline__ uint32_t as_u(__half2 x) { return *reinterpret_cast<uint32_t*>(&x); }
__device__ __forceinline__ hc hmul(hc a, hc b) {
    return {as_u(__hfma2(__hneg2(as_h2(a.i)), as_h2(b.i), __hmul2(as_h2(a.r), as_h2(b.r)))),
            as_u(__hfma2(as_h2(a.i), as_h2(b.r), __hmul2(as_h2(a.r), as_h2(b.i))))};
}
__device__ __forceinline__ hc hpack(cplx a, cplx b) { return {pack_f16(a.r, b.r), pack_f16(a.i, b.i)}; }
__device__ __forceinline__ void sts16(uint32_t a, uint32_t v) { asm volatile("st.shared.u16 [%0], %1;" ::"r"(a), "r"(v) : "memory"); }

template <class Hook, class Hook2>
__device__ __forceinline__ void kgen(uint32_t tab, int lane, uint2 la, uint2 aim, uint2 cre, uint2 cim, float dt, float skip, int dch, Hook main_done, Hook2 half_done) {
    const int g = lane >> 2, t = lane & 3;
    const float dt2 = 2.f * dt;
    const uint32_t am = bmax2(bmax2(cre.x & 0x7fff7fffu, cre.y & 0x7fff7fffu), bmax2(cim.x & 0x7fff7fffu, cim.y & 0x7fff7fffu));
    const float mx = dt2 * fmaxf(bf_lo(am), bf_hi(am));
    const uint32_t eb = min(max(__reduce_max_sync(0xffffffffu, __float_as_uint(mx)) >> 23, 1u), 252u);
    const float cscale = dt2 * __uint_as_float((253u - eb) << 23);
    const float scale_inv = __uint_as_float((eb + 1u) << 23);
    float k0 = (bf_lo(cre.x) + bf_hi(cre.x)) + (bf_lo(cre.y) + bf_hi(cre.y));
#pragma unroll
    for (int o = 16; o; o >>= 1) k0 += __shfl_xor_sync(0xffffffffu, k0, o);
    const float ndt = -1.4426950408889634f * dt;
    STAMP(40); KSTAMP(0);

    float acc[5][4];
#pragma unroll
    for (int i = 0; i < 5; i++) { acc[i][0] = acc[i][1] = acc[i][2] = acc[i][3] = 0.f; }

    const uint32_t rec = tab + t * 512, sw = (uint32_t)t << 5;
    const uint32_t ad_l = rec + (((uint32_t)g << 4) ^ sw), ad_h = rec + 128 + (((uint32_t)g << 3) ^ sw);
    const uint32_t ad_2 = rec + (0xc0u ^ sw) + ((g & 1) << 3), ad_3 = rec + (0xd0u ^ sw) + ((g & 2) << 2);
    const uint32_t ad_4 = rec + (0xe0u ^ sw) + ((g & 4) << 1), ad_z = rec + (0xf0u ^ sw);
    const uint32_t wrec = tab + lane * 256 + ((lane & 7) << 4);

#pragma unroll 1
    for (int bb = 0; bb < 2; bb++) {
        cplx z[2][11], cz[2];
#pragma unroll
        for (int e = 0; e < 2; e++) {
            const float lg = e ? bf_hi(la.x) : bf_lo(la.x), ai = (e ? bf_hi(aim.x) : bf_lo(aim.x)) * dt;
            const float cr = (e ? bf_hi(cre.x) : bf_lo(cre.x)) * cscale, ci = (e ? bf_hi(cim.x) : bf_lo(cim.x)) * cscale;
            const float a2 = bf_round(ex2f(lg * 1.4426950408889634f)) * ndt;
            z[e][0] = cexpp(a2, ai);
            z[e][5] = cexpp(a2 * 32.f, ai * -32.f);
#pragma unroll
            for (int i = 1; i < 11; i++) if (i != 5) z[e][i] = (i == 3 || i == 7) ? csq<true>(z[e][i - 1]) : csq<false>(z[e][i - 1]);
            cz[e] = {fmaf(cr, z[e][0].r, -(ci * z[e][0].i)), fmaf(cr, z[e][0].i, ci * z[e][0].r)};
        }
        la.x = la.y; aim.x = aim.y; cre.x = cre.y; cim.x = cim.y;
        const hc z1 = hpack(z[0][0], z[1][0]), z2 = hpack(z[0][1], z[1][1]), z4 = hpack(z[0][2], z[1][2]);
        hc L[8], H[8];
        L[1] = hpack(z[0][3], z[1][3]); L[2] = hpack(z[0][4], z[1][4]); L[4] = hpack(z[0][5], z[1][5]);
        const hc y64 = hpack(z[0][6], z[1][6]), z128 = hpack(z[0][7], z[1][7]), z256 = hpack(z[0][8], z[1][8]);
        const hc z512 = hpack(z[0][9], z[1][9]), z1024 = hpack(z[0][10], z[1][10]);
        H[0] = hpack(cz[0], cz[1]);
        H[1] = hmul(H[0], z1); H[2] = hmul(H[0], z2); H[3] = hmul(H[1], z2);
        L[3] = hmul(L[1], L[2]);
#pragma unroll
        for (int i = 0; i < 4; i++) { H[4 + i] = hmul(H[i], z4); if (i) L[4 + i] = hmul(L[i], L[4]); }
        __syncwarp();
        sts128(wrec, 0x3c003c00u, y64.r, 0u, y64.i);
#pragma unroll
        for (int i = 1; i < 8; i++) { const hc q = hmul(L[i], y64); sts128(wrec ^ (i << 4), L[i].r, q.r, L[i].i, q.i); }
#pragma unroll
        for (int i = 0; i < 4; i++) sts128((wrec ^ (i << 4)) + 128, H[2 * i].r, H[2 * i].i, H[2 * i + 1].r, H[2 * i + 1].i);
        {
            const hc a = hmul(z256, z1), b = hmul(z256, z128), c = hmul(z256, z2), d = hmul(z512, z4);
            sts128((wrec ^ 0x40) + 128, a.r, a.i, b.r, b.i);
            sts128((wrec ^ 0x50) + 128, c.r, c.i, z512.r, z512.i);
            sts128((wrec ^ 0x60) + 128, d.r, d.i, z1024.r, z1024.i);
            sts64((wrec ^ 0x70) + 128, z128.r, z128.i);
        }
        __syncwarp();
        KSTAMP(1 + 2 * bb);
#pragma unroll kKgUnroll
        for (int k2 = 0; k2 < 4; k2++) {
#pragma unroll
            for (uint32_t s = 0; s < 2; s++) {
                const uint32_t o = k2 * 2048 + s * 256, x = s << 4;
                const uint4 l = lds128((ad_l ^ x) + o);
                const uint2 h0 = lds64((ad_h ^ x) + o), m2 = lds64((ad_2 ^ x) + o), m3 = lds64((ad_3 ^ x) + o);
                const uint2 m4 = lds64((ad_4 ^ x) + o), mz = lds64((ad_z ^ x) + o);
                const hc H0 = {h0.x, h0.y};
                const hc H1 = hmul(H0, {mz.x, mz.y}), H2 = hmul(H0, {m2.x, m2.y}), H3 = hmul(H2, {m3.x, m3.y}), H4 = hmul(H3, {m4.x, m4.y});
                mma_f16(acc[0], l.x, l.y, l.z, l.w, H0.r, H0.i);
                mma_f16(acc[1], l.x, l.y, l.z, l.w, H1.r, H1.i);
                mma_f16(acc[2], l.x, l.y, l.z, l.w, H2.r, H2.i);
                mma_f16(acc[3], l.x, l.y, l.z, l.w, H3.r, H3.i);
                mma_f16(acc[4], l.x, l.y, l.z, l.w, H4.r, H4.i);
            }
        }
        KSTAMP(2 + 2 * bb);
        if (bb == 0) half_done();
    }
    __syncwarp();
    main_done();
    KSTAMP(5);
#pragma unroll
    for (int i = 0; i < 4; i++) sts128(tab + 2048 + 512 * i + 16 * lane, 0, 0, 0, 0);
    if (lane < 15) sts32(tab + 4 * lane, 0);
    __syncwarp();
    const uint32_t d0 = tab + T_DENSE + 4 + 8 * lane, src = (lane + 31) & 31;
    const uint32_t p0 = pack_bf16(fmaf(k0, dt2, skip), 0.f);
    uint32_t prev = p0;
#pragma unroll
    for (int i = 0; i < 4; i++) {
        const uint32_t pk = pack_bf16(acc[i >> 1][2 * (i & 1) + 1] * scale_inv, acc[i >> 1][2 * (i & 1)] * scale_inv);
        sts64(d0 + 256 * i, __byte_perm(pk, __shfl_sync(0xffffffffu, lane == 31 ? prev : pk, src), 0x5432), pk);
        prev = pk;
    }
    const uint32_t w0 = pack_bf16(acc[2][0] * scale_inv, acc[2][1] * scale_inv), w1 = pack_bf16(acc[2][2] * scale_inv, acc[2][3] * scale_inv);
    const uint32_t sa = (lane & 1) ? 0x5410u : 0x5454u, sb2 = (lane & 1) ? 0x1010u : 0x5410u;
#pragma unroll
    for (int hf = 0; hf < 2; hf++) {
        const uint32_t w = hf ? w1 : w0;
        const uint32_t pv = __shfl_sync(0xffffffffu, lane != 31 ? w : hf ? w0 : __byte_perm(prev, w1, 0x5410), src);
        sts64(d0 + 1024 + 256 * hf, __byte_perm(w, pv, sa), __byte_perm(w, pv, sb2));
        sts64(d0 + 1536 + 256 * hf, __byte_perm(w, pv, sa + 0x2222u), __byte_perm(w, pv, sb2 + 0x2222u));
    }
    const uint32_t d3 = tab + T_R2 + 160 + 320 * (t & 1) + 16 * (g >> 1) + 8 * (g & 1) + 4 * (t >> 1), d3n = d3 + (g >= 6 ? 32 : 0);
    const uint32_t d4 = tab + T_R3 + 80 + 160 * t + 4 * g, d4n = d4 + (g >= 6 ? 16 : 0);
    uint32_t p3;
#pragma unroll
    for (int hf = 0; hf < 2; hf++)
#pragma unroll
        for (int e = 0; e < 2; e++) {
            const float v3 = acc[3][2 * hf + e] * scale_inv;
            const uint32_t p4 = pack_bf16(acc[4][2 * hf + e] * scale_inv, 0.f);
            p3 = pack_bf16(v3, v3);
            sts16(d3 + 64 * hf + 160 * e, p3);
            sts16((hf ? d3n : d3) + 64 * hf + 160 * e + 18, p3);
            sts16(d4 + 32 * hf + 80 * e, p4);
            sts16((hf ? d4n : d4) + 32 * hf + 80 * e + 10, p4);
        }
    if (lane == 31) {
        const uint32_t k512 = __byte_perm(w1, 0, 0x3232);
        sts32(tab + T_DENSE, p0);
        sts64(tab + T_DENSE + 4 * 513, k512, k512); sts16(tab + T_DENSE + 4 * 515 + 2, k512);
        sts16(tab + T_PATCH + 4 * 17, p3); sts32(tab + T_PATCH + 4 * 18, p3); sts16(tab + T_PATCH + 4 * 19 + 2, p3);
    }
    __syncwarp();
}

__device__ __forceinline__ void load_toep(uint32_t* a, uint32_t p, uint32_t zero) {
    a[0] = lds32(p); a[1] = lds32(p + 32); a[2] = lds32(p - 32); a[3] = lds32(p + zero);
}
#define DENSE_BLK 2
__device__ __forceinline__ void dense_step(float (&acc)[16][4], uint32_t (&R)[8][4], const uint32_t (&A)[4][4], uint32_t (&An)[4][4],
                                           uint32_t va, uint32_t vmin, uint32_t pn, uint32_t zero, int bit) {
#pragma unroll
    for (int i0 = 0; i0 < 8; i0 += DENSE_BLK) {
#pragma unroll 1
        do {
#pragma unroll
            for (int i = i0; i < i0 + DENSE_BLK; i++) {
                const int ip = (i - DENSE_BLK) & 7;
                ldsm4(R[ip], ip == 0 ? max(va - 16, vmin) : va + ip * 128 - (i0 ? 16 : 0));
                if ((i & 1) == 0) load_toep(An[i >> 1], pn + (i >> 1) * 512, zero);
#pragma unroll
                for (int ka = 0; ka < 4; ka++) {
                    mma_v(acc[i + ka], A[ka], R[i][0], R[i][1]);
                    if (i + 8 + ka < 16) mma_v(acc[i + 8 + ka], A[ka], R[i][2], R[i][3]);
                }
            }
        } while (zero & (1u << (bit + i0)));
    }
}
struct DenseTaps {
    uint32_t A[4][4], E[4], F[4], e8[2], f8[2];
    __device__ __forceinline__ DenseTaps(uint32_t pb, uint32_t zero) {
        constexpr int PP = T_PATCH - T_DENSE + 56;
#pragma unroll
        for (int i = 0; i < 4; i++) load_toep(A[i], pb + 512 * i, zero);
        load_toep(E, pb + 2048, zero);
        load_toep(F, pb + PP, zero);
        e8[0] = lds32(pb + zero + 2048 + 32); e8[1] = lds32(pb + 2048 + 64);
        f8[0] = lds32(pb + zero + PP + 32); f8[1] = lds32(pb + PP + 64);
    }
};
__device__ __forceinline__ void dense_phase(float (&acc)[16][4], uint32_t vrow, uint32_t pb, DenseTaps& tp, uint32_t zero, int lane) {
    uint32_t R[8][4], A1[4][4];
    const uint32_t vp = vrow + ((lane >> 3) & 1) * VT_PLANE, vmin = lane < 16 ? vp - 16 : 0u;
    uint32_t va = vp + (lane >> 4) * 1024 + (lane & 7) * 16;
    {
        uint32_t H[3][4];
#pragma unroll
        for (int i = 0; i < 3; i++) ldsm4(H[i], vrow + VT_PLANE - 16 + lane * 16 + i * 512);
#pragma unroll
        for (int i = 0; i < 8; i++) ldsm4(R[i], va + i * 128);
#pragma unroll
        for (int i = 0; i < 12; i++) mma_bf16_k8(acc[i + 4], tp.e8[0], tp.e8[1], H[i >> 2][i & 3]);
#pragma unroll
        for (int i = 0; i < 8; i++) mma_bf16_k8(acc[i + 8], tp.f8[0], tp.f8[1], H[i >> 2][i & 3]);
#pragma unroll
        for (int i = 0; i < 12; i++) mma_v(acc[i + 4], tp.E, R[i & 7][2 * (i >> 3)], R[i & 7][2 * (i >> 3) + 1]);
#pragma unroll
        for (int i = 0; i < 8; i++) mma_v(acc[i + 8], tp.F, R[i][0], R[i][1]);
    }
#pragma unroll 1
    for (int rho = 0; rho < 8; rho += 2) {
        dense_step(acc, R, tp.A, A1, va, vmin, pb + 64, zero, 0);
        dense_step(acc, R, A1, tp.A, va - 16, vmin, pb + zero + 128, -zero, 8);
        pb += 128; va -= 32;
    }
}
__device__ __forceinline__ uint32_t ones2(int c, int lo, int hi) {
    return (((uint32_t)(c - lo) <= (uint32_t)(hi - lo)) ? 0x3f80u : 0u) | (((uint32_t)(c + 1 - lo) <= (uint32_t)(hi - lo)) ? 0x3f800000u : 0u);
}
struct Boxes {
    uint32_t q[4], ha[2];
    __device__ __forceinline__ Boxes(uint32_t vrow, int lane, int O, int L1, int H1, int L2, int H2) {
        const int g = lane >> 2, t = lane & 3, d = 2 * t - g;
        q[0] = ones2(d, L1, H1); q[1] = ones2(d, L2, H2); q[2] = ones2(d + 8, L1, H1); q[3] = ones2(d + 8, L2, H2);
#pragma unroll
        for (int i = 0; i < 2; i++) { ha[i] = vrow + 16 * g + tok_off(O + 8 * i + 2 * t); pin(ha[i]); pin(q[i]); pin(q[2 + i]); }
    }
    __device__ __forceinline__ uint32_t any() const { return (q[0] | q[1] | q[2]) | (q[3] | ha[0] | ha[1]); }
    __device__ __forceinline__ void load(int j, uint32_t* v, uint32_t zero) const {
        const uint32_t o = j * 128;
        v[0] = lds32(ha[0] + o); v[1] = lds32(ha[1] + zero + o); v[2] = lds32(ha[1] + o);
        v[3] = lds32(ha[0] + zero + o + 16); v[4] = lds32(ha[0] + o + 16); v[5] = lds32(ha[1] + o + 16);
    }
    __device__ __forceinline__ void sums(const uint32_t* v, float* Z, float* X, float* Y) const {
        mma_bf16_z(Z, q[0], q[1], q[2], q[3], v[0], v[1]);
        mma_bf16_z(X, q[0], q[1], q[2], q[3], v[2], v[3]);
        mma_bf16_z(Y, q[0], q[1], q[2], q[3], v[4], v[5]);
    }
};
template <class After>
__device__ __forceinline__ void tail_phase(float (&acc)[16][4], const Boxes& b2, const Boxes& b3, uint32_t tp2, uint32_t tp3, uint32_t zero, After after) {
    uint2 tp[10];
    uint32_t v[6], a0[4], a1[4];
    float Z[4], X[4], Y[4];
    b2.load(0, v, zero);
#pragma unroll
    for (int i = 0; i < 5; i++) { const uint4 c = lds128(tp2 + 160 * i); tp[i] = make_uint2(c.x, c.y); tp[5 + i] = make_uint2(c.z, c.w); }
#pragma unroll
    for (int j = -1; j < 20; j++) {
        if (j < 19) {
            (j < 11 ? b2 : b3).sums(v, Z, X, Y);
            if (j < 10) b2.load(j + 2, v, zero); else if (j < 18) b3.load(j - 10, v, zero);
        }
        if (j >= 0 && j < 12) {
#pragma unroll
            for (int b = 0; b < 5; b++) if (j + 4 + b < 16) mma_v(acc[j + 4 + b], a1, tp[5 + b].x, tp[5 + b].y);
        }
        if (j < 11) { a1[0] = pack_v(Z[0], Z[1]); a1[1] = pack_w(X[0], X[1]); a1[2] = pack_v(Z[2], Z[3]); a1[3] = pack_w(X[2], X[3]); }
        if (j >= 0 && j < 12) {
#pragma unroll
            for (int b = 0; b < 5; b++) if (j + 4 + b < 16) mma_v(acc[j + 4 + b], a0, tp[b].x, tp[b].y);
            if (j >= 7 && j < 11) { tp[11 - j] = lds64(tp3 + 80 * (10 - j)); tp[16 - j] = lds64(tp3 + 80 * (14 - j)); }
        } else if (j >= 12) {
#pragma unroll
            for (int b = 0; b < 8; b++) if (j - 4 + b < 16) mma_v(acc[j - 4 + b], a0, tp[b < 4 ? b + 1 : b + 2].x, tp[b < 4 ? b + 1 : b + 2].y);
        }
        if (j < 11) { a0[0] = pack_v(X[0], X[1]); a0[1] = pack_v(Y[0], Y[1]); a0[2] = pack_v(X[2], X[3]); a0[3] = pack_v(Y[2], Y[3]); }
        else if (j < 19) { a0[0] = pack_v(X[0], X[1]); a0[1] = pack_v(Y[0], Y[1]); a0[2] = pack_v(Z[2], Z[3]); a0[3] = pack_v(X[2], X[3]); }
        after(j);
    }
}
template <int G>
__device__ __forceinline__ void emit(const float (&acc)[16][4], uint32_t dst0, uint32_t dst1, uint32_t bar0, uint32_t bar1) {
#pragma unroll
    for (int o = 0; o < 2; o++)
#pragma unroll
        for (int hf = 0; hf < 2; hf++) {
            const int n = 8 * G + 4 * o;
            st_async128((o ? dst1 : dst0) + G * 16384 + hf * 512, pack_bf16(acc[n][2 * hf], acc[n][2 * hf + 1]), pack_bf16(acc[n + 1][2 * hf], acc[n + 1][2 * hf + 1]),
                        pack_bf16(acc[n + 2][2 * hf], acc[n + 2][2 * hf + 1]), pack_bf16(acc[n + 3][2 * hf], acc[n + 3][2 * hf + 1]), (o ? bar1 : bar0) + 8 * G);
        }
}
__device__ __forceinline__ void finish(uint32_t src, uint32_t xa) {
    uint32_t s[4][4];
    uint4 x[4];
#pragma unroll
    for (int i = 0; i < 4; i++) {
        ldsm4t(s[i], (src ^ ((i & 1) << 5)) + (i >> 1) * 8192);
        x[i] = lds128((xa ^ ((i >> 1) << 4)) + (i & 1) * 256);
    }
#pragma unroll
    for (int i = 0; i < 4; i++)
        sts128((xa ^ ((i >> 1) << 4)) + (i & 1) * 256, badd2(x[i].x, s[i][0]), badd2(x[i].y, s[i][1]), badd2(x[i].z, s[i][2]), badd2(x[i].w, s[i][3]));
}

__device__ __noinline__ float centred_var(uint32_t rows, float mu, int lane) {
    float var = 0.f;
#pragma unroll 1
    for (int rr = 0; rr < 16; rr++) {
        const float c0 = __shfl_sync(0xffffffffu, mu, rr);
        float c = 0.f;
#pragma unroll 1
        for (int k = 0; k < 16; k++) {
            const uint32_t q = lds32(rows + rr * ROW_PITCH + k * 128 + lane * 4);
            const float d0 = bf_lo(q) - c0, d1 = bf_hi(q) - c0;
            c = fmaf(d0, d0, fmaf(d1, d1, c));
        }
#pragma unroll 1
        for (int o = 16; o; o >>= 1) c += __shfl_xor_sync(0xffffffffu, c, o);
        if ((lane & 15) == rr) var = c * (1.f / DM);
    }
    return var;
}
__device__ __noinline__ float centred_score(uint32_t rows, uint32_t wbuf, uint32_t s0, uint32_t s1, int lane) {
    float sc = 0.f;
#pragma unroll 1
    for (int rr = 0; rr < 16; rr++) {
        const uint32_t t0 = __shfl_sync(0xffffffffu, s0, rr), t1 = __shfl_sync(0xffffffffu, s1, rr);
        float c = 0.f;
#pragma unroll 1
        for (int k = 0; k < 16; k++) {
            const uint32_t xn = normalize2(lds32(rows + rr * ROW_PITCH + k * 128 + lane * 4), t0, t1);
            const uint32_t wq = lds32(wbuf + (k >> 2) * 1024 + (k & 3) * 128 + lane * 4);
            c = fmaf(bf_lo(xn), bf_lo(wq), fmaf(bf_hi(xn), bf_hi(wq), c));
        }
#pragma unroll 1
        for (int o = 16; o; o >>= 1) c += __shfl_xor_sync(0xffffffffu, c, o);
        if ((lane & 15) == rr) sc = c;
    }
    return sc;
}

__global__ void __cluster_dims__(2, 1, 1) __launch_bounds__(NTHR, 1)
fused_kernel(const __grid_constant__ Ptrs p, const __grid_constant__ Maps maps) {
    extern __shared__ __align__(1024) unsigned char smem[];
    const int tid = threadIdx.x, lane = tid & 31, b = blockIdx.x;
    const int dch = 8 * b + (tid >> 5) - 4;
    uint2 la, aim, cre, cim;
    uint32_t ldt16, dsk16, epoch;
    uint4 wq;
    if ((uint32_t)(tid - 128) < 256u) {
        la = ldg64(p.logA + dch * NMODE + 4 * lane); aim = ldg64(p.Aim + dch * NMODE + 4 * lane);
        cre = ldg64(p.Cre + dch * NMODE + 4 * lane); cim = ldg64(p.Cim + dch * NMODE + 4 * lane);
        ldt16 = ldg16(p.ldt + dch); dsk16 = ldg16(p.dsk + dch);
    }
    if (tid < 128) { wq = ldg128(p.wr + 8 * tid); epoch = ld_relaxed_32(&p.sc->epoch); }
    const uint32_t sb = s_u32(smem);
    const int warp = __shfl_sync(0xffffffffu, tid >> 5, 0);
    const int h = b & 1, cl = b >> 1;
    const uint32_t bar0 = sb + OFF_BAR;
    const int m = lane >> 3, r = lane & 7, g = lane >> 2, t = lane & 3;
    const bool has_gu = b < GU_CTAS;
    if (warp == 4) { STAMP(0); GSTAMP(24); }

    if (warp >= 12) {
        asm volatile("setmaxnreg.dec.sync.aligned.u32 24;");
        const int a = warp - 12;
        uint32_t due = now_ns() + ST_T0 + (uint32_t)(128 * a + b) * ST_PER / 128;
        const bool el = elect_one();
        if (a == 1 && el) {
#pragma unroll
            for (int j = 0; j < 4; j++) mbar_init(bar0 + 8 * (B_ROW + j), 1);
            asm volatile("fence.mbarrier_init.release.cluster;" ::: "memory");
            fence_async();
#pragma unroll 1
            for (int j = 0; j < 4; j++) {
                mbar_expect_tx(bar0 + 8 * (B_ROW + j), 8192);
#pragma unroll
                for (int i = 0; i < 4; i++)
                    bulk_g2s(sb + OFF_VT + (4 * j + i) * ROW_PITCH, p.u + (size_t)(16 * b + 4 * j + i) * DM, 2048, bar0 + 8 * (B_ROW + j));
            }
        }
        if (a == 2 && el) {
#pragma unroll
            for (int i = B_XT; i < NBAR; i++) mbar_init(bar0 + 8 * i, (i == B_SFREE || i == B_UPD) ? 4 : (i >= B_FREE + 4 && i < B_FREE + 8) ? 2 : 1);
            asm volatile("fence.mbarrier_init.release.cluster;" ::: "memory");
            fence_async();
            mbar_expect_tx(bar0 + 8 * B_XT, 65536);
            mbar_expect_tx(bar0 + 8 * B_RECV, 16384);
            mbar_expect_tx(bar0 + 8 * B_RECV + 8, 16384);
            mbar_expect_tx(bar0 + 8 * B_RED, 512);
        }
        if (a == 3 && el) {
#pragma unroll
            for (int i = 0; i < 5; i++) asm volatile("prefetch.tensormap [%0];" ::"l"(&maps.u + i) : "memory");
        }
        __syncwarp();
        cluster_arrive();
        cluster_wait();
        STAMP(18);
        mbar_wait_lazy<40>(bar0 + 8 * (B_ROW + a), 0);
        if (el) {
#pragma unroll
            for (int i = 0; i < 4; i++)
                tma_load_tile(sb + OFF_XT + h * 32768 + a * 4096 + (i & 1) * 16384 + (i >> 1) * 2048, &maps.u, 16 * cl, 4 * a + (i & 2), 16 * (i & 1) + 8 * h, bar0 + 8 * B_XT);
        }
        if (el) {
#pragma unroll 1
            for (int k = has_gu ? 0 : 4; k < 6; k++) {
                const int i = 4 * k + a, s = k < 3 ? i : i - 12;
#pragma unroll 1
                for (int left; (left = (int)(due - now_ns())) > 0;) __nanosleep(left >> 1);
                due += k == 0 ? 4 * ST_PER + ST_GAP : k < 3 ? 4 * ST_PER : 4 * ST_PER2;
                const bool scr = (0xcf0 >> s) & 1, again = k >= 3 && has_gu, mid = (s >> 2) == 1;
                if (scr || again) mbar_wait(bar0 + 8 * (B_FREE + s), scr && again);
                const uint32_t dst = sb + (mid ? OFF_PRIV + 4096 + a * 16384 : OFF_RING + (s >> 3) * 32768 + a * 8192), bar = bar0 + 8 * (B_FULL + s);
                const uint32_t dst2 = dst + (mid ? 8192 : 4096);
                if (k < 4) {
                    mbar_expect_tx(bar, 8192);
                    tma_load_2d(dst, &maps.wg, 32 * b, 64 * i, bar);
                    tma_load_2d(dst2, &maps.wu, 32 * b, 64 * i, bar);
                } else {
                    const int c1 = 1792 * h + 448 * a + 224 * (k & 1);
                    mbar_expect_tx(bar, 7168);
                    tma_load_2d(dst, &maps.wd, 16 * cl, c1, bar);
                    tma_load_2d(dst2, &maps.wd, 16 * cl, c1 + 112, bar);
                }
            }
            STAMP(19);
        }
    } else if (warp >= 4) {
        const int w = warp - 4;
        cluster_arrive();
        asm volatile("setmaxnreg.inc.sync.aligned.u32 168;");
        const uint32_t vrow = sb + OFF_VT + w * VT_PITCH + VT_PAD, tab = sb + OFF_PRIV + w * 8192;
        const uint32_t so = sb + OFF_XT + (8 * h + w) * 1024 + ((lane ^ ((w & 1) << 1)) << 4);
        uint32_t dst0 = mapa(so + 32768, 0), dst1 = mapa(so, 1);
        const uint32_t rb0 = mapa(bar0 + 8 * B_RECV, 0), rb1 = mapa(bar0 + 8 * B_RECV, 1);
        const uint32_t box = sb + OFF_XT + h * 32768 + w * 2048;
        uint32_t fs = sb + OFF_XT + (h ^ 1) * 32768 + (2 * m + (r & 1)) * 1024 + (w >> 2) * 512 + (((8 * (w & 3) + (r & 4) + ((r >> 1) & 1)) ^ ((r & 1) << 1)) << 4);
        uint32_t fx = box + (g >> 1) * 512 + (t >> 1) * 144 + (2 * (t & 1) + (g & 1)) * 32;
        uint32_t tpo = 80 + (g - 2 * t) * 8 - (g < 2 * t ? 16 : 0);
        uint32_t xa = sb + OFF_XT + (w & 2) * 16384 + (w >> 2) * 16384 + (w & 1) * 1024 + (g >> 1) * 2048 + (g & 1) * 128 + t * 32 + ((h ^ (g & 1)) << 4);
        uint32_t va = sb + OFF_VT + (2 * m + (r & 1)) * VT_PITCH + VT_PAD + (16 * w + (r >> 1)) * 16;
        uint32_t qa = sb + OFF_ST + 2048 * w + 128 * t + 16 * (g ^ (2 * t));
        uint4 x[8];
        pin(dst0); pin(dst1); pin(fs); pin(fx); pin(tpo); pin(xa); pin(va); pin(qa);
        const Boxes b2(vrow, lane, -18, 5, 7, 0, 4), b3(vrow, lane, -20, 1, 7, 0, 8);
        if (__any_sync(0xffffffffu, ((dst0 | dst1 | fs) | (fx | tpo | xa) | (va | qa) | (b2.any() | b3.any())) & p.zero)) __trap();
        cluster_wait();
        pin(la.x); pin(la.y); pin(aim.x); pin(aim.y); pin(cre.x); pin(cre.y); pin(cim.x); pin(cim.y); pin(ldt16); pin(dsk16);
        kgen(tab, lane, la, aim, cre, cim, bf_round(ex2f(bf_lo(ldt16) * 1.4426950408889634f)), 1.f + bf_lo(dsk16), dch, [&]() {
            STAMP(21);
            if (elect_one()) mbar_arrive(bar0 + 8 * (B_FREE + 4 + (w >> 1)));
            mbar_wait_lazy<40>(bar0 + 8 * B_XT, 0);
#pragma unroll
            for (int i = 0; i < 8; i++) x[i] = lds128(xa + (i & 1) * 8192 + (i >> 1) * 256);
        }, [&]() {
        });
        STAMP(1); KSTAMP(6);
        const uint32_t pb = tab + T_DENSE + (g - 2 * t) * 4;
        DenseTaps dt(pb, p.zero);
        {
            uint4 q[4];
            mbar_wait(bar0 + 8 * (B_ST + w), 0);
#pragma unroll
            for (int n = 0; n < 4; n++) q[n] = lds128(qa + 512 * n);
            if (lane < 4) sts128(vrow - VT_PAD + (lane >> 1) * VT_PLANE + (lane & 1) * 16, 0, 0, 0, 0);
            STAMP(2); GSTAMP(28);
#pragma unroll
            for (int i = 0; i < 8; i++) {
                const uint32_t s0 = (i & 1) ? q[i >> 1].z : q[i >> 1].x, s1 = (i & 1) ? q[i >> 1].w : q[i >> 1].y;
                stsm4t(va + (i >> 1) * 64 + (i & 1) * VT_PLANE, normalize2(x[i].x, s0, s1), normalize2(x[i].y, s0, s1),
                       normalize2(x[i].z, s0, s1), normalize2(x[i].w, s0, s1));
            }
            named_sync(2, 256);
            if (elect_one()) {
                if (w < 3) mbar_arrive(bar0 + 8 * (w == 2 ? B_V : B_FREE + 10 + w));
            }
        }
        STAMP(3); KSTAMP(7);
        float acc[16][4];
#pragma unroll
        for (int i = 0; i < 16; i++) { acc[i][0] = acc[i][1] = acc[i][2] = acc[i][3] = 0.f; }
        dense_phase(acc, vrow, pb, dt, p.zero, lane);
        STAMP(4); KSTAMP(8);
        tail_phase(acc, b2, b3, tab + T_R2 + 2 * tpo, tab + T_R3 + tpo, p.zero, [&](int j) {
            if (j == 3) {
                mbar_wait(bar0 + 8 * B_SFREE, 0);
                emit<0>(acc, dst0, dst1, rb0, rb1);
                STAMP(5);
            }
            if (j == 7) {
                mbar_wait(bar0 + 8 * B_RECV, 0);
                finish(fs, fx);
                fence_async();
                __syncwarp();
                if (elect_one()) tma_store_tile(&maps.out, box, 16 * cl, 2 * w, 8 * h);
                STAMP(20);
            }
        });
        emit<1>(acc, dst0, dst1, rb0, rb1);
        STAMP(30);
        mbar_wait(bar0 + 8 * (B_RECV + 1), 0);
        STAMP(6);
        finish(fs + 16384, fx + 16384);
        const bool ready = mbar_test(bar0 + 8 * B_UPD, 0);
        const bool el = elect_one();
#pragma unroll 1
        for (int pass = 0; pass < 2; pass++) {
            if ((pass != 0) == ready) {
                fence_async();
                __syncwarp();
                if (el) tma_store_tile(&maps.out, box + 16384, 16 * cl, 2 * w, 16 + 8 * h);
            } else {
                if (el) asm volatile("cp.async.bulk.wait_group 0;" ::: "memory");
                __syncwarp();
                mbar_wait_lazy<40>(bar0 + 8 * B_UPD, 0);
                const int tok = 2047 - (int)(lds32(sb + OFF_MISC + 48 + 8 * g) & 2047);
                if ((((tok >> 6) & 8) | ((tok >> 1) & 7)) == 8 * h + w) {
                    const uint32_t xa = box + (tok >> 10) * 16384 + ((tok >> 6) & 7) * 256 + (tok & 1) * 128 + ((tok >> 4) & 3) * 32 + (((t >> 1) ^ (tok & 1)) << 4) + (t & 1) * 8;
                    const uint2 o0 = lds64(xa);
                    const float4 up = lds128f(sb + OFF_RED + 16 * lane);
                    const uint2 o1 = make_uint2(badd2(o0.x, pack_bf16(up.x, up.y)), badd2(o0.y, pack_bf16(up.z, up.w)));
                    if (ready && tok >= 1024) sts64(xa, o1.x, o1.y);
                    else *reinterpret_cast<uint2*>(p.out + (size_t)tok * DM + 16 * cl + 4 * t) = o1;
                }
            }
        }
        if (el) asm volatile("cp.async.bulk.wait_group.read 0;" ::: "memory");
        STAMP(7);
    } else {
        const int a = warp;
        cluster_arrive();
        asm volatile("setmaxnreg.inc.sync.aligned.u32 152;");
        const uint32_t tag = __shfl_sync(0xffffffffu, epoch, 0) + 1u, misc = sb + OFF_MISC, abar = bar0 + 8 * (B_AUX + a);
        uint32_t aph = 0;
        uint2* pub = p.sc->stat + 16 * b + 2 * (r ^ (2 * (b & 3))) + m;
        uint32_t* cnt_s = &p.sc->n_stat[b & 96];
        pin(pub); pin(cnt_s);
        if (tid < 64) sts32(sb + OFF_RED + 4 * tid, 0);
        const uint32_t wbuf = sb + OFF_LN + a * 1024, part = sb + OFF_LN + 4096;
        {
            sts128(wbuf + 16 * lane, wq.x, wq.y, wq.z, wq.w);
            sts128(wbuf + 512 + 16 * lane, 0x3f803f80u, 0x3f803f80u, 0x3f803f80u, 0x3f803f80u);
            float wsum = ((bf_lo(wq.x) + bf_hi(wq.x)) + (bf_lo(wq.y) + bf_hi(wq.y))) + ((bf_lo(wq.z) + bf_hi(wq.z)) + (bf_lo(wq.w) + bf_hi(wq.w)));
#pragma unroll
            for (int o = 16; o; o >>= 1) wsum += __shfl_xor_sync(0xffffffffu, wsum, o);
            sts32f(part + 1024 + 4 * a, wsum);
            uint32_t wf[4][4];
#pragma unroll
            for (int i = 0; i < 4; i++) ldsm4(wf[i], wbuf + ((uint32_t)(r - 1) < 2u ? 16 * (r - 1) : 512) + 32 * m + 128 * i);
            uint32_t ra = sb + OFF_VT + r * ROW_PITCH + 512 * a + 16 * m, pa = part + a * 256 + g * 16;
            cluster_wait();
            STAMP(22);
#pragma unroll 1
            for (int hf = 0; hf < 2; hf++) {
                if (a < 2) mbar_wait(bar0 + 8 * (B_ROW + a) + 16 * hf, 0);
                named_sync(1, 128);
                STAMP(23);
                uint32_t x[8][4];
                float cs[2][4], q[8][4];
#pragma unroll
                for (int i = 0; i < 40; i++) (i < 8 ? cs[i >> 2 & 1] : q[(i - 8) >> 2 & 7])[i & 3] = 0.f;
#pragma unroll
                for (int k = 0; k < 8; k++) ldsm4(x[k], ra + k * 64);
                const uint32_t dep = (x[6][3] | x[7][3]) & p.zero;
                x[0][0] |= dep; x[0][2] |= dep; x[1][0] |= dep; x[1][2] |= dep;
#pragma unroll
                for (int k = 0; k < 8; k++) {
                    mma_bf16(cs[k & 1], x[k][0], x[k][1], x[k][2], x[k][3], wf[k >> 1][2 * (k & 1)], wf[k >> 1][2 * (k & 1) + 1]);
#pragma unroll
                    for (int i = 0; i < 4; i++) mma_bf16_k8(q[4 * (k & 1) + i], x[k][i & 2], x[k][i | 1], x[k][i]);
                }
                const float c2 = cs[0][2] + cs[1][2];
                if (t == 0) sts64f(pa, (cs[0][0] + cs[1][0]) + c2, cs[0][1] + cs[1][1]);
                if (t == 1) sts32f(pa + 12, c2);
                const float e0 = ((q[0][0] + q[2][0]) + (q[4][0] + q[6][0])) + ((q[1][2] + q[3][2]) + (q[5][2] + q[7][2]));
                const float e1 = ((q[0][1] + q[2][1]) + (q[4][1] + q[6][1])) + ((q[1][3] + q[3][3]) + (q[5][3] + q[7][3]));
                if (t == (g >> 1)) sts32f(pa + 8, (g & 1) ? e1 : e0);
                ra += 8 * ROW_PITCH; pa += 128;
            }
        }
        STAMP(31);
        named_sync(1, 128);
        if (a == 0) {
            const uint32_t pa = part + (lane & 15) * 16;
            const float4 p0 = lds128f(pa), p1 = lds128f(pa + 256), p2 = lds128f(pa + 512), p3 = lds128f(pa + 768), ws = lds128f(part + 1024);
            const float mu = ((p0.x + p1.x) + (p2.x + p3.x)) * (1.f / DM);
            float var = ((p0.z + p1.z) + (p2.z + p3.z)) * (1.f / DM) - mu * mu;
            const bool centred = __any_sync(0xffffffffu, !(mu * mu <= 4.f * var));
            if (centred) var = centred_var(sb + OFF_VT, mu, lane);
            const float ri = rcpf(bf_round(sqrtaf(bf_round(bf_round(var) + 1e-5f))));
            const uint32_t s0 = pack_bf16(mu, ri), s1 = (pack_bf16(ri - bf_hi(s0), 0.f) & 0xfffcu) | (tag & 3);
            float sc = ((((p0.y + p1.y) + (p2.y + p3.y)) + ((p0.w + p1.w) + (p2.w + p3.w))) - bf_lo(s0) * ((ws.x + ws.y) + (ws.z + ws.w))) * ri;
            if (centred) sc = centred_score(sb + OFF_VT, sb + OFF_LN, s0, s1, lane);
            const uint32_t sb16 = pack_bf16(0.f, sc);
            if (lane < 16) st_relaxed_64(pub, s0, s1 | (sb16 ^ (((uint32_t)((int)sb16 >> 31) & 0x7fff0000u) | 0x80000000u)));
            if (lane == 0) red_add(cnt_s, 1);
            STAMP(9); GSTAMP(25);
        }
        const uint32_t slot0 = sb + OFF_RING + a * 8192, slot1 = sb + OFF_PRIV + a * 16384 + 4096, fbar = bar0 + 8 * (B_FULL + a);
        uint32_t mine = 0, row[2] = {0, 0};
        {
            uint32_t q[16];
            named_sync(1, 128);
            wait_count(&p.sc->n_stat[32 * a], 32 * tag - FEW_ST);
            STAMP(41);
#pragma unroll 1
            for (uint32_t it = 0;; spin_guard(it)) {
                if (elect_one()) {
                    mbar_expect_tx(abar, 4096);
                    bulk_g2s(sb + OFF_ST + 4096 * a, p.sc->stat + 512 * a, 4096, abar);
                }
                mbar_wait(abar, aph);
                aph ^= 1;
                uint32_t bad = 0;
#pragma unroll
                for (int n = 0; n < 8; n++) {
                    const uint4 u = lds128v(sb + OFF_ST + 4096 * a + 512 * n + 16 * lane);
                    q[2 * n] = u.y; q[2 * n + 1] = u.w;
                    bad = or_xor(bad, u.y, tag);
                }
                const bool ok = __all_sync(0xffffffffu, (bad & 3) == 0);
                asm volatile("{ .reg .pred p; setp.ne.u32 p, %1, 0; @p mbarrier.arrive.shared::cta.b64 _, [%0]; }" ::"r"(bar0 + 8 * B_ST + 16 * a + 8 * lane), "r"((uint32_t)(ok && lane < 2)) : "memory");
                if (ok) break;
            }
            STAMP(8);
            const uint32_t inv = 2047 - 512 * a - 16 * m - (r ^ (2 * m));
#pragma unroll
            for (int i = 0; i < 16; i++) asm("lop3.b32 %0, %0, %1, %2, 0x9b;" : "+r"(q[i]) : "r"(inv), "r"(0xffff0000u | (64 * (i >> 1) + 8 * (i & 1))));
            auto below = [&](uint32_t x) {
                uint32_t d[4];
#pragma unroll
                for (int i = 0; i < 16; i++) d[i & 3] = i < 4 ? x + q[i] : min(d[i & 3], x + q[i]);
                d[0] = min(min(d[0], d[1]), min(d[2], d[3]));
                return d[0] < x ? x - 1 - d[0] : 0u;
            };
            const uint32_t mx0 = ~min(min(min(min(q[0], q[1]), min(q[2], q[3])), min(min(q[4], q[5]), min(q[6], q[7]))),
                                      min(min(min(q[8], q[9]), min(q[10], q[11])), min(min(q[12], q[13]), min(q[14], q[15]))));
            const uint32_t gm = min(__reduce_max_sync(0xffffffffu, lane < 16 ? mx0 : 0u), __reduce_max_sync(0xffffffffu, lane < 16 ? 0u : mx0));
            if (lane == 0) sts32(misc + 16 + 4 * a, gm);
            named_sync(1, 128);
            STAMP(42);
            if (b == 0 && tid == 0) st_relaxed_32(&p.sc->epoch, tag);
            const uint4 t0 = lds128(misc + 16);
            uint32_t tau = min(min(t0.x, t0.y), min(t0.z, t0.w));
            uint32_t mx = mx0, cnt = 0, bal;
            const uint32_t list = sb + OFF_RED + 64 * a;
#pragma unroll 1
            while ((bal = __ballot_sync(0xffffffffu, mx >= tau)) != 0) {
                const uint32_t pos = cnt + __popc(bal & ((1u << lane) - 1u));
                cnt += __popc(bal);
                if (cnt > 16) break;
                if (mx >= tau) sts32(list + 4 * pos, mx);
                mx = below(mx);
            }
            if (cnt > 16) {
                mx = mx0;
#pragma unroll 1
                for (int j = 0; j < 8; j++) {
                    const uint32_t top = __reduce_max_sync(0xffffffffu, mx), nx = below(mx);
                    if (mx == top) { sts32(list + 4 * j, mx); sts32(list + 32 + 4 * j, 0); mx = nx; }
                }
            }
            named_sync(1, 128);
            STAMP(43);
            const uint2 k = lds64(sb + OFF_RED + 8 * lane);
            uint32_t hi = max(k.x, k.y), lo = min(k.x, k.y);
            mbar_wait(bar0 + 8 * B_V, 0);
#pragma unroll
            for (int j = 0; j < 8; j++) {
                const uint32_t top = __reduce_max_sync(0xffffffffu, hi);
                const bool won = hi == top;
                hi = won ? lo : hi;
                lo = won ? 0u : lo;
                if (g == j) mine = top;
                if (a == (j >> 1)) row[j & 1] = top;
            }
        }
        STAMP(11);
        const int tok = 2047 - (int)(mine & 2047);
        const uint32_t xs = sb + OFF_XT + (h ^ 1) * 32768;
        if (has_gu) {
            const int tok0 = 2047 - (int)(row[0] & 2047), tok1 = 2047 - (int)(row[1] & 2047);
            if (elect_one()) {
                mbar_expect_tx(abar, 4096);
                bulk_g2s(xs + 2 * a * ROW_PITCH, p.u + (size_t)tok0 * DM, 2048, abar);
                bulk_g2s(xs + (2 * a + 1) * ROW_PITCH, p.u + (size_t)tok1 * DM, 2048, abar);
            }
        }
        STAMP(44);
        const uint2 st = ld_relaxed_64(p.sc->stat + (tok & ~15) + 2 * ((tok & 7) ^ ((tok >> 3) & 6)) + ((tok >> 3) & 1));
        if (a == 0 && t == 0) sts64(misc + 48 + 8 * g, mine, __float_as_uint(bf_hi(st.x) + bf_lo(st.y)));
        uint32_t xq[8][4];
        if (a == 0) STAMP(45);
        if (has_gu) {
            mbar_wait(abar, aph);
            aph ^= 1;
            STAMP(46);
            named_sync(1, 128);
#pragma unroll
            for (int j = 0; j < 8; j++) {
                ldsm4(xq[j], xs + r * ROW_PITCH + m * 16 + 128 * a + (j >> 1) * 512 + (j & 1) * 64);
#pragma unroll
                for (int i = 0; i < 4; i++) xq[j][i] = bsub2_lo(xq[j][i], st.x);
            }
        }
        __syncwarp();
        if (elect_one()) mbar_arrive_peer(mapa(bar0 + 8 * B_SFREE, h ^ 1) + (has_gu ? (xq[5][0] | xq[6][0] | xq[7][0]) & p.zero : 0u));
        if (has_gu) {
            STAMP(12);
            float gacc[8][4];
#pragma unroll
            for (int i = 0; i < 8; i++) { gacc[i][0] = gacc[i][1] = gacc[i][2] = gacc[i][3] = 0.f; }
            uint4* pubh = &p.sc->h[b * 32 + lane];
            uint32_t* cnt_h = &p.sc->n_h[32 * (b / 14)];
            pin(pubh); pin(cnt_h);
            const uint32_t ko = (r + ((m >> 1) << 3)) * 64 + (((r >> 1) & 3) << 4);
#pragma unroll
            for (int c = 0; c < 4; c++) {
                mbar_wait(fbar + 32 * (c % 3), c / 3);
                STAMP(36 + c);
                const uint32_t rowa = (c == 1 ? slot1 + (m & 1) * 8192 : slot0 + (c == 2) * 32768 + (m & 1) * 4096) + ko;
                uint32_t af[16][4];
#pragma unroll
                for (int ks = 0; ks < 4; ks++)
#pragma unroll
                    for (int mt = 0; mt < 4; mt++) ldsm4t(af[4 * ks + mt], (rowa ^ (mt << 4)) + ks * 1024);
                const uint32_t dep = ((af[12][3] | af[13][3]) | (af[14][3] | af[15][3])) & p.zero;
                __syncwarp();
                if (c < 3 && elect_one()) { if (c == 1) mbar_arrive2(bar0 + 8 * (B_FREE + 4 + a) + dep); else mbar_arrive(bar0 + 8 * (B_FREE + 4 * c + a) + dep); }
#pragma unroll
                for (int ks = 0; ks < 4; ks++) {
                    const uint32_t* q = xq[2 * c + (ks >> 1)] + 2 * (ks & 1);
#pragma unroll
                    for (int mt = 0; mt < 4; mt++)
                        mma_bf16(gacc[4 * (ks & 1) + mt], af[4 * ks + mt][0], af[4 * ks + mt][1], af[4 * ks + mt][2], af[4 * ks + mt][3],
                                 q[0] | (ks < 2 ? dep : 0u), q[1]);
                }
            }
            STAMP(13);
#pragma unroll
            for (int mt = 0; mt < 4; mt++) {
#pragma unroll
                for (int j = 0; j < 4; j++) gacc[mt][j] += gacc[4 + mt][j];
                sts128f(slot0 + mt * 512 + lane * 16, gacc[mt]);
            }
            named_sync(1, 128);
            const uint32_t base = sb + OFF_RING + 16 * tid;
            const float4 p0 = lds128f(base), p1 = lds128f(base + 8192), p2 = lds128f(base + 16384), p3 = lds128f(base + 24576);
            const float r0 = lds32f(misc + 52 + 16 * t), r1 = lds32f(misc + 60 + 16 * t);
            const float g0 = bf_round(((p0.x + p1.x) + (p2.x + p3.x)) * r0), g1 = bf_round(((p0.y + p1.y) + (p2.y + p3.y)) * r1);
            const float h0 = bf_round(g0 * rcpf(1.f + ex2f(-1.4426950408889634f * g0))) * bf_round(((p0.z + p1.z) + (p2.z + p3.z)) * r0);
            const float h1 = bf_round(g1 * rcpf(1.f + ex2f(-1.4426950408889634f * g1))) * bf_round(((p0.w + p1.w) + (p2.w + p3.w)) * r1);
            uint32_t hw;
            asm volatile("movmatrix.sync.aligned.m8n8.trans.b16 %0, %1;" : "=r"(hw) : "r"(pack_bf16(h0, h1)));
            sts32(sb + OFF_RING + 7168 + 16 * lane + 4 * a, hw);
            named_sync(1, 128);
            if (a == 0) {
                const uint4 q = lds128(base + 7168);
                st_relaxed_128(pubh, q.x, q.y, q.z, (q.w & ~1u) | (tag & 1));
                if (lane == 0) red_add(cnt_h, 1);
            }
            STAMP(14);
        }
        float dacc[4];
        {
            wait_count(&p.sc->n_h[32 * (4 * h + a)], 14 * tag - FEW_H);
            STAMP(33);
            uint4 hq[14];
#pragma unroll 1
            for (uint32_t it = 0;; spin_guard(it)) {
                if (elect_one()) {
                    mbar_expect_tx(abar, 7168);
                    bulk_g2s(slot0, &p.sc->h[(56 * h + 14 * a) * 32], 7168, abar);
                }
                mbar_wait(abar, aph);
                aph ^= 1;
                uint32_t bad = 0;
#pragma unroll
                for (int j = 0; j < 14; j++) { hq[j] = lds128(slot0 + 512 * j + 16 * lane); bad = or_xor(bad, hq[j].w, tag); }
                if (__all_sync(0xffffffffu, (bad & 1) == 0)) break;
            }
            STAMP(15);
            const uint32_t wo = (r + ((m >> 1) << 3)) * 32 + (((m & 1) ^ (r >> 2)) << 4);
            float d[7][4];
#pragma unroll
            for (int i = 0; i < 7; i++) { d[i][0] = d[i][1] = d[i][2] = d[i][3] = 0.f; }
#pragma unroll
            for (int s = 0; s < 2; s++) {
                mbar_wait(fbar + 32 + 32 * s, has_gu);
                uint32_t af[14][4];
#pragma unroll
                for (int j = 0; j < 14; j++) ldsm4t(af[j], (s ? slot0 + 32768 + (j / 7) * 4096 : slot1 + (j / 7) * 8192) + wo + (j % 7) * 512);
                const uint32_t dep = (af[11][3] | af[12][3] | af[13][3]) & p.zero;
#pragma unroll
                for (int j = 0; j < 14; j++) {
                    const uint4 q = hq[7 * s + (j >> 1)];
                    mma_bf16(d[j % 7], af[j][0], af[j][1], af[j][2], af[j][3], ((j & 1) ? q.z : q.x) | (j < 7 ? dep : 0u), (j & 1) ? q.w : q.y);
                }
            }
#pragma unroll
            for (int j = 0; j < 4; j++) dacc[j] = ((d[0][j] + d[1][j]) + (d[2][j] + d[3][j])) + ((d[4][j] + d[5][j]) + d[6][j]);
        }
        STAMP(16);
        {
            sts128f(slot0 + 7680 + lane * 16, dacc);
            named_sync(1, 128);
            const int tk = tid >> 4, col = tid & 15;
            const uint32_t base = sb + OFF_RING + 7680 + ((col & 7) * 4 + (tk >> 1)) * 16 + (((col >> 3) << 1) + (tk & 1)) * 4;
            const float y0 = (lds32f(base) + lds32f(base + 8192)) + (lds32f(base + 16384) + lds32f(base + 24576));
            const uint32_t red = sb + OFF_RED + 4 * tid, key = lds32(misc + 48 + 8 * tk);
            mbar_wait(bar0 + 8 * B_SFREE, 0);
            asm volatile("st.async.weak.shared::cluster.mbarrier::complete_tx::bytes.f32 [%0], %1, [%2];"
                         ::"r"(mapa(red, h ^ 1)), "f"(y0), "r"(mapa(bar0 + 8 * B_RED, h ^ 1)) : "memory");
            const float rv = __uint_as_float(unorder_key(key >> 16) << 16);
            const float sg = bf_round(rcpf(1.f + ex2f(-1.4426950408889634f * rv)));
            mbar_wait(bar0 + 8 * B_RED, 0);
            sts32f(red, bf_round(y0 + lds32f(red)) * sg);
            __syncwarp();
            if (elect_one()) mbar_arrive(bar0 + 8 * B_UPD);
        }
        STAMP(17); GSTAMP(29);
    }
}

typedef CUresult (*EncodeFn)(CUtensorMap*, CUtensorMapDataType, cuuint32_t, void*, const cuuint64_t*, const cuuint64_t*,
                             const cuuint32_t*, const cuuint32_t*, CUtensorMapInterleave, CUtensorMapSwizzle,
                             CUtensorMapL2promotion, CUtensorMapFloatOOBfill);

void make_map(EncodeFn enc, CUtensorMap* m, const void* ptr, uint64_t cols, uint64_t rows, uint32_t bc, uint32_t br,
              CUtensorMapSwizzle sw, CUtensorMapL2promotion pr) {
    cuuint64_t dims[2] = {cols, rows};
    cuuint64_t str[1] = {cols * 2};
    cuuint32_t box[2] = {bc, br};
    cuuint32_t es[2] = {1, 1};
    enc(m, CU_TENSOR_MAP_DATA_TYPE_BFLOAT16, 2, const_cast<void*>(ptr), dims, str, box, es, CU_TENSOR_MAP_INTERLEAVE_NONE, sw, pr,
        CU_TENSOR_MAP_FLOAT_OOB_FILL_NONE);
}
void make_tile_map(EncodeFn enc, CUtensorMap* m, const void* ptr) {
    cuuint64_t dims[4] = {DM, 4, 16, SEQ / 64};
    cuuint64_t str[3] = {16 * DM * 2, DM * 2, 64 * DM * 2};
    cuuint32_t box[4] = {16, 4, 2, 8};
    cuuint32_t es[4] = {1, 1, 1, 1};
    enc(m, CU_TENSOR_MAP_DATA_TYPE_BFLOAT16, 4, const_cast<void*>(ptr), dims, str, box, es, CU_TENSOR_MAP_INTERLEAVE_NONE,
        CU_TENSOR_MAP_SWIZZLE_32B, CU_TENSOR_MAP_L2_PROMOTION_NONE, CU_TENSOR_MAP_FLOAT_OOB_FILL_NONE);
}

}

#define WD_PROMO CU_TENSOR_MAP_L2_PROMOTION_L2_64B
extern "C" void kernel_launch(void* const* d_in, const int* in_sizes, int n_in, void* d_out, int out_size) {
    (void)in_sizes; (void)n_in; (void)out_size;
    static EncodeFn enc = nullptr;
    static void* scratch = nullptr;
    if (!enc) {
        void* fn = nullptr;
        cudaDriverEntryPointQueryResult q;
        cudaGetDriverEntryPoint("cuTensorMapEncodeTiled", &fn, cudaEnableDefault, &q);
        enc = (EncodeFn)fn;
        cudaGetSymbolAddress(&scratch, g_scratch);
        cudaFuncSetAttribute(fused_kernel, cudaFuncAttributeMaxDynamicSharedMemorySize, SMEM_BYTES);
    }
    Maps maps;
    make_tile_map(enc, &maps.u, d_in[0]);
    make_tile_map(enc, &maps.out, d_out);
    make_map(enc, &maps.wg, d_in[9], FF, DM, 32, 64, CU_TENSOR_MAP_SWIZZLE_64B, CU_TENSOR_MAP_L2_PROMOTION_L2_128B);
    make_map(enc, &maps.wu, d_in[10], FF, DM, 32, 64, CU_TENSOR_MAP_SWIZZLE_64B, CU_TENSOR_MAP_L2_PROMOTION_L2_128B);
    make_map(enc, &maps.wd, d_in[11], DM, FF, 16, 112, CU_TENSOR_MAP_SWIZZLE_32B, WD_PROMO);
    Ptrs p;
    p.sc = (Scratch*)scratch;
    p.u = (const __nv_bfloat16*)d_in[0];
    p.logA = (const __nv_bfloat16*)d_in[1];
    p.Aim = (const __nv_bfloat16*)d_in[2];
    p.Cre = (const __nv_bfloat16*)d_in[3];
    p.Cim = (const __nv_bfloat16*)d_in[4];
    p.ldt = (const __nv_bfloat16*)d_in[5];
    p.dsk = (const __nv_bfloat16*)d_in[6];
    p.wr = (const __nv_bfloat16*)d_in[8];
    p.out = (__nv_bfloat16*)d_out;
    p.zero = 0;
    fused_kernel<<<NCTA, NTHR, SMEM_BYTES, cudaStreamPerThread>>>(p, maps);
}
```

```cpp
#include <cuda_runtime.h>
#include <cuda_bf16.h>
#include <cuda_fp16.h>
#include <cuda.h>
#include <stdint.h>

namespace {

constexpr int SEQ = 2048, DM = 1024, NMODE = 128, FF = 3584;
constexpr int NCTA = 128, NTHR = 512;
constexpr int GU_CTAS = 112;

constexpr int OFF_XT = 0;
constexpr int OFF_RING = 65536;
constexpr int OFF_PRIV = OFF_RING + 65536;
constexpr int OFF_VT = OFF_PRIV + 65536;
constexpr int VT_PAD = 32, VT_PLANE = VT_PAD + 2048, VT_PITCH = 2 * VT_PLANE, ROW_PITCH = 2064;
constexpr int OFF_BAR = OFF_VT + 8 * VT_PITCH;
constexpr int OFF_MISC = OFF_BAR + 384;
constexpr int OFF_RED = OFF_MISC + 112;
constexpr int OFF_STAMP = OFF_RED + 512;
constexpr int SMEM_BYTES = OFF_STAMP + 256;
constexpr int OFF_LN = OFF_RING + 7 * 8192;
constexpr int OFF_ST = OFF_RING + 6 * 8192;
static_assert(SMEM_BYTES <= 232448, "shared memory");

constexpr int B_ROW = 0, B_XT = 4, B_V = 5, B_SFREE = 7, B_RECV = 8, B_RED = 10, B_UPD = 11, B_ST = 12, B_FREE = 20, B_FULL = 32, B_AUX = 44, NBAR = 48;

constexpr int T_DENSE = 60;
constexpr int T_PATCH = 2208;
constexpr int T_R2 = 2368;
constexpr int T_R3 = 3296;

constexpr uint32_t SPIN_LIMIT = 1u << 20;
#define KG_UNROLL 4
constexpr int kKgUnroll = KG_UNROLL;
#define DENSE_UNROLL 1
constexpr int kDenseUnroll = DENSE_UNROLL;
#define ST_T0 3200
#define FEW_ST 0
#define FEW_H 0
#define ST_GAP 0
#define ST_PER 310
#define ST_PER2 300

struct Scratch {
    uint2 stat[SEQ];
    uint4 h[GU_CTAS * 32];
    uint32_t n_stat[4 * 32];
    uint32_t n_h[8 * 32];
    uint32_t epoch;
};
__device__ __align__(128) Scratch g_scratch;

struct Ptrs {
    Scratch* sc;
    const __nv_bfloat16 *logA, *Aim, *Cre, *Cim, *ldt, *dsk, *u, *wr;
    __nv_bfloat16* out;
    uint32_t zero;
};
struct Maps {
    CUtensorMap u, out, wg, wu, wd;
};

#define STAMP(i) do { } while (0)
#define KSTAMP(i) do { } while (0)
#define GSTAMP(i) do { } while (0)

__device__ __forceinline__ uint32_t s_u32(const void* p) { return (uint32_t)__cvta_generic_to_shared(p); }
__device__ __forceinline__ void mbar_init(uint32_t b, uint32_t n) {
    asm volatile("mbarrier.init.shared::cta.b64 [%0], %1;" ::"r"(b), "r"(n) : "memory");
}
__device__ __forceinline__ void mbar_expect_tx(uint32_t b, uint32_t bytes) {
    asm volatile("mbarrier.arrive.expect_tx.shared::cta.b64 _, [%0], %1;" ::"r"(b), "r"(bytes) : "memory");
}
__device__ __forceinline__ void mbar_arrive(uint32_t b) {
    asm volatile("mbarrier.arrive.shared::cta.b64 _, [%0];" ::"r"(b) : "memory");
}
__device__ __forceinline__ void mbar_arrive2(uint32_t b) {
    asm volatile("mbarrier.arrive.shared::cta.b64 _, [%0], 2;" ::"r"(b) : "memory");
}
__device__ __forceinline__ void mbar_arrive_peer(uint32_t b_cluster) {
    asm volatile("mbarrier.arrive.relaxed.cluster.shared::cluster.b64 _, [%0];" ::"r"(b_cluster) : "memory");
}
__device__ __forceinline__ void mbar_wait(uint32_t b, uint32_t parity) {
    asm volatile("{\n\t.reg .pred p;\n\t.reg .u32 c;\n\tmov.u32 c, 0;\n"
                 "W:\n\tmbarrier.try_wait.parity.shared::cta.b64 p, [%0], %1, 4000;\n\t@p bra D;\n\t"
                 "add.u32 c, c, 1;\n\tsetp.lt.u32 p, c, 1048576;\n\t@p bra W;\n\ttrap;\nD:\n\t}"
                 ::"r"(b), "r"(parity) : "memory");
}
template <int NS>
__device__ __forceinline__ void mbar_wait_lazy(uint32_t b, uint32_t parity) {
    asm volatile("{\n\t.reg .pred p;\n\t.reg .u32 c;\n\tmov.u32 c, 0;\n"
                 "W:\n\tmbarrier.test_wait.parity.shared::cta.b64 p, [%0], %1;\n\t@p bra D;\n\tnanosleep.u32 %2;\n\t"
                 "add.u32 c, c, 1;\n\tsetp.lt.u32 p, c, 4194304;\n\t@p bra W;\n\ttrap;\nD:\n\t}"
                 ::"r"(b), "r"(parity), "n"(NS) : "memory");
}
__device__ __forceinline__ bool mbar_test(uint32_t b, uint32_t parity) {
    uint32_t ok;
    asm volatile("{ .reg .pred p; mbarrier.test_wait.parity.shared::cta.b64 p, [%1], %2; selp.u32 %0, 1, 0, p; }" : "=r"(ok) : "r"(b), "r"(parity) : "memory");
    return __all_sync(0xffffffffu, ok != 0);
}
__device__ __forceinline__ bool elect_one() {
    uint32_t p;
    asm volatile("{ .reg .pred P; elect.sync _|P, 0xffffffff; selp.u32 %0, 1, 0, P; }" : "=r"(p));
    return p != 0;
}
__device__ __forceinline__ uint32_t mapa(uint32_t a, uint32_t rank) {
    uint32_t r;
    asm("mapa.shared::cluster.u32 %0, %1, %2;" : "=r"(r) : "r"(a), "r"(rank));
    return r;
}
__device__ __forceinline__ void cluster_arrive() { asm volatile("barrier.cluster.arrive.relaxed.aligned;" ::: "memory"); }
__device__ __forceinline__ void cluster_wait() { asm volatile("barrier.cluster.wait.acquire.aligned;" ::: "memory"); }
__device__ __forceinline__ void tma_load_2d(uint32_t dst, const CUtensorMap* m, int c0, int c1, uint32_t bar) {
    asm volatile("cp.async.bulk.tensor.2d.shared::cluster.global.mbarrier::complete_tx::bytes [%0], [%1, {%3, %4}], [%2];"
                 ::"r"(dst), "l"(m), "r"(bar), "r"(c0), "r"(c1) : "memory");
}
__device__ __forceinline__ void tma_load_tile(uint32_t dst, const CUtensorMap* m, int c0, int c2, int c3, uint32_t bar) {
    asm volatile("cp.async.bulk.tensor.4d.shared::cluster.global.mbarrier::complete_tx::bytes.multicast::cluster [%0], [%1, {%3, %4, %5, %6}], [%2], %7;"
                 ::"r"(dst), "l"(m), "r"(bar), "r"(c0), "r"(0), "r"(c2), "r"(c3), "h"((uint16_t)3) : "memory");
}
__device__ __forceinline__ void tma_store_tile(const CUtensorMap* m, uint32_t src, int c0, int c2, int c3) {
    asm volatile("cp.async.bulk.tensor.4d.global.shared::cta.bulk_group [%0, {%2, %3, %4, %5}], [%1];"
                 ::"l"(m), "r"(src), "r"(c0), "r"(0), "r"(c2), "r"(c3) : "memory");
    asm volatile("cp.async.bulk.commit_group;" ::: "memory");
}
__device__ __forceinline__ void bulk_g2s(uint32_t dst, const void* src, uint32_t bytes, uint32_t bar) {
    asm volatile("cp.async.bulk.shared::cluster.global.mbarrier::complete_tx::bytes [%0], [%1], %2, [%3];"
                 ::"r"(dst), "l"(src), "r"(bytes), "r"(bar) : "memory");
}
__device__ __forceinline__ void st_async128(uint32_t dst_cluster, uint32_t x, uint32_t y, uint32_t z, uint32_t w, uint32_t bar_cluster) {
    asm volatile("st.async.weak.shared::cluster.mbarrier::complete_tx::bytes.v4.b32 [%0], {%1,%2,%3,%4}, [%5];"
                 ::"r"(dst_cluster), "r"(x), "r"(y), "r"(z), "r"(w), "r"(bar_cluster) : "memory");
}
__device__ __forceinline__ void fence_async() { asm volatile("fence.proxy.async.shared::cta;" ::: "memory"); }
__device__ __forceinline__ void named_sync(int id, int n) { asm volatile("bar.sync %0, %1;" ::"r"(id), "r"(n) : "memory"); }

__device__ __forceinline__ void ldsm4(uint32_t* r, uint32_t a) {
    asm volatile("ldmatrix.sync.aligned.m8n8.x4.shared.b16 {%0,%1,%2,%3}, [%4];"
                 : "=r"(r[0]), "=r"(r[1]), "=r"(r[2]), "=r"(r[3]) : "r"(a));
}
__device__ __forceinline__ void ldsm4t(uint32_t* r, uint32_t a) {
    asm volatile("ldmatrix.sync.aligned.m8n8.x4.trans.shared.b16 {%0,%1,%2,%3}, [%4];"
                 : "=r"(r[0]), "=r"(r[1]), "=r"(r[2]), "=r"(r[3]) : "r"(a));
}
__device__ __forceinline__ void stsm4t(uint32_t a, uint32_t x, uint32_t y, uint32_t z, uint32_t w) {
    asm volatile("stmatrix.sync.aligned.m8n8.x4.trans.shared.b16 [%0], {%1,%2,%3,%4};"
                 ::"r"(a), "r"(x), "r"(y), "r"(z), "r"(w) : "memory");
}
__device__ __forceinline__ uint32_t lds32(uint32_t a) { uint32_t v; asm volatile("ld.shared.u32 %0, [%1];" : "=r"(v) : "r"(a)); return v; }
__device__ __forceinline__ float lds32f(uint32_t a) { float v; asm volatile("ld.shared.f32 %0, [%1];" : "=f"(v) : "r"(a)); return v; }
__device__ __forceinline__ uint2 lds64(uint32_t a) { uint2 v; asm volatile("ld.shared.v2.u32 {%0,%1}, [%2];" : "=r"(v.x), "=r"(v.y) : "r"(a)); return v; }
__device__ __forceinline__ uint4 lds128(uint32_t a) {
    uint4 v; asm volatile("ld.shared.v4.u32 {%0,%1,%2,%3}, [%4];" : "=r"(v.x), "=r"(v.y), "=r"(v.z), "=r"(v.w) : "r"(a)); return v;
}
__device__ __forceinline__ uint4 lds128v(uint32_t a) {
    uint4 v; asm volatile("ld.volatile.shared.v4.u32 {%0,%1,%2,%3}, [%4];" : "=r"(v.x), "=r"(v.y), "=r"(v.z), "=r"(v.w) : "r"(a)); return v;
}
__device__ __forceinline__ uint32_t or_xor(uint32_t a, uint32_t b, uint32_t c) {
    uint32_t r; asm("lop3.b32 %0, %1, %2, %3, 0xf6;" : "=r"(r) : "r"(a), "r"(b), "r"(c)); return r;
}
__device__ __forceinline__ float4 lds128f(uint32_t a) {
    float4 v; asm volatile("ld.shared.v4.f32 {%0,%1,%2,%3}, [%4];" : "=f"(v.x), "=f"(v.y), "=f"(v.z), "=f"(v.w) : "r"(a)); return v;
}
__device__ __forceinline__ void sts32(uint32_t a, uint32_t v) { asm volatile("st.shared.u32 [%0], %1;" ::"r"(a), "r"(v) : "memory"); }
__device__ __forceinline__ void sts32f(uint32_t a, float v) { asm volatile("st.shared.f32 [%0], %1;" ::"r"(a), "f"(v) : "memory"); }
__device__ __forceinline__ void sts64(uint32_t a, uint32_t x, uint32_t y) { asm volatile("st.shared.v2.u32 [%0], {%1,%2};" ::"r"(a), "r"(x), "r"(y) : "memory"); }
__device__ __forceinline__ void sts64f(uint32_t a, float x, float y) { asm volatile("st.shared.v2.f32 [%0], {%1,%2};" ::"r"(a), "f"(x), "f"(y) : "memory"); }
__device__ __forceinline__ void sts128(uint32_t a, uint32_t x, uint32_t y, uint32_t z, uint32_t w) {
    asm volatile("st.shared.v4.u32 [%0], {%1,%2,%3,%4};" ::"r"(a), "r"(x), "r"(y), "r"(z), "r"(w) : "memory");
}
__device__ __forceinline__ void sts128f(uint32_t a, const float* v) {
    asm volatile("st.shared.v4.f32 [%0], {%1,%2,%3,%4};" ::"r"(a), "f"(v[0]), "f"(v[1]), "f"(v[2]), "f"(v[3]) : "memory");
}
__device__ __forceinline__ uint4 ldg128(const void* p) {
    uint4 v; asm volatile("ld.global.nc.L1::no_allocate.v4.u32 {%0,%1,%2,%3}, [%4];" : "=r"(v.x), "=r"(v.y), "=r"(v.z), "=r"(v.w) : "l"(p)); return v;
}
__device__ __forceinline__ uint2 ldg64(const void* p) {
    uint2 v; asm volatile("ld.global.nc.L1::no_allocate.v2.u32 {%0,%1}, [%2];" : "=r"(v.x), "=r"(v.y) : "l"(p)); return v;
}
__device__ __forceinline__ uint32_t ldg32(const void* p) {
    uint32_t v; asm volatile("ld.global.nc.u32 %0, [%1];" : "=r"(v) : "l"(p)); return v;
}
__device__ __forceinline__ uint32_t ldg16(const void* p) {
    uint32_t v; asm volatile("ld.global.nc.u16 %0, [%1];" : "=r"(v) : "l"(p)); return v;
}
__device__ __forceinline__ uint4 ld_relaxed_128(const void* p) {
    uint4 v; asm volatile("ld.relaxed.gpu.global.v4.u32 {%0,%1,%2,%3}, [%4];" : "=r"(v.x), "=r"(v.y), "=r"(v.z), "=r"(v.w) : "l"(p) : "memory"); return v;
}
__device__ __forceinline__ void ld_relaxed_128_unless(uint4& q, const void* p, bool have) {
    asm volatile("{ .reg .pred p; setp.eq.u32 p, %5, 0; @p ld.relaxed.gpu.global.v4.u32 {%0,%1,%2,%3}, [%4]; }"
                 : "+r"(q.x), "+r"(q.y), "+r"(q.z), "+r"(q.w) : "l"(p), "r"((uint32_t)have) : "memory");
}
__device__ __forceinline__ uint2 ld_relaxed_64(const void* p) {
    uint2 v; asm volatile("ld.relaxed.gpu.global.v2.u32 {%0,%1}, [%2];" : "=r"(v.x), "=r"(v.y) : "l"(p) : "memory"); return v;
}
__device__ __forceinline__ uint32_t ld_relaxed_32(const void* p) {
    uint32_t v; asm volatile("ld.relaxed.gpu.global.u32 %0, [%1];" : "=r"(v) : "l"(p) : "memory"); return v;
}
__device__ __forceinline__ void st_relaxed_128(void* p, uint32_t x, uint32_t y, uint32_t z, uint32_t w) {
    asm volatile("st.relaxed.gpu.global.v4.u32 [%0], {%1,%2,%3,%4};" ::"l"(p), "r"(x), "r"(y), "r"(z), "r"(w) : "memory");
}
__device__ __forceinline__ void st_relaxed_64(void* p, uint32_t x, uint32_t y) {
    asm volatile("st.relaxed.gpu.global.v2.u32 [%0], {%1,%2};" ::"l"(p), "r"(x), "r"(y) : "memory");
}
__device__ __forceinline__ void st_relaxed_32(void* p, uint32_t v) {
    asm volatile("st.relaxed.gpu.global.u32 [%0], %1;" ::"l"(p), "r"(v) : "memory");
}
__device__ __forceinline__ void red_add(void* p, uint32_t v) { asm volatile("red.relaxed.gpu.global.add.u32 [%0], %1;" ::"l"(p), "r"(v) : "memory"); }
__device__ __forceinline__ uint32_t now_ns() { uint32_t t; asm volatile("mov.u32 %0, %%globaltimer_lo;" : "=r"(t) :: "memory"); return t; }
__device__ __forceinline__ void spin_guard(uint32_t& it) { if (++it > SPIN_LIMIT) __trap(); }
__device__ __forceinline__ void wait_count(const uint32_t* p, uint32_t target) {
#pragma unroll 1
    for (uint32_t it = 0; __any_sync(0xffffffffu, (int)(ld_relaxed_32(p) - target) < 0); spin_guard(it)) { }
}
__device__ __forceinline__ void mma_bf16(float* c, uint32_t a0, uint32_t a1, uint32_t a2, uint32_t a3, uint32_t b0, uint32_t b1) {
    asm("mma.sync.aligned.m16n8k16.row.col.f32.bf16.bf16.f32 {%0,%1,%2,%3}, {%4,%5,%6,%7}, {%8,%9}, {%0,%1,%2,%3};"
                 : "+f"(c[0]), "+f"(c[1]), "+f"(c[2]), "+f"(c[3]) : "r"(a0), "r"(a1), "r"(a2), "r"(a3), "r"(b0), "r"(b1));
}
__device__ __forceinline__ void mma_bf16_k8(float* c, uint32_t a0, uint32_t a1, uint32_t b0) {
    asm("mma.sync.aligned.m16n8k8.row.col.f32.bf16.bf16.f32 {%0,%1,%2,%3}, {%4,%5}, {%6}, {%0,%1,%2,%3};"
                 : "+f"(c[0]), "+f"(c[1]), "+f"(c[2]), "+f"(c[3]) : "r"(a0), "r"(a1), "r"(b0));
}
__device__ __forceinline__ void mma_v(float* c, const uint32_t* a, uint32_t b0, uint32_t b1) {
    asm volatile("mma.sync.aligned.m16n8k16.row.col.f32.bf16.bf16.f32 {%0,%1,%2,%3}, {%4,%5,%6,%7}, {%8,%9}, {%0,%1,%2,%3};"
                 : "+f"(c[0]), "+f"(c[1]), "+f"(c[2]), "+f"(c[3]) : "r"(a[0]), "r"(a[1]), "r"(a[2]), "r"(a[3]), "r"(b0), "r"(b1));
}
__device__ __forceinline__ void mma_bf16_z(float* c, uint32_t a0, uint32_t a1, uint32_t a2, uint32_t a3, uint32_t b0, uint32_t b1) {
    asm volatile("mma.sync.aligned.m16n8k16.row.col.f32.bf16.bf16.f32 {%0,%1,%2,%3}, {%4,%5,%6,%7}, {%8,%9}, {%10,%10,%10,%10};"
        : "=f"(c[0]), "=f"(c[1]), "=f"(c[2]), "=f"(c[3]) : "r"(a0), "r"(a1), "r"(a2), "r"(a3), "r"(b0), "r"(b1), "f"(0.f));
}
__device__ __forceinline__ void mma_f16(float* c, uint32_t a0, uint32_t a1, uint32_t a2, uint32_t a3, uint32_t b0, uint32_t b1) {
    asm("mma.sync.aligned.m16n8k16.row.col.f32.f16.f16.f32 {%0,%1,%2,%3}, {%4,%5,%6,%7}, {%8,%9}, {%0,%1,%2,%3};"
                 : "+f"(c[0]), "+f"(c[1]), "+f"(c[2]), "+f"(c[3]) : "r"(a0), "r"(a1), "r"(a2), "r"(a3), "r"(b0), "r"(b1));
}
__device__ __forceinline__ uint32_t pack_bf16(float lo, float hi) {
    uint32_t r; asm("cvt.rn.bf16x2.f32 %0, %1, %2;" : "=r"(r) : "f"(hi), "f"(lo)); return r;
}
__device__ __forceinline__ uint32_t pack_v(float lo, float hi) {
    uint32_t r; asm volatile("cvt.rn.bf16x2.f32 %0, %1, %2;" : "=r"(r) : "f"(hi), "f"(lo)); return r;
}
__device__ __forceinline__ uint32_t pack_w(float lo, float hi) {
    uint32_t r; asm volatile("cvt.rn.satfinite.bf16x2.f32 %0, %1, %2;" : "=r"(r) : "f"(hi), "f"(lo)); return r;
}
__device__ __forceinline__ void pin(uint32_t& x) { asm volatile("" : "+r"(x)); }
template <class T> __device__ __forceinline__ void pin(T*& x) { asm volatile("" : "+l"(x)); }
__device__ __forceinline__ uint32_t pack_f16(float lo, float hi) {
    uint32_t r; asm("cvt.rn.f16x2.f32 %0, %1, %2;" : "=r"(r) : "f"(hi), "f"(lo)); return r;
}
__device__ __forceinline__ float bf_lo(uint32_t v) { return __uint_as_float(v << 16); }
__device__ __forceinline__ float bf_hi(uint32_t v) { return __uint_as_float(v & 0xffff0000u); }
__device__ __forceinline__ float bf_round(float x) { return __uint_as_float(pack_bf16(0.f, x)); }
__device__ __forceinline__ uint32_t badd2(uint32_t a, uint32_t b) { uint32_t r; asm("add.rn.bf16x2 %0, %1, %2;" : "=r"(r) : "r"(a), "r"(b)); return r; }
__device__ __forceinline__ uint32_t bsub2_lo(uint32_t a, uint32_t b) {
    uint32_t r; asm("{ .reg .b16 m, h; .reg .b32 m2; mov.b32 {m, h}, %2; mov.b32 m2, {m, m}; sub.rn.bf16x2 %0, %1, m2; }" : "=r"(r) : "r"(a), "r"(b)); return r;
}
__device__ __forceinline__ uint32_t bmax2(uint32_t a, uint32_t b) { uint32_t r; asm("max.bf16x2 %0, %1, %2;" : "=r"(r) : "r"(a), "r"(b)); return r; }
__device__ __forceinline__ uint32_t normalize2(uint32_t x, uint32_t s0, uint32_t s1) {
    uint32_t r;
    asm("{ .reg .b16 m, h, l, k; .reg .b32 m2, h2, l2, d, t;\n\t"
        "mov.b32 {m, h}, %2; mov.b32 {l, k}, %3; mov.b32 m2, {m, m}; mov.b32 h2, {h, h}; mov.b32 l2, {l, l};\n\t"
        "sub.rn.bf16x2 d, %1, m2; mul.rn.bf16x2 t, d, l2; fma.rn.bf16x2 %0, d, h2, t; }" : "=r"(r) : "r"(x), "r"(s0), "r"(s1));
    return r;
}
__device__ __forceinline__ float rcpf(float x) { float r; asm("rcp.approx.ftz.f32 %0, %1;" : "=f"(r) : "f"(x)); return r; }
__device__ __forceinline__ float sqrtaf(float x) { float r; asm("sqrt.approx.ftz.f32 %0, %1;" : "=f"(r) : "f"(x)); return r; }
__device__ __forceinline__ float ex2f(float x) { float r; asm("ex2.approx.ftz.f32 %0, %1;" : "=f"(r) : "f"(x)); return r; }

__device__ __forceinline__ int tok_off(int t) { return ((t >> 3) & 1) * VT_PLANE + (t >> 4) * 16 + (t & 7) * 2; }

__device__ __forceinline__ uint32_t order_key(uint32_t b16) { return b16 ^ ((b16 & 0x8000u) ? 0xffffu : 0x8000u); }
__device__ __forceinline__ uint32_t unorder_key(uint32_t k16) { return k16 ^ ((k16 & 0x8000u) ? 0x8000u : 0xffffu); }

struct cplx { float r, i; };
struct hc { uint32_t r, i; };
template <bool CONJ> __device__ __forceinline__ cplx csq(cplx a) {
    float im;
    asm("{ .reg .f32 t; mul.ftz.f32 t, %1, %2; mul.ftz.f32 %0, t, 0f40000000; }" : "=f"(im) : "f"(CONJ ? -a.r : a.r), "f"(a.i));
    return {fmaf(a.r, a.r, -(a.i * a.i)), im};
}
__device__ __forceinline__ cplx cexpp(float a2, float ai) {
    float m = ex2f(a2), s, c;
    __sincosf(ai, &s, &c);
    return {m * c, m * s};
}
__device__ __forceinline__ __half2 as_h2(uint32_t x) { return *reinterpret_cast<__half2*>(&x); }
__device__ __forceinline__ uint32_t as_u(__half2 x) { return *reinterpret_cast<uint32_t*>(&x); }
__device__ __forceinline__ hc hmul(hc a, hc b) {
    return {as_u(__hfma2(__hneg2(as_h2(a.i)), as_h2(b.i), __hmul2(as_h2(a.r), as_h2(b.r)))),
            as_u(__hfma2(as_h2(a.i), as_h2(b.r), __hmul2(as_h2(a.r), as_h2(b.i))))};
}
__device__ __forceinline__ hc hpack(cplx a, cplx b) { return {pack_f16(a.r, b.r), pack_f16(a.i, b.i)}; }
__device__ __forceinline__ void sts16(uint32_t a, uint32_t v) { asm volatile("st.shared.u16 [%0], %1;" ::"r"(a), "r"(v) : "memory"); }

template <class Hook, class Hook2>
__device__ __forceinline__ void kgen(uint32_t tab, int lane, uint2 la, uint2 aim, uint2 cre, uint2 cim, float dt, float skip, int dch, Hook main_done, Hook2 half_done) {
    const int g = lane >> 2, t = lane & 3;
    const float dt2 = 2.f * dt;
    const uint32_t am = bmax2(bmax2(cre.x & 0x7fff7fffu, cre.y & 0x7fff7fffu), bmax2(cim.x & 0x7fff7fffu, cim.y & 0x7fff7fffu));
    const float mx = dt2 * fmaxf(bf_lo(am), bf_hi(am));
    const uint32_t eb = min(max(__reduce_max_sync(0xffffffffu, __float_as_uint(mx)) >> 23, 1u), 252u);
    const float cscale = dt2 * __uint_as_float((253u - eb) << 23);
    const float scale_inv = __uint_as_float((eb + 1u) << 23);
    float k0 = (bf_lo(cre.x) + bf_hi(cre.x)) + (bf_lo(cre.y) + bf_hi(cre.y));
#pragma unroll
    for (int o = 16; o; o >>= 1) k0 += __shfl_xor_sync(0xffffffffu, k0, o);
    const float ndt = -1.4426950408889634f * dt;
    STAMP(40); KSTAMP(0);

    float acc[5][4];
#pragma unroll
    for (int i = 0; i < 5; i++) { acc[i][0] = acc[i][1] = acc[i][2] = acc[i][3] = 0.f; }

    const uint32_t rec = tab + t * 512, sw = (uint32_t)t << 5;
    const uint32_t ad_l = rec + (((uint32_t)g << 4) ^ sw), ad_h = rec + 128 + (((uint32_t)g << 3) ^ sw);
    const uint32_t ad_2 = rec + (0xc0u ^ sw) + ((g & 1) << 3), ad_3 = rec + (0xd0u ^ sw) + ((g & 2) << 2);
    const uint32_t ad_4 = rec + (0xe0u ^ sw) + ((g & 4) << 1), ad_z = rec + (0xf0u ^ sw);
    const uint32_t wrec = tab + lane * 256 + ((lane & 7) << 4);

#pragma unroll 1
    for (int bb = 0; bb < 2; bb++) {
        cplx z[2][11], cz[2];
#pragma unroll
        for (int e = 0; e < 2; e++) {
            const float lg = e ? bf_hi(la.x) : bf_lo(la.x), ai = (e ? bf_hi(aim.x) : bf_lo(aim.x)) * dt;
            const float cr = (e ? bf_hi(cre.x) : bf_lo(cre.x)) * cscale, ci = (e ? bf_hi(cim.x) : bf_lo(cim.x)) * cscale;
            const float a2 = bf_round(ex2f(lg * 1.4426950408889634f)) * ndt;
            z[e][0] = cexpp(a2, ai);
            z[e][5] = cexpp(a2 * 32.f, ai * -32.f);
#pragma unroll
            for (int i = 1; i < 11; i++) if (i != 5) z[e][i] = (i == 3 || i == 7) ? csq<true>(z[e][i - 1]) : csq<false>(z[e][i - 1]);
            cz[e] = {fmaf(cr, z[e][0].r, -(ci * z[e][0].i)), fmaf(cr, z[e][0].i, ci * z[e][0].r)};
        }
        la.x = la.y; aim.x = aim.y; cre.x = cre.y; cim.x = cim.y;
        const hc z1 = hpack(z[0][0], z[1][0]), z2 = hpack(z[0][1], z[1][1]), z4 = hpack(z[0][2], z[1][2]);
        hc L[8], H[8];
        L[1] = hpack(z[0][3], z[1][3]); L[2] = hpack(z[0][4], z[1][4]); L[4] = hpack(z[0][5], z[1][5]);
        const hc y64 = hpack(z[0][6], z[1][6]), z128 = hpack(z[0][7], z[1][7]), z256 = hpack(z[0][8], z[1][8]);
        const hc z512 = hpack(z[0][9], z[1][9]), z1024 = hpack(z[0][10], z[1][10]);
        H[0] = hpack(cz[0], cz[1]);
        H[1] = hmul(H[0], z1); H[2] = hmul(H[0], z2); H[3] = hmul(H[1], z2);
        L[3] = hmul(L[1], L[2]);
#pragma unroll
        for (int i = 0; i < 4; i++) { H[4 + i] = hmul(H[i], z4); if (i) L[4 + i] = hmul(L[i], L[4]); }
        __syncwarp();
        sts128(wrec, 0x3c003c00u, y64.r, 0u, y64.i);
#pragma unroll
        for (int i = 1; i < 8; i++) { const hc q = hmul(L[i], y64); sts128(wrec ^ (i << 4), L[i].r, q.r, L[i].i, q.i); }
#pragma unroll
        for (int i = 0; i < 4; i++) sts128((wrec ^ (i << 4)) + 128, H[2 * i].r, H[2 * i].i, H[2 * i + 1].r, H[2 * i + 1].i);
        {
            const hc a = hmul(z256, z1), b = hmul(z256, z128), c = hmul(z256, z2), d = hmul(z512, z4);
            sts128((wrec ^ 0x40) + 128, a.r, a.i, b.r, b.i);
            sts128((wrec ^ 0x50) + 128, c.r, c.i, z512.r, z512.i);
            sts128((wrec ^ 0x60) + 128, d.r, d.i, z1024.r, z1024.i);
            sts64((wrec ^ 0x70) + 128, z128.r, z128.i);
        }
        __syncwarp();
        KSTAMP(1 + 2 * bb);
#pragma unroll kKgUnroll
        for (int k2 = 0; k2 < 4; k2++) {
#pragma unroll
            for (uint32_t s = 0; s < 2; s++) {
                const uint32_t o = k2 * 2048 + s * 256, x = s << 4;
                const uint4 l = lds128((ad_l ^ x) + o);
                const uint2 h0 = lds64((ad_h ^ x) + o), m2 = lds64((ad_2 ^ x) + o), m3 = lds64((ad_3 ^ x) + o);
                const uint2 m4 = lds64((ad_4 ^ x) + o), mz = lds64((ad_z ^ x) + o);
                const hc H0 = {h0.x, h0.y};
                const hc H1 = hmul(H0, {mz.x, mz.y}), H2 = hmul(H0, {m2.x, m2.y}), H3 = hmul(H2, {m3.x, m3.y}), H4 = hmul(H3, {m4.x, m4.y});
                mma_f16(acc[0], l.x, l.y, l.z, l.w, H0.r, H0.i);
                mma_f16(acc[1], l.x, l.y, l.z, l.w, H1.r, H1.i);
                mma_f16(acc[2], l.x, l.y, l.z, l.w, H2.r, H2.i);
                mma_f16(acc[3], l.x, l.y, l.z, l.w, H3.r, H3.i);
                mma_f16(acc[4], l.x, l.y, l.z, l.w, H4.r, H4.i);
            }
        }
        KSTAMP(2 + 2 * bb);
        if (bb == 0) half_done();
    }
    __syncwarp();
    main_done();
    KSTAMP(5);
#pragma unroll
    for (int i = 0; i < 4; i++) sts128(tab + 2048 + 512 * i + 16 * lane, 0, 0, 0, 0);
    if (lane < 15) sts32(tab + 4 * lane, 0);
    __syncwarp();
    const uint32_t d0 = tab + T_DENSE + 4 + 8 * lane, src = (lane + 31) & 31;
    const uint32_t p0 = pack_bf16(fmaf(k0, dt2, skip), 0.f);
    uint32_t prev = p0;
#pragma unroll
    for (int i = 0; i < 4; i++) {
        const uint32_t pk = pack_bf16(acc[i >> 1][2 * (i & 1) + 1] * scale_inv, acc[i >> 1][2 * (i & 1)] * scale_inv);
        sts64(d0 + 256 * i, __byte_perm(pk, __shfl_sync(0xffffffffu, lane == 31 ? prev : pk, src), 0x5432), pk);
        prev = pk;
    }
    const uint32_t w0 = pack_bf16(acc[2][0] * scale_inv, acc[2][1] * scale_inv), w1 = pack_bf16(acc[2][2] * scale_inv, acc[2][3] * scale_inv);
    const uint32_t sa = (lane & 1) ? 0x5410u : 0x5454u, sb2 = (lane & 1) ? 0x1010u : 0x5410u;
#pragma unroll
    for (int hf = 0; hf < 2; hf++) {
        const uint32_t w = hf ? w1 : w0;
        const uint32_t pv = __shfl_sync(0xffffffffu, lane != 31 ? w : hf ? w0 : __byte_perm(prev, w1, 0x5410), src);
        sts64(d0 + 1024 + 256 * hf, __byte_perm(w, pv, sa), __byte_perm(w, pv, sb2));
        sts64(d0 + 1536 + 256 * hf, __byte_perm(w, pv, sa + 0x2222u), __byte_perm(w, pv, sb2 + 0x2222u));
    }
    const uint32_t d3 = tab + T_R2 + 160 + 320 * (t & 1) + 16 * (g >> 1) + 8 * (g & 1) + 4 * (t >> 1), d3n = d3 + (g >= 6 ? 32 : 0);
    const uint32_t d4 = tab + T_R3 + 80 + 160 * t + 4 * g, d4n = d4 + (g >= 6 ? 16 : 0);
    uint32_t p3;
#pragma unroll
    for (int hf = 0; hf < 2; hf++)
#pragma unroll
        for (int e = 0; e < 2; e++) {
            const float v3 = acc[3][2 * hf + e] * scale_inv;
            const uint32_t p4 = pack_bf16(acc[4][2 * hf + e] * scale_inv, 0.f);
            p3 = pack_bf16(v3, v3);
            sts16(d3 + 64 * hf + 160 * e, p3);
            sts16((hf ? d3n : d3) + 64 * hf + 160 * e + 18, p3);
            sts16(d4 + 32 * hf + 80 * e, p4);
            sts16((hf ? d4n : d4) + 32 * hf + 80 * e + 10, p4);
        }
    if (lane == 31) {
        const uint32_t k512 = __byte_perm(w1, 0, 0x3232);
        sts32(tab + T_DENSE, p0);
        sts64(tab + T_DENSE + 4 * 513, k512, k512); sts16(tab + T_DENSE + 4 * 515 + 2, k512);
        sts16(tab + T_PATCH + 4 * 17, p3); sts32(tab + T_PATCH + 4 * 18, p3); sts16(tab + T_PATCH + 4 * 19 + 2, p3);
    }
    __syncwarp();
}

__device__ __forceinline__ void load_toep(uint32_t* a, uint32_t p, uint32_t zero) {
    a[0] = lds32(p); a[1] = lds32(p + 32); a[2] = lds32(p - 32); a[3] = lds32(p + zero);
}
#define DENSE_BLK 2
__device__ __forceinline__ void dense_step(float (&acc)[16][4], uint32_t (&R)[8][4], const uint32_t (&A)[4][4], uint32_t (&An)[4][4],
                                           uint32_t va, uint32_t vmin, uint32_t pn, uint32_t zero, int bit) {
#pragma unroll
    for (int i0 = 0; i0 < 8; i0 += DENSE_BLK) {
#pragma unroll 1
        do {
#pragma unroll
            for (int i = i0; i < i0 + DENSE_BLK; i++) {
                const int ip = (i - DENSE_BLK) & 7;
                ldsm4(R[ip], ip == 0 ? max(va - 16, vmin) : va + ip * 128 - (i0 ? 16 : 0));
                if ((i & 1) == 0) load_toep(An[i >> 1], pn + (i >> 1) * 512, zero);
#pragma unroll
                for (int ka = 0; ka < 4; ka++) {
                    mma_v(acc[i + ka], A[ka], R[i][0], R[i][1]);
                    if (i + 8 + ka < 16) mma_v(acc[i + 8 + ka], A[ka], R[i][2], R[i][3]);
                }
            }
        } while (zero & (1u << (bit + i0)));
    }
}
struct DenseTaps {
    uint32_t A[4][4], E[4], F[4], e8[2], f8[2];
    __device__ __forceinline__ DenseTaps(uint32_t pb, uint32_t zero) {
        constexpr int PP = T_PATCH - T_DENSE + 56;
#pragma unroll
        for (int i = 0; i < 4; i++) load_toep(A[i], pb + 512 * i, zero);
        load_toep(E, pb + 2048, zero);
        load_toep(F, pb + PP, zero);
        e8[0] = lds32(pb + zero + 2048 + 32); e8[1] = lds32(pb + 2048 + 64);
        f8[0] = lds32(pb + zero + PP + 32); f8[1] = lds32(pb + PP + 64);
    }
};
__device__ __forceinline__ void dense_phase(float (&acc)[16][4], uint32_t vrow, uint32_t pb, DenseTaps& tp, uint32_t zero, int lane) {
    uint32_t R[8][4], A1[4][4];
    const uint32_t vp = vrow + ((lane >> 3) & 1) * VT_PLANE, vmin = lane < 16 ? vp - 16 : 0u;
    uint32_t va = vp + (lane >> 4) * 1024 + (lane & 7) * 16;
    {
        uint32_t H[3][4];
#pragma unroll
        for (int i = 0; i < 3; i++) ldsm4(H[i], vrow + VT_PLANE - 16 + lane * 16 + i * 512);
#pragma unroll
        for (int i = 0; i < 8; i++) ldsm4(R[i], va + i * 128);
#pragma unroll
        for (int i = 0; i < 12; i++) mma_bf16_k8(acc[i + 4], tp.e8[0], tp.e8[1], H[i >> 2][i & 3]);
#pragma unroll
        for (int i = 0; i < 8; i++) mma_bf16_k8(acc[i + 8], tp.f8[0], tp.f8[1], H[i >> 2][i & 3]);
#pragma unroll
        for (int i = 0; i < 12; i++) mma_v(acc[i + 4], tp.E, R[i & 7][2 * (i >> 3)], R[i & 7][2 * (i >> 3) + 1]);
#pragma unroll
        for (int i = 0; i < 8; i++) mma_v(acc[i + 8], tp.F, R[i][0], R[i][1]);
    }
#pragma unroll 1
    for (int rho = 0; rho < 8; rho += 2) {
        dense_step(acc, R, tp.A, A1, va, vmin, pb + 64, zero, 0);
        dense_step(acc, R, A1, tp.A, va - 16, vmin, pb + zero + 128, -zero, 8);
        pb += 128; va -= 32;
    }
}
__device__ __forceinline__ uint32_t ones2(int c, int lo, int hi) {
    return (((uint32_t)(c - lo) <= (uint32_t)(hi - lo)) ? 0x3f80u : 0u) | (((uint32_t)(c + 1 - lo) <= (uint32_t)(hi - lo)) ? 0x3f800000u : 0u);
}
struct Boxes {
    uint32_t q[4], ha[2];
    __device__ __forceinline__ Boxes(uint32_t vrow, int lane, int O, int L1, int H1, int L2, int H2) {
        const int g = lane >> 2, t = lane & 3, d = 2 * t - g;
        q[0] = ones2(d, L1, H1); q[1] = ones2(d, L2, H2); q[2] = ones2(d + 8, L1, H1); q[3] = ones2(d + 8, L2, H2);
#pragma unroll
        for (int i = 0; i < 2; i++) { ha[i] = vrow + 16 * g + tok_off(O + 8 * i + 2 * t); pin(ha[i]); pin(q[i]); pin(q[2 + i]); }
    }
    __device__ __forceinline__ uint32_t any() const { return (q[0] | q[1] | q[2]) | (q[3] | ha[0] | ha[1]); }
    __device__ __forceinline__ void load(int j, uint32_t* v, uint32_t zero) const {
        const uint32_t o = j * 128;
        v[0] = lds32(ha[0] + o); v[1] = lds32(ha[1] + zero + o); v[2] = lds32(ha[1] + o);
        v[3] = lds32(ha[0] + zero + o + 16); v[4] = lds32(ha[0] + o + 16); v[5] = lds32(ha[1] + o + 16);
    }
    __device__ __forceinline__ void sums(const uint32_t* v, float* Z, float* X, float* Y) const {
        mma_bf16_z(Z, q[0], q[1], q[2], q[3], v[0], v[1]);
        mma_bf16_z(X, q[0], q[1], q[2], q[3], v[2], v[3]);
        mma_bf16_z(Y, q[0], q[1], q[2], q[3], v[4], v[5]);
    }
};
template <class After>
__device__ __forceinline__ void tail_phase(float (&acc)[16][4], const Boxes& b2, const Boxes& b3, uint32_t tp2, uint32_t tp3, uint32_t zero, After after) {
    uint2 tp[10];
    uint32_t v[6], a0[4], a1[4];
    float Z[4], X[4], Y[4];
    b2.load(0, v, zero);
#pragma unroll
    for (int i = 0; i < 5; i++) { const uint4 c = lds128(tp2 + 160 * i); tp[i] = make_uint2(c.x, c.y); tp[5 + i] = make_uint2(c.z, c.w); }
#pragma unroll
    for (int j = -1; j < 20; j++) {
        if (j < 19) {
            (j < 11 ? b2 : b3).sums(v, Z, X, Y);
            if (j < 10) b2.load(j + 2, v, zero); else if (j < 18) b3.load(j - 10, v, zero);
        }
        if (j >= 0 && j < 12) {
#pragma unroll
            for (int b = 0; b < 5; b++) if (j + 4 + b < 16) mma_v(acc[j + 4 + b], a1, tp[5 + b].x, tp[5 + b].y);
        }
        if (j < 11) { a1[0] = pack_v(Z[0], Z[1]); a1[1] = pack_w(X[0], X[1]); a1[2] = pack_v(Z[2], Z[3]); a1[3] = pack_w(X[2], X[3]); }
        if (j >= 0 && j < 12) {
#pragma unroll
            for (int b = 0; b < 5; b++) if (j + 4 + b < 16) mma_v(acc[j + 4 + b], a0, tp[b].x, tp[b].y);
            if (j >= 7 && j < 11) { tp[11 - j] = lds64(tp3 + 80 * (10 - j)); tp[16 - j] = lds64(tp3 + 80 * (14 - j)); }
        } else if (j >= 12) {
#pragma unroll
            for (int b = 0; b < 8; b++) if (j - 4 + b < 16) mma_v(acc[j - 4 + b], a0, tp[b < 4 ? b + 1 : b + 2].x, tp[b < 4 ? b + 1 : b + 2].y);
        }
        if (j < 11) { a0[0] = pack_v(X[0], X[1]); a0[1] = pack_v(Y[0], Y[1]); a0[2] = pack_v(X[2], X[3]); a0[3] = pack_v(Y[2], Y[3]); }
        else if (j < 19) { a0[0] = pack_v(X[0], X[1]); a0[1] = pack_v(Y[0], Y[1]); a0[2] = pack_v(Z[2], Z[3]); a0[3] = pack_v(X[2], X[3]); }
        after(j);
    }
}
template <int G>
__device__ __forceinline__ void emit(const float (&acc)[16][4], int h, uint32_t own, uint32_t peer, uint32_t bar, uint32_t bar_peer) {
#pragma unroll
    for (int o = 0; o < 2; o++)
#pragma unroll
        for (int hf = 0; hf < 2; hf++) {
            const int n = 8 * G + 4 * o;
            asm volatile("{ .reg .pred p; setp.eq.u32 p, %7, %8;\n\t@p st.shared.v4.u32 [%0], {%1,%2,%3,%4};\n\t"
                         "@!p st.async.weak.shared::cluster.mbarrier::complete_tx::bytes.v4.b32 [%5], {%1,%2,%3,%4}, [%6]; }"
                         ::"r"(own + G * 16384 + hf * 512), "r"(pack_bf16(acc[n][2 * hf], acc[n][2 * hf + 1])), "r"(pack_bf16(acc[n + 1][2 * hf], acc[n + 1][2 * hf + 1])),
                         "r"(pack_bf16(acc[n + 2][2 * hf], acc[n + 2][2 * hf + 1])), "r"(pack_bf16(acc[n + 3][2 * hf], acc[n + 3][2 * hf + 1])),
                         "r"(peer + G * 16384 + hf * 512), "r"(bar_peer + 8 * G), "r"(h), "r"(o) : "memory");
        }
    __syncwarp();
    if (elect_one()) mbar_arrive(bar + 8 * G);
}
__device__ __forceinline__ void finish(uint32_t src, uint32_t xa) {
    uint32_t s[4][4];
    uint4 x[4];
#pragma unroll
    for (int i = 0; i < 4; i++) {
        ldsm4t(s[i], (src ^ ((i & 1) << 5)) + (i >> 1) * 8192);
        x[i] = lds128((xa ^ ((i >> 1) << 4)) + (i & 1) * 256);
    }
#pragma unroll
    for (int i = 0; i < 4; i++)
        sts128((xa ^ ((i >> 1) << 4)) + (i & 1) * 256, badd2(x[i].x, s[i][0]), badd2(x[i].y, s[i][1]), badd2(x[i].z, s[i][2]), badd2(x[i].w, s[i][3]));
}

__device__ __noinline__ float centred_var(uint32_t rows, float mu, int lane) {
    float var = 0.f;
#pragma unroll 1
    for (int rr = 0; rr < 16; rr++) {
        const float c0 = __shfl_sync(0xffffffffu, mu, rr);
        float c = 0.f;
#pragma unroll 1
        for (int k = 0; k < 16; k++) {
            const uint32_t q = lds32(rows + rr * ROW_PITCH + k * 128 + lane * 4);
            const float d0 = bf_lo(q) - c0, d1 = bf_hi(q) - c0;
            c = fmaf(d0, d0, fmaf(d1, d1, c));
        }
#pragma unroll 1
        for (int o = 16; o; o >>= 1) c += __shfl_xor_sync(0xffffffffu, c, o);
        if ((lane & 15) == rr) var = c * (1.f / DM);
    }
    return var;
}
__device__ __noinline__ float centred_score(uint32_t rows, uint32_t wbuf, uint32_t s0, uint32_t s1, int lane) {
    float sc = 0.f;
#pragma unroll 1
    for (int rr = 0; rr < 16; rr++) {
        const uint32_t t0 = __shfl_sync(0xffffffffu, s0, rr), t1 = __shfl_sync(0xffffffffu, s1, rr);
        float c = 0.f;
#pragma unroll 1
        for (int k = 0; k < 16; k++) {
            const uint32_t xn = normalize2(lds32(rows + rr * ROW_PITCH + k * 128 + lane * 4), t0, t1);
            const uint32_t wq = lds32(wbuf + (k >> 2) * 1024 + (k & 3) * 128 + lane * 4);
            c = fmaf(bf_lo(xn), bf_lo(wq), fmaf(bf_hi(xn), bf_hi(wq), c));
        }
#pragma unroll 1
        for (int o = 16; o; o >>= 1) c += __shfl_xor_sync(0xffffffffu, c, o);
        if ((lane & 15) == rr) sc = c;
    }
    return sc;
}

__global__ void __cluster_dims__(2, 1, 1) __launch_bounds__(NTHR, 1)
fused_kernel(const __grid_constant__ Ptrs p, const __grid_constant__ Maps maps) {
    extern __shared__ __align__(1024) unsigned char smem[];
    const int tid = threadIdx.x, lane = tid & 31, b = blockIdx.x;
    const int dch = 8 * b + (tid >> 5) - 4;
    uint2 la, aim, cre, cim;
    uint32_t ldt16, dsk16, epoch;
    uint4 wq;
    if ((uint32_t)(tid - 128) < 256u) {
        la = ldg64(p.logA + dch * NMODE + 4 * lane); aim = ldg64(p.Aim + dch * NMODE + 4 * lane);
        cre = ldg64(p.Cre + dch * NMODE + 4 * lane); cim = ldg64(p.Cim + dch * NMODE + 4 * lane);
        ldt16 = ldg16(p.ldt + dch); dsk16 = ldg16(p.dsk + dch);
    }
    if (tid < 128) { wq = ldg128(p.wr + 8 * tid); epoch = ld_relaxed_32(&p.sc->epoch); }
    const uint32_t sb = s_u32(smem);
    const int warp = __shfl_sync(0xffffffffu, tid >> 5, 0);
    const int h = b & 1, cl = b >> 1;
    const uint32_t bar0 = sb + OFF_BAR;
    const int m = lane >> 3, r = lane & 7, g = lane >> 2, t = lane & 3;
    const bool has_gu = b < GU_CTAS;
    if (warp == 4) { STAMP(0); GSTAMP(24); }

    if (warp >= 12) {
        asm volatile("setmaxnreg.dec.sync.aligned.u32 24;");
        const int a = warp - 12;
        uint32_t due = now_ns() + ST_T0 + (uint32_t)(128 * a + b) * ST_PER / 128;
        const bool el = elect_one();
        if (a == 1 && el) {
#pragma unroll
            for (int j = 0; j < 4; j++) mbar_init(bar0 + 8 * (B_ROW + j), 1);
            asm volatile("fence.mbarrier_init.release.cluster;" ::: "memory");
            fence_async();
#pragma unroll 1
            for (int j = 0; j < 4; j++) {
                mbar_expect_tx(bar0 + 8 * (B_ROW + j), 8192);
#pragma unroll
                for (int i = 0; i < 4; i++)
                    bulk_g2s(sb + OFF_VT + (4 * j + i) * ROW_PITCH, p.u + (size_t)(16 * b + 4 * j + i) * DM, 2048, bar0 + 8 * (B_ROW + j));
            }
        }
        if (a == 2 && el) {
#pragma unroll
            for (int i = B_XT; i < NBAR; i++) mbar_init(bar0 + 8 * i, i == B_SFREE ? 8 : i == B_UPD ? 4 : (i == B_RECV || i == B_RECV + 1) ? 9 : (i >= B_FREE + 4 && i < B_FREE + 8) ? 2 : 1);
            asm volatile("fence.mbarrier_init.release.cluster;" ::: "memory");
            fence_async();
            mbar_expect_tx(bar0 + 8 * B_XT, 65536);
            mbar_expect_tx(bar0 + 8 * B_RECV, 8192);
            mbar_expect_tx(bar0 + 8 * B_RECV + 8, 8192);
            mbar_expect_tx(bar0 + 8 * B_RED, 512);
        }
        if (a == 3 && el) {
#pragma unroll
            for (int i = 0; i < 5; i++) asm volatile("prefetch.tensormap [%0];" ::"l"(&maps.u + i) : "memory");
        }
        __syncwarp();
        cluster_arrive();
        cluster_wait();
        STAMP(18);
        mbar_wait_lazy<40>(bar0 + 8 * (B_ROW + a), 0);
        if (el) {
#pragma unroll
            for (int i = 0; i < 4; i++)
                tma_load_tile(sb + OFF_XT + h * 32768 + a * 4096 + (i & 1) * 16384 + (i >> 1) * 2048, &maps.u, 16 * cl, 4 * a + (i & 2), 16 * (i & 1) + 8 * h, bar0 + 8 * B_XT);
        }
        if (el) {
#pragma unroll 1
            for (int k = has_gu ? 0 : 4; k < 6; k++) {
                const int i = 4 * k + a, s = k < 3 ? i : i - 12;
#pragma unroll 1
                for (int left; (left = (int)(due - now_ns())) > 0;) __nanosleep(left >> 1);
                due += k == 0 ? 4 * ST_PER + ST_GAP : k < 3 ? 4 * ST_PER : 4 * ST_PER2;
                const bool scr = (0xcf0 >> s) & 1, again = k >= 3 && has_gu, mid = (s >> 2) == 1;
                if (scr || again) mbar_wait(bar0 + 8 * (B_FREE + s), scr && again);
                const uint32_t dst = sb + (mid ? OFF_PRIV + 4096 + a * 16384 : OFF_RING + (s >> 3) * 32768 + a * 8192), bar = bar0 + 8 * (B_FULL + s);
                const uint32_t dst2 = dst + (mid ? 8192 : 4096);
                if (k < 4) {
                    mbar_expect_tx(bar, 8192);
                    tma_load_2d(dst, &maps.wg, 32 * b, 64 * i, bar);
                    tma_load_2d(dst2, &maps.wu, 32 * b, 64 * i, bar);
                } else {
                    const int c1 = 1792 * h + 448 * a + 224 * (k & 1);
                    mbar_expect_tx(bar, 7168);
                    tma_load_2d(dst, &maps.wd, 16 * cl, c1, bar);
                    tma_load_2d(dst2, &maps.wd, 16 * cl, c1 + 112, bar);
                }
            }
            STAMP(19);
        }
    } else if (warp >= 4) {
        const int w = warp - 4;
        cluster_arrive();
        asm volatile("setmaxnreg.inc.sync.aligned.u32 168;");
        const uint32_t vrow = sb + OFF_VT + w * VT_PITCH + VT_PAD, tab = sb + OFF_PRIV + w * 8192;
        const uint32_t so = sb + OFF_XT + (8 * h + w) * 1024 + ((lane ^ ((w & 1) << 1)) << 4);
        uint32_t dst0 = so + (h ^ 1) * 32768, dst1 = mapa(so + h * 32768, h ^ 1);
        const uint32_t rb0 = bar0 + 8 * B_RECV, rb1 = mapa(rb0, h ^ 1);
        const uint32_t box = sb + OFF_XT + h * 32768 + w * 2048;
        uint32_t fs = sb + OFF_XT + (h ^ 1) * 32768 + (2 * m + (r & 1)) * 1024 + (w >> 2) * 512 + (((8 * (w & 3) + (r & 4) + ((r >> 1) & 1)) ^ ((r & 1) << 1)) << 4);
        uint32_t fx = box + (g >> 1) * 512 + (t >> 1) * 144 + (2 * (t & 1) + (g & 1)) * 32;
        uint32_t tpo = 80 + (g - 2 * t) * 8 - (g < 2 * t ? 16 : 0);
        uint32_t xa = sb + OFF_XT + (w & 2) * 16384 + (w >> 2) * 16384 + (w & 1) * 1024 + (g >> 1) * 2048 + (g & 1) * 128 + t * 32 + ((h ^ (g & 1)) << 4);
        uint32_t va = sb + OFF_VT + (2 * m + (r & 1)) * VT_PITCH + VT_PAD + (16 * w + (r >> 1)) * 16;
        uint32_t qa = sb + OFF_ST + 2048 * w + 128 * t + 16 * (g ^ (2 * t));
        uint4 x[8];
        pin(dst0); pin(dst1); pin(fs); pin(fx); pin(tpo); pin(xa); pin(va); pin(qa);
        const Boxes b2(vrow, lane, -18, 5, 7, 0, 4), b3(vrow, lane, -20, 1, 7, 0, 8);
        if (__any_sync(0xffffffffu, ((dst0 | dst1 | fs) | (fx | tpo | xa) | (va | qa) | (b2.any() | b3.any())) & p.zero)) __trap();
        cluster_wait();
        pin(la.x); pin(la.y); pin(aim.x); pin(aim.y); pin(cre.x); pin(cre.y); pin(cim.x); pin(cim.y); pin(ldt16); pin(dsk16);
        kgen(tab, lane, la, aim, cre, cim, bf_round(ex2f(bf_lo(ldt16) * 1.4426950408889634f)), 1.f + bf_lo(dsk16), dch, [&]() {
            STAMP(21);
            if (elect_one()) mbar_arrive(bar0 + 8 * (B_FREE + 4 + (w >> 1)));
            mbar_wait_lazy<40>(bar0 + 8 * B_XT, 0);
#pragma unroll
            for (int i = 0; i < 8; i++) x[i] = lds128(xa + (i & 1) * 8192 + (i >> 1) * 256);
        }, [&]() {
        });
        STAMP(1); KSTAMP(6);
        const uint32_t pb = tab + T_DENSE + (g - 2 * t) * 4;
        DenseTaps dt(pb, p.zero);
        {
            uint4 q[4];
            mbar_wait(bar0 + 8 * (B_ST + w), 0);
#pragma unroll
            for (int n = 0; n < 4; n++) q[n] = lds128(qa + 512 * n);
            if (lane < 4) sts128(vrow - VT_PAD + (lane >> 1) * VT_PLANE + (lane & 1) * 16, 0, 0, 0, 0);
            STAMP(2); GSTAMP(28);
#pragma unroll
            for (int i = 0; i < 8; i++) {
                const uint32_t s0 = (i & 1) ? q[i >> 1].z : q[i >> 1].x, s1 = (i & 1) ? q[i >> 1].w : q[i >> 1].y;
                stsm4t(va + (i >> 1) * 64 + (i & 1) * VT_PLANE, normalize2(x[i].x, s0, s1), normalize2(x[i].y, s0, s1),
                       normalize2(x[i].z, s0, s1), normalize2(x[i].w, s0, s1));
            }
            named_sync(2, 256);
            if (elect_one()) {
                if (w < 3) mbar_arrive(bar0 + 8 * (w == 2 ? B_V : B_FREE + 10 + w));
            }
        }
        STAMP(3); KSTAMP(7);
        float acc[16][4];
#pragma unroll
        for (int i = 0; i < 16; i++) { acc[i][0] = acc[i][1] = acc[i][2] = acc[i][3] = 0.f; }
        dense_phase(acc, vrow, pb, dt, p.zero, lane);
        STAMP(4); KSTAMP(8);
        tail_phase(acc, b2, b3, tab + T_R2 + 2 * tpo, tab + T_R3 + tpo, p.zero, [&](int j) {
            if (j == 3) {
                mbar_wait(bar0 + 8 * B_SFREE, 0);
                emit<0>(acc, h, dst0, dst1, rb0, rb1);
                STAMP(5);
            }
            if (j == 7) {
                mbar_wait(bar0 + 8 * B_RECV, 0);
                finish(fs, fx);
                fence_async();
                __syncwarp();
                if (elect_one()) tma_store_tile(&maps.out, box, 16 * cl, 2 * w, 8 * h);
                STAMP(20);
            }
        });
        emit<1>(acc, h, dst0, dst1, rb0, rb1);
        STAMP(30);
        mbar_wait(bar0 + 8 * (B_RECV + 1), 0);
        STAMP(6);
        finish(fs + 16384, fx + 16384);
        const bool ready = mbar_test(bar0 + 8 * B_UPD, 0);
        const bool el = elect_one();
#pragma unroll 1
        for (int pass = 0; pass < 2; pass++) {
            if ((pass != 0) == ready) {
                fence_async();
                __syncwarp();
                if (el) tma_store_tile(&maps.out, box + 16384, 16 * cl, 2 * w, 16 + 8 * h);
            } else {
                if (el) asm volatile("cp.async.bulk.wait_group 0;" ::: "memory");
                __syncwarp();
                mbar_wait_lazy<40>(bar0 + 8 * B_UPD, 0);
                const int tok = 2047 - (int)(lds32(sb + OFF_MISC + 48 + 8 * g) & 2047);
                if ((((tok >> 6) & 8) | ((tok >> 1) & 7)) == 8 * h + w) {
                    const uint32_t xa = box + (tok >> 10) * 16384 + ((tok >> 6) & 7) * 256 + (tok & 1) * 128 + ((tok >> 4) & 3) * 32 + (((t >> 1) ^ (tok & 1)) << 4) + (t & 1) * 8;
                    const uint2 o0 = lds64(xa);
                    const float4 up = lds128f(sb + OFF_RED + 16 * lane);
                    const uint2 o1 = make_uint2(badd2(o0.x, pack_bf16(up.x, up.y)), badd2(o0.y, pack_bf16(up.z, up.w)));
                    if (ready && tok >= 1024) sts64(xa, o1.x, o1.y);
                    else *reinterpret_cast<uint2*>(p.out + (size_t)tok * DM + 16 * cl + 4 * t) = o1;
                }
            }
        }
        if (el) asm volatile("cp.async.bulk.wait_group.read 0;" ::: "memory");
        STAMP(7);
    } else {
        const int a = warp;
        cluster_arrive();
        asm volatile("setmaxnreg.inc.sync.aligned.u32 152;");
        const uint32_t tag = __shfl_sync(0xffffffffu, epoch, 0) + 1u, misc = sb + OFF_MISC, abar = bar0 + 8 * (B_AUX + a);
        uint32_t aph = 0;
        uint2* pub = p.sc->stat + 16 * b + 2 * (r ^ (2 * (b & 3))) + m;
        uint32_t* cnt_s = &p.sc->n_stat[b & 96];
        pin(pub); pin(cnt_s);
        if (tid < 64) sts32(sb + OFF_RED + 4 * tid, 0);
        const uint32_t wbuf = sb + OFF_LN + a * 1024, part = sb + OFF_LN + 4096;
        {
            sts128(wbuf + 16 * lane, wq.x, wq.y, wq.z, wq.w);
            sts128(wbuf + 512 + 16 * lane, 0x3f803f80u, 0x3f803f80u, 0x3f803f80u, 0x3f803f80u);
            float wsum = ((bf_lo(wq.x) + bf_hi(wq.x)) + (bf_lo(wq.y) + bf_hi(wq.y))) + ((bf_lo(wq.z) + bf_hi(wq.z)) + (bf_lo(wq.w) + bf_hi(wq.w)));
#pragma unroll
            for (int o = 16; o; o >>= 1) wsum += __shfl_xor_sync(0xffffffffu, wsum, o);
            sts32f(part + 1024 + 4 * a, wsum);
            uint32_t wf[4][4];
#pragma unroll
            for (int i = 0; i < 4; i++) ldsm4(wf[i], wbuf + ((uint32_t)(r - 1) < 2u ? 16 * (r - 1) : 512) + 32 * m + 128 * i);
            uint32_t ra = sb + OFF_VT + r * ROW_PITCH + 512 * a + 16 * m, pa = part + a * 256 + g * 16;
            cluster_wait();
            STAMP(22);
#pragma unroll 1
            for (int hf = 0; hf < 2; hf++) {
                if (a < 2) mbar_wait(bar0 + 8 * (B_ROW + a) + 16 * hf, 0);
                named_sync(1, 128);
                STAMP(23);
                uint32_t x[8][4];
                float cs[2][4], q[8][4];
#pragma unroll
                for (int i = 0; i < 40; i++) (i < 8 ? cs[i >> 2 & 1] : q[(i - 8) >> 2 & 7])[i & 3] = 0.f;
#pragma unroll
                for (int k = 0; k < 8; k++) ldsm4(x[k], ra + k * 64);
                const uint32_t dep = (x[6][3] | x[7][3]) & p.zero;
                x[0][0] |= dep; x[0][2] |= dep; x[1][0] |= dep; x[1][2] |= dep;
#pragma unroll
                for (int k = 0; k < 8; k++) {
                    mma_bf16(cs[k & 1], x[k][0], x[k][1], x[k][2], x[k][3], wf[k >> 1][2 * (k & 1)], wf[k >> 1][2 * (k & 1) + 1]);
#pragma unroll
                    for (int i = 0; i < 4; i++) mma_bf16_k8(q[4 * (k & 1) + i], x[k][i & 2], x[k][i | 1], x[k][i]);
                }
                const float c2 = cs[0][2] + cs[1][2];
                if (t == 0) sts64f(pa, (cs[0][0] + cs[1][0]) + c2, cs[0][1] + cs[1][1]);
                if (t == 1) sts32f(pa + 12, c2);
                const float e0 = ((q[0][0] + q[2][0]) + (q[4][0] + q[6][0])) + ((q[1][2] + q[3][2]) + (q[5][2] + q[7][2]));
                const float e1 = ((q[0][1] + q[2][1]) + (q[4][1] + q[6][1])) + ((q[1][3] + q[3][3]) + (q[5][3] + q[7][3]));
                if (t == (g >> 1)) sts32f(pa + 8, (g & 1) ? e1 : e0);
                ra += 8 * ROW_PITCH; pa += 128;
            }
        }
        STAMP(31);
        named_sync(1, 128);
        if (a == 0) {
            const uint32_t pa = part + (lane & 15) * 16;
            const float4 p0 = lds128f(pa), p1 = lds128f(pa + 256), p2 = lds128f(pa + 512), p3 = lds128f(pa + 768), ws = lds128f(part + 1024);
            const float mu = ((p0.x + p1.x) + (p2.x + p3.x)) * (1.f / DM);
            float var = ((p0.z + p1.z) + (p2.z + p3.z)) * (1.f / DM) - mu * mu;
            const bool centred = __any_sync(0xffffffffu, !(mu * mu <= 4.f * var));
            if (centred) var = centred_var(sb + OFF_VT, mu, lane);
            const float ri = rcpf(bf_round(sqrtaf(bf_round(bf_round(var) + 1e-5f))));
            const uint32_t s0 = pack_bf16(mu, ri), s1 = (pack_bf16(ri - bf_hi(s0), 0.f) & 0xfffcu) | (tag & 3);
            float sc = ((((p0.y + p1.y) + (p2.y + p3.y)) + ((p0.w + p1.w) + (p2.w + p3.w))) - bf_lo(s0) * ((ws.x + ws.y) + (ws.z + ws.w))) * ri;
            if (centred) sc = centred_score(sb + OFF_VT, sb + OFF_LN, s0, s1, lane);
            const uint32_t sb16 = pack_bf16(0.f, sc);
            if (lane < 16) st_relaxed_64(pub, s0, s1 | (sb16 ^ (((uint32_t)((int)sb16 >> 31) & 0x7fff0000u) | 0x80000000u)));
            if (lane == 0) red_add(cnt_s, 1);
            STAMP(9); GSTAMP(25);
        }
        const uint32_t slot0 = sb + OFF_RING + a * 8192, slot1 = sb + OFF_PRIV + a * 16384 + 4096, fbar = bar0 + 8 * (B_FULL + a);
        uint32_t mine = 0, row[2] = {0, 0};
        {
            uint32_t q[16];
            named_sync(1, 128);
            wait_count(&p.sc->n_stat[32 * a], 32 * tag - FEW_ST);
            STAMP(41);
#pragma unroll 1
            for (uint32_t it = 0;; spin_guard(it)) {
                if (elect_one()) {
                    mbar_expect_tx(abar, 4096);
                    bulk_g2s(sb + OFF_ST + 4096 * a, p.sc->stat + 512 * a, 4096, abar);
                }
                mbar_wait(abar, aph);
                aph ^= 1;
                uint32_t bad = 0;
#pragma unroll
                for (int n = 0; n < 8; n++) {
                    const uint4 u = lds128v(sb + OFF_ST + 4096 * a + 512 * n + 16 * lane);
                    q[2 * n] = u.y; q[2 * n + 1] = u.w;
                    bad = or_xor(bad, u.y, tag);
                }
                const bool ok = __all_sync(0xffffffffu, (bad & 3) == 0);
                asm volatile("{ .reg .pred p; setp.ne.u32 p, %1, 0; @p mbarrier.arrive.shared::cta.b64 _, [%0]; }" ::"r"(bar0 + 8 * B_ST + 16 * a + 8 * lane), "r"((uint32_t)(ok && lane < 2)) : "memory");
                if (ok) break;
            }
            STAMP(8);
            const uint32_t inv = 2047 - 512 * a - 16 * m - (r ^ (2 * m));
#pragma unroll
            for (int i = 0; i < 16; i++) asm("lop3.b32 %0, %0, %1, %2, 0x9b;" : "+r"(q[i]) : "r"(inv), "r"(0xffff0000u | (64 * (i >> 1) + 8 * (i & 1))));
            auto below = [&](uint32_t x) {
                uint32_t d[4];
#pragma unroll
                for (int i = 0; i < 16; i++) d[i & 3] = i < 4 ? x + q[i] : min(d[i & 3], x + q[i]);
                d[0] = min(min(d[0], d[1]), min(d[2], d[3]));
                return d[0] < x ? x - 1 - d[0] : 0u;
            };
            const uint32_t mx0 = ~min(min(min(min(q[0], q[1]), min(q[2], q[3])), min(min(q[4], q[5]), min(q[6], q[7]))),
                                      min(min(min(q[8], q[9]), min(q[10], q[11])), min(min(q[12], q[13]), min(q[14], q[15]))));
            const uint32_t gm = min(__reduce_max_sync(0xffffffffu, lane < 16 ? mx0 : 0u), __reduce_max_sync(0xffffffffu, lane < 16 ? 0u : mx0));
            if (lane == 0) sts32(misc + 16 + 4 * a, gm);
            named_sync(1, 128);
            STAMP(42);
            if (b == 0 && tid == 0) st_relaxed_32(&p.sc->epoch, tag);
            const uint4 t0 = lds128(misc + 16);
            uint32_t tau = min(min(t0.x, t0.y), min(t0.z, t0.w));
            uint32_t mx = mx0, cnt = 0, bal;
            const uint32_t list = sb + OFF_RED + 64 * a;
#pragma unroll 1
            while ((bal = __ballot_sync(0xffffffffu, mx >= tau)) != 0) {
                const uint32_t pos = cnt + __popc(bal & ((1u << lane) - 1u));
                cnt += __popc(bal);
                if (cnt > 16) break;
                if (mx >= tau) sts32(list + 4 * pos, mx);
                mx = below(mx);
            }
            if (cnt > 16) {
                mx = mx0;
#pragma unroll 1
                for (int j = 0; j < 8; j++) {
                    const uint32_t top = __reduce_max_sync(0xffffffffu, mx), nx = below(mx);
                    if (mx == top) { sts32(list + 4 * j, mx); sts32(list + 32 + 4 * j, 0); mx = nx; }
                }
            }
            named_sync(1, 128);
            STAMP(43);
            const uint2 k = lds64(sb + OFF_RED + 8 * lane);
            uint32_t hi = max(k.x, k.y), lo = min(k.x, k.y);
            mbar_wait(bar0 + 8 * B_V, 0);
#pragma unroll
            for (int j = 0; j < 8; j++) {
                const uint32_t top = __reduce_max_sync(0xffffffffu, hi);
                const bool won = hi == top;
                hi = won ? lo : hi;
                lo = won ? 0u : lo;
                if (g == j) mine = top;
                if (a == (j >> 1)) row[j & 1] = top;
            }
        }
        STAMP(11);
        const int tok = 2047 - (int)(mine & 2047);
        const uint32_t xs = sb + OFF_XT + (h ^ 1) * 32768;
        if (has_gu) {
            const int tok0 = 2047 - (int)(row[0] & 2047), tok1 = 2047 - (int)(row[1] & 2047);
            if (elect_one()) {
                mbar_expect_tx(abar, 4096);
                bulk_g2s(xs + 2 * a * ROW_PITCH, p.u + (size_t)tok0 * DM, 2048, abar);
                bulk_g2s(xs + (2 * a + 1) * ROW_PITCH, p.u + (size_t)tok1 * DM, 2048, abar);
            }
        }
        STAMP(44);
        const uint2 st = ld_relaxed_64(p.sc->stat + (tok & ~15) + 2 * ((tok & 7) ^ ((tok >> 3) & 6)) + ((tok >> 3) & 1));
        if (a == 0 && t == 0) sts64(misc + 48 + 8 * g, mine, __float_as_uint(bf_hi(st.x) + bf_lo(st.y)));
        uint32_t xq[8][4];
        if (a == 0) STAMP(45);
        if (has_gu) {
            mbar_wait(abar, aph);
            aph ^= 1;
            STAMP(46);
            named_sync(1, 128);
#pragma unroll
            for (int j = 0; j < 8; j++) {
                ldsm4(xq[j], xs + r * ROW_PITCH + m * 16 + 128 * a + (j >> 1) * 512 + (j & 1) * 64);
#pragma unroll
                for (int i = 0; i < 4; i++) xq[j][i] = bsub2_lo(xq[j][i], st.x);
            }
        }
        __syncwarp();
        if (lane < 2) mbar_arrive_peer(mapa(bar0 + 8 * B_SFREE, lane) + (has_gu ? (xq[5][0] | xq[6][0] | xq[7][0]) & p.zero : 0u));
        if (has_gu) {
            STAMP(12);
            float gacc[8][4];
#pragma unroll
            for (int i = 0; i < 8; i++) { gacc[i][0] = gacc[i][1] = gacc[i][2] = gacc[i][3] = 0.f; }
            uint4* pubh = &p.sc->h[b * 32 + lane];
            uint32_t* cnt_h = &p.sc->n_h[32 * (b / 14)];
            pin(pubh); pin(cnt_h);
            const uint32_t ko = (r + ((m >> 1) << 3)) * 64 + (((r >> 1) & 3) << 4);
#pragma unroll
            for (int c = 0; c < 4; c++) {
                mbar_wait(fbar + 32 * (c % 3), c / 3);
                STAMP(36 + c);
                const uint32_t rowa = (c == 1 ? slot1 + (m & 1) * 8192 : slot0 + (c == 2) * 32768 + (m & 1) * 4096) + ko;
                uint32_t af[16][4];
#pragma unroll
                for (int ks = 0; ks < 4; ks++)
#pragma unroll
                    for (int mt = 0; mt < 4; mt++) ldsm4t(af[4 * ks + mt], (rowa ^ (mt << 4)) + ks * 1024);
                const uint32_t dep = ((af[12][3] | af[13][3]) | (af[14][3] | af[15][3])) & p.zero;
                __syncwarp();
                if (c < 3 && elect_one()) { if (c == 1) mbar_arrive2(bar0 + 8 * (B_FREE + 4 + a) + dep); else mbar_arrive(bar0 + 8 * (B_FREE + 4 * c + a) + dep); }
#pragma unroll
                for (int ks = 0; ks < 4; ks++) {
                    const uint32_t* q = xq[2 * c + (ks >> 1)] + 2 * (ks & 1);
#pragma unroll
                    for (int mt = 0; mt < 4; mt++)
                        mma_bf16(gacc[4 * (ks & 1) + mt], af[4 * ks + mt][0], af[4 * ks + mt][1], af[4 * ks + mt][2], af[4 * ks + mt][3],
                                 q[0] | (ks < 2 ? dep : 0u), q[1]);
                }
            }
            STAMP(13);
#pragma unroll
            for (int mt = 0; mt < 4; mt++) {
#pragma unroll
                for (int j = 0; j < 4; j++) gacc[mt][j] += gacc[4 + mt][j];
                sts128f(slot0 + mt * 512 + lane * 16, gacc[mt]);
            }
            named_sync(1, 128);
            const uint32_t base = sb + OFF_RING + 16 * tid;
            const float4 p0 = lds128f(base), p1 = lds128f(base + 8192), p2 = lds128f(base + 16384), p3 = lds128f(base + 24576);
            const float r0 = lds32f(misc + 52 + 16 * t), r1 = lds32f(misc + 60 + 16 * t);
            const float g0 = bf_round(((p0.x + p1.x) + (p2.x + p3.x)) * r0), g1 = bf_round(((p0.y + p1.y) + (p2.y + p3.y)) * r1);
            const float h0 = bf_round(g0 * rcpf(1.f + ex2f(-1.4426950408889634f * g0))) * bf_round(((p0.z + p1.z) + (p2.z + p3.z)) * r0);
            const float h1 = bf_round(g1 * rcpf(1.f + ex2f(-1.4426950408889634f * g1))) * bf_round(((p0.w + p1.w) + (p2.w + p3.w)) * r1);
            uint32_t hw;
            asm volatile("movmatrix.sync.aligned.m8n8.trans.b16 %0, %1;" : "=r"(hw) : "r"(pack_bf16(h0, h1)));
            sts32(sb + OFF_RING + 7168 + 16 * lane + 4 * a, hw);
            named_sync(1, 128);
            if (a == 0) {
                const uint4 q = lds128(base + 7168);
                st_relaxed_128(pubh, q.x, q.y, q.z, (q.w & ~1u) | (tag & 1));
                if (lane == 0) red_add(cnt_h, 1);
            }
            STAMP(14);
        }
        float dacc[4];
        {
            wait_count(&p.sc->n_h[32 * (4 * h + a)], 14 * tag - FEW_H);
            STAMP(33);
            uint4 hq[14];
#pragma unroll 1
            for (uint32_t it = 0;; spin_guard(it)) {
                if (elect_one()) {
                    mbar_expect_tx(abar, 7168);
                    bulk_g2s(slot0, &p.sc->h[(56 * h + 14 * a) * 32], 7168, abar);
                }
                mbar_wait(abar, aph);
                aph ^= 1;
                uint32_t bad = 0;
#pragma unroll
                for (int j = 0; j < 14; j++) { hq[j] = lds128(slot0 + 512 * j + 16 * lane); bad = or_xor(bad, hq[j].w, tag); }
                if (__all_sync(0xffffffffu, (bad & 1) == 0)) break;
            }
            STAMP(15);
            const uint32_t wo = (r + ((m >> 1) << 3)) * 32 + (((m & 1) ^ (r >> 2)) << 4);
            float d[7][4];
#pragma unroll
            for (int i = 0; i < 7; i++) { d[i][0] = d[i][1] = d[i][2] = d[i][3] = 0.f; }
#pragma unroll
            for (int s = 0; s < 2; s++) {
                mbar_wait(fbar + 32 + 32 * s, has_gu);
                uint32_t af[14][4];
#pragma unroll
                for (int j = 0; j < 14; j++) ldsm4t(af[j], (s ? slot0 + 32768 + (j / 7) * 4096 : slot1 + (j / 7) * 8192) + wo + (j % 7) * 512);
                const uint32_t dep = (af[11][3] | af[12][3] | af[13][3]) & p.zero;
#pragma unroll
                for (int j = 0; j < 14; j++) {
                    const uint4 q = hq[7 * s + (j >> 1)];
                    mma_bf16(d[j % 7], af[j][0], af[j][1], af[j][2], af[j][3], ((j & 1) ? q.z : q.x) | (j < 7 ? dep : 0u), (j & 1) ? q.w : q.y);
                }
            }
#pragma unroll
            for (int j = 0; j < 4; j++) dacc[j] = ((d[0][j] + d[1][j]) + (d[2][j] + d[3][j])) + ((d[4][j] + d[5][j]) + d[6][j]);
        }
        STAMP(16);
        {
            sts128f(slot0 + 7680 + lane * 16, dacc);
            named_sync(1, 128);
            const int tk = tid >> 4, col = tid & 15;
            const uint32_t base = sb + OFF_RING + 7680 + ((col & 7) * 4 + (tk >> 1)) * 16 + (((col >> 3) << 1) + (tk & 1)) * 4;
            const float y0 = (lds32f(base) + lds32f(base + 8192)) + (lds32f(base + 16384) + lds32f(base + 24576));
            const uint32_t red = sb + OFF_RED + 4 * tid, key = lds32(misc + 48 + 8 * tk);
            mbar_wait(bar0 + 8 * B_SFREE, 0);
            asm volatile("st.async.weak.shared::cluster.mbarrier::complete_tx::bytes.f32 [%0], %1, [%2];"
                         ::"r"(mapa(red, h ^ 1)), "f"(y0), "r"(mapa(bar0 + 8 * B_RED, h ^ 1)) : "memory");
            const float rv = __uint_as_float(unorder_key(key >> 16) << 16);
            const float sg = bf_round(rcpf(1.f + ex2f(-1.4426950408889634f * rv)));
            mbar_wait(bar0 + 8 * B_RED, 0);
            sts32f(red, bf_round(y0 + lds32f(red)) * sg);
            __syncwarp();
            if (elect_one()) mbar_arrive(bar0 + 8 * B_UPD);
        }
        STAMP(17); GSTAMP(29);
    }
}

typedef CUresult (*EncodeFn)(CUtensorMap*, CUtensorMapDataType, cuuint32_t, void*, const cuuint64_t*, const cuuint64_t*,
                             const cuuint32_t*, const cuuint32_t*, CUtensorMapInterleave, CUtensorMapSwizzle,
                             CUtensorMapL2promotion, CUtensorMapFloatOOBfill);

void make_map(EncodeFn enc, CUtensorMap* m, const void* ptr, uint64_t cols, uint64_t rows, uint32_t bc, uint32_t br,
              CUtensorMapSwizzle sw, CUtensorMapL2promotion pr) {
    cuuint64_t dims[2] = {cols, rows};
    cuuint64_t str[1] = {cols * 2};
    cuuint32_t box[2] = {bc, br};
    cuuint32_t es[2] = {1, 1};
    enc(m, CU_TENSOR_MAP_DATA_TYPE_BFLOAT16, 2, const_cast<void*>(ptr), dims, str, box, es, CU_TENSOR_MAP_INTERLEAVE_NONE, sw, pr,
        CU_TENSOR_MAP_FLOAT_OOB_FILL_NONE);
}
void make_tile_map(EncodeFn enc, CUtensorMap* m, const void* ptr) {
    cuuint64_t dims[4] = {DM, 4, 16, SEQ / 64};
    cuuint64_t str[3] = {16 * DM * 2, DM * 2, 64 * DM * 2};
    cuuint32_t box[4] = {16, 4, 2, 8};
    cuuint32_t es[4] = {1, 1, 1, 1};
    enc(m, CU_TENSOR_MAP_DATA_TYPE_BFLOAT16, 4, const_cast<void*>(ptr), dims, str, box, es, CU_TENSOR_MAP_INTERLEAVE_NONE,
        CU_TENSOR_MAP_SWIZZLE_32B, CU_TENSOR_MAP_L2_PROMOTION_NONE, CU_TENSOR_MAP_FLOAT_OOB_FILL_NONE);
}

}

#define WD_PROMO CU_TENSOR_MAP_L2_PROMOTION_L2_64B
extern "C" void kernel_launch(void* const* d_in, const int* in_sizes, int n_in, void* d_out, int out_size) {
    (void)in_sizes; (void)n_in; (void)out_size;
    static EncodeFn enc = nullptr;
    static void* scratch = nullptr;
    if (!enc) {
        void* fn = nullptr;
        cudaDriverEntryPointQueryResult q;
        cudaGetDriverEntryPoint("cuTensorMapEncodeTiled", &fn, cudaEnableDefault, &q);
        enc = (EncodeFn)fn;
        cudaGetSymbolAddress(&scratch, g_scratch);
        cudaFuncSetAttribute(fused_kernel, cudaFuncAttributeMaxDynamicSharedMemorySize, SMEM_BYTES);
    }
    Maps maps;
    make_tile_map(enc, &maps.u, d_in[0]);
    make_tile_map(enc, &maps.out, d_out);
    make_map(enc, &maps.wg, d_in[9], FF, DM, 32, 64, CU_TENSOR_MAP_SWIZZLE_64B, CU_TENSOR_MAP_L2_PROMOTION_L2_128B);
    make_map(enc, &maps.wu, d_in[10], FF, DM, 32, 64, CU_TENSOR_MAP_SWIZZLE_64B, CU_TENSOR_MAP_L2_PROMOTION_L2_128B);
    make_map(enc, &maps.wd, d_in[11], DM, FF, 16, 112, CU_TENSOR_MAP_SWIZZLE_32B, WD_PROMO);
    Ptrs p;
    p.sc = (Scratch*)scratch;
    p.u = (const __nv_bfloat16*)d_in[0];
    p.logA = (const __nv_bfloat16*)d_in[1];
    p.Aim = (const __nv_bfloat16*)d_in[2];
    p.Cre = (const __nv_bfloat16*)d_in[3];
    p.Cim = (const __nv_bfloat16*)d_in[4];
    p.ldt = (const __nv_bfloat16*)d_in[5];
    p.dsk = (const __nv_bfloat16*)d_in[6];
    p.wr = (const __nv_bfloat16*)d_in[8];
    p.out = (__nv_bfloat16*)d_out;
    p.zero = 0;
    fused_kernel<<<NCTA, NTHR, SMEM_BYTES, cudaStreamPerThread>>>(p, maps);
}
```

```cpp
#include <cuda_runtime.h>
#include <cuda_bf16.h>
#include <cuda_fp16.h>
#include <cuda.h>
#include <stdint.h>

namespace {

constexpr int SEQ = 2048, DM = 1024, NMODE = 128, FF = 3584;
constexpr int NCTA = 128, NTHR = 512;
constexpr int GU_CTAS = 112;

constexpr int OFF_XT = 0;
constexpr int OFF_RING = 65536;
constexpr int OFF_PRIV = OFF_RING + 65536;
constexpr int OFF_VT = OFF_PRIV + 65536;
constexpr int VT_PAD = 32, VT_PLANE = VT_PAD + 2048, VT_PITCH = 2 * VT_PLANE, ROW_PITCH = 2064;
constexpr int OFF_BAR = OFF_VT + 8 * VT_PITCH;
constexpr int OFF_MISC = OFF_BAR + 384;
constexpr int OFF_RED = OFF_MISC + 112;
constexpr int OFF_STAMP = OFF_RED + 512;
constexpr int SMEM_BYTES = OFF_STAMP + 256;
constexpr int OFF_LN = OFF_RING + 7 * 8192;
constexpr int OFF_ST = OFF_RING + 6 * 8192;
static_assert(SMEM_BYTES <= 232448, "shared memory");

constexpr int B_ROW = 0, B_XT = 4, B_V = 5, B_SFREE = 7, B_RECV = 8, B_RED = 10, B_UPD = 11, B_ST = 12, B_FREE = 20, B_FULL = 32, B_AUX = 44, NBAR = 48;

constexpr int T_DENSE = 60;
constexpr int T_PATCH = 2208;
constexpr int T_R2 = 2368;
constexpr int T_R3 = 3296;

constexpr uint32_t SPIN_LIMIT = 1u << 20;
#define KG_UNROLL 4
constexpr int kKgUnroll = KG_UNROLL;
#define DENSE_UNROLL 1
constexpr int kDenseUnroll = DENSE_UNROLL;
#define ST_T0 2900
#define FEW_ST 0
#define FEW_H 0
#define ST_GAP 0
#define ST_PER 310
#define ST_PER2 300

struct Scratch {
    uint2 stat[SEQ];
    uint4 h[GU_CTAS * 32];
    uint32_t n_stat[4 * 32];
    uint32_t n_h[8 * 32];
    uint32_t epoch;
};
__device__ __align__(128) Scratch g_scratch;

struct Ptrs {
    Scratch* sc;
    const __nv_bfloat16 *logA, *Aim, *Cre, *Cim, *ldt, *dsk, *u, *wr;
    __nv_bfloat16* out;
    uint32_t zero;
};
struct Maps {
    CUtensorMap u, out, wg, wu, wd;
};

#define STAMP(i) do { } while (0)
#define KSTAMP(i) do { } while (0)
#define GSTAMP(i) do { } while (0)

__device__ __forceinline__ uint32_t s_u32(const void* p) { return (uint32_t)__cvta_generic_to_shared(p); }
__device__ __forceinline__ void mbar_init(uint32_t b, uint32_t n) {
    asm volatile("mbarrier.init.shared::cta.b64 [%0], %1;" ::"r"(b), "r"(n) : "memory");
}
__device__ __forceinline__ void mbar_expect_tx(uint32_t b, uint32_t bytes) {
    asm volatile("mbarrier.arrive.expect_tx.shared::cta.b64 _, [%0], %1;" ::"r"(b), "r"(bytes) : "memory");
}
__device__ __forceinline__ void mbar_arrive(uint32_t b) {
    asm volatile("mbarrier.arrive.shared::cta.b64 _, [%0];" ::"r"(b) : "memory");
}
__device__ __forceinline__ void mbar_arrive2(uint32_t b) {
    asm volatile("mbarrier.arrive.shared::cta.b64 _, [%0], 2;" ::"r"(b) : "memory");
}
__device__ __forceinline__ void mbar_arrive_peer(uint32_t b_cluster) {
    asm volatile("mbarrier.arrive.relaxed.cluster.shared::cluster.b64 _, [%0];" ::"r"(b_cluster) : "memory");
}
__device__ __forceinline__ void mbar_wait(uint32_t b, uint32_t parity) {
    asm volatile("{\n\t.reg .pred p;\n\t.reg .u32 c;\n\tmov.u32 c, 0;\n"
                 "W:\n\tmbarrier.try_wait.parity.shared::cta.b64 p, [%0], %1, 4000;\n\t@p bra D;\n\t"
                 "add.u32 c, c, 1;\n\tsetp.lt.u32 p, c, 1048576;\n\t@p bra W;\n\ttrap;\nD:\n\t}"
                 ::"r"(b), "r"(parity) : "memory");
}
template <int NS>
__device__ __forceinline__ void mbar_wait_lazy(uint32_t b, uint32_t parity) {
    asm volatile("{\n\t.reg .pred p;\n\t.reg .u32 c;\n\tmov.u32 c, 0;\n"
                 "W:\n\tmbarrier.test_wait.parity.shared::cta.b64 p, [%0], %1;\n\t@p bra D;\n\tnanosleep.u32 %2;\n\t"
                 "add.u32 c, c, 1;\n\tsetp.lt.u32 p, c, 4194304;\n\t@p bra W;\n\ttrap;\nD:\n\t}"
                 ::"r"(b), "r"(parity), "n"(NS) : "memory");
}
__device__ __forceinline__ bool mbar_test(uint32_t b, uint32_t parity) {
    uint32_t ok;
    asm volatile("{ .reg .pred p; mbarrier.test_wait.parity.shared::cta.b64 p, [%1], %2; selp.u32 %0, 1, 0, p; }" : "=r"(ok) : "r"(b), "r"(parity) : "memory");
    return __all_sync(0xffffffffu, ok != 0);
}
__device__ __forceinline__ bool elect_one() {
    uint32_t p;
    asm volatile("{ .reg .pred P; elect.sync _|P, 0xffffffff; selp.u32 %0, 1, 0, P; }" : "=r"(p));
    return p != 0;
}
__device__ __forceinline__ uint32_t mapa(uint32_t a, uint32_t rank) {
    uint32_t r;
    asm("mapa.shared::cluster.u32 %0, %1, %2;" : "=r"(r) : "r"(a), "r"(rank));
    return r;
}
__device__ __forceinline__ void cluster_arrive() { asm volatile("barrier.cluster.arrive.relaxed.aligned;" ::: "memory"); }
__device__ __forceinline__ void cluster_wait() { asm volatile("barrier.cluster.wait.acquire.aligned;" ::: "memory"); }
__device__ __forceinline__ void tma_load_2d(uint32_t dst, const CUtensorMap* m, int c0, int c1, uint32_t bar) {
    asm volatile("cp.async.bulk.tensor.2d.shared::cluster.global.mbarrier::complete_tx::bytes [%0], [%1, {%3, %4}], [%2];"
                 ::"r"(dst), "l"(m), "r"(bar), "r"(c0), "r"(c1) : "memory");
}
__device__ __forceinline__ void tma_load_tile(uint32_t dst, const CUtensorMap* m, int c0, int c2, int c3, uint32_t bar) {
    asm volatile("cp.async.bulk.tensor.4d.shared::cluster.global.mbarrier::complete_tx::bytes.multicast::cluster [%0], [%1, {%3, %4, %5, %6}], [%2], %7;"
                 ::"r"(dst), "l"(m), "r"(bar), "r"(c0), "r"(0), "r"(c2), "r"(c3), "h"((uint16_t)3) : "memory");
}
__device__ __forceinline__ void tma_store_tile(const CUtensorMap* m, uint32_t src, int c0, int c2, int c3) {
    asm volatile("cp.async.bulk.tensor.4d.global.shared::cta.bulk_group [%0, {%2, %3, %4, %5}], [%1];"
                 ::"l"(m), "r"(src), "r"(c0), "r"(0), "r"(c2), "r"(c3) : "memory");
    asm volatile("cp.async.bulk.commit_group;" ::: "memory");
}
__device__ __forceinline__ void bulk_g2s(uint32_t dst, const void* src, uint32_t bytes, uint32_t bar) {
    asm volatile("cp.async.bulk.shared::cluster.global.mbarrier::complete_tx::bytes [%0], [%1], %2, [%3];"
                 ::"r"(dst), "l"(src), "r"(bytes), "r"(bar) : "memory");
}
__device__ __forceinline__ void st_async128(uint32_t dst_cluster, uint32_t x, uint32_t y, uint32_t z, uint32_t w, uint32_t bar_cluster) {
    asm volatile("st.async.weak.shared::cluster.mbarrier::complete_tx::bytes.v4.b32 [%0], {%1,%2,%3,%4}, [%5];"
                 ::"r"(dst_cluster), "r"(x), "r"(y), "r"(z), "r"(w), "r"(bar_cluster) : "memory");
}
__device__ __forceinline__ void fence_async() { asm volatile("fence.proxy.async.shared::cta;" ::: "memory"); }
__device__ __forceinline__ void named_sync(int id, int n) { asm volatile("bar.sync %0, %1;" ::"r"(id), "r"(n) : "memory"); }

__device__ __forceinline__ void ldsm4(uint32_t* r, uint32_t a) {
    asm volatile("ldmatrix.sync.aligned.m8n8.x4.shared.b16 {%0,%1,%2,%3}, [%4];"
                 : "=r"(r[0]), "=r"(r[1]), "=r"(r[2]), "=r"(r[3]) : "r"(a));
}
__device__ __forceinline__ void ldsm4t(uint32_t* r, uint32_t a) {
    asm volatile("ldmatrix.sync.aligned.m8n8.x4.trans.shared.b16 {%0,%1,%2,%3}, [%4];"
                 : "=r"(r[0]), "=r"(r[1]), "=r"(r[2]), "=r"(r[3]) : "r"(a));
}
__device__ __forceinline__ void stsm4t(uint32_t a, uint32_t x, uint32_t y, uint32_t z, uint32_t w) {
    asm volatile("stmatrix.sync.aligned.m8n8.x4.trans.shared.b16 [%0], {%1,%2,%3,%4};"
                 ::"r"(a), "r"(x), "r"(y), "r"(z), "r"(w) : "memory");
}
__device__ __forceinline__ uint32_t lds32(uint32_t a) { uint32_t v; asm volatile("ld.shared.u32 %0, [%1];" : "=r"(v) : "r"(a)); return v; }
__device__ __forceinline__ float lds32f(uint32_t a) { float v; asm volatile("ld.shared.f32 %0, [%1];" : "=f"(v) : "r"(a)); return v; }
__device__ __forceinline__ uint2 lds64(uint32_t a) { uint2 v; asm volatile("ld.shared.v2.u32 {%0,%1}, [%2];" : "=r"(v.x), "=r"(v.y) : "r"(a)); return v; }
__device__ __forceinline__ uint4 lds128(uint32_t a) {
    uint4 v; asm volatile("ld.shared.v4.u32 {%0,%1,%2,%3}, [%4];" : "=r"(v.x), "=r"(v.y), "=r"(v.z), "=r"(v.w) : "r"(a)); return v;
}
__device__ __forceinline__ uint4 lds128v(uint32_t a) {
    uint4 v; asm volatile("ld.volatile.shared.v4.u32 {%0,%1,%2,%3}, [%4];" : "=r"(v.x), "=r"(v.y), "=r"(v.z), "=r"(v.w) : "r"(a)); return v;
}
__device__ __forceinline__ uint32_t or_xor(uint32_t a, uint32_t b, uint32_t c) {
    uint32_t r; asm("lop3.b32 %0, %1, %2, %3, 0xf6;" : "=r"(r) : "r"(a), "r"(b), "r"(c)); return r;
}
__device__ __forceinline__ float4 lds128f(uint32_t a) {
    float4 v; asm volatile("ld.shared.v4.f32 {%0,%1,%2,%3}, [%4];" : "=f"(v.x), "=f"(v.y), "=f"(v.z), "=f"(v.w) : "r"(a)); return v;
}
__device__ __forceinline__ void sts32(uint32_t a, uint32_t v) { asm volatile("st.shared.u32 [%0], %1;" ::"r"(a), "r"(v) : "memory"); }
__device__ __forceinline__ void sts32f(uint32_t a, float v) { asm volatile("st.shared.f32 [%0], %1;" ::"r"(a), "f"(v) : "memory"); }
__device__ __forceinline__ void sts64(uint32_t a, uint32_t x, uint32_t y) { asm volatile("st.shared.v2.u32 [%0], {%1,%2};" ::"r"(a), "r"(x), "r"(y) : "memory"); }
__device__ __forceinline__ void sts64f(uint32_t a, float x, float y) { asm volatile("st.shared.v2.f32 [%0], {%1,%2};" ::"r"(a), "f"(x), "f"(y) : "memory"); }
__device__ __forceinline__ void sts128(uint32_t a, uint32_t x, uint32_t y, uint32_t z, uint32_t w) {
    asm volatile("st.shared.v4.u32 [%0], {%1,%2,%3,%4};" ::"r"(a), "r"(x), "r"(y), "r"(z), "r"(w) : "memory");
}
__device__ __forceinline__ void sts128f(uint32_t a, const float* v) {
    asm volatile("st.shared.v4.f32 [%0], {%1,%2,%3,%4};" ::"r"(a), "f"(v[0]), "f"(v[1]), "f"(v[2]), "f"(v[3]) : "memory");
}
__device__ __forceinline__ uint4 ldg128(const void* p) {
    uint4 v; asm volatile("ld.global.nc.L1::no_allocate.v4.u32 {%0,%1,%2,%3}, [%4];" : "=r"(v.x), "=r"(v.y), "=r"(v.z), "=r"(v.w) : "l"(p)); return v;
}
__device__ __forceinline__ uint2 ldg64(const void* p) {
    uint2 v; asm volatile("ld.global.nc.L1::no_allocate.v2.u32 {%0,%1}, [%2];" : "=r"(v.x), "=r"(v.y) : "l"(p)); return v;
}
__device__ __forceinline__ uint32_t ldg32(const void* p) {
    uint32_t v; asm volatile("ld.global.nc.u32 %0, [%1];" : "=r"(v) : "l"(p)); return v;
}
__device__ __forceinline__ uint32_t ldg16(const void* p) {
    uint32_t v; asm volatile("ld.global.nc.u16 %0, [%1];" : "=r"(v) : "l"(p)); return v;
}
__device__ __forceinline__ uint4 ld_relaxed_128(const void* p) {
    uint4 v; asm volatile("ld.relaxed.gpu.global.v4.u32 {%0,%1,%2,%3}, [%4];" : "=r"(v.x), "=r"(v.y), "=r"(v.z), "=r"(v.w) : "l"(p) : "memory"); return v;
}
__device__ __forceinline__ void ld_relaxed_128_unless(uint4& q, const void* p, bool have) {
    asm volatile("{ .reg .pred p; setp.eq.u32 p, %5, 0; @p ld.relaxed.gpu.global.v4.u32 {%0,%1,%2,%3}, [%4]; }"
                 : "+r"(q.x), "+r"(q.y), "+r"(q.z), "+r"(q.w) : "l"(p), "r"((uint32_t)have) : "memory");
}
__device__ __forceinline__ uint2 ld_relaxed_64(const void* p) {
    uint2 v; asm volatile("ld.relaxed.gpu.global.v2.u32 {%0,%1}, [%2];" : "=r"(v.x), "=r"(v.y) : "l"(p) : "memory"); return v;
}
__device__ __forceinline__ uint32_t ld_relaxed_32(const void* p) {
    uint32_t v; asm volatile("ld.relaxed.gpu.global.u32 %0, [%1];" : "=r"(v) : "l"(p) : "memory"); return v;
}
__device__ __forceinline__ void st_relaxed_128(void* p, uint32_t x, uint32_t y, uint32_t z, uint32_t w) {
    asm volatile("st.relaxed.gpu.global.v4.u32 [%0], {%1,%2,%3,%4};" ::"l"(p), "r"(x), "r"(y), "r"(z), "r"(w) : "memory");
}
__device__ __forceinline__ void st_relaxed_64(void* p, uint32_t x, uint32_t y) {
    asm volatile("st.relaxed.gpu.global.v2.u32 [%0], {%1,%2};" ::"l"(p), "r"(x), "r"(y) : "memory");
}
__device__ __forceinline__ void st_relaxed_32(void* p, uint32_t v) {
    asm volatile("st.relaxed.gpu.global.u32 [%0], %1;" ::"l"(p), "r"(v) : "memory");
}
__device__ __forceinline__ void red_add(void* p, uint32_t v) { asm volatile("red.relaxed.gpu.global.add.u32 [%0], %1;" ::"l"(p), "r"(v) : "memory"); }
__device__ __forceinline__ uint32_t now_ns() { uint32_t t; asm volatile("mov.u32 %0, %%globaltimer_lo;" : "=r"(t) :: "memory"); return t; }
__device__ __forceinline__ void spin_guard(uint32_t& it) { if (++it > SPIN_LIMIT) __trap(); }
__device__ __forceinline__ void wait_count(const uint32_t* p, uint32_t target) {
#pragma unroll 1
    for (uint32_t it = 0; __any_sync(0xffffffffu, (int)(ld_relaxed_32(p) - target) < 0); spin_guard(it)) { }
}
__device__ __forceinline__ void mma_bf16(float* c, uint32_t a0, uint32_t a1, uint32_t a2, uint32_t a3, uint32_t b0, uint32_t b1) {
    asm("mma.sync.aligned.m16n8k16.row.col.f32.bf16.bf16.f32 {%0,%1,%2,%3}, {%4,%5,%6,%7}, {%8,%9}, {%0,%1,%2,%3};"
                 : "+f"(c[0]), "+f"(c[1]), "+f"(c[2]), "+f"(c[3]) : "r"(a0), "r"(a1), "r"(a2), "r"(a3), "r"(b0), "r"(b1));
}
__device__ __forceinline__ void mma_bf16_k8(float* c, uint32_t a0, uint32_t a1, uint32_t b0) {
    asm("mma.sync.aligned.m16n8k8.row.col.f32.bf16.bf16.f32 {%0,%1,%2,%3}, {%4,%5}, {%6}, {%0,%1,%2,%3};"
                 : "+f"(c[0]), "+f"(c[1]), "+f"(c[2]), "+f"(c[3]) : "r"(a0), "r"(a1), "r"(b0));
}
__device__ __forceinline__ void mma_v(float* c, const uint32_t* a, uint32_t b0, uint32_t b1) {
    asm volatile("mma.sync.aligned.m16n8k16.row.col.f32.bf16.bf16.f32 {%0,%1,%2,%3}, {%4,%5,%6,%7}, {%8,%9}, {%0,%1,%2,%3};"
                 : "+f"(c[0]), "+f"(c[1]), "+f"(c[2]), "+f"(c[3]) : "r"(a[0]), "r"(a[1]), "r"(a[2]), "r"(a[3]), "r"(b0), "r"(b1));
}
__device__ __forceinline__ void mma_bf16_z(float* c, uint32_t a0, uint32_t a1, uint32_t a2, uint32_t a3, uint32_t b0, uint32_t b1) {
    asm volatile("mma.sync.aligned.m16n8k16.row.col.f32.bf16.bf16.f32 {%0,%1,%2,%3}, {%4,%5,%6,%7}, {%8,%9}, {%10,%10,%10,%10};"
        : "=f"(c[0]), "=f"(c[1]), "=f"(c[2]), "=f"(c[3]) : "r"(a0), "r"(a1), "r"(a2), "r"(a3), "r"(b0), "r"(b1), "f"(0.f));
}
__device__ __forceinline__ void mma_f16(float* c, uint32_t a0, uint32_t a1, uint32_t a2, uint32_t a3, uint32_t b0, uint32_t b1) {
    asm("mma.sync.aligned.m16n8k16.row.col.f32.f16.f16.f32 {%0,%1,%2,%3}, {%4,%5,%6,%7}, {%8,%9}, {%0,%1,%2,%3};"
                 : "+f"(c[0]), "+f"(c[1]), "+f"(c[2]), "+f"(c[3]) : "r"(a0), "r"(a1), "r"(a2), "r"(a3), "r"(b0), "r"(b1));
}
__device__ __forceinline__ uint32_t pack_bf16(float lo, float hi) {
    uint32_t r; asm("cvt.rn.bf16x2.f32 %0, %1, %2;" : "=r"(r) : "f"(hi), "f"(lo)); return r;
}
__device__ __forceinline__ uint32_t pack_v(float lo, float hi) {
    uint32_t r; asm volatile("cvt.rn.bf16x2.f32 %0, %1, %2;" : "=r"(r) : "f"(hi), "f"(lo)); return r;
}
__device__ __forceinline__ uint32_t pack_w(float lo, float hi) {
    uint32_t r; asm volatile("cvt.rn.satfinite.bf16x2.f32 %0, %1, %2;" : "=r"(r) : "f"(hi), "f"(lo)); return r;
}
__device__ __forceinline__ void pin(uint32_t& x) { asm volatile("" : "+r"(x)); }
template <class T> __device__ __forceinline__ void pin(T*& x) { asm volatile("" : "+l"(x)); }
__device__ __forceinline__ uint32_t pack_f16(float lo, float hi) {
    uint32_t r; asm("cvt.rn.f16x2.f32 %0, %1, %2;" : "=r"(r) : "f"(hi), "f"(lo)); return r;
}
__device__ __forceinline__ float bf_lo(uint32_t v) { return __uint_as_float(v << 16); }
__device__ __forceinline__ float bf_hi(uint32_t v) { return __uint_as_float(v & 0xffff0000u); }
__device__ __forceinline__ float bf_round(float x) { return __uint_as_float(pack_bf16(0.f, x)); }
__device__ __forceinline__ uint32_t badd2(uint32_t a, uint32_t b) { uint32_t r; asm("add.rn.bf16x2 %0, %1, %2;" : "=r"(r) : "r"(a), "r"(b)); return r; }
__device__ __forceinline__ uint32_t bsub2_lo(uint32_t a, uint32_t b) {
    uint32_t r; asm("{ .reg .b16 m, h; .reg .b32 m2; mov.b32 {m, h}, %2; mov.b32 m2, {m, m}; sub.rn.bf16x2 %0, %1, m2; }" : "=r"(r) : "r"(a), "r"(b)); return r;
}
__device__ __forceinline__ uint32_t bmax2(uint32_t a, uint32_t b) { uint32_t r; asm("max.bf16x2 %0, %1, %2;" : "=r"(r) : "r"(a), "r"(b)); return r; }
__device__ __forceinline__ uint32_t normalize2(uint32_t x, uint32_t s0, uint32_t s1) {
    uint32_t r;
    asm("{ .reg .b16 m, h, l, k; .reg .b32 m2, h2, l2, d, t;\n\t"
        "mov.b32 {m, h}, %2; mov.b32 {l, k}, %3; mov.b32 m2, {m, m}; mov.b32 h2, {h, h}; mov.b32 l2, {l, l};\n\t"
        "sub.rn.bf16x2 d, %1, m2; mul.rn.bf16x2 t, d, l2; fma.rn.bf16x2 %0, d, h2, t; }" : "=r"(r) : "r"(x), "r"(s0), "r"(s1));
    return r;
}
__device__ __forceinline__ float rcpf(float x) { float r; asm("rcp.approx.ftz.f32 %0, %1;" : "=f"(r) : "f"(x)); return r; }
__device__ __forceinline__ float sqrtaf(float x) { float r; asm("sqrt.approx.ftz.f32 %0, %1;" : "=f"(r) : "f"(x)); return r; }
__device__ __forceinline__ float ex2f(float x) { float r; asm("ex2.approx.ftz.f32 %0, %1;" : "=f"(r) : "f"(x)); return r; }

__device__ __forceinline__ int tok_off(int t) { return ((t >> 3) & 1) * VT_PLANE + (t >> 4) * 16 + (t & 7) * 2; }

__device__ __forceinline__ uint32_t order_key(uint32_t b16) { return b16 ^ ((b16 & 0x8000u) ? 0xffffu : 0x8000u); }
__device__ __forceinline__ uint32_t unorder_key(uint32_t k16) { return k16 ^ ((k16 & 0x8000u) ? 0x8000u : 0xffffu); }

struct cplx { float r, i; };
struct hc { uint32_t r, i; };
template <bool CONJ> __device__ __forceinline__ cplx csq(cplx a) {
    float im;
    asm("{ .reg .f32 t; mul.ftz.f32 t, %1, %2; mul.ftz.f32 %0, t, 0f40000000; }" : "=f"(im) : "f"(CONJ ? -a.r : a.r), "f"(a.i));
    return {fmaf(a.r, a.r, -(a.i * a.i)), im};
}
__device__ __forceinline__ cplx cexpp(float a2, float ai) {
    float m = ex2f(a2), s, c;
    __sincosf(ai, &s, &c);
    return {m * c, m * s};
}
__device__ __forceinline__ __half2 as_h2(uint32_t x) { return *reinterpret_cast<__half2*>(&x); }
__device__ __forceinline__ uint32_t as_u(__half2 x) { return *reinterpret_cast<uint32_t*>(&x); }
__device__ __forceinline__ hc hmul(hc a, hc b) {
    return {as_u(__hfma2(__hneg2(as_h2(a.i)), as_h2(b.i), __hmul2(as_h2(a.r), as_h2(b.r)))),
            as_u(__hfma2(as_h2(a.i), as_h2(b.r), __hmul2(as_h2(a.r), as_h2(b.i))))};
}
__device__ __forceinline__ hc hpack(cplx a, cplx b) { return {pack_f16(a.r, b.r), pack_f16(a.i, b.i)}; }
__device__ __forceinline__ void sts16(uint32_t a, uint32_t v) { asm volatile("st.shared.u16 [%0], %1;" ::"r"(a), "r"(v) : "memory"); }

template <class Hook, class Hook2>
__device__ __forceinline__ void kgen(uint32_t tab, int lane, uint2 la, uint2 aim, uint2 cre, uint2 cim, float dt, float skip, int dch, Hook main_done, Hook2 half_done) {
    const int g = lane >> 2, t = lane & 3;
    const float dt2 = 2.f * dt;
    const uint32_t am = bmax2(bmax2(cre.x & 0x7fff7fffu, cre.y & 0x7fff7fffu), bmax2(cim.x & 0x7fff7fffu, cim.y & 0x7fff7fffu));
    const float mx = dt2 * fmaxf(bf_lo(am), bf_hi(am));
    const uint32_t eb = min(max(__reduce_max_sync(0xffffffffu, __float_as_uint(mx)) >> 23, 1u), 252u);
    const float cscale = dt2 * __uint_as_float((253u - eb) << 23);
    const float scale_inv = __uint_as_float((eb + 1u) << 23);
    float k0 = (bf_lo(cre.x) + bf_hi(cre.x)) + (bf_lo(cre.y) + bf_hi(cre.y));
#pragma unroll
    for (int o = 16; o; o >>= 1) k0 += __shfl_xor_sync(0xffffffffu, k0, o);
    const float ndt = -1.4426950408889634f * dt;
    STAMP(40); KSTAMP(0);

    float acc[5][4];
#pragma unroll
    for (int i = 0; i < 5; i++) { acc[i][0] = acc[i][1] = acc[i][2] = acc[i][3] = 0.f; }

    const uint32_t rec = tab + t * 512, sw = (uint32_t)t << 5;
    const uint32_t ad_l = rec + (((uint32_t)g << 4) ^ sw), ad_h = rec + 128 + (((uint32_t)g << 3) ^ sw);
    const uint32_t ad_2 = rec + (0xc0u ^ sw) + ((g & 1) << 3), ad_3 = rec + (0xd0u ^ sw) + ((g & 2) << 2);
    const uint32_t ad_4 = rec + (0xe0u ^ sw) + ((g & 4) << 1), ad_z = rec + (0xf0u ^ sw);
    const uint32_t wrec = tab + lane * 256 + ((lane & 7) << 4);

#pragma unroll 1
    for (int bb = 0; bb < 2; bb++) {
        cplx z[2][11], cz[2];
#pragma unroll
        for (int e = 0; e < 2; e++) {
            const float lg = e ? bf_hi(la.x) : bf_lo(la.x), ai = (e ? bf_hi(aim.x) : bf_lo(aim.x)) * dt;
            const float cr = (e ? bf_hi(cre.x) : bf_lo(cre.x)) * cscale, ci = (e ? bf_hi(cim.x) : bf_lo(cim.x)) * cscale;
            const float a2 = bf_round(ex2f(lg * 1.4426950408889634f)) * ndt;
            z[e][0] = cexpp(a2, ai);
            z[e][5] = cexpp(a2 * 32.f, ai * -32.f);
#pragma unroll
            for (int i = 1; i < 11; i++) if (i != 5) z[e][i] = (i == 3 || i == 7) ? csq<true>(z[e][i - 1]) : csq<false>(z[e][i - 1]);
            cz[e] = {fmaf(cr, z[e][0].r, -(ci * z[e][0].i)), fmaf(cr, z[e][0].i, ci * z[e][0].r)};
        }
        la.x = la.y; aim.x = aim.y; cre.x = cre.y; cim.x = cim.y;
        const hc z1 = hpack(z[0][0], z[1][0]), z2 = hpack(z[0][1], z[1][1]), z4 = hpack(z[0][2], z[1][2]);
        hc L[8], H[8];
        L[1] = hpack(z[0][3], z[1][3]); L[2] = hpack(z[0][4], z[1][4]); L[4] = hpack(z[0][5], z[1][5]);
        const hc y64 = hpack(z[0][6], z[1][6]), z128 = hpack(z[0][7], z[1][7]), z256 = hpack(z[0][8], z[1][8]);
        const hc z512 = hpack(z[0][9], z[1][9]), z1024 = hpack(z[0][10], z[1][10]);
        H[0] = hpack(cz[0], cz[1]);
        H[1] = hmul(H[0], z1); H[2] = hmul(H[0], z2); H[3] = hmul(H[1], z2);
        L[3] = hmul(L[1], L[2]);
#pragma unroll
        for (int i = 0; i < 4; i++) { H[4 + i] = hmul(H[i], z4); if (i) L[4 + i] = hmul(L[i], L[4]); }
        __syncwarp();
        sts128(wrec, 0x3c003c00u, y64.r, 0u, y64.i);
#pragma unroll
        for (int i = 1; i < 8; i++) { const hc q = hmul(L[i], y64); sts128(wrec ^ (i << 4), L[i].r, q.r, L[i].i, q.i); }
#pragma unroll
        for (int i = 0; i < 4; i++) sts128((wrec ^ (i << 4)) + 128, H[2 * i].r, H[2 * i].i, H[2 * i + 1].r, H[2 * i + 1].i);
        {
            const hc a = hmul(z256, z1), b = hmul(z256, z128), c = hmul(z256, z2), d = hmul(z512, z4);
            sts128((wrec ^ 0x40) + 128, a.r, a.i, b.r, b.i);
            sts128((wrec ^ 0x50) + 128, c.r, c.i, z512.r, z512.i);
            sts128((wrec ^ 0x60) + 128, d.r, d.i, z1024.r, z1024.i);
            sts64((wrec ^ 0x70) + 128, z128.r, z128.i);
        }
        __syncwarp();
        KSTAMP(1 + 2 * bb);
#pragma unroll kKgUnroll
        for (int k2 = 0; k2 < 4; k2++) {
#pragma unroll
            for (uint32_t s = 0; s < 2; s++) {
                const uint32_t o = k2 * 2048 + s * 256, x = s << 4;
                const uint4 l = lds128((ad_l ^ x) + o);
                const uint2 h0 = lds64((ad_h ^ x) + o), m2 = lds64((ad_2 ^ x) + o), m3 = lds64((ad_3 ^ x) + o);
                const uint2 m4 = lds64((ad_4 ^ x) + o), mz = lds64((ad_z ^ x) + o);
                const hc H0 = {h0.x, h0.y};
                const hc H1 = hmul(H0, {mz.x, mz.y}), H2 = hmul(H0, {m2.x, m2.y}), H3 = hmul(H2, {m3.x, m3.y}), H4 = hmul(H3, {m4.x, m4.y});
                mma_f16(acc[0], l.x, l.y, l.z, l.w, H0.r, H0.i);
                mma_f16(acc[1], l.x, l.y, l.z, l.w, H1.r, H1.i);
                mma_f16(acc[2], l.x, l.y, l.z, l.w, H2.r, H2.i);
                mma_f16(acc[3], l.x, l.y, l.z, l.w, H3.r, H3.i);
                mma_f16(acc[4], l.x, l.y, l.z, l.w, H4.r, H4.i);
            }
        }
        KSTAMP(2 + 2 * bb);
        if (bb == 0) half_done();
    }
    __syncwarp();
    main_done();
    KSTAMP(5);
#pragma unroll
    for (int i = 0; i < 4; i++) sts128(tab + 2048 + 512 * i + 16 * lane, 0, 0, 0, 0);
    if (lane < 15) sts32(tab + 4 * lane, 0);
    __syncwarp();
    const uint32_t d0 = tab + T_DENSE + 4 + 8 * lane, src = (lane + 31) & 31;
    const uint32_t p0 = pack_bf16(fmaf(k0, dt2, skip), 0.f);
    uint32_t prev = p0;
#pragma unroll
    for (int i = 0; i < 4; i++) {
        const uint32_t pk = pack_bf16(acc[i >> 1][2 * (i & 1) + 1] * scale_inv, acc[i >> 1][2 * (i & 1)] * scale_inv);
        sts64(d0 + 256 * i, __byte_perm(pk, __shfl_sync(0xffffffffu, lane == 31 ? prev : pk, src), 0x5432), pk);
        prev = pk;
    }
    const uint32_t w0 = pack_bf16(acc[2][0] * scale_inv, acc[2][1] * scale_inv), w1 = pack_bf16(acc[2][2] * scale_inv, acc[2][3] * scale_inv);
    const uint32_t sa = (lane & 1) ? 0x5410u : 0x5454u, sb2 = (lane & 1) ? 0x1010u : 0x5410u;
#pragma unroll
    for (int hf = 0; hf < 2; hf++) {
        const uint32_t w = hf ? w1 : w0;
        const uint32_t pv = __shfl_sync(0xffffffffu, lane != 31 ? w : hf ? w0 : __byte_perm(prev, w1, 0x5410), src);
        sts64(d0 + 1024 + 256 * hf, __byte_perm(w, pv, sa), __byte_perm(w, pv, sb2));
        sts64(d0 + 1536 + 256 * hf, __byte_perm(w, pv, sa + 0x2222u), __byte_perm(w, pv, sb2 + 0x2222u));
    }
    const uint32_t d3 = tab + T_R2 + 160 + 320 * (t & 1) + 16 * (g >> 1) + 8 * (g & 1) + 4 * (t >> 1), d3n = d3 + (g >= 6 ? 32 : 0);
    const uint32_t d4 = tab + T_R3 + 80 + 160 * t + 4 * g, d4n = d4 + (g >= 6 ? 16 : 0);
    uint32_t p3;
#pragma unroll
    for (int hf = 0; hf < 2; hf++)
#pragma unroll
        for (int e = 0; e < 2; e++) {
            const float v3 = acc[3][2 * hf + e] * scale_inv;
            const uint32_t p4 = pack_bf16(acc[4][2 * hf + e] * scale_inv, 0.f);
            p3 = pack_bf16(v3, v3);
            sts16(d3 + 64 * hf + 160 * e, p3);
            sts16((hf ? d3n : d3) + 64 * hf + 160 * e + 18, p3);
            sts16(d4 + 32 * hf + 80 * e, p4);
            sts16((hf ? d4n : d4) + 32 * hf + 80 * e + 10, p4);
        }
    if (lane == 31) {
        const uint32_t k512 = __byte_perm(w1, 0, 0x3232);
        sts32(tab + T_DENSE, p0);
        sts64(tab + T_DENSE + 4 * 513, k512, k512); sts16(tab + T_DENSE + 4 * 515 + 2, k512);
        sts16(tab + T_PATCH + 4 * 17, p3); sts32(tab + T_PATCH + 4 * 18, p3); sts16(tab + T_PATCH + 4 * 19 + 2, p3);
    }
    __syncwarp();
}

__device__ __forceinline__ void load_toep(uint32_t* a, uint32_t p, uint32_t zero) {
    a[0] = lds32(p); a[1] = lds32(p + 32); a[2] = lds32(p - 32); a[3] = lds32(p + zero);
}
#define DENSE_BLK 2
__device__ __forceinline__ void dense_step(float (&acc)[16][4], uint32_t (&R)[8][4], const uint32_t (&A)[4][4], uint32_t (&An)[4][4],
                                           uint32_t va, uint32_t vmin, uint32_t pn, uint32_t zero, int bit) {
#pragma unroll
    for (int i0 = 0; i0 < 8; i0 += DENSE_BLK) {
#pragma unroll 1
        do {
#pragma unroll
            for (int i = i0; i < i0 + DENSE_BLK; i++) {
                const int ip = (i - DENSE_BLK) & 7;
                ldsm4(R[ip], ip == 0 ? max(va - 16, vmin) : va + ip * 128 - (i0 ? 16 : 0));
                if ((i & 1) == 0) load_toep(An[i >> 1], pn + (i >> 1) * 512, zero);
#pragma unroll
                for (int ka = 0; ka < 4; ka++) {
                    mma_v(acc[i + ka], A[ka], R[i][0], R[i][1]);
                    if (i + 8 + ka < 16) mma_v(acc[i + 8 + ka], A[ka], R[i][2], R[i][3]);
                }
            }
        } while (zero & (1u << (bit + i0)));
    }
}
struct DenseTaps {
    uint32_t A[4][4], E[4], F[4], e8[2], f8[2];
    __device__ __forceinline__ DenseTaps(uint32_t pb, uint32_t zero) {
        constexpr int PP = T_PATCH - T_DENSE + 56;
#pragma unroll
        for (int i = 0; i < 4; i++) load_toep(A[i], pb + 512 * i, zero);
        load_toep(E, pb + 2048, zero);
        load_toep(F, pb + PP, zero);
        e8[0] = lds32(pb + zero + 2048 + 32); e8[1] = lds32(pb + 2048 + 64);
        f8[0] = lds32(pb + zero + PP + 32); f8[1] = lds32(pb + PP + 64);
    }
};
__device__ __forceinline__ void dense_phase(float (&acc)[16][4], uint32_t vrow, uint32_t pb, DenseTaps& tp, uint32_t zero, int lane) {
    uint32_t R[8][4], A1[4][4];
    const uint32_t vp = vrow + ((lane >> 3) & 1) * VT_PLANE, vmin = lane < 16 ? vp - 16 : 0u;
    uint32_t va = vp + (lane >> 4) * 1024 + (lane & 7) * 16;
    {
        uint32_t H[3][4];
#pragma unroll
        for (int i = 0; i < 3; i++) ldsm4(H[i], vrow + VT_PLANE - 16 + lane * 16 + i * 512);
#pragma unroll
        for (int i = 0; i < 8; i++) ldsm4(R[i], va + i * 128);
#pragma unroll
        for (int i = 0; i < 12; i++) mma_bf16_k8(acc[i + 4], tp.e8[0], tp.e8[1], H[i >> 2][i & 3]);
#pragma unroll
        for (int i = 0; i < 8; i++) mma_bf16_k8(acc[i + 8], tp.f8[0], tp.f8[1], H[i >> 2][i & 3]);
#pragma unroll
        for (int i = 0; i < 12; i++) mma_v(acc[i + 4], tp.E, R[i & 7][2 * (i >> 3)], R[i & 7][2 * (i >> 3) + 1]);
#pragma unroll
        for (int i = 0; i < 8; i++) mma_v(acc[i + 8], tp.F, R[i][0], R[i][1]);
    }
#pragma unroll 1
    for (int rho = 0; rho < 8; rho += 2) {
        dense_step(acc, R, tp.A, A1, va, vmin, pb + 64, zero, 0);
        dense_step(acc, R, A1, tp.A, va - 16, vmin, pb + zero + 128, -zero, 8);
        pb += 128; va -= 32;
    }
}
__device__ __forceinline__ uint32_t ones2(int c, int lo, int hi) {
    return (((uint32_t)(c - lo) <= (uint32_t)(hi - lo)) ? 0x3f80u : 0u) | (((uint32_t)(c + 1 - lo) <= (uint32_t)(hi - lo)) ? 0x3f800000u : 0u);
}
struct Boxes {
    uint32_t q[4], ha[2];
    __device__ __forceinline__ Boxes(uint32_t vrow, int lane, int O, int L1, int H1, int L2, int H2) {
        const int g = lane >> 2, t = lane & 3, d = 2 * t - g;
        q[0] = ones2(d, L1, H1); q[1] = ones2(d, L2, H2); q[2] = ones2(d + 8, L1, H1); q[3] = ones2(d + 8, L2, H2);
#pragma unroll
        for (int i = 0; i < 2; i++) { ha[i] = vrow + 16 * g + tok_off(O + 8 * i + 2 * t); pin(ha[i]); pin(q[i]); pin(q[2 + i]); }
    }
    __device__ __forceinline__ uint32_t any() const { return (q[0] | q[1] | q[2]) | (q[3] | ha[0] | ha[1]); }
    __device__ __forceinline__ void load(int j, uint32_t* v, uint32_t zero) const {
        const uint32_t o = j * 128;
        v[0] = lds32(ha[0] + o); v[1] = lds32(ha[1] + zero + o); v[2] = lds32(ha[1] + o);
        v[3] = lds32(ha[0] + zero + o + 16); v[4] = lds32(ha[0] + o + 16); v[5] = lds32(ha[1] + o + 16);
    }
    __device__ __forceinline__ void sums(const uint32_t* v, float* Z, float* X, float* Y) const {
        mma_bf16_z(Z, q[0], q[1], q[2], q[3], v[0], v[1]);
        mma_bf16_z(X, q[0], q[1], q[2], q[3], v[2], v[3]);
        mma_bf16_z(Y, q[0], q[1], q[2], q[3], v[4], v[5]);
    }
};
template <class After>
__device__ __forceinline__ void tail_phase(float (&acc)[16][4], const Boxes& b2, const Boxes& b3, uint32_t tp2, uint32_t tp3, uint32_t zero, After after) {
    uint2 tp[10];
    uint32_t v[6], a0[4], a1[4];
    float Z[4], X[4], Y[4];
    b2.load(0, v, zero);
#pragma unroll
    for (int i = 0; i < 5; i++) { const uint4 c = lds128(tp2 + 160 * i); tp[i] = make_uint2(c.x, c.y); tp[5 + i] = make_uint2(c.z, c.w); }
#pragma unroll
    for (int j = -1; j < 20; j++) {
        if (j < 19) {
            (j < 11 ? b2 : b3).sums(v, Z, X, Y);
            if (j < 10) b2.load(j + 2, v, zero); else if (j < 18) b3.load(j - 10, v, zero);
        }
        if (j >= 0 && j < 12) {
#pragma unroll
            for (int b = 0; b < 5; b++) if (j + 4 + b < 16) mma_v(acc[j + 4 + b], a1, tp[5 + b].x, tp[5 + b].y);
        }
        if (j < 11) { a1[0] = pack_v(Z[0], Z[1]); a1[1] = pack_w(X[0], X[1]); a1[2] = pack_v(Z[2], Z[3]); a1[3] = pack_w(X[2], X[3]); }
        if (j >= 0 && j < 12) {
#pragma unroll
            for (int b = 0; b < 5; b++) if (j + 4 + b < 16) mma_v(acc[j + 4 + b], a0, tp[b].x, tp[b].y);
            if (j >= 7 && j < 11) { tp[11 - j] = lds64(tp3 + 80 * (10 - j)); tp[16 - j] = lds64(tp3 + 80 * (14 - j)); }
        } else if (j >= 12) {
#pragma unroll
            for (int b = 0; b < 8; b++) if (j - 4 + b < 16) mma_v(acc[j - 4 + b], a0, tp[b < 4 ? b + 1 : b + 2].x, tp[b < 4 ? b + 1 : b + 2].y);
        }
        if (j < 11) { a0[0] = pack_v(X[0], X[1]); a0[1] = pack_v(Y[0], Y[1]); a0[2] = pack_v(X[2], X[3]); a0[3] = pack_v(Y[2], Y[3]); }
        else if (j < 19) { a0[0] = pack_v(X[0], X[1]); a0[1] = pack_v(Y[0], Y[1]); a0[2] = pack_v(Z[2], Z[3]); a0[3] = pack_v(X[2], X[3]); }
        after(j);
    }
}
template <int G>
__device__ __forceinline__ void emit(const float (&acc)[16][4], int h, uint32_t own, uint32_t peer, uint32_t bar, uint32_t bar_peer) {
#pragma unroll
    for (int o = 0; o < 2; o++)
#pragma unroll
        for (int hf = 0; hf < 2; hf++) {
            const int n = 8 * G + 4 * o;
            asm volatile("{ .reg .pred p; setp.eq.u32 p, %7, %8;\n\t@p st.shared.v4.u32 [%0], {%1,%2,%3,%4};\n\t"
                         "@!p st.async.weak.shared::cluster.mbarrier::complete_tx::bytes.v4.b32 [%5], {%1,%2,%3,%4}, [%6]; }"
                         ::"r"(own + G * 16384 + hf * 512), "r"(pack_bf16(acc[n][2 * hf], acc[n][2 * hf + 1])), "r"(pack_bf16(acc[n + 1][2 * hf], acc[n + 1][2 * hf + 1])),
                         "r"(pack_bf16(acc[n + 2][2 * hf], acc[n + 2][2 * hf + 1])), "r"(pack_bf16(acc[n + 3][2 * hf], acc[n + 3][2 * hf + 1])),
                         "r"(peer + G * 16384 + hf * 512), "r"(bar_peer + 8 * G), "r"(h), "r"(o) : "memory");
        }
    __syncwarp();
    if (elect_one()) mbar_arrive(bar + 8 * G);
}
__device__ __forceinline__ void finish(uint32_t src, uint32_t xa) {
    uint32_t s[4][4];
    uint4 x[4];
#pragma unroll
    for (int i = 0; i < 4; i++) {
        ldsm4t(s[i], (src ^ ((i & 1) << 5)) + (i >> 1) * 8192);
        x[i] = lds128((xa ^ ((i >> 1) << 4)) + (i & 1) * 256);
    }
#pragma unroll
    for (int i = 0; i < 4; i++)
        sts128((xa ^ ((i >> 1) << 4)) + (i & 1) * 256, badd2(x[i].x, s[i][0]), badd2(x[i].y, s[i][1]), badd2(x[i].z, s[i][2]), badd2(x[i].w, s[i][3]));
}

__device__ __noinline__ float centred_var(uint32_t rows, float mu, int lane) {
    float var = 0.f;
#pragma unroll 1
    for (int rr = 0; rr < 16; rr++) {
        const float c0 = __shfl_sync(0xffffffffu, mu, rr);
        float c = 0.f;
#pragma unroll 1
        for (int k = 0; k < 16; k++) {
            const uint32_t q = lds32(rows + rr * ROW_PITCH + k * 128 + lane * 4);
            const float d0 = bf_lo(q) - c0, d1 = bf_hi(q) - c0;
            c = fmaf(d0, d0, fmaf(d1, d1, c));
        }
#pragma unroll 1
        for (int o = 16; o; o >>= 1) c += __shfl_xor_sync(0xffffffffu, c, o);
        if ((lane & 15) == rr) var = c * (1.f / DM);
    }
    return var;
}
__device__ __noinline__ float centred_score(uint32_t rows, uint32_t wbuf, uint32_t s0, uint32_t s1, int lane) {
    float sc = 0.f;
#pragma unroll 1
    for (int rr = 0; rr < 16; rr++) {
        const uint32_t t0 = __shfl_sync(0xffffffffu, s0, rr), t1 = __shfl_sync(0xffffffffu, s1, rr);
        float c = 0.f;
#pragma unroll 1
        for (int k = 0; k < 16; k++) {
            const uint32_t xn = normalize2(lds32(rows + rr * ROW_PITCH + k * 128 + lane * 4), t0, t1);
            const uint32_t wq = lds32(wbuf + (k >> 2) * 1024 + (k & 3) * 128 + lane * 4);
            c = fmaf(bf_lo(xn), bf_lo(wq), fmaf(bf_hi(xn), bf_hi(wq), c));
        }
#pragma unroll 1
        for (int o = 16; o; o >>= 1) c += __shfl_xor_sync(0xffffffffu, c, o);
        if ((lane & 15) == rr) sc = c;
    }
    return sc;
}

__global__ void __cluster_dims__(2, 1, 1) __launch_bounds__(NTHR, 1)
fused_kernel(const __grid_constant__ Ptrs p, const __grid_constant__ Maps maps) {
    extern __shared__ __align__(1024) unsigned char smem[];
    const int tid = threadIdx.x, lane = tid & 31, b = blockIdx.x;
    const int dch = 8 * b + (tid >> 5) - 4;
    uint2 la, aim, cre, cim;
    uint32_t ldt16, dsk16, epoch;
    uint4 wq;
    if ((uint32_t)(tid - 128) < 256u) {
        la = ldg64(p.logA + dch * NMODE + 4 * lane); aim = ldg64(p.Aim + dch * NMODE + 4 * lane);
        cre = ldg64(p.Cre + dch * NMODE + 4 * lane); cim = ldg64(p.Cim + dch * NMODE + 4 * lane);
        ldt16 = ldg16(p.ldt + dch); dsk16 = ldg16(p.dsk + dch);
    }
    if (tid < 128) { wq = ldg128(p.wr + 8 * tid); epoch = ld_relaxed_32(&p.sc->epoch); }
    const uint32_t sb = s_u32(smem);
    const int warp = __shfl_sync(0xffffffffu, tid >> 5, 0);
    const int h = b & 1, cl = b >> 1;
    const uint32_t bar0 = sb + OFF_BAR;
    const int m = lane >> 3, r = lane & 7, g = lane >> 2, t = lane & 3;
    const bool has_gu = b < GU_CTAS;
    if (warp == 4) { STAMP(0); GSTAMP(24); }

    if (warp >= 12) {
        asm volatile("setmaxnreg.dec.sync.aligned.u32 24;");
        const int a = warp - 12;
        uint32_t due = now_ns() + ST_T0 + (uint32_t)(128 * a + b) * ST_PER / 128;
        const bool el = elect_one();
        if (a == 1 && el) {
#pragma unroll
            for (int j = 0; j < 4; j++) mbar_init(bar0 + 8 * (B_ROW + j), 1);
            asm volatile("fence.mbarrier_init.release.cluster;" ::: "memory");
            fence_async();
#pragma unroll 1
            for (int j = 0; j < 4; j++) {
                mbar_expect_tx(bar0 + 8 * (B_ROW + j), 8192);
#pragma unroll
                for (int i = 0; i < 4; i++)
                    bulk_g2s(sb + OFF_VT + (4 * j + i) * ROW_PITCH, p.u + (size_t)(16 * b + 4 * j + i) * DM, 2048, bar0 + 8 * (B_ROW + j));
            }
        }
        if (a == 2 && el) {
#pragma unroll
            for (int i = B_XT; i < NBAR; i++) mbar_init(bar0 + 8 * i, i == B_SFREE ? 8 : i == B_UPD ? 4 : (i == B_RECV || i == B_RECV + 1) ? 9 : (i >= B_FREE + 4 && i < B_FREE + 8) ? 2 : 1);
            asm volatile("fence.mbarrier_init.release.cluster;" ::: "memory");
            fence_async();
            mbar_expect_tx(bar0 + 8 * B_XT, 65536);
            mbar_expect_tx(bar0 + 8 * B_RECV, 8192);
            mbar_expect_tx(bar0 + 8 * B_RECV + 8, 8192);
            mbar_expect_tx(bar0 + 8 * B_RED, 512);
        }
        if (a == 3 && el) {
#pragma unroll
            for (int i = 0; i < 5; i++) asm volatile("prefetch.tensormap [%0];" ::"l"(&maps.u + i) : "memory");
        }
        __syncwarp();
        cluster_arrive();
        cluster_wait();
        STAMP(18);
        mbar_wait_lazy<40>(bar0 + 8 * (B_ROW + a), 0);
        if (el) {
#pragma unroll
            for (int i = 0; i < 4; i++)
                tma_load_tile(sb + OFF_XT + h * 32768 + a * 4096 + (i & 1) * 16384 + (i >> 1) * 2048, &maps.u, 16 * cl, 4 * a + (i & 2), 16 * (i & 1) + 8 * h, bar0 + 8 * B_XT);
        }
        if (el) {
#pragma unroll 1
            for (int k = has_gu ? 0 : 4; k < 6; k++) {
                const int i = 4 * k + a, s = k < 3 ? i : i - 12;
#pragma unroll 1
                for (int left; (left = (int)(due - now_ns())) > 0;) __nanosleep(left >> 1);
                due += k == 0 ? 4 * ST_PER + ST_GAP : k < 3 ? 4 * ST_PER : 4 * ST_PER2;
                const bool scr = (0xcf0 >> s) & 1, again = k >= 3 && has_gu, mid = (s >> 2) == 1;
                if (scr || again) mbar_wait(bar0 + 8 * (B_FREE + s), scr && again);
                const uint32_t dst = sb + (mid ? OFF_PRIV + 4096 + a * 16384 : OFF_RING + (s >> 3) * 32768 + a * 8192), bar = bar0 + 8 * (B_FULL + s);
                const uint32_t dst2 = dst + (mid ? 8192 : 4096);
                if (k < 4) {
                    mbar_expect_tx(bar, 8192);
                    tma_load_2d(dst, &maps.wg, 32 * b, 64 * i, bar);
                    tma_load_2d(dst2, &maps.wu, 32 * b, 64 * i, bar);
                } else {
                    const int c1 = 1792 * h + 448 * a + 224 * (k & 1);
                    mbar_expect_tx(bar, 7168);
                    tma_load_2d(dst, &maps.wd, 16 * cl, c1, bar);
                    tma_load_2d(dst2, &maps.wd, 16 * cl, c1 + 112, bar);
                }
            }
            STAMP(19);
        }
    } else if (warp >= 4) {
        const int w = warp - 4;
        cluster_arrive();
        asm volatile("setmaxnreg.inc.sync.aligned.u32 168;");
        const uint32_t vrow = sb + OFF_VT + w * VT_PITCH + VT_PAD, tab = sb + OFF_PRIV + w * 8192;
        const uint32_t so = sb + OFF_XT + (8 * h + w) * 1024 + ((lane ^ ((w & 1) << 1)) << 4);
        uint32_t dst0 = so + (h ^ 1) * 32768;
        const uint32_t rb0 = bar0 + 8 * B_RECV, rb1 = mapa(rb0, h ^ 1);
        const uint32_t box = sb + OFF_XT + h * 32768 + w * 2048;
        uint32_t fs = sb + OFF_XT + (h ^ 1) * 32768 + (2 * m + (r & 1)) * 1024 + (w >> 2) * 512 + (((8 * (w & 3) + (r & 4) + ((r >> 1) & 1)) ^ ((r & 1) << 1)) << 4);
        uint32_t fx = box + (g >> 1) * 512 + (t >> 1) * 144 + (2 * (t & 1) + (g & 1)) * 32;
        uint32_t tpo = 80 + (g - 2 * t) * 8 - (g < 2 * t ? 16 : 0);
        uint32_t xa = sb + OFF_XT + (w & 2) * 16384 + (w >> 2) * 16384 + (w & 1) * 1024 + (g >> 1) * 2048 + (g & 1) * 128 + t * 32 + ((h ^ (g & 1)) << 4);
        uint32_t va = sb + OFF_VT + (2 * m + (r & 1)) * VT_PITCH + VT_PAD + (16 * w + (r >> 1)) * 16;
        uint32_t qa = sb + OFF_ST + 2048 * w + 128 * t + 16 * (g ^ (2 * t));
        uint4 x[8];
        pin(dst0); pin(fs); pin(fx); pin(tpo); pin(xa); pin(va); pin(qa);
        const Boxes b2(vrow, lane, -18, 5, 7, 0, 4), b3(vrow, lane, -20, 1, 7, 0, 8);
        if (__any_sync(0xffffffffu, ((dst0 | fs) | (fx | tpo | xa) | (va | qa) | (b2.any() | b3.any())) & p.zero)) __trap();
        cluster_wait();
        pin(la.x); pin(la.y); pin(aim.x); pin(aim.y); pin(cre.x); pin(cre.y); pin(cim.x); pin(cim.y); pin(ldt16); pin(dsk16);
        kgen(tab, lane, la, aim, cre, cim, bf_round(ex2f(bf_lo(ldt16) * 1.4426950408889634f)), 1.f + bf_lo(dsk16), dch, [&]() {
            STAMP(21);
            if (elect_one()) mbar_arrive(bar0 + 8 * (B_FREE + 4 + (w >> 1)));
            mbar_wait_lazy<40>(bar0 + 8 * B_XT, 0);
#pragma unroll
            for (int i = 0; i < 8; i++) x[i] = lds128(xa + (i & 1) * 8192 + (i >> 1) * 256);
        }, [&]() {
        });
        STAMP(1); KSTAMP(6);
        const uint32_t pb = tab + T_DENSE + (g - 2 * t) * 4;
        DenseTaps dt(pb, p.zero);
        {
            uint4 q[4];
            mbar_wait(bar0 + 8 * (B_ST + w), 0);
#pragma unroll
            for (int n = 0; n < 4; n++) q[n] = lds128(qa + 512 * n);
            if (lane < 4) sts128(vrow - VT_PAD + (lane >> 1) * VT_PLANE + (lane & 1) * 16, 0, 0, 0, 0);
            STAMP(2); GSTAMP(28);
#pragma unroll
            for (int i = 0; i < 8; i++) {
                const uint32_t s0 = (i & 1) ? q[i >> 1].z : q[i >> 1].x, s1 = (i & 1) ? q[i >> 1].w : q[i >> 1].y;
                stsm4t(va + (i >> 1) * 64 + (i & 1) * VT_PLANE, normalize2(x[i].x, s0, s1), normalize2(x[i].y, s0, s1),
                       normalize2(x[i].z, s0, s1), normalize2(x[i].w, s0, s1));
            }
            named_sync(2, 256);
            if (elect_one()) {
                if (w < 3) mbar_arrive(bar0 + 8 * (w == 2 ? B_V : B_FREE + 10 + w));
            }
        }
        STAMP(3); KSTAMP(7);
        float acc[16][4];
#pragma unroll
        for (int i = 0; i < 16; i++) { acc[i][0] = acc[i][1] = acc[i][2] = acc[i][3] = 0.f; }
        dense_phase(acc, vrow, pb, dt, p.zero, lane);
        STAMP(4); KSTAMP(8);
        const uint32_t dst1 = mapa(dst0 + (h ? 32768 : -32768), h ^ 1);
        tail_phase(acc, b2, b3, tab + T_R2 + 2 * tpo, tab + T_R3 + tpo, p.zero, [&](int j) {
            if (j == 3) {
                mbar_wait(bar0 + 8 * B_SFREE, 0);
                emit<0>(acc, h, dst0, dst1, rb0, rb1);
                STAMP(5);
            }
            if (j == 7) {
                mbar_wait(bar0 + 8 * B_RECV, 0);
                finish(fs, fx);
                fence_async();
                __syncwarp();
                if (elect_one()) tma_store_tile(&maps.out, box, 16 * cl, 2 * w, 8 * h);
                STAMP(20);
            }
        });
        emit<1>(acc, h, dst0, dst1, rb0, rb1);
        STAMP(30);
        mbar_wait(bar0 + 8 * (B_RECV + 1), 0);
        STAMP(6);
        finish(fs + 16384, fx + 16384);
        const bool ready = mbar_test(bar0 + 8 * B_UPD, 0);
        const bool el = elect_one();
#pragma unroll 1
        for (int pass = 0; pass < 2; pass++) {
            if ((pass != 0) == ready) {
                fence_async();
                __syncwarp();
                if (el) tma_store_tile(&maps.out, box + 16384, 16 * cl, 2 * w, 16 + 8 * h);
            } else {
                if (el) asm volatile("cp.async.bulk.wait_group 0;" ::: "memory");
                __syncwarp();
                mbar_wait_lazy<40>(bar0 + 8 * B_UPD, 0);
                const int tok = 2047 - (int)(lds32(sb + OFF_MISC + 48 + 8 * g) & 2047);
                if ((((tok >> 6) & 8) | ((tok >> 1) & 7)) == 8 * h + w) {
                    const uint32_t xa = box + (tok >> 10) * 16384 + ((tok >> 6) & 7) * 256 + (tok & 1) * 128 + ((tok >> 4) & 3) * 32 + (((t >> 1) ^ (tok & 1)) << 4) + (t & 1) * 8;
                    const uint2 o0 = lds64(xa);
                    const float4 up = lds128f(sb + OFF_RED + 16 * lane);
                    const uint2 o1 = make_uint2(badd2(o0.x, pack_bf16(up.x, up.y)), badd2(o0.y, pack_bf16(up.z, up.w)));
                    if (ready && tok >= 1024) sts64(xa, o1.x, o1.y);
                    else *reinterpret_cast<uint2*>(p.out + (size_t)tok * DM + 16 * cl + 4 * t) = o1;
                }
            }
        }
        if (el) asm volatile("cp.async.bulk.wait_group.read 0;" ::: "memory");
        STAMP(7);
    } else {
        const int a = warp;
        cluster_arrive();
        asm volatile("setmaxnreg.inc.sync.aligned.u32 152;");
        const uint32_t tag = __shfl_sync(0xffffffffu, epoch, 0) + 1u, misc = sb + OFF_MISC, abar = bar0 + 8 * (B_AUX + a);
        uint32_t aph = 0;
        uint2* pub = p.sc->stat + 16 * b + 2 * (r ^ (2 * (b & 3))) + m;
        uint32_t* cnt_s = &p.sc->n_stat[b & 96];
        pin(pub); pin(cnt_s);
        if (tid < 64) sts32(sb + OFF_RED + 4 * tid, 0);
        const uint32_t wbuf = sb + OFF_LN + a * 1024, part = sb + OFF_LN + 4096;
        {
            sts128(wbuf + 16 * lane, wq.x, wq.y, wq.z, wq.w);
            sts128(wbuf + 512 + 16 * lane, 0x3f803f80u, 0x3f803f80u, 0x3f803f80u, 0x3f803f80u);
            float wsum = ((bf_lo(wq.x) + bf_hi(wq.x)) + (bf_lo(wq.y) + bf_hi(wq.y))) + ((bf_lo(wq.z) + bf_hi(wq.z)) + (bf_lo(wq.w) + bf_hi(wq.w)));
#pragma unroll
            for (int o = 16; o; o >>= 1) wsum += __shfl_xor_sync(0xffffffffu, wsum, o);
            sts32f(part + 1024 + 4 * a, wsum);
            uint32_t wf[4][4];
#pragma unroll
            for (int i = 0; i < 4; i++) ldsm4(wf[i], wbuf + ((uint32_t)(r - 1) < 2u ? 16 * (r - 1) : 512) + 32 * m + 128 * i);
            uint32_t ra = sb + OFF_VT + r * ROW_PITCH + 512 * a + 16 * m, pa = part + a * 256 + g * 16;
            cluster_wait();
            STAMP(22);
#pragma unroll 1
            for (int hf = 0; hf < 2; hf++) {
                if (a < 2) mbar_wait(bar0 + 8 * (B_ROW + a) + 16 * hf, 0);
                named_sync(1, 128);
                STAMP(23);
                uint32_t x[8][4];
                float cs[2][4], q[8][4];
#pragma unroll
                for (int i = 0; i < 40; i++) (i < 8 ? cs[i >> 2 & 1] : q[(i - 8) >> 2 & 7])[i & 3] = 0.f;
#pragma unroll
                for (int k = 0; k < 8; k++) ldsm4(x[k], ra + k * 64);
                const uint32_t dep = (x[6][3] | x[7][3]) & p.zero;
                x[0][0] |= dep; x[0][2] |= dep; x[1][0] |= dep; x[1][2] |= dep;
#pragma unroll
                for (int k = 0; k < 8; k++) {
                    mma_bf16(cs[k & 1], x[k][0], x[k][1], x[k][2], x[k][3], wf[k >> 1][2 * (k & 1)], wf[k >> 1][2 * (k & 1) + 1]);
#pragma unroll
                    for (int i = 0; i < 4; i++) mma_bf16_k8(q[4 * (k & 1) + i], x[k][i & 2], x[k][i | 1], x[k][i]);
                }
                const float c2 = cs[0][2] + cs[1][2];
                if (t == 0) sts64f(pa, (cs[0][0] + cs[1][0]) + c2, cs[0][1] + cs[1][1]);
                if (t == 1) sts32f(pa + 12, c2);
                const float e0 = ((q[0][0] + q[2][0]) + (q[4][0] + q[6][0])) + ((q[1][2] + q[3][2]) + (q[5][2] + q[7][2]));
                const float e1 = ((q[0][1] + q[2][1]) + (q[4][1] + q[6][1])) + ((q[1][3] + q[3][3]) + (q[5][3] + q[7][3]));
                if (t == (g >> 1)) sts32f(pa + 8, (g & 1) ? e1 : e0);
                ra += 8 * ROW_PITCH; pa += 128;
            }
        }
        STAMP(31);
        named_sync(1, 128);
        if (a == 0) {
            const uint32_t pa = part + (lane & 15) * 16;
            const float4 p0 = lds128f(pa), p1 = lds128f(pa + 256), p2 = lds128f(pa + 512), p3 = lds128f(pa + 768), ws = lds128f(part + 1024);
            const float mu = ((p0.x + p1.x) + (p2.x + p3.x)) * (1.f / DM);
            float var = ((p0.z + p1.z) + (p2.z + p3.z)) * (1.f / DM) - mu * mu;
            const bool centred = __any_sync(0xffffffffu, !(mu * mu <= 4.f * var));
            if (centred) var = centred_var(sb + OFF_VT, mu, lane);
            const float ri = rcpf(bf_round(sqrtaf(bf_round(bf_round(var) + 1e-5f))));
            const uint32_t s0 = pack_bf16(mu, ri), s1 = (pack_bf16(ri - bf_hi(s0), 0.f) & 0xfffcu) | (tag & 3);
            float sc = ((((p0.y + p1.y) + (p2.y + p3.y)) + ((p0.w + p1.w) + (p2.w + p3.w))) - bf_lo(s0) * ((ws.x + ws.y) + (ws.z + ws.w))) * ri;
            if (centred) sc = centred_score(sb + OFF_VT, sb + OFF_LN, s0, s1, lane);
            const uint32_t sb16 = pack_bf16(0.f, sc);
            if (lane < 16) st_relaxed_64(pub, s0, s1 | (sb16 ^ (((uint32_t)((int)sb16 >> 31) & 0x7fff0000u) | 0x80000000u)));
            if (lane == 0) red_add(cnt_s, 1);
            STAMP(9); GSTAMP(25);
        }
        const uint32_t slot0 = sb + OFF_RING + a * 8192, slot1 = sb + OFF_PRIV + a * 16384 + 4096, fbar = bar0 + 8 * (B_FULL + a);
        uint32_t mine = 0, row[2] = {0, 0};
        {
            uint32_t q[16];
            named_sync(1, 128);
            wait_count(&p.sc->n_stat[32 * a], 32 * tag - FEW_ST);
            STAMP(41);
#pragma unroll 1
            for (uint32_t it = 0;; spin_guard(it)) {
                if (elect_one()) {
                    mbar_expect_tx(abar, 4096);
                    bulk_g2s(sb + OFF_ST + 4096 * a, p.sc->stat + 512 * a, 4096, abar);
                }
                mbar_wait(abar, aph);
                aph ^= 1;
                uint32_t bad = 0;
#pragma unroll
                for (int n = 0; n < 8; n++) {
                    const uint4 u = lds128v(sb + OFF_ST + 4096 * a + 512 * n + 16 * lane);
                    q[2 * n] = u.y; q[2 * n + 1] = u.w;
                    bad = or_xor(bad, u.y, tag);
                }
                const bool ok = __all_sync(0xffffffffu, (bad & 3) == 0);
                asm volatile("{ .reg .pred p; setp.ne.u32 p, %1, 0; @p mbarrier.arrive.shared::cta.b64 _, [%0]; }" ::"r"(bar0 + 8 * B_ST + 16 * a + 8 * lane), "r"((uint32_t)(ok && lane < 2)) : "memory");
                if (ok) break;
            }
            STAMP(8);
            const uint32_t inv = 2047 - 512 * a - 16 * m - (r ^ (2 * m));
#pragma unroll
            for (int i = 0; i < 16; i++) asm("lop3.b32 %0, %0, %1, %2, 0x9b;" : "+r"(q[i]) : "r"(inv), "r"(0xffff0000u | (64 * (i >> 1) + 8 * (i & 1))));
            auto below = [&](uint32_t x) {
                uint32_t d[4];
#pragma unroll
                for (int i = 0; i < 16; i++) d[i & 3] = i < 4 ? x + q[i] : min(d[i & 3], x + q[i]);
                d[0] = min(min(d[0], d[1]), min(d[2], d[3]));
                return d[0] < x ? x - 1 - d[0] : 0u;
            };
            const uint32_t mx0 = ~min(min(min(min(q[0], q[1]), min(q[2], q[3])), min(min(q[4], q[5]), min(q[6], q[7]))),
                                      min(min(min(q[8], q[9]), min(q[10], q[11])), min(min(q[12], q[13]), min(q[14], q[15]))));
            const uint32_t gm = min(__reduce_max_sync(0xffffffffu, lane < 16 ? mx0 : 0u), __reduce_max_sync(0xffffffffu, lane < 16 ? 0u : mx0));
            if (lane == 0) sts32(misc + 16 + 4 * a, gm);
            named_sync(1, 128);
            STAMP(42);
            if (b == 0 && tid == 0) st_relaxed_32(&p.sc->epoch, tag);
            const uint4 t0 = lds128(misc + 16);
            uint32_t tau = min(min(t0.x, t0.y), min(t0.z, t0.w));
            uint32_t mx = mx0, cnt = 0, bal;
            const uint32_t list = sb + OFF_RED + 64 * a;
#pragma unroll 1
            while ((bal = __ballot_sync(0xffffffffu, mx >= tau)) != 0) {
                const uint32_t pos = cnt + __popc(bal & ((1u << lane) - 1u));
                cnt += __popc(bal);
                if (cnt > 16) break;
                if (mx >= tau) sts32(list + 4 * pos, mx);
                mx = below(mx);
            }
            if (cnt > 16) {
                mx = mx0;
#pragma unroll 1
                for (int j = 0; j < 8; j++) {
                    const uint32_t top = __reduce_max_sync(0xffffffffu, mx), nx = below(mx);
                    if (mx == top) { sts32(list + 4 * j, mx); sts32(list + 32 + 4 * j, 0); mx = nx; }
                }
            }
            named_sync(1, 128);
            STAMP(43);
            const uint2 k = lds64(sb + OFF_RED + 8 * lane);
            uint32_t hi = max(k.x, k.y), lo = min(k.x, k.y);
            mbar_wait(bar0 + 8 * B_V, 0);
#pragma unroll
            for (int j = 0; j < 8; j++) {
                const uint32_t top = __reduce_max_sync(0xffffffffu, hi);
                const bool won = hi == top;
                hi = won ? lo : hi;
                lo = won ? 0u : lo;
                if (g == j) mine = top;
                if (a == (j >> 1)) row[j & 1] = top;
            }
        }
        STAMP(11);
        const int tok = 2047 - (int)(mine & 2047);
        const uint32_t xs = sb + OFF_XT + (h ^ 1) * 32768;
        if (has_gu) {
            const int tok0 = 2047 - (int)(row[0] & 2047), tok1 = 2047 - (int)(row[1] & 2047);
            if (elect_one()) {
                mbar_expect_tx(abar, 4096);
                bulk_g2s(xs + 2 * a * ROW_PITCH, p.u + (size_t)tok0 * DM, 2048, abar);
                bulk_g2s(xs + (2 * a + 1) * ROW_PITCH, p.u + (size_t)tok1 * DM, 2048, abar);
            }
        }
        STAMP(44);
        const uint2 st = ld_relaxed_64(p.sc->stat + (tok & ~15) + 2 * ((tok & 7) ^ ((tok >> 3) & 6)) + ((tok >> 3) & 1));
        if (a == 0 && t == 0) sts64(misc + 48 + 8 * g, mine, __float_as_uint(bf_hi(st.x) + bf_lo(st.y)));
        uint32_t xq[8][4];
        if (a == 0) STAMP(45);
        if (has_gu) {
            mbar_wait(abar, aph);
            aph ^= 1;
            STAMP(46);
            named_sync(1, 128);
#pragma unroll
            for (int j = 0; j < 8; j++) {
                ldsm4(xq[j], xs + r * ROW_PITCH + m * 16 + 128 * a + (j >> 1) * 512 + (j & 1) * 64);
#pragma unroll
                for (int i = 0; i < 4; i++) xq[j][i] = bsub2_lo(xq[j][i], st.x);
            }
        }
        __syncwarp();
        if (lane < 2) mbar_arrive_peer(mapa(bar0 + 8 * B_SFREE, lane) + (has_gu ? (xq[5][0] | xq[6][0] | xq[7][0]) & p.zero : 0u));
        if (has_gu) {
            STAMP(12);
            float gacc[8][4];
#pragma unroll
            for (int i = 0; i < 8; i++) { gacc[i][0] = gacc[i][1] = gacc[i][2] = gacc[i][3] = 0.f; }
            uint4* pubh = &p.sc->h[b * 32 + lane];
            uint32_t* cnt_h = &p.sc->n_h[32 * (b / 14)];
            pin(pubh); pin(cnt_h);
            const uint32_t ko = (r + ((m >> 1) << 3)) * 64 + (((r >> 1) & 3) << 4);
#pragma unroll
            for (int c = 0; c < 4; c++) {
                mbar_wait(fbar + 32 * (c % 3), c / 3);
                STAMP(36 + c);
                const uint32_t rowa = (c == 1 ? slot1 + (m & 1) * 8192 : slot0 + (c == 2) * 32768 + (m & 1) * 4096) + ko;
                uint32_t af[16][4];
#pragma unroll
                for (int ks = 0; ks < 4; ks++)
#pragma unroll
                    for (int mt = 0; mt < 4; mt++) ldsm4t(af[4 * ks + mt], (rowa ^ (mt << 4)) + ks * 1024);
                const uint32_t dep = ((af[12][3] | af[13][3]) | (af[14][3] | af[15][3])) & p.zero;
                __syncwarp();
                if (c < 3 && elect_one()) { if (c == 1) mbar_arrive2(bar0 + 8 * (B_FREE + 4 + a) + dep); else mbar_arrive(bar0 + 8 * (B_FREE + 4 * c + a) + dep); }
#pragma unroll
                for (int ks = 0; ks < 4; ks++) {
                    const uint32_t* q = xq[2 * c + (ks >> 1)] + 2 * (ks & 1);
#pragma unroll
                    for (int mt = 0; mt < 4; mt++)
                        mma_bf16(gacc[4 * (ks & 1) + mt], af[4 * ks + mt][0], af[4 * ks + mt][1], af[4 * ks + mt][2], af[4 * ks + mt][3],
                                 q[0] | (ks < 2 ? dep : 0u), q[1]);
                }
            }
            STAMP(13);
#pragma unroll
            for (int mt = 0; mt < 4; mt++) {
#pragma unroll
                for (int j = 0; j < 4; j++) gacc[mt][j] += gacc[4 + mt][j];
                sts128f(slot0 + mt * 512 + lane * 16, gacc[mt]);
            }
            named_sync(1, 128);
            const uint32_t base = sb + OFF_RING + 16 * tid;
            const float4 p0 = lds128f(base), p1 = lds128f(base + 8192), p2 = lds128f(base + 16384), p3 = lds128f(base + 24576);
            const float r0 = lds32f(misc + 52 + 16 * t), r1 = lds32f(misc + 60 + 16 * t);
            const float g0 = bf_round(((p0.x + p1.x) + (p2.x + p3.x)) * r0), g1 = bf_round(((p0.y + p1.y) + (p2.y + p3.y)) * r1);
            const float h0 = bf_round(g0 * rcpf(1.f + ex2f(-1.4426950408889634f * g0))) * bf_round(((p0.z + p1.z) + (p2.z + p3.z)) * r0);
            const float h1 = bf_round(g1 * rcpf(1.f + ex2f(-1.4426950408889634f * g1))) * bf_round(((p0.w + p1.w) + (p2.w + p3.w)) * r1);
            uint32_t hw;
            asm volatile("movmatrix.sync.aligned.m8n8.trans.b16 %0, %1;" : "=r"(hw) : "r"(pack_bf16(h0, h1)));
            sts32(sb + OFF_RING + 7168 + 16 * lane + 4 * a, hw);
            named_sync(1, 128);
            if (a == 0) {
                const uint4 q = lds128(base + 7168);
                st_relaxed_128(pubh, q.x, q.y, q.z, (q.w & ~1u) | (tag & 1));
                if (lane == 0) red_add(cnt_h, 1);
            }
            STAMP(14);
        }
        float dacc[4];
        {
            wait_count(&p.sc->n_h[32 * (4 * h + a)], 14 * tag - FEW_H);
            STAMP(33);
            uint4 hq[14];
#pragma unroll 1
            for (uint32_t it = 0;; spin_guard(it)) {
                if (elect_one()) {
                    mbar_expect_tx(abar, 7168);
                    bulk_g2s(slot0, &p.sc->h[(56 * h + 14 * a) * 32], 7168, abar);
                }
                mbar_wait(abar, aph);
                aph ^= 1;
                uint32_t bad = 0;
#pragma unroll
                for (int j = 0; j < 14; j++) { hq[j] = lds128(slot0 + 512 * j + 16 * lane); bad = or_xor(bad, hq[j].w, tag); }
                if (__all_sync(0xffffffffu, (bad & 1) == 0)) break;
            }
            STAMP(15);
            const uint32_t wo = (r + ((m >> 1) << 3)) * 32 + (((m & 1) ^ (r >> 2)) << 4);
            float d[7][4];
#pragma unroll
            for (int i = 0; i < 7; i++) { d[i][0] = d[i][1] = d[i][2] = d[i][3] = 0.f; }
#pragma unroll
            for (int s = 0; s < 2; s++) {
                mbar_wait(fbar + 32 + 32 * s, has_gu);
                uint32_t af[14][4];
#pragma unroll
                for (int j = 0; j < 14; j++) ldsm4t(af[j], (s ? slot0 + 32768 + (j / 7) * 4096 : slot1 + (j / 7) * 8192) + wo + (j % 7) * 512);
                const uint32_t dep = (af[11][3] | af[12][3] | af[13][3]) & p.zero;
#pragma unroll
                for (int j = 0; j < 14; j++) {
                    const uint4 q = hq[7 * s + (j >> 1)];
                    mma_bf16(d[j % 7], af[j][0], af[j][1], af[j][2], af[j][3], ((j & 1) ? q.z : q.x) | (j < 7 ? dep : 0u), (j & 1) ? q.w : q.y);
                }
            }
#pragma unroll
            for (int j = 0; j < 4; j++) dacc[j] = ((d[0][j] + d[1][j]) + (d[2][j] + d[3][j])) + ((d[4][j] + d[5][j]) + d[6][j]);
        }
        STAMP(16);
        {
            sts128f(slot0 + 7680 + lane * 16, dacc);
            named_sync(1, 128);
            const int tk = tid >> 4, col = tid & 15;
            const uint32_t base = sb + OFF_RING + 7680 + ((col & 7) * 4 + (tk >> 1)) * 16 + (((col >> 3) << 1) + (tk & 1)) * 4;
            const float y0 = (lds32f(base) + lds32f(base + 8192)) + (lds32f(base + 16384) + lds32f(base + 24576));
            const uint32_t red = sb + OFF_RED + 4 * tid, key = lds32(misc + 48 + 8 * tk);
            mbar_wait(bar0 + 8 * B_SFREE, 0);
            asm volatile("st.async.weak.shared::cluster.mbarrier::complete_tx::bytes.f32 [%0], %1, [%2];"
                         ::"r"(mapa(red, h ^ 1)), "f"(y0), "r"(mapa(bar0 + 8 * B_RED, h ^ 1)) : "memory");
            const float rv = __uint_as_float(unorder_key(key >> 16) << 16);
            const float sg = bf_round(rcpf(1.f + ex2f(-1.4426950408889634f * rv)));
            mbar_wait(bar0 + 8 * B_RED, 0);
            sts32f(red, bf_round(y0 + lds32f(red)) * sg);
            __syncwarp();
            if (elect_one()) mbar_arrive(bar0 + 8 * B_UPD);
        }
        STAMP(17); GSTAMP(29);
    }
}

typedef CUresult (*EncodeFn)(CUtensorMap*, CUtensorMapDataType, cuuint32_t, void*, const cuuint64_t*, const cuuint64_t*,
                             const cuuint32_t*, const cuuint32_t*, CUtensorMapInterleave, CUtensorMapSwizzle,
                             CUtensorMapL2promotion, CUtensorMapFloatOOBfill);

void make_map(EncodeFn enc, CUtensorMap* m, const void* ptr, uint64_t cols, uint64_t rows, uint32_t bc, uint32_t br,
              CUtensorMapSwizzle sw, CUtensorMapL2promotion pr) {
    cuuint64_t dims[2] = {cols, rows};
    cuuint64_t str[1] = {cols * 2};
    cuuint32_t box[2] = {bc, br};
    cuuint32_t es[2] = {1, 1};
    enc(m, CU_TENSOR_MAP_DATA_TYPE_BFLOAT16, 2, const_cast<void*>(ptr), dims, str, box, es, CU_TENSOR_MAP_INTERLEAVE_NONE, sw, pr,
        CU_TENSOR_MAP_FLOAT_OOB_FILL_NONE);
}
void make_tile_map(EncodeFn enc, CUtensorMap* m, const void* ptr) {
    cuuint64_t dims[4] = {DM, 4, 16, SEQ / 64};
    cuuint64_t str[3] = {16 * DM * 2, DM * 2, 64 * DM * 2};
    cuuint32_t box[4] = {16, 4, 2, 8};
    cuuint32_t es[4] = {1, 1, 1, 1};
    enc(m, CU_TENSOR_MAP_DATA_TYPE_BFLOAT16, 4, const_cast<void*>(ptr), dims, str, box, es, CU_TENSOR_MAP_INTERLEAVE_NONE,
        CU_TENSOR_MAP_SWIZZLE_32B, CU_TENSOR_MAP_L2_PROMOTION_NONE, CU_TENSOR_MAP_FLOAT_OOB_FILL_NONE);
}

}

#define WD_PROMO CU_TENSOR_MAP_L2_PROMOTION_L2_64B
extern "C" void kernel_launch(void* const* d_in, const int* in_sizes, int n_in, void* d_out, int out_size) {
    (void)in_sizes; (void)n_in; (void)out_size;
    static EncodeFn enc = nullptr;
    static void* scratch = nullptr;
    if (!enc) {
        void* fn = nullptr;
        cudaDriverEntryPointQueryResult q;
        cudaGetDriverEntryPoint("cuTensorMapEncodeTiled", &fn, cudaEnableDefault, &q);
        enc = (EncodeFn)fn;
        cudaGetSymbolAddress(&scratch, g_scratch);
        cudaFuncSetAttribute(fused_kernel, cudaFuncAttributeMaxDynamicSharedMemorySize, SMEM_BYTES);
    }
    Maps maps;
    make_tile_map(enc, &maps.u, d_in[0]);
    make_tile_map(enc, &maps.out, d_out);
    make_map(enc, &maps.wg, d_in[9], FF, DM, 32, 64, CU_TENSOR_MAP_SWIZZLE_64B, CU_TENSOR_MAP_L2_PROMOTION_L2_128B);
    make_map(enc, &maps.wu, d_in[10], FF, DM, 32, 64, CU_TENSOR_MAP_SWIZZLE_64B, CU_TENSOR_MAP_L2_PROMOTION_L2_128B);
    make_map(enc, &maps.wd, d_in[11], DM, FF, 16, 112, CU_TENSOR_MAP_SWIZZLE_32B, WD_PROMO);
    Ptrs p;
    p.sc = (Scratch*)scratch;
    p.u = (const __nv_bfloat16*)d_in[0];
    p.logA = (const __nv_bfloat16*)d_in[1];
    p.Aim = (const __nv_bfloat16*)d_in[2];
    p.Cre = (const __nv_bfloat16*)d_in[3];
    p.Cim = (const __nv_bfloat16*)d_in[4];
    p.ldt = (const __nv_bfloat16*)d_in[5];
    p.dsk = (const __nv_bfloat16*)d_in[6];
    p.wr = (const __nv_bfloat16*)d_in[8];
    p.out = (__nv_bfloat16*)d_out;
    p.zero = 0;
    fused_kernel<<<NCTA, NTHR, SMEM_BYTES, cudaStreamPerThread>>>(p, maps);
}
```

```cpp
#include <cuda_runtime.h>
#include <cuda_bf16.h>
#include <cuda_fp16.h>
#include <cuda.h>
#include <stdint.h>

namespace {

constexpr int SEQ = 2048, DM = 1024, NMODE = 128, FF = 3584;
constexpr int NCTA = 128, NTHR = 512;
constexpr int GU_CTAS = 112;
constexpr int NREP = 4;

constexpr int OFF_XT = 0;
constexpr int OFF_RING = 65536;
constexpr int OFF_PRIV = OFF_RING + 65536;
constexpr int OFF_VT = OFF_PRIV + 65536;
constexpr int VT_PAD = 32, VT_PLANE = VT_PAD + 2048, VT_PITCH = 2 * VT_PLANE, ROW_PITCH = 2064;
constexpr int OFF_BAR = OFF_VT + 8 * VT_PITCH;
constexpr int OFF_MISC = OFF_BAR + 384;
constexpr int OFF_XCH = OFF_MISC + 112;
constexpr int SMEM_BYTES = OFF_XCH + 2048;
constexpr int OFF_LN = OFF_RING + 7 * 8192;
constexpr int OFF_ST = OFF_RING + 6 * 8192;
static_assert(SMEM_BYTES <= 232448, "shared memory");

constexpr int B_ROW = 0, B_XT = 4, B_V = 5, B_SFREE = 7, B_RECV = 8, B_RED = 10, B_UPD = 11, B_ST = 12, B_FREE = 20, B_FULL = 32, B_AUX = 44, NBAR = 48;

constexpr int T_DENSE = 60;
constexpr int T_PATCH = 2208;
constexpr int T_R2 = 2368;
constexpr int T_R3 = 3296;

constexpr int T_RED = 4032;
__device__ __forceinline__ uint32_t tab_off(int w) { return OFF_PRIV + w * 8192 + (w & 1) * 4096; }

constexpr uint32_t SPIN_LIMIT = 1u << 20;
#define KG_UNROLL 4
constexpr int kKgUnroll = KG_UNROLL;
#define DENSE_UNROLL 1
constexpr int kDenseUnroll = DENSE_UNROLL;
#define ST_T0 3000
#define FEW_ST 0
#define FEW_H 0
#define ST_GAP 0
#define ST_PER 310
#define ST_PER2 300

struct Exchange {
    uint2 stat[SEQ];
    uint4 h[GU_CTAS * 32];
    uint32_t n_stat[4 * 32];
    uint32_t n_h[8 * 32];
};
struct Scratch {
    Exchange x[NREP];
    uint32_t epoch;
};
__device__ __align__(128) Scratch g_scratch;

struct Ptrs {
    Scratch* sc;
    const __nv_bfloat16 *logA, *Aim, *Cre, *Cim, *ldt, *dsk, *u, *wr;
    __nv_bfloat16* out;
    uint32_t zero;
};
struct Maps {
    CUtensorMap u, out, wg, wu, wd;
};

#define STAMP(i) do { } while (0)
#define KSTAMP(i) do { } while (0)
#define GSTAMP(i) do { } while (0)

__device__ __forceinline__ uint32_t s_u32(const void* p) { return (uint32_t)__cvta_generic_to_shared(p); }
__device__ __forceinline__ void mbar_init(uint32_t b, uint32_t n) {
    asm volatile("mbarrier.init.shared::cta.b64 [%0], %1;" ::"r"(b), "r"(n) : "memory");
}
__device__ __forceinline__ void mbar_expect_tx(uint32_t b, uint32_t bytes) {
    asm volatile("mbarrier.arrive.expect_tx.shared::cta.b64 _, [%0], %1;" ::"r"(b), "r"(bytes) : "memory");
}
__device__ __forceinline__ void mbar_arrive(uint32_t b) {
    asm volatile("mbarrier.arrive.shared::cta.b64 _, [%0];" ::"r"(b) : "memory");
}
__device__ __forceinline__ void mbar_arrive2(uint32_t b) {
    asm volatile("mbarrier.arrive.shared::cta.b64 _, [%0], 2;" ::"r"(b) : "memory");
}
__device__ __forceinline__ void mbar_arrive_peer(uint32_t b_cluster) {
    asm volatile("mbarrier.arrive.relaxed.cluster.shared::cluster.b64 _, [%0];" ::"r"(b_cluster) : "memory");
}
__device__ __forceinline__ void mbar_wait(uint32_t b, uint32_t parity) {
    asm volatile("{\n\t.reg .pred p;\n\t.reg .u32 c;\n\tmov.u32 c, 0;\n"
                 "W:\n\tmbarrier.try_wait.parity.shared::cta.b64 p, [%0], %1;\n\t@p bra D;\n\t"
                 "add.u32 c, c, 1;\n\tsetp.lt.u32 p, c, 1048576;\n\t@p bra W;\n\ttrap;\nD:\n\t}"
                 ::"r"(b), "r"(parity) : "memory");
}
__device__ __forceinline__ bool mbar_test(uint32_t b, uint32_t parity) {
    uint32_t ok;
    asm volatile("{ .reg .pred p; mbarrier.test_wait.parity.shared::cta.b64 p, [%1], %2; selp.u32 %0, 1, 0, p; }" : "=r"(ok) : "r"(b), "r"(parity) : "memory");
    return __all_sync(0xffffffffu, ok != 0);
}
__device__ __forceinline__ bool elect_one() {
    uint32_t p;
    asm volatile("{ .reg .pred P; elect.sync _|P, 0xffffffff; selp.u32 %0, 1, 0, P; }" : "=r"(p));
    return p != 0;
}
__device__ __forceinline__ uint32_t mapa(uint32_t a, uint32_t rank) {
    uint32_t r;
    asm("mapa.shared::cluster.u32 %0, %1, %2;" : "=r"(r) : "r"(a), "r"(rank));
    return r;
}
__device__ __forceinline__ void cluster_arrive() { asm volatile("barrier.cluster.arrive.relaxed.aligned;" ::: "memory"); }
__device__ __forceinline__ void cluster_wait() { asm volatile("barrier.cluster.wait.acquire.aligned;" ::: "memory"); }
__device__ __forceinline__ void tma_load_2d(uint32_t dst, const CUtensorMap* m, int c0, int c1, uint32_t bar) {
    asm volatile("cp.async.bulk.tensor.2d.shared::cluster.global.mbarrier::complete_tx::bytes [%0], [%1, {%3, %4}], [%2];"
                 ::"r"(dst), "l"(m), "r"(bar), "r"(c0), "r"(c1) : "memory");
}
__device__ __forceinline__ void tma_load_tile(uint32_t dst, const CUtensorMap* m, int c0, int c2, int c3, uint32_t bar) {
    asm volatile("cp.async.bulk.tensor.4d.shared::cluster.global.mbarrier::complete_tx::bytes.multicast::cluster [%0], [%1, {%3, %4, %5, %6}], [%2], %7;"
                 ::"r"(dst), "l"(m), "r"(bar), "r"(c0), "r"(0), "r"(c2), "r"(c3), "h"((uint16_t)3) : "memory");
}
__device__ __forceinline__ void tma_store_tile(const CUtensorMap* m, uint32_t src, int c0, int c2, int c3) {
    asm volatile("cp.async.bulk.tensor.4d.global.shared::cta.bulk_group [%0, {%2, %3, %4, %5}], [%1];"
                 ::"l"(m), "r"(src), "r"(c0), "r"(0), "r"(c2), "r"(c3) : "memory");
    asm volatile("cp.async.bulk.commit_group;" ::: "memory");
}
__device__ __forceinline__ void bulk_g2s(uint32_t dst, const void* src, uint32_t bytes, uint32_t bar) {
    asm volatile("cp.async.bulk.shared::cluster.global.mbarrier::complete_tx::bytes [%0], [%1], %2, [%3];"
                 ::"r"(dst), "l"(src), "r"(bytes), "r"(bar) : "memory");
}
__device__ __forceinline__ void cp_async16(uint32_t dst, const void* src) {
    asm volatile("cp.async.cg.shared.global [%0], [%1], 16;" ::"r"(dst), "l"(src) : "memory");
}
__device__ __forceinline__ void st_async128(uint32_t dst_cluster, uint32_t x, uint32_t y, uint32_t z, uint32_t w, uint32_t bar_cluster) {
    asm volatile("st.async.weak.shared::cluster.mbarrier::complete_tx::bytes.v4.b32 [%0], {%1,%2,%3,%4}, [%5];"
                 ::"r"(dst_cluster), "r"(x), "r"(y), "r"(z), "r"(w), "r"(bar_cluster) : "memory");
}
__device__ __forceinline__ void fence_async() { asm volatile("fence.proxy.async.shared::cta;" ::: "memory"); }
__device__ __forceinline__ void named_sync(int id, int n) { asm volatile("bar.sync %0, %1;" ::"r"(id), "r"(n) : "memory"); }

__device__ __forceinline__ void ldsm4(uint32_t* r, uint32_t a) {
    asm volatile("ldmatrix.sync.aligned.m8n8.x4.shared.b16 {%0,%1,%2,%3}, [%4];"
                 : "=r"(r[0]), "=r"(r[1]), "=r"(r[2]), "=r"(r[3]) : "r"(a));
}
__device__ __forceinline__ void ldsm4t(uint32_t* r, uint32_t a) {
    asm volatile("ldmatrix.sync.aligned.m8n8.x4.trans.shared.b16 {%0,%1,%2,%3}, [%4];"
                 : "=r"(r[0]), "=r"(r[1]), "=r"(r[2]), "=r"(r[3]) : "r"(a));
}
__device__ __forceinline__ void stsm4t(uint32_t a, uint32_t x, uint32_t y, uint32_t z, uint32_t w) {
    asm volatile("stmatrix.sync.aligned.m8n8.x4.trans.shared.b16 [%0], {%1,%2,%3,%4};"
                 ::"r"(a), "r"(x), "r"(y), "r"(z), "r"(w) : "memory");
}
__device__ __forceinline__ uint32_t lds32(uint32_t a) { uint32_t v; asm volatile("ld.shared.u32 %0, [%1];" : "=r"(v) : "r"(a)); return v; }
__device__ __forceinline__ float lds32f(uint32_t a) { float v; asm volatile("ld.shared.f32 %0, [%1];" : "=f"(v) : "r"(a)); return v; }
__device__ __forceinline__ uint2 lds64(uint32_t a) { uint2 v; asm volatile("ld.shared.v2.u32 {%0,%1}, [%2];" : "=r"(v.x), "=r"(v.y) : "r"(a)); return v; }
__device__ __forceinline__ uint4 lds128(uint32_t a) {
    uint4 v; asm volatile("ld.shared.v4.u32 {%0,%1,%2,%3}, [%4];" : "=r"(v.x), "=r"(v.y), "=r"(v.z), "=r"(v.w) : "r"(a)); return v;
}
__device__ __forceinline__ uint4 lds128v(uint32_t a) {
    uint4 v; asm volatile("ld.volatile.shared.v4.u32 {%0,%1,%2,%3}, [%4];" : "=r"(v.x), "=r"(v.y), "=r"(v.z), "=r"(v.w) : "r"(a)); return v;
}
__device__ __forceinline__ uint32_t or_xor(uint32_t a, uint32_t b, uint32_t c) {
    uint32_t r; asm("lop3.b32 %0, %1, %2, %3, 0xf6;" : "=r"(r) : "r"(a), "r"(b), "r"(c)); return r;
}
__device__ __forceinline__ float4 lds128f(uint32_t a) {
    float4 v; asm volatile("ld.shared.v4.f32 {%0,%1,%2,%3}, [%4];" : "=f"(v.x), "=f"(v.y), "=f"(v.z), "=f"(v.w) : "r"(a)); return v;
}
__device__ __forceinline__ void sts32(uint32_t a, uint32_t v) { asm volatile("st.shared.u32 [%0], %1;" ::"r"(a), "r"(v) : "memory"); }
__device__ __forceinline__ void sts32f(uint32_t a, float v) { asm volatile("st.shared.f32 [%0], %1;" ::"r"(a), "f"(v) : "memory"); }
__device__ __forceinline__ void sts64(uint32_t a, uint32_t x, uint32_t y) { asm volatile("st.shared.v2.u32 [%0], {%1,%2};" ::"r"(a), "r"(x), "r"(y) : "memory"); }
__device__ __forceinline__ void sts64f(uint32_t a, float x, float y) { asm volatile("st.shared.v2.f32 [%0], {%1,%2};" ::"r"(a), "f"(x), "f"(y) : "memory"); }
__device__ __forceinline__ void sts128(uint32_t a, uint32_t x, uint32_t y, uint32_t z, uint32_t w) {
    asm volatile("st.shared.v4.u32 [%0], {%1,%2,%3,%4};" ::"r"(a), "r"(x), "r"(y), "r"(z), "r"(w) : "memory");
}
__device__ __forceinline__ void sts128f(uint32_t a, const float* v) {
    asm volatile("st.shared.v4.f32 [%0], {%1,%2,%3,%4};" ::"r"(a), "f"(v[0]), "f"(v[1]), "f"(v[2]), "f"(v[3]) : "memory");
}
__device__ __forceinline__ uint4 ldg128(const void* p) {
    uint4 v; asm volatile("ld.global.nc.L1::no_allocate.v4.u32 {%0,%1,%2,%3}, [%4];" : "=r"(v.x), "=r"(v.y), "=r"(v.z), "=r"(v.w) : "l"(p)); return v;
}
__device__ __forceinline__ uint2 ldg64(const void* p) {
    uint2 v; asm volatile("ld.global.nc.L1::no_allocate.v2.u32 {%0,%1}, [%2];" : "=r"(v.x), "=r"(v.y) : "l"(p)); return v;
}
__device__ __forceinline__ uint32_t ldg32(const void* p) {
    uint32_t v; asm volatile("ld.global.nc.u32 %0, [%1];" : "=r"(v) : "l"(p)); return v;
}
__device__ __forceinline__ uint32_t ldg16(const void* p) {
    uint32_t v; asm volatile("ld.global.nc.u16 %0, [%1];" : "=r"(v) : "l"(p)); return v;
}
__device__ __forceinline__ uint4 ld_relaxed_128(const void* p) {
    uint4 v; asm volatile("ld.relaxed.gpu.global.v4.u32 {%0,%1,%2,%3}, [%4];" : "=r"(v.x), "=r"(v.y), "=r"(v.z), "=r"(v.w) : "l"(p) : "memory"); return v;
}
__device__ __forceinline__ void ld_relaxed_128_unless(uint4& q, const void* p, bool have) {
    asm volatile("{ .reg .pred p; setp.eq.u32 p, %5, 0; @p ld.relaxed.gpu.global.v4.u32 {%0,%1,%2,%3}, [%4]; }"
                 : "+r"(q.x), "+r"(q.y), "+r"(q.z), "+r"(q.w) : "l"(p), "r"((uint32_t)have) : "memory");
}
__device__ __forceinline__ uint2 ld_relaxed_64(const void* p) {
    uint2 v; asm volatile("ld.relaxed.gpu.global.v2.u32 {%0,%1}, [%2];" : "=r"(v.x), "=r"(v.y) : "l"(p) : "memory"); return v;
}
__device__ __forceinline__ uint32_t ld_relaxed_32(const void* p) {
    uint32_t v; asm volatile("ld.relaxed.gpu.global.u32 %0, [%1];" : "=r"(v) : "l"(p) : "memory"); return v;
}
__device__ __forceinline__ void st_relaxed_128(void* p, uint32_t x, uint32_t y, uint32_t z, uint32_t w) {
    asm volatile("st.relaxed.gpu.global.v4.u32 [%0], {%1,%2,%3,%4};" ::"l"(p), "r"(x), "r"(y), "r"(z), "r"(w) : "memory");
}
__device__ __forceinline__ void st_relaxed_64(void* p, uint32_t x, uint32_t y) {
    asm volatile("st.relaxed.gpu.global.v2.u32 [%0], {%1,%2};" ::"l"(p), "r"(x), "r"(y) : "memory");
}
__device__ __forceinline__ void st_relaxed_32(void* p, uint32_t v) {
    asm volatile("st.relaxed.gpu.global.u32 [%0], %1;" ::"l"(p), "r"(v) : "memory");
}
__device__ __forceinline__ void red_add(void* p, uint32_t v) { asm volatile("red.relaxed.gpu.global.add.u32 [%0], %1;" ::"l"(p), "r"(v) : "memory"); }
__device__ __forceinline__ uint32_t now_ns() { uint32_t t; asm volatile("mov.u32 %0, %%globaltimer_lo;" : "=r"(t) :: "memory"); return t; }
__device__ __forceinline__ void spin_guard(uint32_t& it) { if (++it > SPIN_LIMIT) __trap(); }
__device__ __forceinline__ void wait_count(const uint32_t* p, uint32_t target) {
#pragma unroll 1
    for (uint32_t it = 0; __any_sync(0xffffffffu, (int)(ld_relaxed_32(p) - target) < 0); spin_guard(it)) { }
}
__device__ __forceinline__ void mma_bf16(float* c, uint32_t a0, uint32_t a1, uint32_t a2, uint32_t a3, uint32_t b0, uint32_t b1) {
    asm("mma.sync.aligned.m16n8k16.row.col.f32.bf16.bf16.f32 {%0,%1,%2,%3}, {%4,%5,%6,%7}, {%8,%9}, {%0,%1,%2,%3};"
                 : "+f"(c[0]), "+f"(c[1]), "+f"(c[2]), "+f"(c[3]) : "r"(a0), "r"(a1), "r"(a2), "r"(a3), "r"(b0), "r"(b1));
}
__device__ __forceinline__ void mma_bf16_k8(float* c, uint32_t a0, uint32_t a1, uint32_t b0) {
    asm("mma.sync.aligned.m16n8k8.row.col.f32.bf16.bf16.f32 {%0,%1,%2,%3}, {%4,%5}, {%6}, {%0,%1,%2,%3};"
                 : "+f"(c[0]), "+f"(c[1]), "+f"(c[2]), "+f"(c[3]) : "r"(a0), "r"(a1), "r"(b0));
}
__device__ __forceinline__ void mma_v(float* c, const uint32_t* a, uint32_t b0, uint32_t b1) {
    asm volatile("mma.sync.aligned.m16n8k16.row.col.f32.bf16.bf16.f32 {%0,%1,%2,%3}, {%4,%5,%6,%7}, {%8,%9}, {%0,%1,%2,%3};"
                 : "+f"(c[0]), "+f"(c[1]), "+f"(c[2]), "+f"(c[3]) : "r"(a[0]), "r"(a[1]), "r"(a[2]), "r"(a[3]), "r"(b0), "r"(b1));
}
__device__ __forceinline__ void mma_bf16_z(float* c, uint32_t a0, uint32_t a1, uint32_t a2, uint32_t a3, uint32_t b0, uint32_t b1) {
    asm volatile("mma.sync.aligned.m16n8k16.row.col.f32.bf16.bf16.f32 {%0,%1,%2,%3}, {%4,%5,%6,%7}, {%8,%9}, {%10,%10,%10,%10};"
        : "=f"(c[0]), "=f"(c[1]), "=f"(c[2]), "=f"(c[3]) : "r"(a0), "r"(a1), "r"(a2), "r"(a3), "r"(b0), "r"(b1), "f"(0.f));
}
__device__ __forceinline__ void mma_f16(float* c, uint32_t a0, uint32_t a1, uint32_t a2, uint32_t a3, uint32_t b0, uint32_t b1) {
    asm("mma.sync.aligned.m16n8k16.row.col.f32.f16.f16.f32 {%0,%1,%2,%3}, {%4,%5,%6,%7}, {%8,%9}, {%0,%1,%2,%3};"
                 : "+f"(c[0]), "+f"(c[1]), "+f"(c[2]), "+f"(c[3]) : "r"(a0), "r"(a1), "r"(a2), "r"(a3), "r"(b0), "r"(b1));
}
__device__ __forceinline__ uint32_t pack_bf16(float lo, float hi) {
    uint32_t r; asm("cvt.rn.bf16x2.f32 %0, %1, %2;" : "=r"(r) : "f"(hi), "f"(lo)); return r;
}
__device__ __forceinline__ uint32_t pack_v(float lo, float hi) {
    uint32_t r; asm volatile("cvt.rn.bf16x2.f32 %0, %1, %2;" : "=r"(r) : "f"(hi), "f"(lo)); return r;
}
__device__ __forceinline__ uint32_t pack_w(float lo, float hi) {
    uint32_t r; asm volatile("cvt.rn.satfinite.bf16x2.f32 %0, %1, %2;" : "=r"(r) : "f"(hi), "f"(lo)); return r;
}
template <int N> __device__ __forceinline__ uint32_t after_all(const uint32_t (&f)[N][4], uint32_t zero) {
    uint32_t d[3] = {0, 0, 0};
#pragma unroll
    for (int i = 0; i < N; i++) d[i % 3] |= f[i][3];
    return (d[0] | d[1] | d[2]) & zero;
}
__device__ __forceinline__ void pin(uint32_t& x) { asm volatile("" : "+r"(x)); }
template <class T> __device__ __forceinline__ void pin(T*& x) { asm volatile("" : "+l"(x)); }
__device__ __forceinline__ uint32_t pack_f16(float lo, float hi) {
    uint32_t r; asm("cvt.rn.f16x2.f32 %0, %1, %2;" : "=r"(r) : "f"(hi), "f"(lo)); return r;
}
__device__ __forceinline__ float bf_lo(uint32_t v) { return __uint_as_float(v << 16); }
__device__ __forceinline__ float bf_hi(uint32_t v) { return __uint_as_float(v & 0xffff0000u); }
__device__ __forceinline__ float bf_round(float x) { return __uint_as_float(pack_bf16(0.f, x)); }
__device__ __forceinline__ uint32_t badd2(uint32_t a, uint32_t b) { uint32_t r; asm("add.rn.bf16x2 %0, %1, %2;" : "=r"(r) : "r"(a), "r"(b)); return r; }
__device__ __forceinline__ uint32_t bsub2_lo(uint32_t a, uint32_t b) {
    uint32_t r; asm("{ .reg .b16 m, h; .reg .b32 m2; mov.b32 {m, h}, %2; mov.b32 m2, {m, m}; sub.rn.bf16x2 %0, %1, m2; }" : "=r"(r) : "r"(a), "r"(b)); return r;
}
__device__ __forceinline__ uint32_t bmax2(uint32_t a, uint32_t b) { uint32_t r; asm("max.bf16x2 %0, %1, %2;" : "=r"(r) : "r"(a), "r"(b)); return r; }
__device__ __forceinline__ uint32_t normalize2(uint32_t x, uint32_t s0, uint32_t s1) {
    uint32_t r;
    asm("{ .reg .b16 m, h, l, k; .reg .b32 m2, h2, l2, d, t;\n\t"
        "mov.b32 {m, h}, %2; mov.b32 {l, k}, %3; mov.b32 m2, {m, m}; mov.b32 h2, {h, h}; mov.b32 l2, {l, l};\n\t"
        "sub.rn.bf16x2 d, %1, m2; mul.rn.bf16x2 t, d, l2; fma.rn.bf16x2 %0, d, h2, t; }" : "=r"(r) : "r"(x), "r"(s0), "r"(s1));
    return r;
}
__device__ __forceinline__ float rcpf(float x) { float r; asm("rcp.approx.ftz.f32 %0, %1;" : "=f"(r) : "f"(x)); return r; }
__device__ __forceinline__ float sqrtaf(float x) { float r; asm("sqrt.approx.ftz.f32 %0, %1;" : "=f"(r) : "f"(x)); return r; }
__device__ __forceinline__ float ex2f(float x) { float r; asm("ex2.approx.ftz.f32 %0, %1;" : "=f"(r) : "f"(x)); return r; }

__device__ __forceinline__ int tok_off(int t) { return ((t >> 3) & 1) * VT_PLANE + (t >> 4) * 16 + (t & 7) * 2; }

__device__ __forceinline__ uint32_t order_key(uint32_t b16) { return b16 ^ ((b16 & 0x8000u) ? 0xffffu : 0x8000u); }
__device__ __forceinline__ uint32_t unorder_key(uint32_t k16) { return k16 ^ ((k16 & 0x8000u) ? 0x8000u : 0xffffu); }

struct cplx { float r, i; };
struct hc { uint32_t r, i; };
template <bool CONJ> __device__ __forceinline__ cplx csq(cplx a) {
    float im;
    asm("{ .reg .f32 t; mul.ftz.f32 t, %1, %2; mul.ftz.f32 %0, t, 0f40000000; }" : "=f"(im) : "f"(CONJ ? -a.r : a.r), "f"(a.i));
    return {fmaf(a.r, a.r, -(a.i * a.i)), im};
}
__device__ __forceinline__ cplx cexpp(float a2, float ai) {
    float m = ex2f(a2), s, c;
    __sincosf(ai, &s, &c);
    return {m * c, m * s};
}
__device__ __forceinline__ __half2 as_h2(uint32_t x) { return *reinterpret_cast<__half2*>(&x); }
__device__ __forceinline__ uint32_t as_u(__half2 x) { return *reinterpret_cast<uint32_t*>(&x); }
__device__ __forceinline__ hc hmul(hc a, hc b) {
    return {as_u(__hfma2(__hneg2(as_h2(a.i)), as_h2(b.i), __hmul2(as_h2(a.r), as_h2(b.r)))),
            as_u(__hfma2(as_h2(a.i), as_h2(b.r), __hmul2(as_h2(a.r), as_h2(b.i))))};
}
__device__ __forceinline__ hc hpack(cplx a, cplx b) { return {pack_f16(a.r, b.r), pack_f16(a.i, b.i)}; }
__device__ __forceinline__ void sts16(uint32_t a, uint32_t v) { asm volatile("st.shared.u16 [%0], %1;" ::"r"(a), "r"(v) : "memory"); }

template <class Hook, class Hook2>
__device__ __forceinline__ void kgen(uint32_t scr, uint32_t tab, int lane, uint2 la, uint2 aim, uint2 cre, uint2 cim, float dt, float skip, int dch, Hook main_done, Hook2 half_done) {
    const int g = lane >> 2, t = lane & 3;
    const float dt2 = 2.f * dt;
    const uint32_t am = bmax2(bmax2(cre.x & 0x7fff7fffu, cre.y & 0x7fff7fffu), bmax2(cim.x & 0x7fff7fffu, cim.y & 0x7fff7fffu));
    const float mx = dt2 * fmaxf(bf_lo(am), bf_hi(am));
    const uint32_t eb = min(max(__reduce_max_sync(0xffffffffu, __float_as_uint(mx)) >> 23, 1u), 252u);
    const float cscale = dt2 * __uint_as_float((253u - eb) << 23);
    const float scale_inv = __uint_as_float((eb + 1u) << 23);
    float k0 = (bf_lo(cre.x) + bf_hi(cre.x)) + (bf_lo(cre.y) + bf_hi(cre.y));
#pragma unroll
    for (int o = 16; o; o >>= 1) k0 += __shfl_xor_sync(0xffffffffu, k0, o);
    const float ndt = -1.4426950408889634f * dt;
    STAMP(40); KSTAMP(0);

    float acc[5][4];
#pragma unroll
    for (int i = 0; i < 5; i++) { acc[i][0] = acc[i][1] = acc[i][2] = acc[i][3] = 0.f; }

    const uint32_t rec = scr + t * 512, sw = (uint32_t)t << 5;
    const uint32_t ad_l = rec + (((uint32_t)g << 4) ^ sw), ad_h = rec + 128 + (((uint32_t)g << 3) ^ sw);
    const uint32_t ad_2 = rec + (0xc0u ^ sw) + ((g & 1) << 3), ad_3 = rec + (0xd0u ^ sw) + ((g & 2) << 2);
    const uint32_t ad_4 = rec + (0xe0u ^ sw) + ((g & 4) << 1), ad_z = rec + (0xf0u ^ sw);
    const uint32_t wrec = scr + lane * 256 + ((lane & 7) << 4);

#pragma unroll 1
    for (int bb = 0; bb < 2; bb++) {
        cplx z[2][11], cz[2];
#pragma unroll
        for (int e = 0; e < 2; e++) {
            const float lg = e ? bf_hi(la.x) : bf_lo(la.x), ai = (e ? bf_hi(aim.x) : bf_lo(aim.x)) * dt;
            const float cr = (e ? bf_hi(cre.x) : bf_lo(cre.x)) * cscale, ci = (e ? bf_hi(cim.x) : bf_lo(cim.x)) * cscale;
            const float a2 = bf_round(ex2f(lg * 1.4426950408889634f)) * ndt;
            z[e][0] = cexpp(a2, ai);
            z[e][5] = cexpp(a2 * 32.f, ai * -32.f);
#pragma unroll
            for (int i = 1; i < 11; i++) if (i != 5) z[e][i] = (i == 3 || i == 7) ? csq<true>(z[e][i - 1]) : csq<false>(z[e][i - 1]);
            cz[e] = {fmaf(cr, z[e][0].r, -(ci * z[e][0].i)), fmaf(cr, z[e][0].i, ci * z[e][0].r)};
        }
        la.x = la.y; aim.x = aim.y; cre.x = cre.y; cim.x = cim.y;
        const hc z1 = hpack(z[0][0], z[1][0]), z2 = hpack(z[0][1], z[1][1]), z4 = hpack(z[0][2], z[1][2]);
        hc L[8], H[8];
        L[1] = hpack(z[0][3], z[1][3]); L[2] = hpack(z[0][4], z[1][4]); L[4] = hpack(z[0][5], z[1][5]);
        const hc y64 = hpack(z[0][6], z[1][6]), z128 = hpack(z[0][7], z[1][7]), z256 = hpack(z[0][8], z[1][8]);
        const hc z512 = hpack(z[0][9], z[1][9]), z1024 = hpack(z[0][10], z[1][10]);
        H[0] = hpack(cz[0], cz[1]);
        H[1] = hmul(H[0], z1); H[2] = hmul(H[0], z2); H[3] = hmul(H[1], z2);
        L[3] = hmul(L[1], L[2]);
#pragma unroll
        for (int i = 0; i < 4; i++) { H[4 + i] = hmul(H[i], z4); if (i) L[4 + i] = hmul(L[i], L[4]); }
        __syncwarp();
        sts128(wrec, 0x3c003c00u, y64.r, 0u, y64.i);
#pragma unroll
        for (int i = 1; i < 8; i++) { const hc q = hmul(L[i], y64); sts128(wrec ^ (i << 4), L[i].r, q.r, L[i].i, q.i); }
#pragma unroll
        for (int i = 0; i < 4; i++) sts128((wrec ^ (i << 4)) + 128, H[2 * i].r, H[2 * i].i, H[2 * i + 1].r, H[2 * i + 1].i);
        {
            const hc a = hmul(z256, z1), b = hmul(z256, z128), c = hmul(z256, z2), d = hmul(z512, z4);
            sts128((wrec ^ 0x40) + 128, a.r, a.i, b.r, b.i);
            sts128((wrec ^ 0x50) + 128, c.r, c.i, z512.r, z512.i);
            sts128((wrec ^ 0x60) + 128, d.r, d.i, z1024.r, z1024.i);
            sts64((wrec ^ 0x70) + 128, z128.r, z128.i);
        }
        __syncwarp();
        KSTAMP(1 + 2 * bb);
#pragma unroll kKgUnroll
        for (int k2 = 0; k2 < 4; k2++) {
#pragma unroll
            for (uint32_t s = 0; s < 2; s++) {
                const uint32_t o = k2 * 2048 + s * 256, x = s << 4;
                const uint4 l = lds128((ad_l ^ x) + o);
                const uint2 h0 = lds64((ad_h ^ x) + o), m2 = lds64((ad_2 ^ x) + o), m3 = lds64((ad_3 ^ x) + o);
                const uint2 m4 = lds64((ad_4 ^ x) + o), mz = lds64((ad_z ^ x) + o);
                const hc H0 = {h0.x, h0.y};
                const hc H1 = hmul(H0, {mz.x, mz.y}), H2 = hmul(H0, {m2.x, m2.y}), H3 = hmul(H2, {m3.x, m3.y}), H4 = hmul(H3, {m4.x, m4.y});
                mma_f16(acc[0], l.x, l.y, l.z, l.w, H0.r, H0.i);
                mma_f16(acc[1], l.x, l.y, l.z, l.w, H1.r, H1.i);
                mma_f16(acc[2], l.x, l.y, l.z, l.w, H2.r, H2.i);
                mma_f16(acc[3], l.x, l.y, l.z, l.w, H3.r, H3.i);
                mma_f16(acc[4], l.x, l.y, l.z, l.w, H4.r, H4.i);
            }
        }
        KSTAMP(2 + 2 * bb);
        if (bb == 0) half_done();
    }
    __syncwarp();
    main_done();
    KSTAMP(5);
#pragma unroll
    for (int i = 0; i < 4; i++) sts128(tab + 2048 + 512 * i + 16 * lane, 0, 0, 0, 0);
    if (lane < 15) sts32(tab + 4 * lane, 0);
    __syncwarp();
    const uint32_t d0 = tab + T_DENSE + 4 + 8 * lane, src = (lane + 31) & 31;
    const uint32_t p0 = pack_bf16(fmaf(k0, dt2, skip), 0.f);
    uint32_t prev = p0;
#pragma unroll
    for (int i = 0; i < 4; i++) {
        const uint32_t pk = pack_bf16(acc[i >> 1][2 * (i & 1) + 1] * scale_inv, acc[i >> 1][2 * (i & 1)] * scale_inv);
        sts64(d0 + 256 * i, __byte_perm(pk, __shfl_sync(0xffffffffu, lane == 31 ? prev : pk, src), 0x5432), pk);
        prev = pk;
    }
    const uint32_t w0 = pack_bf16(acc[2][0] * scale_inv, acc[2][1] * scale_inv), w1 = pack_bf16(acc[2][2] * scale_inv, acc[2][3] * scale_inv);
    const uint32_t sa = (lane & 1) ? 0x5410u : 0x5454u, sb2 = (lane & 1) ? 0x1010u : 0x5410u;
#pragma unroll
    for (int hf = 0; hf < 2; hf++) {
        const uint32_t w = hf ? w1 : w0;
        const uint32_t pv = __shfl_sync(0xffffffffu, lane != 31 ? w : hf ? w0 : __byte_perm(prev, w1, 0x5410), src);
        sts64(d0 + 1024 + 256 * hf, __byte_perm(w, pv, sa), __byte_perm(w, pv, sb2));
        sts64(d0 + 1536 + 256 * hf, __byte_perm(w, pv, sa + 0x2222u), __byte_perm(w, pv, sb2 + 0x2222u));
    }
    const uint32_t d3 = tab + T_R2 + 160 + 320 * (t & 1) + 16 * (g >> 1) + 8 * (g & 1) + 4 * (t >> 1), d3n = d3 + (g >= 6 ? 32 : 0);
    const uint32_t d4 = tab + T_R3 + 80 + 160 * t + 4 * g, d4n = d4 + (g >= 6 ? 16 : 0);
    uint32_t p3;
#pragma unroll
    for (int hf = 0; hf < 2; hf++)
#pragma unroll
        for (int e = 0; e < 2; e++) {
            const float v3 = acc[3][2 * hf + e] * scale_inv;
            const uint32_t p4 = pack_bf16(acc[4][2 * hf + e] * scale_inv, 0.f);
            p3 = pack_bf16(v3, v3);
            sts16(d3 + 64 * hf + 160 * e, p3);
            sts16((hf ? d3n : d3) + 64 * hf + 160 * e + 18, p3);
            sts16(d4 + 32 * hf + 80 * e, p4);
            sts16((hf ? d4n : d4) + 32 * hf + 80 * e + 10, p4);
        }
    if (lane == 31) {
        const uint32_t k512 = __byte_perm(w1, 0, 0x3232);
        sts32(tab + T_DENSE, p0);
        sts64(tab + T_DENSE + 4 * 513, k512, k512); sts16(tab + T_DENSE + 4 * 515 + 2, k512);
        sts16(tab + T_PATCH + 4 * 17, p3); sts32(tab + T_PATCH + 4 * 18, p3); sts16(tab + T_PATCH + 4 * 19 + 2, p3);
    }
    __syncwarp();
}

__device__ __forceinline__ void load_toep(uint32_t* a, uint32_t p, uint32_t pz) {
    a[0] = lds32(p); a[1] = lds32(p + 32); a[2] = lds32(pz - 32); a[3] = lds32(pz);
}
#define DENSE_BLK 4
__device__ __forceinline__ void dense_step(float (&acc)[16][4], uint32_t (&R)[8][4], const uint32_t (&A)[4][4], uint32_t (&An)[4][4],
                                           uint32_t va, uint32_t vmin, uint32_t pn, uint32_t pz, uint32_t zero, int bit) {
#pragma unroll
    for (int i0 = 0; i0 < 8; i0 += DENSE_BLK) {
#pragma unroll 1
        do {
#pragma unroll
            for (int i = i0; i < i0 + DENSE_BLK; i++) {
                const int ip = (i - DENSE_BLK) & 7;
                ldsm4(R[ip], ip == 0 ? max(va - 16, vmin) : va + ip * 128 - (i0 ? 16 : 0));
                if ((i & 1) == 0) load_toep(An[i >> 1], pn + (i >> 1) * 512, pz + (i >> 1) * 512);
#pragma unroll
                for (int ka = 0; ka < 4; ka++) {
                    mma_v(acc[i + ka], A[ka], R[i][0], R[i][1]);
                    if (i + 8 + ka < 16) mma_v(acc[i + 8 + ka], A[ka], R[i][2], R[i][3]);
                }
            }
        } while (zero & (1u << (bit + i0)));
    }
}
struct DenseTaps {
    uint32_t A[4][4], E[4], F[4], e8[2], f8[2];
    __device__ __forceinline__ DenseTaps(uint32_t pb, uint32_t pz) {
        constexpr int PP = T_PATCH - T_DENSE + 56;
#pragma unroll
        for (int i = 0; i < 4; i++) load_toep(A[i], pb + 512 * i, pz + 512 * i);
        load_toep(E, pb + 2048, pz + 2048);
        load_toep(F, pb + PP, pz + PP);
        e8[0] = lds32(pz + 2048 + 32); e8[1] = lds32(pb + 2048 + 64);
        f8[0] = lds32(pz + PP + 32); f8[1] = lds32(pb + PP + 64);
    }
};
__device__ __forceinline__ void dense_phase(float (&acc)[16][4], uint32_t vrow, uint32_t pb, DenseTaps& tp, uint32_t zero, int lane) {
    uint32_t R[8][4], A1[4][4];
    const uint32_t vmin = vrow + ((lane >> 3) & 1) * VT_PLANE - 16 + zero;
    uint32_t va = vmin + 16 + (lane >> 4) * 1024 + (lane & 7) * 16, pz = pb + zero;
    {
        uint32_t H[3][4];
#pragma unroll
        for (int i = 0; i < 3; i++) ldsm4(H[i], vrow + VT_PLANE - 16 + lane * 16 + i * 512);
#pragma unroll
        for (int i = 0; i < 8; i++) ldsm4(R[i], va + i * 128);
#pragma unroll
        for (int i = 0; i < 12; i++) mma_bf16_k8(acc[i + 4], tp.e8[0], tp.e8[1], H[i >> 2][i & 3]);
#pragma unroll
        for (int i = 0; i < 8; i++) mma_bf16_k8(acc[i + 8], tp.f8[0], tp.f8[1], H[i >> 2][i & 3]);
#pragma unroll
        for (int i = 0; i < 12; i++) mma_v(acc[i + 4], tp.E, R[i & 7][2 * (i >> 3)], R[i & 7][2 * (i >> 3) + 1]);
#pragma unroll
        for (int i = 0; i < 8; i++) mma_v(acc[i + 8], tp.F, R[i][0], R[i][1]);
    }
#pragma unroll 1
    for (int rho = 0; rho < 8; rho += 2) {
        dense_step(acc, R, tp.A, A1, va, vmin, pb + 64, pz + 64, zero, 0);
        dense_step(acc, R, A1, tp.A, va - 16, vmin, pb + 128, pz + 128, zero, 8);
        pb += 128; pz += 128; va -= 32;
    }
}
__device__ __forceinline__ uint32_t ones2(int c, int lo, int hi) {
    return (((uint32_t)(c - lo) <= (uint32_t)(hi - lo)) ? 0x3f80u : 0u) | (((uint32_t)(c + 1 - lo) <= (uint32_t)(hi - lo)) ? 0x3f800000u : 0u);
}
struct Boxes {
    uint32_t q[4], ha[2];
    __device__ __forceinline__ Boxes(uint32_t vrow, int lane, int O, int L1, int H1, int L2, int H2) {
        const int g = lane >> 2, t = lane & 3, d = 2 * t - g;
        q[0] = ones2(d, L1, H1); q[1] = ones2(d, L2, H2); q[2] = ones2(d + 8, L1, H1); q[3] = ones2(d + 8, L2, H2);
#pragma unroll
        for (int i = 0; i < 2; i++) { ha[i] = vrow + 16 * g + tok_off(O + 8 * i + 2 * t); pin(ha[i]); pin(q[i]); pin(q[2 + i]); }
    }
    __device__ __forceinline__ uint32_t any() const { return (q[0] | q[1] | q[2]) | (q[3] | ha[0] | ha[1]); }
    __device__ __forceinline__ void load(int j, uint32_t* v, uint32_t zero) const {
        const uint32_t o = j * 128;
        v[0] = lds32(ha[0] + o); v[1] = lds32(ha[1] + zero + o); v[2] = lds32(ha[1] + o);
        v[3] = lds32(ha[0] + zero + o + 16); v[4] = lds32(ha[0] + o + 16); v[5] = lds32(ha[1] + o + 16);
    }
    __device__ __forceinline__ void sums(const uint32_t* v, float* Z, float* X, float* Y) const {
        mma_bf16_z(Z, q[0], q[1], q[2], q[3], v[0], v[1]);
        mma_bf16_z(X, q[0], q[1], q[2], q[3], v[2], v[3]);
        mma_bf16_z(Y, q[0], q[1], q[2], q[3], v[4], v[5]);
    }
};
template <class After>
__device__ __forceinline__ void tail_phase(float (&acc)[16][4], const Boxes& b2, const Boxes& b3, uint32_t tp2, uint32_t tp3, uint32_t zero, After after) {
    uint2 tp[10];
    uint32_t v[6], a0[4], a1[4];
    float Z[4], X[4], Y[4];
    b2.load(0, v, zero);
#pragma unroll
    for (int i = 0; i < 5; i++) { const uint4 c = lds128(tp2 + 160 * i); tp[i] = make_uint2(c.x, c.y); tp[5 + i] = make_uint2(c.z, c.w); }
#pragma unroll
    for (int j = -1; j < 20; j++) {
        if (j < 19) {
            (j < 11 ? b2 : b3).sums(v, Z, X, Y);
            if (j < 10) b2.load(j + 2, v, zero); else if (j < 18) b3.load(j - 10, v, zero);
        }
        if (j >= 0 && j < 12) {
#pragma unroll
            for (int b = 0; b < 5; b++) if (j + 4 + b < 16) mma_v(acc[j + 4 + b], a1, tp[5 + b].x, tp[5 + b].y);
        }
        if (j < 11) { a1[0] = pack_v(Z[0], Z[1]); a1[1] = pack_w(X[0], X[1]); a1[2] = pack_v(Z[2], Z[3]); a1[3] = pack_w(X[2], X[3]); }
        if (j >= 0 && j < 12) {
#pragma unroll
            for (int b = 0; b < 5; b++) if (j + 4 + b < 16) mma_v(acc[j + 4 + b], a0, tp[b].x, tp[b].y);
            if (j >= 7 && j < 11) { tp[11 - j] = lds64(tp3 + 80 * (10 - j)); tp[16 - j] = lds64(tp3 + 80 * (14 - j)); }
        } else if (j >= 12) {
#pragma unroll
            for (int b = 0; b < 8; b++) if (j - 4 + b < 16) mma_v(acc[j - 4 + b], a0, tp[b < 4 ? b + 1 : b + 2].x, tp[b < 4 ? b + 1 : b + 2].y);
        }
        if (j < 11) { a0[0] = pack_v(X[0], X[1]); a0[1] = pack_v(Y[0], Y[1]); a0[2] = pack_v(X[2], X[3]); a0[3] = pack_v(Y[2], Y[3]); }
        else if (j < 19) { a0[0] = pack_v(X[0], X[1]); a0[1] = pack_v(Y[0], Y[1]); a0[2] = pack_v(Z[2], Z[3]); a0[3] = pack_v(X[2], X[3]); }
        after(j);
    }
}
template <int G>
__device__ __forceinline__ void emit(const float (&acc)[16][4], int h, uint32_t own, uint32_t peer, uint32_t bar, uint32_t bar_peer) {
#pragma unroll
    for (int o = 0; o < 2; o++)
#pragma unroll
        for (int hf = 0; hf < 2; hf++) {
            const int n = 8 * G + 4 * o;
            asm volatile("{ .reg .pred p; setp.eq.u32 p, %7, %8;\n\t@p st.shared.v4.u32 [%0], {%1,%2,%3,%4};\n\t"
                         "@!p st.async.weak.shared::cluster.mbarrier::complete_tx::bytes.v4.b32 [%5], {%1,%2,%3,%4}, [%6]; }"
                         ::"r"(own + G * 16384 + hf * 512), "r"(pack_bf16(acc[n][2 * hf], acc[n][2 * hf + 1])), "r"(pack_bf16(acc[n + 1][2 * hf], acc[n + 1][2 * hf + 1])),
                         "r"(pack_bf16(acc[n + 2][2 * hf], acc[n + 2][2 * hf + 1])), "r"(pack_bf16(acc[n + 3][2 * hf], acc[n + 3][2 * hf + 1])),
                         "r"(peer + G * 16384 + hf * 512), "r"(bar_peer + 8 * G), "r"(h), "r"(o) : "memory");
        }
    __syncwarp();
    if (elect_one()) mbar_arrive(bar + 8 * G);
}
__device__ __forceinline__ void finish(uint32_t src, uint32_t xa) {
    uint32_t s[4][4];
    uint4 x[4];
#pragma unroll
    for (int i = 0; i < 4; i++) {
        ldsm4t(s[i], (src ^ ((i & 1) << 5)) + (i >> 1) * 8192);
        x[i] = lds128((xa ^ ((i >> 1) << 4)) + (i & 1) * 256);
    }
#pragma unroll
    for (int i = 0; i < 4; i++)
        sts128((xa ^ ((i >> 1) << 4)) + (i & 1) * 256, badd2(x[i].x, s[i][0]), badd2(x[i].y, s[i][1]), badd2(x[i].z, s[i][2]), badd2(x[i].w, s[i][3]));
}

__device__ __noinline__ float centred_var(uint32_t rows, float mu, int lane) {
    float var = 0.f;
#pragma unroll 1
    for (int rr = 0; rr < 16; rr++) {
        const float c0 = __shfl_sync(0xffffffffu, mu, rr);
        float c = 0.f;
#pragma unroll 1
        for (int k = 0; k < 16; k++) {
            const uint32_t q = lds32(rows + rr * ROW_PITCH + k * 128 + lane * 4);
            const float d0 = bf_lo(q) - c0, d1 = bf_hi(q) - c0;
            c = fmaf(d0, d0, fmaf(d1, d1, c));
        }
#pragma unroll 1
        for (int o = 16; o; o >>= 1) c += __shfl_xor_sync(0xffffffffu, c, o);
        if ((lane & 15) == rr) var = c * (1.f / DM);
    }
    return var;
}
__device__ __noinline__ float centred_score(uint32_t rows, uint32_t wbuf, uint32_t s0, uint32_t s1, int lane) {
    float sc = 0.f;
#pragma unroll 1
    for (int rr = 0; rr < 16; rr++) {
        const uint32_t t0 = __shfl_sync(0xffffffffu, s0, rr), t1 = __shfl_sync(0xffffffffu, s1, rr);
        float c = 0.f;
#pragma unroll 1
        for (int k = 0; k < 16; k++) {
            const uint32_t xn = normalize2(lds32(rows + rr * ROW_PITCH + k * 128 + lane * 4), t0, t1);
            const uint32_t wq = lds32(wbuf + (k >> 2) * 1024 + (k & 3) * 128 + lane * 4);
            c = fmaf(bf_lo(xn), bf_lo(wq), fmaf(bf_hi(xn), bf_hi(wq), c));
        }
#pragma unroll 1
        for (int o = 16; o; o >>= 1) c += __shfl_xor_sync(0xffffffffu, c, o);
        if ((lane & 15) == rr) sc = c;
    }
    return sc;
}

__global__ void __cluster_dims__(2, 1, 1) __launch_bounds__(NTHR, 1)
fused_kernel(const __grid_constant__ Ptrs p, const __grid_constant__ Maps maps) {
    extern __shared__ __align__(1024) unsigned char smem[];
    const int tid = threadIdx.x, lane = tid & 31, b = blockIdx.x;
    const int dch = 8 * b + (tid >> 5) - 4;
    uint2 la, aim, cre, cim;
    uint32_t ldt16, dsk16, epoch;
    uint4 wq;
    if ((uint32_t)(tid - 128) < 256u) {
        la = ldg64(p.logA + dch * NMODE + 4 * lane); aim = ldg64(p.Aim + dch * NMODE + 4 * lane);
        cre = ldg64(p.Cre + dch * NMODE + 4 * lane); cim = ldg64(p.Cim + dch * NMODE + 4 * lane);
        ldt16 = ldg16(p.ldt + dch); dsk16 = ldg16(p.dsk + dch);
    }
    if (tid < 128) { wq = ldg128(p.wr + 8 * tid); epoch = ld_relaxed_32(&p.sc->epoch); }
    const uint32_t sb = s_u32(smem);
    const int warp = __shfl_sync(0xffffffffu, tid >> 5, 0);
    const int h = b & 1, cl = b >> 1;
    const uint32_t bar0 = sb + OFF_BAR;
    const int m = lane >> 3, r = lane & 7, g = lane >> 2, t = lane & 3;
    const bool has_gu = b < GU_CTAS;
    if (warp == 4) { STAMP(0); GSTAMP(24); }

    if (warp >= 12) {
        asm volatile("setmaxnreg.dec.sync.aligned.u32 24;");
        const int a = warp - 12;
        uint32_t due = now_ns() + ST_T0 + (uint32_t)(128 * a + b) * ST_PER / 128;
        const bool el = elect_one();
        if (a == 1 && el) {
#pragma unroll
            for (int j = 0; j < 4; j++) mbar_init(bar0 + 8 * (B_ROW + j), 1);
            asm volatile("fence.mbarrier_init.release.cluster;" ::: "memory");
            fence_async();
#pragma unroll 1
            for (int j = 0; j < 4; j++) {
                mbar_expect_tx(bar0 + 8 * (B_ROW + j), 8192);
#pragma unroll
                for (int i = 0; i < 4; i++)
                    bulk_g2s(sb + OFF_VT + (4 * j + i) * ROW_PITCH, p.u + (size_t)(16 * b + 4 * j + i) * DM, 2048, bar0 + 8 * (B_ROW + j));
            }
        }
        if (a == 2 && el) {
#pragma unroll
            for (int i = B_XT; i < NBAR; i++) mbar_init(bar0 + 8 * i, i == B_SFREE ? 8 : i == B_UPD ? 4 : (i == B_RECV || i == B_RECV + 1) ? 9 : (i >= B_FREE + 4 && i < B_FREE + 8) ? 2 : 1);
            asm volatile("fence.mbarrier_init.release.cluster;" ::: "memory");
            fence_async();
            mbar_expect_tx(bar0 + 8 * B_XT, 65536);
            mbar_expect_tx(bar0 + 8 * B_RECV, 8192);
            mbar_expect_tx(bar0 + 8 * B_RECV + 8, 8192);
            mbar_expect_tx(bar0 + 8 * B_RED, 512);
        }
        if (a == 3 && el) {
#pragma unroll
            for (int i = 0; i < 5; i++) asm volatile("prefetch.tensormap [%0];" ::"l"(&maps.u + i) : "memory");
        }
        __syncwarp();
        cluster_arrive();
        cluster_wait();
        STAMP(18);
        mbar_wait(bar0 + 8 * (B_ROW + a), 0);
        if (el) {
#pragma unroll
            for (int i = 0; i < 4; i++)
                tma_load_tile(sb + OFF_XT + h * 32768 + a * 4096 + (i & 1) * 16384 + (i >> 1) * 2048, &maps.u, 16 * cl, 4 * a + (i & 2), 16 * (i & 1) + 8 * h, bar0 + 8 * B_XT);
        }
        if (el) {
#pragma unroll 1
            for (int k = has_gu ? 0 : 4; k < 6; k++) {
                const int i = 4 * k + a, s = k < 3 ? i : i - 12;
#pragma unroll 1
                for (int left; (left = (int)(due - now_ns())) > 0;) __nanosleep(left >> 1);
                due += k == 0 ? 4 * ST_PER + ST_GAP : k < 3 ? 4 * ST_PER : 4 * ST_PER2;
                const bool scr = (0xcf0 >> s) & 1, again = k >= 3 && has_gu, mid = (s >> 2) == 1;
                if (scr || again) mbar_wait(bar0 + 8 * (B_FREE + s), scr && again);
                const uint32_t dst = sb + (mid ? OFF_PRIV + 4096 + a * 16384 : OFF_RING + (s >> 3) * 32768 + a * 8192), bar = bar0 + 8 * (B_FULL + s);
                if (k < 4) {
                    mbar_expect_tx(bar, 8192);
                    tma_load_2d(dst, &maps.wg, 64 * cl, 512 * h + 32 * i, bar);
                    tma_load_2d(dst + 4096, &maps.wu, 64 * cl, 512 * h + 32 * i, bar);
                } else {
                    mbar_expect_tx(bar, 7168);
                    tma_load_2d(dst, &maps.wd, 16 * cl, 1792 * h + 448 * a + 224 * (k & 1), bar);
                }
            }
            STAMP(19);
        }
    } else if (warp >= 4) {
        const int w = warp - 4;
        cluster_arrive();
        asm volatile("setmaxnreg.inc.sync.aligned.u32 168;");
        const uint32_t vrow = sb + OFF_VT + w * VT_PITCH + VT_PAD, tab = sb + tab_off(w);
        const uint32_t so = sb + OFF_XT + (8 * h + w) * 1024 + ((lane ^ ((w & 1) << 1)) << 4);
        uint32_t dst0 = so + (h ^ 1) * 32768;
        const uint32_t rb0 = bar0 + 8 * B_RECV, rb1 = mapa(rb0, h ^ 1);
        const uint32_t box = sb + OFF_XT + h * 32768 + w * 2048;
        uint32_t fs = sb + OFF_XT + (h ^ 1) * 32768 + (2 * m + (r & 1)) * 1024 + (w >> 2) * 512 + (((8 * (w & 3) + (r & 4) + ((r >> 1) & 1)) ^ ((r & 1) << 1)) << 4);
        uint32_t fx = box + (g >> 1) * 512 + (t >> 1) * 144 + (2 * (t & 1) + (g & 1)) * 32;
        uint32_t tpo = 80 + (g - 2 * t) * 8 - (g < 2 * t ? 16 : 0);
        uint32_t xa = sb + OFF_XT + (w & 2) * 16384 + (w >> 2) * 16384 + (w & 1) * 1024 + (g >> 1) * 2048 + (g & 1) * 128 + t * 32 + ((h ^ (g & 1)) << 4);
        uint32_t va = sb + OFF_VT + (2 * m + (r & 1)) * VT_PITCH + VT_PAD + (16 * w + (r >> 1)) * 16;
        uint32_t qa = sb + OFF_ST + 2048 * w + 128 * t + 16 * (g ^ (2 * t));
        uint4 x[8];
        pin(dst0); pin(fs); pin(fx); pin(tpo); pin(xa); pin(va); pin(qa);
        const Boxes b2(vrow, lane, -18, 5, 7, 0, 4), b3(vrow, lane, -20, 1, 7, 0, 8);
        if (__any_sync(0xffffffffu, ((dst0 | fs) | (fx | tpo | xa) | (va | qa) | (b2.any() | b3.any())) & p.zero)) __trap();
        cluster_wait();
        pin(la.x); pin(la.y); pin(aim.x); pin(aim.y); pin(cre.x); pin(cre.y); pin(cim.x); pin(cim.y); pin(ldt16); pin(dsk16);
        kgen(sb + OFF_PRIV + w * 8192, tab, lane, la, aim, cre, cim, bf_round(ex2f(bf_lo(ldt16) * 1.4426950408889634f)), 1.f + bf_lo(dsk16), dch, [&]() {
            STAMP(21);
            if (elect_one()) mbar_arrive(bar0 + 8 * (B_FREE + 4 + (w >> 1)));
            mbar_wait(bar0 + 8 * B_XT, 0);
#pragma unroll
            for (int i = 0; i < 8; i++) x[i] = lds128(xa + (i & 1) * 8192 + (i >> 1) * 256);
        }, [&]() {
        });
        STAMP(1); KSTAMP(6);
        const uint32_t pb = tab + T_DENSE + (g - 2 * t) * 4;
        DenseTaps dt(pb, pb + p.zero);
        {
            uint4 q[4];
            mbar_wait(bar0 + 8 * (B_ST + w), 0);
#pragma unroll
            for (int n = 0; n < 4; n++) q[n] = lds128(qa + 512 * n);
            if (lane < 4) sts128(vrow - VT_PAD + (lane >> 1) * VT_PLANE + (lane & 1) * 16, 0, 0, 0, 0);
            STAMP(2); GSTAMP(28);
#pragma unroll
            for (int i = 0; i < 8; i++) {
                const uint32_t s0 = (i & 1) ? q[i >> 1].z : q[i >> 1].x, s1 = (i & 1) ? q[i >> 1].w : q[i >> 1].y;
                stsm4t(va + (i >> 1) * 64 + (i & 1) * VT_PLANE, normalize2(x[i].x, s0, s1), normalize2(x[i].y, s0, s1),
                       normalize2(x[i].z, s0, s1), normalize2(x[i].w, s0, s1));
            }
            named_sync(2, 256);
            if (elect_one()) {
                if (w < 3) mbar_arrive(bar0 + 8 * (w == 2 ? B_V : B_FREE + 10 + w));
            }
        }
        STAMP(3); KSTAMP(7);
        float acc[16][4];
#pragma unroll
        for (int i = 0; i < 16; i++) { acc[i][0] = acc[i][1] = acc[i][2] = acc[i][3] = 0.f; }
        dense_phase(acc, vrow, pb, dt, p.zero, lane);
        STAMP(4); KSTAMP(8);
        const uint32_t dst1 = mapa(dst0 + (h ? 32768 : -32768), h ^ 1);
        tail_phase(acc, b2, b3, tab + T_R2 + 2 * tpo, tab + T_R3 + tpo, p.zero, [&](int j) {
            if (j == 3) {
                mbar_wait(bar0 + 8 * B_SFREE, 0);
                emit<0>(acc, h, dst0, dst1, rb0, rb1);
                STAMP(5);
            }
            if (j == 7) {
                mbar_wait(bar0 + 8 * B_RECV, 0);
                finish(fs, fx);
                fence_async();
                __syncwarp();
                if (elect_one()) tma_store_tile(&maps.out, box, 16 * cl, 2 * w, 8 * h);
                STAMP(20);
            }
        });
        emit<1>(acc, h, dst0, dst1, rb0, rb1);
        STAMP(30);
        mbar_wait(bar0 + 8 * (B_RECV + 1), 0);
        STAMP(6);
        finish(fs + 16384, fx + 16384);
        const bool ready = mbar_test(bar0 + 8 * B_UPD, 0);
        const bool el = elect_one();
#pragma unroll 1
        for (int pass = 0; pass < 2; pass++) {
            if ((pass != 0) == ready) {
                fence_async();
                __syncwarp();
                if (el) tma_store_tile(&maps.out, box + 16384, 16 * cl, 2 * w, 16 + 8 * h);
            } else {
                if (el) asm volatile("cp.async.bulk.wait_group 0;" ::: "memory");
                __syncwarp();
                mbar_wait(bar0 + 8 * B_UPD, 0);
                const int tok = 2047 - (int)(lds32(sb + OFF_MISC + 48 + 8 * g) & 2047);
                if ((((tok >> 6) & 8) | ((tok >> 1) & 7)) == 8 * h + w) {
                    const uint32_t xa = box + (tok >> 10) * 16384 + ((tok >> 6) & 7) * 256 + (tok & 1) * 128 + ((tok >> 4) & 3) * 32 + (((t >> 1) ^ (tok & 1)) << 4) + (t & 1) * 8;
                    const uint2 o0 = lds64(xa);
                    const float4 up = lds128f(sb + tab_off(g) + T_RED + 16 * t);
                    const uint2 o1 = make_uint2(badd2(o0.x, pack_bf16(up.x, up.y)), badd2(o0.y, pack_bf16(up.z, up.w)));
                    if (ready && tok >= 1024) sts64(xa, o1.x, o1.y);
                    else *reinterpret_cast<uint2*>(p.out + (size_t)tok * DM + 16 * cl + 4 * t) = o1;
                }
            }
        }
        if (el) asm volatile("cp.async.bulk.wait_group.read 0;" ::: "memory");
        STAMP(7);
    } else {
        const int a = warp;
        cluster_arrive();
        asm volatile("setmaxnreg.inc.sync.aligned.u32 152;");
        const uint32_t tag = __shfl_sync(0xffffffffu, epoch, 0) + 1u, misc = sb + OFF_MISC, abar = bar0 + 8 * (B_AUX + a);
        uint32_t aph = 0;
        const Exchange* in = &p.sc->x[cl & (NREP - 1)];
        uint2* pub = p.sc->x[m >> 1].stat + 16 * b + 2 * (r ^ (2 * (b & 3))) + (m & 1);
        uint32_t* cnt_s = &p.sc->x[t].n_stat[b & 96];
        pin(pub); pin(cnt_s);
        if (tid < 64) sts32(sb + OFF_XCH + 4 * tid, 0);
        const uint32_t wbuf = sb + OFF_LN + a * 1024, part = sb + OFF_LN + 4096;
        {
            sts128(wbuf + 16 * lane, wq.x, wq.y, wq.z, wq.w);
            sts128(wbuf + 512 + 16 * lane, 0x3f803f80u, 0x3f803f80u, 0x3f803f80u, 0x3f803f80u);
            float wsum = ((bf_lo(wq.x) + bf_hi(wq.x)) + (bf_lo(wq.y) + bf_hi(wq.y))) + ((bf_lo(wq.z) + bf_hi(wq.z)) + (bf_lo(wq.w) + bf_hi(wq.w)));
#pragma unroll
            for (int o = 16; o; o >>= 1) wsum += __shfl_xor_sync(0xffffffffu, wsum, o);
            sts32f(part + 1024 + 4 * a, wsum);
            uint32_t wf[4][4];
#pragma unroll
            for (int i = 0; i < 4; i++) ldsm4(wf[i], wbuf + ((uint32_t)(r - 1) < 2u ? 16 * (r - 1) : 512) + 32 * m + 128 * i);
            uint32_t ra = sb + OFF_VT + r * ROW_PITCH + 512 * a + 16 * m, pa = part + a * 256 + g * 16;
            cluster_wait();
            STAMP(22);
#pragma unroll 1
            for (int hf = 0; hf < 2; hf++) {
                mbar_wait(bar0 + 8 * B_ROW + 16 * hf, 0);
                mbar_wait(bar0 + 8 * B_ROW + 16 * hf + 8, 0);
                STAMP(23);
                uint32_t x[8][4];
                float cs[2][4], q[8][4];
#pragma unroll
                for (int i = 0; i < 40; i++) (i < 8 ? cs[i >> 2 & 1] : q[(i - 8) >> 2 & 7])[i & 3] = 0.f;
#pragma unroll
                for (int k = 0; k < 8; k++) ldsm4(x[k], ra + k * 64);
                const bool more = __any_sync(0xffffffffu, after_all(x, p.zero));
#pragma unroll 1
                do {
#pragma unroll
                    for (int k = 0; k < 8; k++) {
                        mma_v(cs[k & 1], x[k], wf[k >> 1][2 * (k & 1)], wf[k >> 1][2 * (k & 1) + 1]);
#pragma unroll
                        for (int i = 0; i < 4; i++) mma_bf16_k8(q[4 * (k & 1) + i], x[k][i & 2], x[k][i | 1], x[k][i]);
                    }
                } while (more);
                const float c2 = cs[0][2] + cs[1][2];
                if (t == 0) sts64f(pa, (cs[0][0] + cs[1][0]) + c2, cs[0][1] + cs[1][1]);
                if (t == 1) sts32f(pa + 12, c2);
                const float e0 = ((q[0][0] + q[2][0]) + (q[4][0] + q[6][0])) + ((q[1][2] + q[3][2]) + (q[5][2] + q[7][2]));
                const float e1 = ((q[0][1] + q[2][1]) + (q[4][1] + q[6][1])) + ((q[1][3] + q[3][3]) + (q[5][3] + q[7][3]));
                if (t == (g >> 1)) sts32f(pa + 8, (g & 1) ? e1 : e0);
                ra += 8 * ROW_PITCH; pa += 128;
            }
        }
        STAMP(31);
        named_sync(1, 128);
        if (a == 0) {
            const uint32_t pa = part + (lane & 15) * 16;
            const float4 p0 = lds128f(pa), p1 = lds128f(pa + 256), p2 = lds128f(pa + 512), p3 = lds128f(pa + 768), ws = lds128f(part + 1024);
            const float mu = ((p0.x + p1.x) + (p2.x + p3.x)) * (1.f / DM);
            float var = ((p0.z + p1.z) + (p2.z + p3.z)) * (1.f / DM) - mu * mu;
            const bool centred = __any_sync(0xffffffffu, !(mu * mu <= 4.f * var));
            if (centred) var = centred_var(sb + OFF_VT, mu, lane);
            const float ri = rcpf(bf_round(sqrtaf(bf_round(bf_round(var) + 1e-5f))));
            const uint32_t s0 = pack_bf16(mu, ri), s1 = (pack_bf16(ri - bf_hi(s0), 0.f) & 0xfffcu) | (tag & 3);
            float sc = ((((p0.y + p1.y) + (p2.y + p3.y)) + ((p0.w + p1.w) + (p2.w + p3.w))) - bf_lo(s0) * ((ws.x + ws.y) + (ws.z + ws.w))) * ri;
            if (centred) sc = centred_score(sb + OFF_VT, sb + OFF_LN, s0, s1, lane);
            const uint32_t sb16 = pack_bf16(0.f, sc);
            const uint32_t s2 = s1 | (sb16 ^ (((uint32_t)((int)sb16 >> 31) & 0x7fff0000u) | 0x80000000u));
            st_relaxed_64(pub, s0, s2);
            st_relaxed_64(pub + 2 * sizeof(Exchange) / 8, s0, s2);
            if (lane < NREP) red_add(cnt_s, 1);
            STAMP(9); GSTAMP(25);
        }
        const uint32_t slot0 = sb + OFF_RING + a * 8192, slot1 = sb + OFF_PRIV + a * 16384 + 4096, fbar = bar0 + 8 * (B_FULL + a);
        uint32_t mine = 0, row[2] = {0, 0};
        {
            uint32_t q[16];
            named_sync(1, 128);
            wait_count(&in->n_stat[32 * a], 32 * tag - FEW_ST);
            STAMP(41);
#pragma unroll 1
            for (uint32_t it = 0;; spin_guard(it)) {
                if (elect_one()) {
                    mbar_expect_tx(abar, 4096);
                    bulk_g2s(sb + OFF_ST + 4096 * a, in->stat + 512 * a, 4096, abar);
                }
                mbar_wait(abar, aph);
                aph ^= 1;
                uint32_t bad = 0;
#pragma unroll
                for (int n = 0; n < 8; n++) {
                    const uint4 u = lds128v(sb + OFF_ST + 4096 * a + 512 * n + 16 * lane);
                    q[2 * n] = u.y; q[2 * n + 1] = u.w;
                    bad = or_xor(bad, u.y, tag);
                }
                const bool ok = __all_sync(0xffffffffu, (bad & 3) == 0);
                asm volatile("{ .reg .pred p; setp.ne.u32 p, %1, 0; @p mbarrier.arrive.shared::cta.b64 _, [%0]; }" ::"r"(bar0 + 8 * B_ST + 16 * a + 8 * lane), "r"((uint32_t)(ok && lane < 2)) : "memory");
                if (ok) break;
            }
            STAMP(8);
            const uint32_t inv = 2047 - 512 * a - 16 * m - (r ^ (2 * m));
#pragma unroll
            for (int i = 0; i < 16; i++) asm("lop3.b32 %0, %0, %1, %2, 0x9b;" : "+r"(q[i]) : "r"(inv), "r"(0xffff0000u | (64 * (i >> 1) + 8 * (i & 1))));
            auto below = [&](uint32_t x) {
                uint32_t d[4];
#pragma unroll
                for (int i = 0; i < 16; i++) d[i & 3] = i < 4 ? x + q[i] : min(d[i & 3], x + q[i]);
                d[0] = min(min(d[0], d[1]), min(d[2], d[3]));
                return d[0] < x ? x - 1 - d[0] : 0u;
            };
            const uint32_t mx0 = ~min(min(min(min(q[0], q[1]), min(q[2], q[3])), min(min(q[4], q[5]), min(q[6], q[7]))),
                                      min(min(min(q[8], q[9]), min(q[10], q[11])), min(min(q[12], q[13]), min(q[14], q[15]))));
            const uint32_t gm = min(__reduce_max_sync(0xffffffffu, lane < 16 ? mx0 : 0u), __reduce_max_sync(0xffffffffu, lane < 16 ? 0u : mx0));
            if (lane == 0) sts32(misc + 16 + 4 * a, gm);
            named_sync(1, 128);
            STAMP(42);
            if (b == 0 && tid == 0) st_relaxed_32(&p.sc->epoch, tag);
            const uint4 t0 = lds128(misc + 16);
            uint32_t tau = min(min(t0.x, t0.y), min(t0.z, t0.w));
            uint32_t mx = mx0, cnt = 0, bal;
            const uint32_t list = sb + OFF_XCH + 64 * a;
#pragma unroll 1
            while ((bal = __ballot_sync(0xffffffffu, mx >= tau)) != 0) {
                const uint32_t pos = cnt + __popc(bal & ((1u << lane) - 1u));
                cnt += __popc(bal);
                if (cnt > 16) break;
                if (mx >= tau) sts32(list + 4 * pos, mx);
                mx = below(mx);
            }
            if (cnt > 16) {
                mx = mx0;
#pragma unroll 1
                for (int j = 0; j < 8; j++) {
                    const uint32_t top = __reduce_max_sync(0xffffffffu, mx), nx = below(mx);
                    if (mx == top) { sts32(list + 4 * j, mx); sts32(list + 32 + 4 * j, 0); mx = nx; }
                }
            }
            named_sync(1, 128);
            STAMP(43);
            const uint2 k = lds64(sb + OFF_XCH + 8 * lane);
            uint32_t hi = max(k.x, k.y), lo = min(k.x, k.y);
            mbar_wait(bar0 + 8 * B_V, 0);
#pragma unroll
            for (int j = 0; j < 8; j++) {
                const uint32_t top = __reduce_max_sync(0xffffffffu, hi);
                const bool won = hi == top;
                hi = won ? lo : hi;
                lo = won ? 0u : lo;
                if (g == j) mine = top;
                if (a == (j >> 1)) row[j & 1] = top;
            }
        }
        STAMP(11);
        const int tok = 2047 - (int)(mine & 2047);
        const uint32_t xs = sb + OFF_XT + (h ^ 1) * 32768;
        if (has_gu) {
            if (elect_one()) {
                mbar_expect_tx(abar, 2048);
#pragma unroll
                for (int j = 0; j < 2; j++) bulk_g2s(xs + (2 * a + j) * 1040, p.u + (size_t)(2047 - (row[j] & 2047)) * DM + 512 * h, 1024, abar);
            }
        }
        STAMP(44);
        const uint2 st = ld_relaxed_64(in->stat + (tok & ~15) + 2 * ((tok & 7) ^ ((tok >> 3) & 6)) + ((tok >> 3) & 1));
        if (a == 0 && t == 0) sts64(misc + 48 + 8 * g, mine, __float_as_uint(bf_hi(st.x) + bf_lo(st.y)));
        uint32_t xq[4][4];
        if (a == 0) STAMP(45);
        if (has_gu) {
            mbar_wait(abar, aph);
            aph ^= 1;
            STAMP(46);
            named_sync(1, 128);
#pragma unroll
            for (int j = 0; j < 4; j++) {
                ldsm4(xq[j], xs + r * 1040 + m * 16 + 64 * a + 256 * j);
#pragma unroll
                for (int i = 0; i < 4; i++) xq[j][i] = bsub2_lo(xq[j][i], st.x);
            }
        }
        __syncwarp();
        if (lane < 2) mbar_arrive_peer(mapa(bar0 + 8 * B_SFREE, lane) + (has_gu ? ((xq[0][0] | xq[1][0]) | (xq[2][0] | xq[3][0])) & p.zero : 0u));
        if (has_gu) {
            STAMP(12);
            float gacc[8][4];
#pragma unroll
            for (int i = 0; i < 8; i++) { gacc[i][0] = gacc[i][1] = gacc[i][2] = gacc[i][3] = 0.f; }
            uint4* pubh = &p.sc->x[a].h[b * 32 + lane];
            uint32_t* cnt_h = &p.sc->x[a].n_h[32 * (b / 14) + lane];
            pin(pubh); pin(cnt_h);
            if (elect_one()) mbar_expect_tx(abar, 512);
            uint32_t ko[8];
#pragma unroll
            for (int mt = 0; mt < 8; mt++) ko[mt] = (m & 1) * 4096 + (r + ((m >> 1) << 3)) * 128 + ((r ^ (4 * h) ^ mt) << 4);
#pragma unroll
            for (int c = 0; c < 4; c++) {
                if (c == 3) mbar_wait(bar0 + 8 * B_SFREE, 0);
                mbar_wait(fbar + 32 * (c % 3), c / 3);
                STAMP(36 + c);
                uint32_t af[16][4];
#pragma unroll
                for (int i = 0; i < 16; i++) ldsm4t(af[i], (c == 1 ? slot1 : slot0 + (c == 2) * 32768) + ko[i & 7] + (i >> 3) * 2048);
                __syncwarp();
                if (c < 3 && elect_one()) { if (c == 1) mbar_arrive2(bar0 + 8 * (B_FREE + 4 + a)); else mbar_arrive(bar0 + 8 * (B_FREE + 4 * c + a)); }
                xq[c][0] |= after_all(af, p.zero);
#pragma unroll 1
                do {
#pragma unroll
                    for (int i = 0; i < 16; i++) mma_v(gacc[i & 7], af[i], xq[c][2 * (i >> 3)], xq[c][2 * (i >> 3) + 1]);
                } while (p.zero & (1u << c));
            }
            STAMP(13);
#pragma unroll
            for (int mt = 0; mt < 8; mt++) sts128f(slot0 + mt * 512 + lane * 16, gacc[mt]);
            named_sync(1, 128);
            const uint32_t base = sb + OFF_RING + 16 * tid;
            {
                const float4 p0 = lds128f(base + 2048), p1 = lds128f(base + 10240), p2 = lds128f(base + 18432), p3 = lds128f(base + 26624);
                st_async128(mapa(sb + OFF_XCH + 16 * tid, h ^ 1), __float_as_uint((p0.x + p1.x) + (p2.x + p3.x)), __float_as_uint((p0.y + p1.y) + (p2.y + p3.y)),
                            __float_as_uint((p0.z + p1.z) + (p2.z + p3.z)), __float_as_uint((p0.w + p1.w) + (p2.w + p3.w)), mapa(abar, h ^ 1));
            }
            const float4 p0 = lds128f(base), p1 = lds128f(base + 8192), p2 = lds128f(base + 16384), p3 = lds128f(base + 24576);
            const float r0 = lds32f(misc + 52 + 16 * t), r1 = lds32f(misc + 60 + 16 * t);
            const float4 own = make_float4((p0.x + p1.x) + (p2.x + p3.x), (p0.y + p1.y) + (p2.y + p3.y), (p0.z + p1.z) + (p2.z + p3.z), (p0.w + p1.w) + (p2.w + p3.w));
            mbar_wait(abar, aph);
            aph ^= 1;
            const float4 oth = lds128f(sb + OFF_XCH + 16 * tid);
            const float g0 = bf_round((own.x + oth.x) * r0), g1 = bf_round((own.y + oth.y) * r1);
            const float h0 = bf_round(g0 * rcpf(1.f + ex2f(-1.4426950408889634f * g0))) * bf_round((own.z + oth.z) * r0);
            const float h1 = bf_round(g1 * rcpf(1.f + ex2f(-1.4426950408889634f * g1))) * bf_round((own.w + oth.w) * r1);
            uint32_t hw;
            asm volatile("movmatrix.sync.aligned.m8n8.trans.b16 %0, %1;" : "=r"(hw) : "r"(pack_bf16(h0, h1)));
            sts32(sb + OFF_RING + 7168 + 16 * lane + 4 * a, hw);
            named_sync(1, 128);
            const uint4 q = lds128(sb + OFF_RING + 7168 + 16 * lane);
            st_relaxed_128(pubh, q.x, q.y, q.z, (q.w & ~1u) | (tag & 1));
            if (lane == 0) red_add(cnt_h, 1);
            STAMP(14);
        }
        float dacc[4];
        {
            uint32_t wo = (r + ((m >> 1) << 3)) * 32 + (((m & 1) ^ (r >> 2)) << 4), af[14][4];
            pin(wo);
            float d[7][4];
#pragma unroll
            for (int i = 0; i < 7; i++) { d[i][0] = d[i][1] = d[i][2] = d[i][3] = 0.f; }
            mbar_wait(fbar + 32, has_gu);
#pragma unroll
            for (int j = 0; j < 14; j++) ldsm4t(af[j], slot1 + wo + j * 512);
            wait_count(&in->n_h[32 * (4 * h + a)], 14 * tag - FEW_H);
            STAMP(33);
            uint4 hq[14];
#pragma unroll 1
            for (uint32_t it = 0;; spin_guard(it)) {
                uint32_t bad = 0;
                if (elect_one()) {
                    mbar_expect_tx(abar, 7168);
                    bulk_g2s(slot0, &in->h[(56 * h + 14 * a) * 32], 7168, abar);
                }
                mbar_wait(abar, aph);
                aph ^= 1;
#pragma unroll
                for (int j = 0; j < 14; j++) { hq[j] = lds128(slot0 + 512 * j + 16 * lane); bad = or_xor(bad, hq[j].w, tag); }
                if (__all_sync(0xffffffffu, (bad & 1) == 0)) break;
            }
            STAMP(15);
#pragma unroll
            for (int s = 0; s < 2; s++) {
                if (s) {
                    mbar_wait(fbar + 64, has_gu);
#pragma unroll
                    for (int j = 0; j < 14; j++) ldsm4t(af[j], slot0 + 32768 + wo + j * 512);
                }
                const bool more = __any_sync(0xffffffffu, after_all(af, p.zero));
#pragma unroll 1
                do {
#pragma unroll
                    for (int j = 0; j < 14; j++) {
                        const uint4 q = hq[7 * s + (j >> 1)];
                        mma_v(d[j % 7], af[j], (j & 1) ? q.z : q.x, (j & 1) ? q.w : q.y);
                    }
                } while (more);
            }
#pragma unroll
            for (int j = 0; j < 4; j++) dacc[j] = ((d[0][j] + d[1][j]) + (d[2][j] + d[3][j])) + ((d[4][j] + d[5][j]) + d[6][j]);
        }
        STAMP(16);
        {
            sts128f(slot0 + 7680 + lane * 16, dacc);
            named_sync(1, 128);
            const int tk = tid >> 4, col = tid & 15;
            const uint32_t base = sb + OFF_RING + 7680 + ((col & 7) * 4 + (tk >> 1)) * 16 + (((col >> 3) << 1) + (tk & 1)) * 4;
            const float y0 = (lds32f(base) + lds32f(base + 8192)) + (lds32f(base + 16384) + lds32f(base + 24576));
            const uint32_t red = sb + tab_off(tk) + T_RED + 4 * col, key = lds32(misc + 48 + 8 * tk);
            mbar_wait(bar0 + 8 * B_SFREE, 0);
            asm volatile("st.async.weak.shared::cluster.mbarrier::complete_tx::bytes.f32 [%0], %1, [%2];"
                         ::"r"(mapa(red, h ^ 1)), "f"(y0), "r"(mapa(bar0 + 8 * B_RED, h ^ 1)) : "memory");
            const float rv = __uint_as_float(unorder_key(key >> 16) << 16);
            const float sg = bf_round(rcpf(1.f + ex2f(-1.4426950408889634f * rv)));
            mbar_wait(bar0 + 8 * B_RED, 0);
            sts32f(red, bf_round(y0 + lds32f(red)) * sg);
            __syncwarp();
            if (elect_one()) mbar_arrive(bar0 + 8 * B_UPD);
        }
        STAMP(17); GSTAMP(29);
    }
}

typedef CUresult (*EncodeFn)(CUtensorMap*, CUtensorMapDataType, cuuint32_t, void*, const cuuint64_t*, const cuuint64_t*,
                             const cuuint32_t*, const cuuint32_t*, CUtensorMapInterleave, CUtensorMapSwizzle,
                             CUtensorMapL2promotion, CUtensorMapFloatOOBfill);

void make_map(EncodeFn enc, CUtensorMap* m, const void* ptr, uint64_t cols, uint64_t rows, uint32_t bc, uint32_t br,
              CUtensorMapSwizzle sw, CUtensorMapL2promotion pr) {
    cuuint64_t dims[2] = {cols, rows};
    cuuint64_t str[1] = {cols * 2};
    cuuint32_t box[2] = {bc, br};
    cuuint32_t es[2] = {1, 1};
    enc(m, CU_TENSOR_MAP_DATA_TYPE_BFLOAT16, 2, const_cast<void*>(ptr), dims, str, box, es, CU_TENSOR_MAP_INTERLEAVE_NONE, sw, pr,
        CU_TENSOR_MAP_FLOAT_OOB_FILL_NONE);
}
void make_tile_map(EncodeFn enc, CUtensorMap* m, const void* ptr) {
    cuuint64_t dims[4] = {DM, 4, 16, SEQ / 64};
    cuuint64_t str[3] = {16 * DM * 2, DM * 2, 64 * DM * 2};
    cuuint32_t box[4] = {16, 4, 2, 8};
    cuuint32_t es[4] = {1, 1, 1, 1};
    enc(m, CU_TENSOR_MAP_DATA_TYPE_BFLOAT16, 4, const_cast<void*>(ptr), dims, str, box, es, CU_TENSOR_MAP_INTERLEAVE_NONE,
        CU_TENSOR_MAP_SWIZZLE_32B, CU_TENSOR_MAP_L2_PROMOTION_NONE, CU_TENSOR_MAP_FLOAT_OOB_FILL_NONE);
}

}

#define WD_PROMO CU_TENSOR_MAP_L2_PROMOTION_L2_64B
extern "C" void kernel_launch(void* const* d_in, const int* in_sizes, int n_in, void* d_out, int out_size) {
    (void)in_sizes; (void)n_in; (void)out_size;
    static EncodeFn enc = nullptr;
    static void* scratch = nullptr;
    if (!enc) {
        void* fn = nullptr;
        cudaDriverEntryPointQueryResult q;
        cudaGetDriverEntryPoint("cuTensorMapEncodeTiled", &fn, cudaEnableDefault, &q);
        enc = (EncodeFn)fn;
        cudaGetSymbolAddress(&scratch, g_scratch);
        cudaFuncSetAttribute(fused_kernel, cudaFuncAttributeMaxDynamicSharedMemorySize, SMEM_BYTES);
    }
    Maps maps;
    make_tile_map(enc, &maps.u, d_in[0]);
    make_tile_map(enc, &maps.out, d_out);
    make_map(enc, &maps.wg, d_in[9], FF, DM, 64, 32, CU_TENSOR_MAP_SWIZZLE_128B, CU_TENSOR_MAP_L2_PROMOTION_L2_128B);
    make_map(enc, &maps.wu, d_in[10], FF, DM, 64, 32, CU_TENSOR_MAP_SWIZZLE_128B, CU_TENSOR_MAP_L2_PROMOTION_L2_128B);
    make_map(enc, &maps.wd, d_in[11], DM, FF, 16, 224, CU_TENSOR_MAP_SWIZZLE_32B, WD_PROMO);
    Ptrs p;
    p.sc = (Scratch*)scratch;
    p.u = (const __nv_bfloat16*)d_in[0];
    p.logA = (const __nv_bfloat16*)d_in[1];
    p.Aim = (const __nv_bfloat16*)d_in[2];
    p.Cre = (const __nv_bfloat16*)d_in[3];
    p.Cim = (const __nv_bfloat16*)d_in[4];
    p.ldt = (const __nv_bfloat16*)d_in[5];
    p.dsk = (const __nv_bfloat16*)d_in[6];
    p.wr = (const __nv_bfloat16*)d_in[8];
    p.out = (__nv_bfloat16*)d_out;
    p.zero = 0;
    fused_kernel<<<NCTA, NTHR, SMEM_BYTES, cudaStreamPerThread>>>(p, maps);
}
```

```cpp
#include <cuda_runtime.h>
#include <cuda_bf16.h>
#include <cuda_fp16.h>
#include <cuda.h>
#include <stdint.h>

namespace {

constexpr int SEQ = 2048, DM = 1024, NMODE = 128, FF = 3584;
constexpr int NCTA = 128, NTHR = 512;
constexpr int GU_CTAS = 112;
constexpr int NREP = 4;

constexpr int OFF_XT = 0;
constexpr int OFF_RING = 65536;
constexpr int OFF_PRIV = OFF_RING + 65536;
constexpr int OFF_VT = OFF_PRIV + 65536;
constexpr int VT_PAD = 32, VT_PLANE = VT_PAD + 2048, VT_PITCH = 2 * VT_PLANE, ROW_PITCH = 2064;
constexpr int OFF_BAR = OFF_VT + 8 * VT_PITCH;
constexpr int OFF_MISC = OFF_BAR + 384;
constexpr int OFF_XCH = OFF_MISC + 112;
constexpr int SMEM_BYTES = OFF_XCH + 2048;
constexpr int OFF_LN = OFF_RING + 7 * 8192;
constexpr int OFF_ST = OFF_RING + 6 * 8192;
static_assert(SMEM_BYTES <= 232448, "shared memory");

constexpr int B_ROW = 0, B_XT = 4, B_V = 5, B_LN = 6, B_SFREE = 7, B_RECV = 8, B_RED = 10, B_UPD = 11, B_ST = 12, B_FREE = 20, B_FULL = 32, B_AUX = 44, NBAR = 48;

constexpr int T_DENSE = 60;
constexpr int T_PATCH = 2208;
constexpr int T_R2 = 2368;
constexpr int T_R3 = 3296;

constexpr int T_RED = 4032;
__device__ __forceinline__ uint32_t tab_off(int w) { return OFF_PRIV + w * 8192 + (w & 1) * 4096; }

constexpr uint32_t SPIN_LIMIT = 1u << 20;
#define KG_UNROLL 4
constexpr int kKgUnroll = KG_UNROLL;
#define BB_UNROLL 2
constexpr int kBbUnroll = BB_UNROLL;
#define DENSE_UNROLL 1
constexpr int kDenseUnroll = DENSE_UNROLL;
#define ST_T0 2550
#define LN_PAUSE 0xf0
#define FEW_ST 0
#define FEW_H 0
#define ST_GAP 0
#define ST_PER 310
#define ST_PER2 300

struct Exchange {
    uint2 stat[SEQ];
    uint4 h[GU_CTAS * 32];
    uint32_t n_stat[4 * 32];
    uint32_t n_h[8 * 32];
};
struct Scratch {
    Exchange x[NREP];
    uint32_t epoch;
};
__device__ __align__(128) Scratch g_scratch;

struct Ptrs {
    Scratch* sc;
    const __nv_bfloat16 *logA, *Aim, *Cre, *Cim, *ldt, *dsk, *u, *wr;
    __nv_bfloat16* out;
    uint32_t zero;
};
struct Maps {
    CUtensorMap u, out, wg, wu, wd;
};

#define STAMP(i) do { } while (0)
#define KSTAMP(i) do { } while (0)
#define GSTAMP(i) do { } while (0)

__device__ __forceinline__ uint32_t s_u32(const void* p) { return (uint32_t)__cvta_generic_to_shared(p); }
__device__ __forceinline__ void mbar_init(uint32_t b, uint32_t n) {
    asm volatile("mbarrier.init.shared::cta.b64 [%0], %1;" ::"r"(b), "r"(n) : "memory");
}
__device__ __forceinline__ void mbar_expect_tx(uint32_t b, uint32_t bytes) {
    asm volatile("mbarrier.arrive.expect_tx.shared::cta.b64 _, [%0], %1;" ::"r"(b), "r"(bytes) : "memory");
}
__device__ __forceinline__ void mbar_arrive(uint32_t b) {
    asm volatile("mbarrier.arrive.shared::cta.b64 _, [%0];" ::"r"(b) : "memory");
}
__device__ __forceinline__ void mbar_arrive2(uint32_t b) {
    asm volatile("mbarrier.arrive.shared::cta.b64 _, [%0], 2;" ::"r"(b) : "memory");
}
__device__ __forceinline__ void mbar_arrive_peer(uint32_t b_cluster) {
    asm volatile("mbarrier.arrive.relaxed.cluster.shared::cluster.b64 _, [%0];" ::"r"(b_cluster) : "memory");
}
__device__ __forceinline__ void mbar_wait(uint32_t b, uint32_t parity) {
    asm volatile("{\n\t.reg .pred p;\n\t.reg .u32 c;\n\tmov.u32 c, 0;\n"
                 "W:\n\tmbarrier.try_wait.parity.shared::cta.b64 p, [%0], %1;\n\t@p bra D;\n\t"
                 "add.u32 c, c, 1;\n\tsetp.lt.u32 p, c, 1048576;\n\t@p bra W;\n\ttrap;\nD:\n\t}"
                 ::"r"(b), "r"(parity) : "memory");
}
__device__ __forceinline__ bool mbar_test(uint32_t b, uint32_t parity) {
    uint32_t ok;
    asm volatile("{ .reg .pred p; mbarrier.test_wait.parity.shared::cta.b64 p, [%1], %2; selp.u32 %0, 1, 0, p; }" : "=r"(ok) : "r"(b), "r"(parity) : "memory");
    return __all_sync(0xffffffffu, ok != 0);
}
__device__ __forceinline__ bool elect_one() {
    uint32_t p;
    asm volatile("{ .reg .pred P; elect.sync _|P, 0xffffffff; selp.u32 %0, 1, 0, P; }" : "=r"(p));
    return p != 0;
}
__device__ __forceinline__ uint32_t mapa(uint32_t a, uint32_t rank) {
    uint32_t r;
    asm("mapa.shared::cluster.u32 %0, %1, %2;" : "=r"(r) : "r"(a), "r"(rank));
    return r;
}
__device__ __forceinline__ void cluster_arrive() { asm volatile("barrier.cluster.arrive.relaxed.aligned;" ::: "memory"); }
__device__ __forceinline__ void cluster_wait() { asm volatile("barrier.cluster.wait.acquire.aligned;" ::: "memory"); }
__device__ __forceinline__ void tma_load_2d(uint32_t dst, const CUtensorMap* m, int c0, int c1, uint32_t bar) {
    asm volatile("cp.async.bulk.tensor.2d.shared::cluster.global.mbarrier::complete_tx::bytes [%0], [%1, {%3, %4}], [%2];"
                 ::"r"(dst), "l"(m), "r"(bar), "r"(c0), "r"(c1) : "memory");
}
__device__ __forceinline__ void tma_load_tile(uint32_t dst, const CUtensorMap* m, int c0, int c2, int c3, uint32_t bar) {
    asm volatile("cp.async.bulk.tensor.4d.shared::cluster.global.mbarrier::complete_tx::bytes.multicast::cluster [%0], [%1, {%3, %4, %5, %6}], [%2], %7;"
                 ::"r"(dst), "l"(m), "r"(bar), "r"(c0), "r"(0), "r"(c2), "r"(c3), "h"((uint16_t)3) : "memory");
}
__device__ __forceinline__ void tma_store_tile(const CUtensorMap* m, uint32_t src, int c0, int c2, int c3) {
    asm volatile("cp.async.bulk.tensor.4d.global.shared::cta.bulk_group [%0, {%2, %3, %4, %5}], [%1];"
                 ::"l"(m), "r"(src), "r"(c0), "r"(0), "r"(c2), "r"(c3) : "memory");
    asm volatile("cp.async.bulk.commit_group;" ::: "memory");
}
__device__ __forceinline__ void bulk_g2s(uint32_t dst, const void* src, uint32_t bytes, uint32_t bar) {
    asm volatile("cp.async.bulk.shared::cluster.global.mbarrier::complete_tx::bytes [%0], [%1], %2, [%3];"
                 ::"r"(dst), "l"(src), "r"(bytes), "r"(bar) : "memory");
}
__device__ __forceinline__ void cp_async16(uint32_t dst, const void* src) {
    asm volatile("cp.async.cg.shared.global [%0], [%1], 16;" ::"r"(dst), "l"(src) : "memory");
}
__device__ __forceinline__ void st_async128(uint32_t dst_cluster, uint32_t x, uint32_t y, uint32_t z, uint32_t w, uint32_t bar_cluster) {
    asm volatile("st.async.weak.shared::cluster.mbarrier::complete_tx::bytes.v4.b32 [%0], {%1,%2,%3,%4}, [%5];"
                 ::"r"(dst_cluster), "r"(x), "r"(y), "r"(z), "r"(w), "r"(bar_cluster) : "memory");
}
__device__ __forceinline__ void fence_async() { asm volatile("fence.proxy.async.shared::cta;" ::: "memory"); }
__device__ __forceinline__ void named_sync(int id, int n) { asm volatile("bar.sync %0, %1;" ::"r"(id), "r"(n) : "memory"); }

__device__ __forceinline__ void ldsm4(uint32_t* r, uint32_t a) {
    asm volatile("ldmatrix.sync.aligned.m8n8.x4.shared.b16 {%0,%1,%2,%3}, [%4];"
                 : "=r"(r[0]), "=r"(r[1]), "=r"(r[2]), "=r"(r[3]) : "r"(a));
}
__device__ __forceinline__ void ldsm4t(uint32_t* r, uint32_t a) {
    asm volatile("ldmatrix.sync.aligned.m8n8.x4.trans.shared.b16 {%0,%1,%2,%3}, [%4];"
                 : "=r"(r[0]), "=r"(r[1]), "=r"(r[2]), "=r"(r[3]) : "r"(a));
}
__device__ __forceinline__ void stsm4t(uint32_t a, uint32_t x, uint32_t y, uint32_t z, uint32_t w) {
    asm volatile("stmatrix.sync.aligned.m8n8.x4.trans.shared.b16 [%0], {%1,%2,%3,%4};"
                 ::"r"(a), "r"(x), "r"(y), "r"(z), "r"(w) : "memory");
}
__device__ __forceinline__ uint32_t lds32(uint32_t a) { uint32_t v; asm volatile("ld.shared.u32 %0, [%1];" : "=r"(v) : "r"(a)); return v; }
__device__ __forceinline__ float lds32f(uint32_t a) { float v; asm volatile("ld.shared.f32 %0, [%1];" : "=f"(v) : "r"(a)); return v; }
__device__ __forceinline__ uint2 lds64(uint32_t a) { uint2 v; asm volatile("ld.shared.v2.u32 {%0,%1}, [%2];" : "=r"(v.x), "=r"(v.y) : "r"(a)); return v; }
__device__ __forceinline__ uint4 lds128(uint32_t a) {
    uint4 v; asm volatile("ld.shared.v4.u32 {%0,%1,%2,%3}, [%4];" : "=r"(v.x), "=r"(v.y), "=r"(v.z), "=r"(v.w) : "r"(a)); return v;
}
__device__ __forceinline__ uint4 lds128v(uint32_t a) {
    uint4 v; asm volatile("ld.volatile.shared.v4.u32 {%0,%1,%2,%3}, [%4];" : "=r"(v.x), "=r"(v.y), "=r"(v.z), "=r"(v.w) : "r"(a)); return v;
}
__device__ __forceinline__ uint32_t or_xor(uint32_t a, uint32_t b, uint32_t c) {
    uint32_t r; asm("lop3.b32 %0, %1, %2, %3, 0xf6;" : "=r"(r) : "r"(a), "r"(b), "r"(c)); return r;
}
__device__ __forceinline__ float4 lds128f(uint32_t a) {
    float4 v; asm volatile("ld.shared.v4.f32 {%0,%1,%2,%3}, [%4];" : "=f"(v.x), "=f"(v.y), "=f"(v.z), "=f"(v.w) : "r"(a)); return v;
}
__device__ __forceinline__ void sts32(uint32_t a, uint32_t v) { asm volatile("st.shared.u32 [%0], %1;" ::"r"(a), "r"(v) : "memory"); }
__device__ __forceinline__ void sts32f(uint32_t a, float v) { asm volatile("st.shared.f32 [%0], %1;" ::"r"(a), "f"(v) : "memory"); }
__device__ __forceinline__ void sts64(uint32_t a, uint32_t x, uint32_t y) { asm volatile("st.shared.v2.u32 [%0], {%1,%2};" ::"r"(a), "r"(x), "r"(y) : "memory"); }
__device__ __forceinline__ void sts64f(uint32_t a, float x, float y) { asm volatile("st.shared.v2.f32 [%0], {%1,%2};" ::"r"(a), "f"(x), "f"(y) : "memory"); }
__device__ __forceinline__ void sts128(uint32_t a, uint32_t x, uint32_t y, uint32_t z, uint32_t w) {
    asm volatile("st.shared.v4.u32 [%0], {%1,%2,%3,%4};" ::"r"(a), "r"(x), "r"(y), "r"(z), "r"(w) : "memory");
}
__device__ __forceinline__ void sts128f(uint32_t a, const float* v) {
    asm volatile("st.shared.v4.f32 [%0], {%1,%2,%3,%4};" ::"r"(a), "f"(v[0]), "f"(v[1]), "f"(v[2]), "f"(v[3]) : "memory");
}
__device__ __forceinline__ uint4 ldg128(const void* p) {
    uint4 v; asm volatile("ld.global.nc.L1::no_allocate.v4.u32 {%0,%1,%2,%3}, [%4];" : "=r"(v.x), "=r"(v.y), "=r"(v.z), "=r"(v.w) : "l"(p)); return v;
}
__device__ __forceinline__ uint2 ldg64(const void* p) {
    uint2 v; asm volatile("ld.global.nc.L1::no_allocate.v2.u32 {%0,%1}, [%2];" : "=r"(v.x), "=r"(v.y) : "l"(p)); return v;
}
__device__ __forceinline__ uint32_t ldg32(const void* p) {
    uint32_t v; asm volatile("ld.global.nc.u32 %0, [%1];" : "=r"(v) : "l"(p)); return v;
}
__device__ __forceinline__ uint32_t ldg16(const void* p) {
    uint32_t v; asm volatile("ld.global.nc.u16 %0, [%1];" : "=r"(v) : "l"(p)); return v;
}
__device__ __forceinline__ uint4 ld_relaxed_128(const void* p) {
    uint4 v; asm volatile("ld.relaxed.gpu.global.v4.u32 {%0,%1,%2,%3}, [%4];" : "=r"(v.x), "=r"(v.y), "=r"(v.z), "=r"(v.w) : "l"(p) : "memory"); return v;
}
__device__ __forceinline__ void ld_relaxed_128_unless(uint4& q, const void* p, bool have) {
    asm volatile("{ .reg .pred p; setp.eq.u32 p, %5, 0; @p ld.relaxed.gpu.global.v4.u32 {%0,%1,%2,%3}, [%4]; }"
                 : "+r"(q.x), "+r"(q.y), "+r"(q.z), "+r"(q.w) : "l"(p), "r"((uint32_t)have) : "memory");
}
__device__ __forceinline__ uint2 ld_relaxed_64(const void* p) {
    uint2 v; asm volatile("ld.relaxed.gpu.global.v2.u32 {%0,%1}, [%2];" : "=r"(v.x), "=r"(v.y) : "l"(p) : "memory"); return v;
}
__device__ __forceinline__ uint32_t ld_relaxed_32(const void* p) {
    uint32_t v; asm volatile("ld.relaxed.gpu.global.u32 %0, [%1];" : "=r"(v) : "l"(p) : "memory"); return v;
}
__device__ __forceinline__ void st_relaxed_128(void* p, uint32_t x, uint32_t y, uint32_t z, uint32_t w) {
    asm volatile("st.relaxed.gpu.global.v4.u32 [%0], {%1,%2,%3,%4};" ::"l"(p), "r"(x), "r"(y), "r"(z), "r"(w) : "memory");
}
__device__ __forceinline__ void st_relaxed_64(void* p, uint32_t x, uint32_t y) {
    asm volatile("st.relaxed.gpu.global.v2.u32 [%0], {%1,%2};" ::"l"(p), "r"(x), "r"(y) : "memory");
}
__device__ __forceinline__ void st_relaxed_32(void* p, uint32_t v) {
    asm volatile("st.relaxed.gpu.global.u32 [%0], %1;" ::"l"(p), "r"(v) : "memory");
}
__device__ __forceinline__ void red_add(void* p, uint32_t v) { asm volatile("red.relaxed.gpu.global.add.u32 [%0], %1;" ::"l"(p), "r"(v) : "memory"); }
__device__ __forceinline__ uint32_t now_ns() { uint32_t t; asm volatile("mov.u32 %0, %%globaltimer_lo;" : "=r"(t) :: "memory"); return t; }
__device__ __forceinline__ void spin_guard(uint32_t& it) { if (++it > SPIN_LIMIT) __trap(); }
__device__ __forceinline__ void wait_count(const uint32_t* p, uint32_t target) {
#pragma unroll 1
    for (uint32_t it = 0; __any_sync(0xffffffffu, (int)(ld_relaxed_32(p) - target) < 0); spin_guard(it)) { }
}
__device__ __forceinline__ void mma_bf16(float* c, uint32_t a0, uint32_t a1, uint32_t a2, uint32_t a3, uint32_t b0, uint32_t b1) {
    asm("mma.sync.aligned.m16n8k16.row.col.f32.bf16.bf16.f32 {%0,%1,%2,%3}, {%4,%5,%6,%7}, {%8,%9}, {%0,%1,%2,%3};"
                 : "+f"(c[0]), "+f"(c[1]), "+f"(c[2]), "+f"(c[3]) : "r"(a0), "r"(a1), "r"(a2), "r"(a3), "r"(b0), "r"(b1));
}
__device__ __forceinline__ void mma_bf16_k8(float* c, uint32_t a0, uint32_t a1, uint32_t b0) {
    asm("mma.sync.aligned.m16n8k8.row.col.f32.bf16.bf16.f32 {%0,%1,%2,%3}, {%4,%5}, {%6}, {%0,%1,%2,%3};"
                 : "+f"(c[0]), "+f"(c[1]), "+f"(c[2]), "+f"(c[3]) : "r"(a0), "r"(a1), "r"(b0));
}
__device__ __forceinline__ void mma_v(float* c, const uint32_t* a, uint32_t b0, uint32_t b1) {
    asm volatile("mma.sync.aligned.m16n8k16.row.col.f32.bf16.bf16.f32 {%0,%1,%2,%3}, {%4,%5,%6,%7}, {%8,%9}, {%0,%1,%2,%3};"
                 : "+f"(c[0]), "+f"(c[1]), "+f"(c[2]), "+f"(c[3]) : "r"(a[0]), "r"(a[1]), "r"(a[2]), "r"(a[3]), "r"(b0), "r"(b1));
}
__device__ __forceinline__ void mma_bf16_z(float* c, uint32_t a0, uint32_t a1, uint32_t a2, uint32_t a3, uint32_t b0, uint32_t b1) {
    asm volatile("mma.sync.aligned.m16n8k16.row.col.f32.bf16.bf16.f32 {%0,%1,%2,%3}, {%4,%5,%6,%7}, {%8,%9}, {%10,%10,%10,%10};"
        : "=f"(c[0]), "=f"(c[1]), "=f"(c[2]), "=f"(c[3]) : "r"(a0), "r"(a1), "r"(a2), "r"(a3), "r"(b0), "r"(b1), "f"(0.f));
}
__device__ __forceinline__ void mma_f16(float* c, uint32_t a0, uint32_t a1, uint32_t a2, uint32_t a3, uint32_t b0, uint32_t b1) {
    asm("mma.sync.aligned.m16n8k16.row.col.f32.f16.f16.f32 {%0,%1,%2,%3}, {%4,%5,%6,%7}, {%8,%9}, {%0,%1,%2,%3};"
                 : "+f"(c[0]), "+f"(c[1]), "+f"(c[2]), "+f"(c[3]) : "r"(a0), "r"(a1), "r"(a2), "r"(a3), "r"(b0), "r"(b1));
}
__device__ __forceinline__ uint32_t pack_bf16(float lo, float hi) {
    uint32_t r; asm("cvt.rn.bf16x2.f32 %0, %1, %2;" : "=r"(r) : "f"(hi), "f"(lo)); return r;
}
__device__ __forceinline__ uint32_t pack_v(float lo, float hi) {
    uint32_t r; asm volatile("cvt.rn.bf16x2.f32 %0, %1, %2;" : "=r"(r) : "f"(hi), "f"(lo)); return r;
}
__device__ __forceinline__ uint32_t pack_w(float lo, float hi) {
    uint32_t r; asm volatile("cvt.rn.satfinite.bf16x2.f32 %0, %1, %2;" : "=r"(r) : "f"(hi), "f"(lo)); return r;
}
template <int N> __device__ __forceinline__ uint32_t after_all(const uint32_t (&f)[N][4], uint32_t zero) {
    uint32_t d[3] = {0, 0, 0};
#pragma unroll
    for (int i = 0; i < N; i++) d[i % 3] |= f[i][3];
    return (d[0] | d[1] | d[2]) & zero;
}
__device__ __forceinline__ void pin(uint32_t& x) { asm volatile("" : "+r"(x)); }
template <class T> __device__ __forceinline__ void pin(T*& x) { asm volatile("" : "+l"(x)); }
__device__ __forceinline__ uint32_t pack_f16(float lo, float hi) {
    uint32_t r; asm("cvt.rn.f16x2.f32 %0, %1, %2;" : "=r"(r) : "f"(hi), "f"(lo)); return r;
}
__device__ __forceinline__ float bf_lo(uint32_t v) { return __uint_as_float(v << 16); }
__device__ __forceinline__ float bf_hi(uint32_t v) { return __uint_as_float(v & 0xffff0000u); }
__device__ __forceinline__ float bf_round(float x) { return __uint_as_float(pack_bf16(0.f, x)); }
__device__ __forceinline__ uint32_t badd2(uint32_t a, uint32_t b) { uint32_t r; asm("add.rn.bf16x2 %0, %1, %2;" : "=r"(r) : "r"(a), "r"(b)); return r; }
__device__ __forceinline__ uint32_t bsub2_lo(uint32_t a, uint32_t b) {
    uint32_t r; asm("{ .reg .b16 m, h; .reg .b32 m2; mov.b32 {m, h}, %2; mov.b32 m2, {m, m}; sub.rn.bf16x2 %0, %1, m2; }" : "=r"(r) : "r"(a), "r"(b)); return r;
}
__device__ __forceinline__ uint32_t bmax2(uint32_t a, uint32_t b) { uint32_t r; asm("max.bf16x2 %0, %1, %2;" : "=r"(r) : "r"(a), "r"(b)); return r; }
__device__ __forceinline__ uint32_t normalize2(uint32_t x, uint32_t s0, uint32_t s1) {
    uint32_t r;
    asm("{ .reg .b16 m, h, l, k; .reg .b32 m2, h2, l2, d, t;\n\t"
        "mov.b32 {m, h}, %2; mov.b32 {l, k}, %3; mov.b32 m2, {m, m}; mov.b32 h2, {h, h}; mov.b32 l2, {l, l};\n\t"
        "sub.rn.bf16x2 d, %1, m2; mul.rn.bf16x2 t, d, l2; fma.rn.bf16x2 %0, d, h2, t; }" : "=r"(r) : "r"(x), "r"(s0), "r"(s1));
    return r;
}
__device__ __forceinline__ float rcpf(float x) { float r; asm("rcp.approx.ftz.f32 %0, %1;" : "=f"(r) : "f"(x)); return r; }
__device__ __forceinline__ float sqrtaf(float x) { float r; asm("sqrt.approx.ftz.f32 %0, %1;" : "=f"(r) : "f"(x)); return r; }
__device__ __forceinline__ float ex2f(float x) { float r; asm("ex2.approx.ftz.f32 %0, %1;" : "=f"(r) : "f"(x)); return r; }

__device__ __forceinline__ int tok_off(int t) { return ((t >> 3) & 1) * VT_PLANE + (t >> 4) * 16 + (t & 7) * 2; }

__device__ __forceinline__ uint32_t order_key(uint32_t b16) { return b16 ^ ((b16 & 0x8000u) ? 0xffffu : 0x8000u); }
__device__ __forceinline__ uint32_t unorder_key(uint32_t k16) { return k16 ^ ((k16 & 0x8000u) ? 0x8000u : 0xffffu); }

struct cplx { float r, i; };
struct hc { uint32_t r, i; };
template <bool CONJ> __device__ __forceinline__ cplx csq(cplx a) {
    float im;
    asm("{ .reg .f32 t; mul.ftz.f32 t, %1, %2; mul.ftz.f32 %0, t, 0f40000000; }" : "=f"(im) : "f"(CONJ ? -a.r : a.r), "f"(a.i));
    return {fmaf(a.r, a.r, -(a.i * a.i)), im};
}
__device__ __forceinline__ cplx cexpp(float a2, float ai) {
    float m = ex2f(a2), s, c;
    __sincosf(ai, &s, &c);
    return {m * c, m * s};
}
__device__ __forceinline__ __half2 as_h2(uint32_t x) { return *reinterpret_cast<__half2*>(&x); }
__device__ __forceinline__ uint32_t as_u(__half2 x) { return *reinterpret_cast<uint32_t*>(&x); }
__device__ __forceinline__ hc hmul(hc a, hc b) {
    return {as_u(__hfma2(as_h2(a.r), as_h2(b.r), __hneg2(__hmul2(as_h2(a.i), as_h2(b.i))))),
            as_u(__hfma2(as_h2(a.r), as_h2(b.i), __hmul2(as_h2(a.i), as_h2(b.r))))};
}
__device__ __forceinline__ hc hpack(cplx a, cplx b) { return {pack_f16(a.r, b.r), pack_f16(a.i, b.i)}; }
__device__ __forceinline__ void sts16(uint32_t a, uint32_t v) { asm volatile("st.shared.u16 [%0], %1;" ::"r"(a), "r"(v) : "memory"); }

struct KgenAddr {
    uint32_t l, h, m2, m3, m4, z, w, wz;
    __device__ __forceinline__ KgenAddr(uint32_t scr, int lane) {
        const int g = lane >> 2, t = lane & 3;
        const uint32_t rec = scr + t * 480;
        l = rec + 16 * g; h = rec + 128 + 8 * g; m2 = rec + 192 + 8 * (g & 1); m3 = rec + 208 + 4 * (g & 2); m4 = rec + 224 + 2 * (g & 4);
        z = scr + 7680 + 16 * t; w = scr + 240 * lane; wz = scr + 7680 + 8 * lane;
        pin(l); pin(h); pin(m2); pin(m3); pin(m4); pin(z); pin(w); pin(wz);
    }
    __device__ __forceinline__ uint32_t any() const { return (l | h | m2) | (m3 | m4 | z) | (w | wz); }
};
template <class Hook, class Hook2>
__device__ __forceinline__ void kgen(const KgenAddr& ad, uint32_t tab, int lane, uint2 la, uint2 aim, uint2 cre, uint2 cim, float dt, float skip, int dch, Hook main_done, Hook2 half_done) {
    const int g = lane >> 2, t = lane & 3;
    const float dt2 = 2.f * dt;
    const uint32_t am = bmax2(bmax2(cre.x & 0x7fff7fffu, cre.y & 0x7fff7fffu), bmax2(cim.x & 0x7fff7fffu, cim.y & 0x7fff7fffu));
    const float mx = dt2 * fmaxf(bf_lo(am), bf_hi(am));
    const uint32_t eb = min(max(__reduce_max_sync(0xffffffffu, __float_as_uint(mx)) >> 23, 1u), 252u);
    const float cscale = dt2 * __uint_as_float((253u - eb) << 23);
    const float scale_inv = __uint_as_float((eb + 1u) << 23);
    float k0 = (bf_lo(cre.x) + bf_hi(cre.x)) + (bf_lo(cre.y) + bf_hi(cre.y));
#pragma unroll
    for (int o = 16; o; o >>= 1) k0 += __shfl_xor_sync(0xffffffffu, k0, o);
    const float ndt = -1.4426950408889634f * dt;
    STAMP(40); KSTAMP(0);

    float acc[5][4];
#pragma unroll
    for (int i = 0; i < 5; i++) { acc[i][0] = acc[i][1] = acc[i][2] = acc[i][3] = 0.f; }

#pragma unroll kBbUnroll
    for (int bb = 0; bb < 2; bb++) {
        cplx z[2][11], cz[2];
#pragma unroll
        for (int e = 0; e < 2; e++) {
            const float lg = e ? bf_hi(la.x) : bf_lo(la.x), ai = (e ? bf_hi(aim.x) : bf_lo(aim.x)) * dt;
            const float cr = (e ? bf_hi(cre.x) : bf_lo(cre.x)) * cscale, ci = (e ? bf_hi(cim.x) : bf_lo(cim.x)) * cscale;
            const float a2 = bf_round(ex2f(lg * 1.4426950408889634f)) * ndt;
            z[e][0] = cexpp(a2, ai);
            z[e][5] = cexpp(a2 * 32.f, ai * -32.f);
#pragma unroll
            for (int i = 1; i < 11; i++) if (i != 5) z[e][i] = (i == 3 || i == 7) ? csq<true>(z[e][i - 1]) : csq<false>(z[e][i - 1]);
            cz[e] = {fmaf(cr, z[e][0].r, -(ci * z[e][0].i)), fmaf(cr, z[e][0].i, ci * z[e][0].r)};
        }
        la.x = la.y; aim.x = aim.y; cre.x = cre.y; cim.x = cim.y;
        const hc z1 = hpack(z[0][0], z[1][0]), z2 = hpack(z[0][1], z[1][1]), z4 = hpack(z[0][2], z[1][2]);
        hc L[8], H[8];
        L[1] = hpack(z[0][3], z[1][3]); L[2] = hpack(z[0][4], z[1][4]); L[4] = hpack(z[0][5], z[1][5]);
        const hc y64 = hpack(z[0][6], z[1][6]), z128 = hpack(z[0][7], z[1][7]), z256 = hpack(z[0][8], z[1][8]);
        const hc z512 = hpack(z[0][9], z[1][9]), z1024 = hpack(z[0][10], z[1][10]);
        H[0] = hpack(cz[0], cz[1]);
        H[1] = hmul(H[0], z1); H[2] = hmul(H[0], z2); H[3] = hmul(H[1], z2);
        L[3] = hmul(L[1], L[2]);
#pragma unroll
        for (int i = 0; i < 4; i++) { H[4 + i] = hmul(H[i], z4); if (i) L[4 + i] = hmul(L[i], L[4]); }
        __syncwarp();
        sts128(ad.w, 0x3c003c00u, y64.r, 0u, y64.i);
#pragma unroll
        for (int i = 1; i < 8; i++) { const hc q = hmul(L[i], y64); sts128(ad.w + 16 * i, L[i].r, q.r, L[i].i, q.i); }
#pragma unroll
        for (int i = 0; i < 4; i++) sts128(ad.w + 128 + 16 * i, H[2 * i].r, H[2 * i].i, H[2 * i + 1].r, H[2 * i + 1].i);
        {
            const hc a = hmul(z256, z1), b = hmul(z256, z128), c = hmul(z256, z2), d = hmul(z512, z4);
            sts128(ad.w + 192, a.r, a.i, b.r, b.i);
            sts128(ad.w + 208, c.r, c.i, z512.r, z512.i);
            sts128(ad.w + 224, d.r, d.i, z1024.r, z1024.i);
            sts64(ad.wz, z128.r, z128.i);
        }
        __syncwarp();
        KSTAMP(1 + 2 * bb);
#pragma unroll kKgUnroll
        for (int k2 = 0; k2 < 4; k2++) {
#pragma unroll
            for (uint32_t s = 0; s < 2; s++) {
                const uint32_t o = k2 * 1920 + s * 240;
                const uint4 l = lds128(ad.l + o);
                const uint2 h0 = lds64(ad.h + o), m2 = lds64(ad.m2 + o), m3 = lds64(ad.m3 + o), m4 = lds64(ad.m4 + o), mz = lds64(ad.z + k2 * 64 + s * 8);
                const hc H0 = {h0.x, h0.y};
                const hc H1 = hmul(H0, {mz.x, mz.y}), H2 = hmul(H0, {m2.x, m2.y}), H3 = hmul(H2, {m3.x, m3.y}), H4 = hmul(H3, {m4.x, m4.y});
                mma_f16(acc[0], l.x, l.y, l.z, l.w, H0.r, H0.i);
                mma_f16(acc[1], l.x, l.y, l.z, l.w, H1.r, H1.i);
                mma_f16(acc[2], l.x, l.y, l.z, l.w, H2.r, H2.i);
                mma_f16(acc[3], l.x, l.y, l.z, l.w, H3.r, H3.i);
                mma_f16(acc[4], l.x, l.y, l.z, l.w, H4.r, H4.i);
            }
        }
        KSTAMP(2 + 2 * bb);
        if (bb == 0) half_done();
    }
    __syncwarp();
    main_done();
    KSTAMP(5);
#pragma unroll
    for (int i = 0; i < 4; i++) sts128(tab + 2048 + 512 * i + 16 * lane, 0, 0, 0, 0);
    if (lane < 15) sts32(tab + 4 * lane, 0);
    __syncwarp();
    const uint32_t d0 = tab + T_DENSE + 4 + 8 * lane, src = (lane + 31) & 31;
    const uint32_t p0 = pack_bf16(fmaf(k0, dt2, skip), 0.f);
    uint32_t prev = p0;
#pragma unroll
    for (int i = 0; i < 4; i++) {
        const uint32_t pk = pack_bf16(acc[i >> 1][2 * (i & 1) + 1] * scale_inv, acc[i >> 1][2 * (i & 1)] * scale_inv);
        sts64(d0 + 256 * i, __byte_perm(pk, __shfl_sync(0xffffffffu, lane == 31 ? prev : pk, src), 0x5432), pk);
        prev = pk;
    }
    const uint32_t w0 = pack_bf16(acc[2][0] * scale_inv, acc[2][1] * scale_inv), w1 = pack_bf16(acc[2][2] * scale_inv, acc[2][3] * scale_inv);
    const uint32_t sa = (lane & 1) ? 0x5410u : 0x5454u, sb2 = (lane & 1) ? 0x1010u : 0x5410u;
#pragma unroll
    for (int hf = 0; hf < 2; hf++) {
        const uint32_t w = hf ? w1 : w0;
        const uint32_t pv = __shfl_sync(0xffffffffu, lane != 31 ? w : hf ? w0 : __byte_perm(prev, w1, 0x5410), src);
        sts64(d0 + 1024 + 256 * hf, __byte_perm(w, pv, sa), __byte_perm(w, pv, sb2));
        sts64(d0 + 1536 + 256 * hf, __byte_perm(w, pv, sa + 0x2222u), __byte_perm(w, pv, sb2 + 0x2222u));
    }
    const uint32_t d3 = tab + T_R2 + 160 + 320 * (t & 1) + 16 * (g >> 1) + 8 * (g & 1) + 4 * (t >> 1), d3n = d3 + (g >= 6 ? 32 : 0);
    const uint32_t d4 = tab + T_R3 + 80 + 160 * t + 4 * g, d4n = d4 + (g >= 6 ? 16 : 0);
    uint32_t p3;
#pragma unroll
    for (int hf = 0; hf < 2; hf++)
#pragma unroll
        for (int e = 0; e < 2; e++) {
            const float v3 = acc[3][2 * hf + e] * scale_inv;
            const uint32_t p4 = pack_bf16(acc[4][2 * hf + e] * scale_inv, 0.f);
            p3 = pack_bf16(v3, v3);
            sts16(d3 + 64 * hf + 160 * e, p3);
            sts16((hf ? d3n : d3) + 64 * hf + 160 * e + 18, p3);
            sts16(d4 + 32 * hf + 80 * e, p4);
            sts16((hf ? d4n : d4) + 32 * hf + 80 * e + 10, p4);
        }
    if (lane == 31) {
        const uint32_t k512 = __byte_perm(w1, 0, 0x3232);
        sts32(tab + T_DENSE, p0);
        sts64(tab + T_DENSE + 4 * 513, k512, k512); sts16(tab + T_DENSE + 4 * 515 + 2, k512);
        sts16(tab + T_PATCH + 4 * 17, p3); sts32(tab + T_PATCH + 4 * 18, p3); sts16(tab + T_PATCH + 4 * 19 + 2, p3);
    }
    __syncwarp();
}

__device__ __forceinline__ void load_toep(uint32_t* a, uint32_t p, uint32_t pz) {
    a[0] = lds32(p); a[1] = lds32(p + 32); a[2] = lds32(pz - 32); a[3] = lds32(pz);
}
#define DENSE_BLK 4
__device__ __forceinline__ void dense_step(float (&acc)[16][4], uint32_t (&R)[8][4], const uint32_t (&A)[4][4], uint32_t (&An)[4][4],
                                           uint32_t va, uint32_t vmin, uint32_t pn, uint32_t pz, uint32_t zero, int bit) {
#pragma unroll
    for (int i0 = 0; i0 < 8; i0 += DENSE_BLK) {
#pragma unroll 1
        do {
#pragma unroll
            for (int i = i0; i < i0 + DENSE_BLK; i++) {
                const int ip = (i - DENSE_BLK) & 7;
                ldsm4(R[ip], ip == 0 ? max(va - 16, vmin) : va + ip * 128 - (i0 ? 16 : 0));
                if ((i & 1) == 0) load_toep(An[i >> 1], pn + (i >> 1) * 512, pz + (i >> 1) * 512);
#pragma unroll
                for (int ka = 0; ka < 4; ka++) {
                    mma_v(acc[i + ka], A[ka], R[i][0], R[i][1]);
                    if (i + 8 + ka < 16) mma_v(acc[i + 8 + ka], A[ka], R[i][2], R[i][3]);
                }
            }
        } while (zero & (1u << (bit + i0)));
    }
}
struct DenseTaps {
    uint32_t A[4][4], E[4], F[4], e8[2], f8[2];
    __device__ __forceinline__ DenseTaps(uint32_t pb, uint32_t pz) {
        constexpr int PP = T_PATCH - T_DENSE + 56;
#pragma unroll
        for (int i = 0; i < 4; i++) load_toep(A[i], pb + 512 * i, pz + 512 * i);
        load_toep(E, pb + 2048, pz + 2048);
        load_toep(F, pb + PP, pz + PP);
        e8[0] = lds32(pz + 2048 + 32); e8[1] = lds32(pb + 2048 + 64);
        f8[0] = lds32(pz + PP + 32); f8[1] = lds32(pb + PP + 64);
    }
};
__device__ __forceinline__ void dense_phase(float (&acc)[16][4], uint32_t vrow, uint32_t pb, DenseTaps& tp, uint32_t zero, int lane) {
    uint32_t R[8][4], A1[4][4];
    const uint32_t vmin = vrow + ((lane >> 3) & 1) * VT_PLANE - 16 + zero;
    uint32_t va = vmin + 16 + (lane >> 4) * 1024 + (lane & 7) * 16, pz = pb + zero;
    {
        uint32_t H[3][4];
#pragma unroll
        for (int i = 0; i < 3; i++) ldsm4(H[i], vrow + VT_PLANE - 16 + lane * 16 + i * 512);
#pragma unroll
        for (int i = 0; i < 8; i++) ldsm4(R[i], va + i * 128);
#pragma unroll
        for (int i = 0; i < 12; i++) mma_bf16_k8(acc[i + 4], tp.e8[0], tp.e8[1], H[i >> 2][i & 3]);
#pragma unroll
        for (int i = 0; i < 8; i++) mma_bf16_k8(acc[i + 8], tp.f8[0], tp.f8[1], H[i >> 2][i & 3]);
#pragma unroll
        for (int i = 0; i < 12; i++) mma_v(acc[i + 4], tp.E, R[i & 7][2 * (i >> 3)], R[i & 7][2 * (i >> 3) + 1]);
#pragma unroll
        for (int i = 0; i < 8; i++) mma_v(acc[i + 8], tp.F, R[i][0], R[i][1]);
    }
#pragma unroll 1
    for (int rho = 0; rho < 8; rho += 2) {
        dense_step(acc, R, tp.A, A1, va, vmin, pb + 64, pz + 64, zero, 0);
        dense_step(acc, R, A1, tp.A, va - 16, vmin, pb + 128, pz + 128, zero, 8);
        pb += 128; pz += 128; va -= 32;
    }
}
__device__ __forceinline__ uint32_t ones2(int c, int lo, int hi) {
    return (((uint32_t)(c - lo) <= (uint32_t)(hi - lo)) ? 0x3f80u : 0u) | (((uint32_t)(c + 1 - lo) <= (uint32_t)(hi - lo)) ? 0x3f800000u : 0u);
}
struct Boxes {
    uint32_t q[4], ha[2];
    __device__ __forceinline__ Boxes(uint32_t vrow, int lane, int O, int L1, int H1, int L2, int H2) {
        const int g = lane >> 2, t = lane & 3, d = 2 * t - g;
        q[0] = ones2(d, L1, H1); q[1] = ones2(d, L2, H2); q[2] = ones2(d + 8, L1, H1); q[3] = ones2(d + 8, L2, H2);
#pragma unroll
        for (int i = 0; i < 2; i++) { ha[i] = vrow + 16 * g + tok_off(O + 8 * i + 2 * t); pin(ha[i]); pin(q[i]); pin(q[2 + i]); }
    }
    __device__ __forceinline__ uint32_t any() const { return (q[0] | q[1] | q[2]) | (q[3] | ha[0] | ha[1]); }
    __device__ __forceinline__ void load(int j, uint32_t* v, uint32_t zero) const {
        const uint32_t o = j * 128;
        v[0] = lds32(ha[0] + o); v[1] = lds32(ha[1] + zero + o); v[2] = lds32(ha[1] + o);
        v[3] = lds32(ha[0] + zero + o + 16); v[4] = lds32(ha[0] + o + 16); v[5] = lds32(ha[1] + o + 16);
    }
    __device__ __forceinline__ void sums(const uint32_t* v, float* Z, float* X, float* Y) const {
        mma_bf16_z(Z, q[0], q[1], q[2], q[3], v[0], v[1]);
        mma_bf16_z(X, q[0], q[1], q[2], q[3], v[2], v[3]);
        mma_bf16_z(Y, q[0], q[1], q[2], q[3], v[4], v[5]);
    }
};
template <class After>
__device__ __forceinline__ void tail_phase(float (&acc)[16][4], const Boxes& b2, const Boxes& b3, uint32_t tp2, uint32_t tp3, uint32_t zero, After after) {
    uint2 tp[10];
    uint32_t v[6], a0[4], a1[4];
    float Z[4], X[4], Y[4];
    b2.load(0, v, zero);
#pragma unroll
    for (int i = 0; i < 5; i++) { const uint4 c = lds128(tp2 + 160 * i); tp[i] = make_uint2(c.x, c.y); tp[5 + i] = make_uint2(c.z, c.w); }
#pragma unroll
    for (int j = -1; j < 20; j++) {
        if (j < 19) {
            (j < 11 ? b2 : b3).sums(v, Z, X, Y);
            if (j < 10) b2.load(j + 2, v, zero); else if (j < 18) b3.load(j - 10, v, zero);
        }
        if (j >= 0 && j < 12) {
#pragma unroll
            for (int b = 0; b < 5; b++) if (j + 4 + b < 16) mma_v(acc[j + 4 + b], a1, tp[5 + b].x, tp[5 + b].y);
        }
        if (j < 11) { a1[0] = pack_v(Z[0], Z[1]); a1[1] = pack_w(X[0], X[1]); a1[2] = pack_v(Z[2], Z[3]); a1[3] = pack_w(X[2], X[3]); }
        if (j >= 0 && j < 12) {
#pragma unroll
            for (int b = 0; b < 5; b++) if (j + 4 + b < 16) mma_v(acc[j + 4 + b], a0, tp[b].x, tp[b].y);
            if (j >= 7 && j < 11) { tp[11 - j] = lds64(tp3 + 80 * (10 - j)); tp[16 - j] = lds64(tp3 + 80 * (14 - j)); }
        } else if (j >= 12) {
#pragma unroll
            for (int b = 0; b < 8; b++) if (j - 4 + b < 16) mma_v(acc[j - 4 + b], a0, tp[b < 4 ? b + 1 : b + 2].x, tp[b < 4 ? b + 1 : b + 2].y);
        }
        if (j < 11) { a0[0] = pack_v(X[0], X[1]); a0[1] = pack_v(Y[0], Y[1]); a0[2] = pack_v(X[2], X[3]); a0[3] = pack_v(Y[2], Y[3]); }
        else if (j < 19) { a0[0] = pack_v(X[0], X[1]); a0[1] = pack_v(Y[0], Y[1]); a0[2] = pack_v(Z[2], Z[3]); a0[3] = pack_v(X[2], X[3]); }
        after(j);
    }
}
template <int G>
__device__ __forceinline__ void emit(const float (&acc)[16][4], int h, uint32_t own, uint32_t peer, uint32_t bar, uint32_t bar_peer) {
#pragma unroll
    for (int o = 0; o < 2; o++)
#pragma unroll
        for (int hf = 0; hf < 2; hf++) {
            const int n = 8 * G + 4 * o;
            asm volatile("{ .reg .pred p; setp.eq.u32 p, %7, %8;\n\t@p st.shared.v4.u32 [%0], {%1,%2,%3,%4};\n\t"
                         "@!p st.async.weak.shared::cluster.mbarrier::complete_tx::bytes.v4.b32 [%5], {%1,%2,%3,%4}, [%6]; }"
                         ::"r"(own + G * 16384 + hf * 512), "r"(pack_bf16(acc[n][2 * hf], acc[n][2 * hf + 1])), "r"(pack_bf16(acc[n + 1][2 * hf], acc[n + 1][2 * hf + 1])),
                         "r"(pack_bf16(acc[n + 2][2 * hf], acc[n + 2][2 * hf + 1])), "r"(pack_bf16(acc[n + 3][2 * hf], acc[n + 3][2 * hf + 1])),
                         "r"(peer + G * 16384 + hf * 512), "r"(bar_peer + 8 * G), "r"(h), "r"(o) : "memory");
        }
    __syncwarp();
    if (elect_one()) mbar_arrive(bar + 8 * G);
}
__device__ __forceinline__ void finish(uint32_t src, uint32_t xa) {
    uint32_t s[4][4];
    uint4 x[4];
#pragma unroll
    for (int i = 0; i < 4; i++) {
        ldsm4t(s[i], (src ^ ((i & 1) << 5)) + (i >> 1) * 8192);
        x[i] = lds128((xa ^ ((i >> 1) << 4)) + (i & 1) * 256);
    }
#pragma unroll
    for (int i = 0; i < 4; i++)
        sts128((xa ^ ((i >> 1) << 4)) + (i & 1) * 256, badd2(x[i].x, s[i][0]), badd2(x[i].y, s[i][1]), badd2(x[i].z, s[i][2]), badd2(x[i].w, s[i][3]));
}

__device__ __noinline__ float centred_var(uint32_t rows, float mu, int lane) {
    float var = 0.f;
#pragma unroll 1
    for (int rr = 0; rr < 16; rr++) {
        const float c0 = __shfl_sync(0xffffffffu, mu, rr);
        float c = 0.f;
#pragma unroll 1
        for (int k = 0; k < 16; k++) {
            const uint32_t q = lds32(rows + rr * ROW_PITCH + k * 128 + lane * 4);
            const float d0 = bf_lo(q) - c0, d1 = bf_hi(q) - c0;
            c = fmaf(d0, d0, fmaf(d1, d1, c));
        }
#pragma unroll 1
        for (int o = 16; o; o >>= 1) c += __shfl_xor_sync(0xffffffffu, c, o);
        if ((lane & 15) == rr) var = c * (1.f / DM);
    }
    return var;
}
__device__ __noinline__ float centred_score(uint32_t rows, uint32_t wbuf, uint32_t s0, uint32_t s1, int lane) {
    float sc = 0.f;
#pragma unroll 1
    for (int rr = 0; rr < 16; rr++) {
        const uint32_t t0 = __shfl_sync(0xffffffffu, s0, rr), t1 = __shfl_sync(0xffffffffu, s1, rr);
        float c = 0.f;
#pragma unroll 1
        for (int k = 0; k < 16; k++) {
            const uint32_t xn = normalize2(lds32(rows + rr * ROW_PITCH + k * 128 + lane * 4), t0, t1);
            const uint32_t wq = lds32(wbuf + (k >> 2) * 1024 + (k & 3) * 128 + lane * 4);
            c = fmaf(bf_lo(xn), bf_lo(wq), fmaf(bf_hi(xn), bf_hi(wq), c));
        }
#pragma unroll 1
        for (int o = 16; o; o >>= 1) c += __shfl_xor_sync(0xffffffffu, c, o);
        if ((lane & 15) == rr) sc = c;
    }
    return sc;
}

__global__ void __cluster_dims__(2, 1, 1) __launch_bounds__(NTHR, 1)
fused_kernel(const __grid_constant__ Ptrs p, const __grid_constant__ Maps maps) {
    extern __shared__ __align__(1024) unsigned char smem[];
    const int tid = threadIdx.x, lane = tid & 31, b = blockIdx.x;
    const int dch = 8 * b + (tid >> 5) - 4;
    uint2 la, aim, cre, cim;
    uint32_t ldt16, dsk16, epoch;
    uint4 wq;
    if ((uint32_t)(tid - 128) < 256u) {
        la = ldg64(p.logA + dch * NMODE + 4 * lane); aim = ldg64(p.Aim + dch * NMODE + 4 * lane);
        cre = ldg64(p.Cre + dch * NMODE + 4 * lane); cim = ldg64(p.Cim + dch * NMODE + 4 * lane);
        ldt16 = ldg16(p.ldt + dch); dsk16 = ldg16(p.dsk + dch);
    }
    if (tid < 128) { wq = ldg128(p.wr + 8 * tid); epoch = ld_relaxed_32(&p.sc->epoch); }
    const uint32_t sb = s_u32(smem);
    const int warp = __shfl_sync(0xffffffffu, tid >> 5, 0);
    const int h = b & 1, cl = b >> 1;
    const uint32_t bar0 = sb + OFF_BAR;
    const int m = lane >> 3, r = lane & 7, g = lane >> 2, t = lane & 3;
    const bool has_gu = b < GU_CTAS;
    if (warp == 4) { STAMP(0); GSTAMP(24); }

    if (warp >= 12) {
        asm volatile("setmaxnreg.dec.sync.aligned.u32 24;");
        const int a = warp - 12;
        uint32_t due = now_ns() + ST_T0 + (uint32_t)(128 * a + b) * ST_PER / 128;
        const bool el = elect_one();
        if (a == 1 && el) {
#pragma unroll
            for (int j = 0; j < 4; j++) mbar_init(bar0 + 8 * (B_ROW + j), 1);
            asm volatile("fence.mbarrier_init.release.cluster;" ::: "memory");
            fence_async();
#pragma unroll 1
            for (int j = 0; j < 4; j++) {
                mbar_expect_tx(bar0 + 8 * (B_ROW + j), 8192);
#pragma unroll
                for (int i = 0; i < 4; i++)
                    bulk_g2s(sb + OFF_VT + (4 * j + i) * ROW_PITCH, p.u + (size_t)(16 * b + 4 * j + i) * DM, 2048, bar0 + 8 * (B_ROW + j));
            }
        }
        if (a == 2 && el) {
#pragma unroll
            for (int i = B_XT; i < NBAR; i++) mbar_init(bar0 + 8 * i, i == B_SFREE ? 8 : i == B_UPD ? 4 : (i == B_RECV || i == B_RECV + 1) ? 9 : (i >= B_FREE + 4 && i < B_FREE + 8) ? 2 : 1);
            asm volatile("fence.mbarrier_init.release.cluster;" ::: "memory");
            fence_async();
            mbar_expect_tx(bar0 + 8 * B_XT, 65536);
            mbar_expect_tx(bar0 + 8 * B_RECV, 8192);
            mbar_expect_tx(bar0 + 8 * B_RECV + 8, 8192);
            mbar_expect_tx(bar0 + 8 * B_RED, 512);
        }
        if (a == 3 && el) {
#pragma unroll
            for (int i = 0; i < 5; i++) asm volatile("prefetch.tensormap [%0];" ::"l"(&maps.u + i) : "memory");
        }
        __syncwarp();
        cluster_arrive();
        cluster_wait();
        STAMP(18);
        mbar_wait(bar0 + 8 * (B_ROW + a), 0);
        if (el) {
#pragma unroll
            for (int i = 0; i < 4; i++)
                tma_load_tile(sb + OFF_XT + h * 32768 + a * 4096 + (i & 1) * 16384 + (i >> 1) * 2048, &maps.u, 16 * cl, 4 * a + (i & 2), 16 * (i & 1) + 8 * h, bar0 + 8 * B_XT);
        }
        if (el) {
#pragma unroll 1
            for (int k = has_gu ? 0 : 4; k < 6; k++) {
                const int i = 4 * k + a, s = k < 3 ? i : i - 12;
#pragma unroll 1
                for (int left; (left = (int)(due - now_ns())) > 0;) __nanosleep(left >> 1);
                due += k == 0 ? 4 * ST_PER + ST_GAP : k < 3 ? 4 * ST_PER : 4 * ST_PER2;
                const bool scr = (0xcf0 >> s) & 1, again = k >= 3 && has_gu, mid = (s >> 2) == 1;
                if (scr || again) mbar_wait(bar0 + 8 * (B_FREE + s), scr && again);
                const uint32_t dst = sb + (mid ? OFF_PRIV + 4096 + a * 16384 : OFF_RING + (s >> 3) * 32768 + a * 8192), bar = bar0 + 8 * (B_FULL + s);
                if (k < 4) {
                    mbar_expect_tx(bar, 8192);
                    tma_load_2d(dst, &maps.wg, 64 * cl, 512 * h + 32 * i, bar);
                    tma_load_2d(dst + 4096, &maps.wu, 64 * cl, 512 * h + 32 * i, bar);
                } else {
                    mbar_expect_tx(bar, 7168);
                    tma_load_2d(dst, &maps.wd, 16 * cl, 1792 * h + 448 * a + 224 * (k & 1), bar);
                }
            }
            STAMP(19);
        }
    } else if (warp >= 4) {
        const int w = warp - 4;
        cluster_arrive();
        asm volatile("setmaxnreg.inc.sync.aligned.u32 168;");
        const uint32_t vrow = sb + OFF_VT + w * VT_PITCH + VT_PAD, tab = sb + tab_off(w);
        const uint32_t so = sb + OFF_XT + (8 * h + w) * 1024 + ((lane ^ ((w & 1) << 1)) << 4);
        uint32_t dst0 = so + (h ^ 1) * 32768;
        const uint32_t rb0 = bar0 + 8 * B_RECV, rb1 = mapa(rb0, h ^ 1);
        const uint32_t box = sb + OFF_XT + h * 32768 + w * 2048;
        uint32_t fs = sb + OFF_XT + (h ^ 1) * 32768 + (2 * m + (r & 1)) * 1024 + (w >> 2) * 512 + (((8 * (w & 3) + (r & 4) + ((r >> 1) & 1)) ^ ((r & 1) << 1)) << 4);
        uint32_t fx = box + (g >> 1) * 512 + (t >> 1) * 144 + (2 * (t & 1) + (g & 1)) * 32;
        uint32_t tpo = 80 + (g - 2 * t) * 8 - (g < 2 * t ? 16 : 0);
        uint32_t xa = sb + OFF_XT + (w & 2) * 16384 + (w >> 2) * 16384 + (w & 1) * 1024 + (g >> 1) * 2048 + (g & 1) * 128 + t * 32 + ((h ^ (g & 1)) << 4);
        uint32_t va = sb + OFF_VT + (2 * m + (r & 1)) * VT_PITCH + VT_PAD + (16 * w + (r >> 1)) * 16;
        uint32_t qa = sb + OFF_ST + 2048 * w + 128 * t + 16 * (g ^ (2 * t));
        pin(dst0); pin(fs); pin(fx); pin(tpo); pin(xa); pin(va); pin(qa);
        const Boxes b2(vrow, lane, -18, 5, 7, 0, 4), b3(vrow, lane, -20, 1, 7, 0, 8);
        const KgenAddr ka(sb + OFF_PRIV + w * 8192, lane);
        if (__any_sync(0xffffffffu, ((dst0 | fs) | (fx | tpo | xa) | (va | qa) | (b2.any() | b3.any() | ka.any())) & p.zero)) __trap();
        cluster_wait();
        pin(la.x); pin(la.y); pin(aim.x); pin(aim.y); pin(cre.x); pin(cre.y); pin(cim.x); pin(cim.y); pin(ldt16); pin(dsk16);
        kgen(ka, tab, lane, la, aim, cre, cim, bf_round(ex2f(bf_lo(ldt16) * 1.4426950408889634f)), 1.f + bf_lo(dsk16), dch, [&]() {
            STAMP(21);
            if (elect_one()) mbar_arrive(bar0 + 8 * (B_FREE + 4 + (w >> 1)));
        }, [&]() {
            if ((LN_PAUSE >> w) & 1) mbar_wait(bar0 + 8 * B_LN, 0);
        });
        STAMP(1); KSTAMP(6);
        const uint32_t pb = tab + T_DENSE + (g - 2 * t) * 4;
        DenseTaps dt(pb, pb + p.zero);
        {
            uint4 q[4], x[8];
            mbar_wait(bar0 + 8 * B_XT, 0);
#pragma unroll
            for (int i = 0; i < 8; i++) x[i] = lds128(xa + (i & 1) * 8192 + (i >> 1) * 256);
            STAMP(47);
            mbar_wait(bar0 + 8 * (B_ST + w), 0);
#pragma unroll
            for (int n = 0; n < 4; n++) q[n] = lds128(qa + 512 * n);
            if (lane < 4) sts128(vrow - VT_PAD + (lane >> 1) * VT_PLANE + (lane & 1) * 16, 0, 0, 0, 0);
            STAMP(2); GSTAMP(28);
#pragma unroll
            for (int i = 0; i < 8; i++) {
                const uint32_t s0 = (i & 1) ? q[i >> 1].z : q[i >> 1].x, s1 = (i & 1) ? q[i >> 1].w : q[i >> 1].y;
                stsm4t(va + (i >> 1) * 64 + (i & 1) * VT_PLANE, normalize2(x[i].x, s0, s1), normalize2(x[i].y, s0, s1),
                       normalize2(x[i].z, s0, s1), normalize2(x[i].w, s0, s1));
            }
            named_sync(2, 256);
            if (elect_one()) {
                if (w < 3) mbar_arrive(bar0 + 8 * (w == 2 ? B_V : B_FREE + 10 + w));
            }
        }
        STAMP(3); KSTAMP(7);
        float acc[16][4];
#pragma unroll
        for (int i = 0; i < 16; i++) { acc[i][0] = acc[i][1] = acc[i][2] = acc[i][3] = 0.f; }
        dense_phase(acc, vrow, pb, dt, p.zero, lane);
        STAMP(4); KSTAMP(8);
        const uint32_t dst1 = mapa(dst0 + (h ? 32768 : -32768), h ^ 1);
        tail_phase(acc, b2, b3, tab + T_R2 + 2 * tpo, tab + T_R3 + tpo, p.zero, [&](int j) {
            if (j == 3) {
                mbar_wait(bar0 + 8 * B_SFREE, 0);
                emit<0>(acc, h, dst0, dst1, rb0, rb1);
                STAMP(5);
            }
            if (j == 7) {
                mbar_wait(bar0 + 8 * B_RECV, 0);
                finish(fs, fx);
                fence_async();
                __syncwarp();
                if (elect_one()) tma_store_tile(&maps.out, box, 16 * cl, 2 * w, 8 * h);
                STAMP(20);
            }
        });
        emit<1>(acc, h, dst0, dst1, rb0, rb1);
        STAMP(30);
        mbar_wait(bar0 + 8 * (B_RECV + 1), 0);
        STAMP(6);
        finish(fs + 16384, fx + 16384);
        const bool ready = mbar_test(bar0 + 8 * B_UPD, 0);
        const bool el = elect_one();
#pragma unroll 1
        for (int pass = 0; pass < 2; pass++) {
            if ((pass != 0) == ready) {
                fence_async();
                __syncwarp();
                if (el) tma_store_tile(&maps.out, box + 16384, 16 * cl, 2 * w, 16 + 8 * h);
            } else {
                if (el) asm volatile("cp.async.bulk.wait_group 0;" ::: "memory");
                __syncwarp();
                mbar_wait(bar0 + 8 * B_UPD, 0);
                const int tok = 2047 - (int)(lds32(sb + OFF_MISC + 48 + 8 * g) & 2047);
                if ((((tok >> 6) & 8) | ((tok >> 1) & 7)) == 8 * h + w) {
                    const uint32_t xa = box + (tok >> 10) * 16384 + ((tok >> 6) & 7) * 256 + (tok & 1) * 128 + ((tok >> 4) & 3) * 32 + (((t >> 1) ^ (tok & 1)) << 4) + (t & 1) * 8;
                    const uint2 o0 = lds64(xa);
                    const float4 up = lds128f(sb + tab_off(g) + T_RED + 16 * t);
                    const uint2 o1 = make_uint2(badd2(o0.x, pack_bf16(up.x, up.y)), badd2(o0.y, pack_bf16(up.z, up.w)));
                    if (ready && tok >= 1024) sts64(xa, o1.x, o1.y);
                    else *reinterpret_cast<uint2*>(p.out + (size_t)tok * DM + 16 * cl + 4 * t) = o1;
                }
            }
        }
        if (el) asm volatile("cp.async.bulk.wait_group.read 0;" ::: "memory");
        STAMP(7);
    } else {
        const int a = warp;
        cluster_arrive();
        asm volatile("setmaxnreg.inc.sync.aligned.u32 152;");
        const uint32_t tag = __shfl_sync(0xffffffffu, epoch, 0) + 1u, misc = sb + OFF_MISC, abar = bar0 + 8 * (B_AUX + a);
        uint32_t aph = 0;
        const Exchange* in = &p.sc->x[cl & (NREP - 1)];
        uint2* pub = p.sc->x[m >> 1].stat + 16 * b + 2 * (r ^ (2 * (b & 3))) + (m & 1);
        uint32_t* cnt_s = &p.sc->x[t].n_stat[b & 96];
        pin(pub); pin(cnt_s);
        if (tid < 64) sts32(sb + OFF_XCH + 4 * tid, 0);
        const uint32_t wbuf = sb + OFF_LN + a * 1024, part = sb + OFF_LN + 4096;
        {
            sts128(wbuf + 16 * lane, wq.x, wq.y, wq.z, wq.w);
            sts128(wbuf + 512 + 16 * lane, 0x3f803f80u, 0x3f803f80u, 0x3f803f80u, 0x3f803f80u);
            float wsum = ((bf_lo(wq.x) + bf_hi(wq.x)) + (bf_lo(wq.y) + bf_hi(wq.y))) + ((bf_lo(wq.z) + bf_hi(wq.z)) + (bf_lo(wq.w) + bf_hi(wq.w)));
#pragma unroll
            for (int o = 16; o; o >>= 1) wsum += __shfl_xor_sync(0xffffffffu, wsum, o);
            sts32f(part + 1024 + 4 * a, wsum);
            uint32_t wf[4][4];
#pragma unroll
            for (int i = 0; i < 4; i++) ldsm4(wf[i], wbuf + ((uint32_t)(r - 1) < 2u ? 16 * (r - 1) : 512) + 32 * m + 128 * i);
            uint32_t ra = sb + OFF_VT + r * ROW_PITCH + 512 * a + 16 * m, pa = part + a * 256 + g * 16;
            cluster_wait();
            STAMP(22);
#pragma unroll 1
            for (int hf = 0; hf < 2; hf++) {
                mbar_wait(bar0 + 8 * B_ROW + 16 * hf, 0);
                mbar_wait(bar0 + 8 * B_ROW + 16 * hf + 8, 0);
                STAMP(23);
                uint32_t x[8][4];
                float cs[2][4], q[8][4];
#pragma unroll
                for (int i = 0; i < 40; i++) (i < 8 ? cs[i >> 2 & 1] : q[(i - 8) >> 2 & 7])[i & 3] = 0.f;
#pragma unroll
                for (int k = 0; k < 8; k++) ldsm4(x[k], ra + k * 64);
                const bool more = __any_sync(0xffffffffu, after_all(x, p.zero));
#pragma unroll 1
                do {
#pragma unroll
                    for (int k = 0; k < 8; k++) {
                        mma_v(cs[k & 1], x[k], wf[k >> 1][2 * (k & 1)], wf[k >> 1][2 * (k & 1) + 1]);
#pragma unroll
                        for (int i = 0; i < 4; i++) mma_bf16_k8(q[4 * (k & 1) + i], x[k][i & 2], x[k][i | 1], x[k][i]);
                    }
                } while (more);
                const float c2 = cs[0][2] + cs[1][2];
                if (t == 0) sts64f(pa, (cs[0][0] + cs[1][0]) + c2, cs[0][1] + cs[1][1]);
                if (t == 1) sts32f(pa + 12, c2);
                const float e0 = ((q[0][0] + q[2][0]) + (q[4][0] + q[6][0])) + ((q[1][2] + q[3][2]) + (q[5][2] + q[7][2]));
                const float e1 = ((q[0][1] + q[2][1]) + (q[4][1] + q[6][1])) + ((q[1][3] + q[3][3]) + (q[5][3] + q[7][3]));
                if (t == (g >> 1)) sts32f(pa + 8, (g & 1) ? e1 : e0);
                ra += 8 * ROW_PITCH; pa += 128;
            }
        }
        STAMP(31);
        named_sync(1, 128);
        if (a == 0) {
            const uint32_t pa = part + (lane & 15) * 16;
            const float4 p0 = lds128f(pa), p1 = lds128f(pa + 256), p2 = lds128f(pa + 512), p3 = lds128f(pa + 768), ws = lds128f(part + 1024);
            const float mu = ((p0.x + p1.x) + (p2.x + p3.x)) * (1.f / DM);
            float var = ((p0.z + p1.z) + (p2.z + p3.z)) * (1.f / DM) - mu * mu;
            const bool centred = __any_sync(0xffffffffu, !(mu * mu <= 4.f * var));
            if (centred) var = centred_var(sb + OFF_VT, mu, lane);
            const float ri = rcpf(bf_round(sqrtaf(bf_round(bf_round(var) + 1e-5f))));
            const uint32_t s0 = pack_bf16(mu, ri), s1 = (pack_bf16(ri - bf_hi(s0), 0.f) & 0xfffcu) | (tag & 3);
            float sc = ((((p0.y + p1.y) + (p2.y + p3.y)) + ((p0.w + p1.w) + (p2.w + p3.w))) - bf_lo(s0) * ((ws.x + ws.y) + (ws.z + ws.w))) * ri;
            if (centred) sc = centred_score(sb + OFF_VT, sb + OFF_LN, s0, s1, lane);
            const uint32_t sb16 = pack_bf16(0.f, sc);
            const uint32_t s2 = s1 | (sb16 ^ (((uint32_t)((int)sb16 >> 31) & 0x7fff0000u) | 0x80000000u));
            st_relaxed_64(pub, s0, s2);
            st_relaxed_64(pub + 2 * sizeof(Exchange) / 8, s0, s2);
            if (lane < NREP) red_add(cnt_s, 1);
            if (elect_one()) mbar_arrive(bar0 + 8 * B_LN);
            STAMP(9); GSTAMP(25);
        }
        const uint32_t slot0 = sb + OFF_RING + a * 8192, slot1 = sb + OFF_PRIV + a * 16384 + 4096, fbar = bar0 + 8 * (B_FULL + a);
        uint32_t mine = 0, row[2] = {0, 0};
        {
            uint32_t q[16];
            named_sync(1, 128);
            wait_count(&in->n_stat[32 * a], 32 * tag - FEW_ST);
            STAMP(41);
#pragma unroll 1
            for (uint32_t it = 0;; spin_guard(it)) {
                if (elect_one()) {
                    mbar_expect_tx(abar, 4096);
                    bulk_g2s(sb + OFF_ST + 4096 * a, in->stat + 512 * a, 4096, abar);
                }
                mbar_wait(abar, aph);
                aph ^= 1;
                uint32_t bad = 0;
#pragma unroll
                for (int n = 0; n < 8; n++) {
                    const uint4 u = lds128v(sb + OFF_ST + 4096 * a + 512 * n + 16 * lane);
                    q[2 * n] = u.y; q[2 * n + 1] = u.w;
                    bad = or_xor(bad, u.y, tag);
                }
                const bool ok = __all_sync(0xffffffffu, (bad & 3) == 0);
                asm volatile("{ .reg .pred p; setp.ne.u32 p, %1, 0; @p mbarrier.arrive.shared::cta.b64 _, [%0]; }" ::"r"(bar0 + 8 * B_ST + 16 * a + 8 * lane), "r"((uint32_t)(ok && lane < 2)) : "memory");
                if (ok) break;
            }
            STAMP(8);
            const uint32_t inv = 2047 - 512 * a - 16 * m - (r ^ (2 * m));
#pragma unroll
            for (int i = 0; i < 16; i++) asm("lop3.b32 %0, %0, %1, %2, 0x9b;" : "+r"(q[i]) : "r"(inv), "r"(0xffff0000u | (64 * (i >> 1) + 8 * (i & 1))));
            auto below = [&](uint32_t x) {
                uint32_t d[4];
#pragma unroll
                for (int i = 0; i < 16; i++) d[i & 3] = i < 4 ? x + q[i] : min(d[i & 3], x + q[i]);
                d[0] = min(min(d[0], d[1]), min(d[2], d[3]));
                return d[0] < x ? x - 1 - d[0] : 0u;
            };
            const uint32_t mx0 = ~min(min(min(min(q[0], q[1]), min(q[2], q[3])), min(min(q[4], q[5]), min(q[6], q[7]))),
                                      min(min(min(q[8], q[9]), min(q[10], q[11])), min(min(q[12], q[13]), min(q[14], q[15]))));
            const uint32_t gm = min(__reduce_max_sync(0xffffffffu, lane < 16 ? mx0 : 0u), __reduce_max_sync(0xffffffffu, lane < 16 ? 0u : mx0));
            if (lane == 0) sts32(misc + 16 + 4 * a, gm);
            named_sync(1, 128);
            STAMP(42);
            if (b == 0 && tid == 0) st_relaxed_32(&p.sc->epoch, tag);
            const uint4 t0 = lds128(misc + 16);
            uint32_t tau = min(min(t0.x, t0.y), min(t0.z, t0.w));
            uint32_t mx = mx0, cnt = 0, bal;
            const uint32_t list = sb + OFF_XCH + 64 * a;
#pragma unroll 1
            while ((bal = __ballot_sync(0xffffffffu, mx >= tau)) != 0) {
                const uint32_t pos = cnt + __popc(bal & ((1u << lane) - 1u));
                cnt += __popc(bal);
                if (cnt > 16) break;
                if (mx >= tau) sts32(list + 4 * pos, mx);
                mx = below(mx);
            }
            if (cnt > 16) {
                mx = mx0;
#pragma unroll 1
                for (int j = 0; j < 8; j++) {
                    const uint32_t top = __reduce_max_sync(0xffffffffu, mx), nx = below(mx);
                    if (mx == top) { sts32(list + 4 * j, mx); sts32(list + 32 + 4 * j, 0); mx = nx; }
                }
            }
            named_sync(1, 128);
            STAMP(43);
            const uint2 k = lds64(sb + OFF_XCH + 8 * lane);
            uint32_t hi = max(k.x, k.y), lo = min(k.x, k.y);
            mbar_wait(bar0 + 8 * B_V, 0);
#pragma unroll
            for (int j = 0; j < 8; j++) {
                const uint32_t top = __reduce_max_sync(0xffffffffu, hi);
                const bool won = hi == top;
                hi = won ? lo : hi;
                lo = won ? 0u : lo;
                if (g == j) mine = top;
                if (a == (j >> 1)) row[j & 1] = top;
            }
        }
        STAMP(11);
        const int tok = 2047 - (int)(mine & 2047);
        const uint32_t xs = sb + OFF_XT + (h ^ 1) * 32768;
        if (has_gu) {
            if (elect_one()) {
                mbar_expect_tx(abar, 2048);
#pragma unroll
                for (int j = 0; j < 2; j++) bulk_g2s(xs + (2 * a + j) * 1040, p.u + (size_t)(2047 - (row[j] & 2047)) * DM + 512 * h, 1024, abar);
            }
        }
        STAMP(44);
        const uint2 st = ld_relaxed_64(in->stat + (tok & ~15) + 2 * ((tok & 7) ^ ((tok >> 3) & 6)) + ((tok >> 3) & 1));
        if (a == 0 && t == 0) sts64(misc + 48 + 8 * g, mine, __float_as_uint(bf_hi(st.x) + bf_lo(st.y)));
        uint32_t xq[4][4];
        if (a == 0) STAMP(45);
        if (has_gu) {
            mbar_wait(abar, aph);
            aph ^= 1;
            STAMP(46);
            named_sync(1, 128);
#pragma unroll
            for (int j = 0; j < 4; j++) {
                ldsm4(xq[j], xs + r * 1040 + m * 16 + 64 * a + 256 * j);
#pragma unroll
                for (int i = 0; i < 4; i++) xq[j][i] = bsub2_lo(xq[j][i], st.x);
            }
        }
        __syncwarp();
        if (lane < 2) mbar_arrive_peer(mapa(bar0 + 8 * B_SFREE, lane) + (has_gu ? ((xq[0][0] | xq[1][0]) | (xq[2][0] | xq[3][0])) & p.zero : 0u));
        if (has_gu) {
            STAMP(12);
            float gacc[8][4];
#pragma unroll
            for (int i = 0; i < 8; i++) { gacc[i][0] = gacc[i][1] = gacc[i][2] = gacc[i][3] = 0.f; }
            uint4* pubh = &p.sc->x[a].h[b * 32 + lane];
            uint32_t* cnt_h = &p.sc->x[a].n_h[32 * (b / 14) + lane];
            pin(pubh); pin(cnt_h);
            if (elect_one()) mbar_expect_tx(abar, 512);
            uint32_t ko[8];
#pragma unroll
            for (int mt = 0; mt < 8; mt++) ko[mt] = (m & 1) * 4096 + (r + ((m >> 1) << 3)) * 128 + ((r ^ (4 * h) ^ mt) << 4);
#pragma unroll
            for (int c = 0; c < 4; c++) {
                if (c == 3) mbar_wait(bar0 + 8 * B_SFREE, 0);
                mbar_wait(fbar + 32 * (c % 3), c / 3);
                STAMP(36 + c);
                uint32_t af[16][4];
#pragma unroll
                for (int i = 0; i < 16; i++) ldsm4t(af[i], (c == 1 ? slot1 : slot0 + (c == 2) * 32768) + ko[i & 7] + (i >> 3) * 2048);
                __syncwarp();
                if (c < 3 && elect_one()) { if (c == 1) mbar_arrive2(bar0 + 8 * (B_FREE + 4 + a)); else mbar_arrive(bar0 + 8 * (B_FREE + 4 * c + a)); }
                xq[c][0] |= after_all(af, p.zero);
#pragma unroll 1
                do {
#pragma unroll
                    for (int i = 0; i < 16; i++) mma_v(gacc[i & 7], af[i], xq[c][2 * (i >> 3)], xq[c][2 * (i >> 3) + 1]);
                } while (p.zero & (1u << c));
                STAMP(52 + c);
            }
            STAMP(13);
#pragma unroll
            for (int mt = 0; mt < 8; mt++) sts128f(slot0 + mt * 512 + lane * 16, gacc[mt]);
            named_sync(1, 128);
            const uint32_t base = sb + OFF_RING + 16 * tid;
            {
                const float4 p0 = lds128f(base + 2048), p1 = lds128f(base + 10240), p2 = lds128f(base + 18432), p3 = lds128f(base + 26624);
                st_async128(mapa(sb + OFF_XCH + 16 * tid, h ^ 1), __float_as_uint((p0.x + p1.x) + (p2.x + p3.x)), __float_as_uint((p0.y + p1.y) + (p2.y + p3.y)),
                            __float_as_uint((p0.z + p1.z) + (p2.z + p3.z)), __float_as_uint((p0.w + p1.w) + (p2.w + p3.w)), mapa(abar, h ^ 1));
            }
            STAMP(56);
            const float4 p0 = lds128f(base), p1 = lds128f(base + 8192), p2 = lds128f(base + 16384), p3 = lds128f(base + 24576);
            const float r0 = lds32f(misc + 52 + 16 * t), r1 = lds32f(misc + 60 + 16 * t);
            const float4 own = make_float4((p0.x + p1.x) + (p2.x + p3.x), (p0.y + p1.y) + (p2.y + p3.y), (p0.z + p1.z) + (p2.z + p3.z), (p0.w + p1.w) + (p2.w + p3.w));
            mbar_wait(abar, aph);
            aph ^= 1;
            STAMP(57);
            const float4 oth = lds128f(sb + OFF_XCH + 16 * tid);
            const float g0 = bf_round((own.x + oth.x) * r0), g1 = bf_round((own.y + oth.y) * r1);
            const float h0 = bf_round(g0 * rcpf(1.f + ex2f(-1.4426950408889634f * g0))) * bf_round((own.z + oth.z) * r0);
            const float h1 = bf_round(g1 * rcpf(1.f + ex2f(-1.4426950408889634f * g1))) * bf_round((own.w + oth.w) * r1);
            uint32_t hw;
            asm volatile("movmatrix.sync.aligned.m8n8.trans.b16 %0, %1;" : "=r"(hw) : "r"(pack_bf16(h0, h1)));
            sts32(sb + OFF_RING + 7168 + 16 * lane + 4 * a, hw);
            STAMP(58);
            named_sync(1, 128);
            const uint4 q = lds128(sb + OFF_RING + 7168 + 16 * lane);
            st_relaxed_128(pubh, q.x, q.y, q.z, (q.w & ~1u) | (tag & 1));
            if (lane == 0) red_add(cnt_h, 1);
            STAMP(14);
        }
        float dacc[4];
        {
            uint32_t wo = (r + ((m >> 1) << 3)) * 32 + (((m & 1) ^ (r >> 2)) << 4), af[14][4];
            pin(wo);
            float d[7][4];
#pragma unroll
            for (int i = 0; i < 7; i++) { d[i][0] = d[i][1] = d[i][2] = d[i][3] = 0.f; }
            mbar_wait(fbar + 32, has_gu);
#pragma unroll
            for (int j = 0; j < 14; j++) ldsm4t(af[j], slot1 + wo + j * 512);
            wait_count(&in->n_h[32 * (4 * h + a)], 14 * tag - FEW_H);
            STAMP(33);
            uint4 hq[14];
#pragma unroll 1
            for (uint32_t it = 0;; spin_guard(it)) {
                uint32_t bad = 0;
                if (elect_one()) {
                    mbar_expect_tx(abar, 7168);
                    bulk_g2s(slot0, &in->h[(56 * h + 14 * a) * 32], 7168, abar);
                }
                mbar_wait(abar, aph);
                aph ^= 1;
#pragma unroll
                for (int j = 0; j < 14; j++) { hq[j] = lds128(slot0 + 512 * j + 16 * lane); bad = or_xor(bad, hq[j].w, tag); }
                if (__all_sync(0xffffffffu, (bad & 1) == 0)) break;
            }
            STAMP(15);
#pragma unroll
            for (int s = 0; s < 2; s++) {
                if (s) {
                    mbar_wait(fbar + 64, has_gu);
#pragma unroll
                    for (int j = 0; j < 14; j++) ldsm4t(af[j], slot0 + 32768 + wo + j * 512);
                }
                const bool more = __any_sync(0xffffffffu, after_all(af, p.zero));
#pragma unroll 1
                do {
#pragma unroll
                    for (int j = 0; j < 14; j++) {
                        const uint4 q = hq[7 * s + (j >> 1)];
                        mma_v(d[j % 7], af[j], (j & 1) ? q.z : q.x, (j & 1) ? q.w : q.y);
                    }
                } while (more);
            }
#pragma unroll
            for (int j = 0; j < 4; j++) dacc[j] = ((d[0][j] + d[1][j]) + (d[2][j] + d[3][j])) + ((d[4][j] + d[5][j]) + d[6][j]);
        }
        STAMP(16);
        {
            sts128f(slot0 + 7680 + lane * 16, dacc);
            named_sync(1, 128);
            const int tk = tid >> 4, col = tid & 15;
            const uint32_t base = sb + OFF_RING + 7680 + ((col & 7) * 4 + (tk >> 1)) * 16 + (((col >> 3) << 1) + (tk & 1)) * 4;
            const float y0 = (lds32f(base) + lds32f(base + 8192)) + (lds32f(base + 16384) + lds32f(base + 24576));
            const uint32_t red = sb + tab_off(tk) + T_RED + 4 * col, key = lds32(misc + 48 + 8 * tk);
            mbar_wait(bar0 + 8 * B_SFREE, 0);
            asm volatile("st.async.weak.shared::cluster.mbarrier::complete_tx::bytes.f32 [%0], %1, [%2];"
                         ::"r"(mapa(red, h ^ 1)), "f"(y0), "r"(mapa(bar0 + 8 * B_RED, h ^ 1)) : "memory");
            const float rv = __uint_as_float(unorder_key(key >> 16) << 16);
            const float sg = bf_round(rcpf(1.f + ex2f(-1.4426950408889634f * rv)));
            mbar_wait(bar0 + 8 * B_RED, 0);
            sts32f(red, bf_round(y0 + lds32f(red)) * sg);
            __syncwarp();
            if (elect_one()) mbar_arrive(bar0 + 8 * B_UPD);
        }
        STAMP(17); GSTAMP(29);
    }
}

typedef CUresult (*EncodeFn)(CUtensorMap*, CUtensorMapDataType, cuuint32_t, void*, const cuuint64_t*, const cuuint64_t*,
                             const cuuint32_t*, const cuuint32_t*, CUtensorMapInterleave, CUtensorMapSwizzle,
                             CUtensorMapL2promotion, CUtensorMapFloatOOBfill);

void make_map(EncodeFn enc, CUtensorMap* m, const void* ptr, uint64_t cols, uint64_t rows, uint32_t bc, uint32_t br,
              CUtensorMapSwizzle sw, CUtensorMapL2promotion pr) {
    cuuint64_t dims[2] = {cols, rows};
    cuuint64_t str[1] = {cols * 2};
    cuuint32_t box[2] = {bc, br};
    cuuint32_t es[2] = {1, 1};
    enc(m, CU_TENSOR_MAP_DATA_TYPE_BFLOAT16, 2, const_cast<void*>(ptr), dims, str, box, es, CU_TENSOR_MAP_INTERLEAVE_NONE, sw, pr,
        CU_TENSOR_MAP_FLOAT_OOB_FILL_NONE);
}
void make_tile_map(EncodeFn enc, CUtensorMap* m, const void* ptr) {
    cuuint64_t dims[4] = {DM, 4, 16, SEQ / 64};
    cuuint64_t str[3] = {16 * DM * 2, DM * 2, 64 * DM * 2};
    cuuint32_t box[4] = {16, 4, 2, 8};
    cuuint32_t es[4] = {1, 1, 1, 1};
    enc(m, CU_TENSOR_MAP_DATA_TYPE_BFLOAT16, 4, const_cast<void*>(ptr), dims, str, box, es, CU_TENSOR_MAP_INTERLEAVE_NONE,
        CU_TENSOR_MAP_SWIZZLE_32B, CU_TENSOR_MAP_L2_PROMOTION_NONE, CU_TENSOR_MAP_FLOAT_OOB_FILL_NONE);
}

}

#define WD_PROMO CU_TENSOR_MAP_L2_PROMOTION_L2_64B
extern "C" void kernel_launch(void* const* d_in, const int* in_sizes, int n_in, void* d_out, int out_size) {
    (void)in_sizes; (void)n_in; (void)out_size;
    static EncodeFn enc = nullptr;
    static void* scratch = nullptr;
    if (!enc) {
        void* fn = nullptr;
        cudaDriverEntryPointQueryResult q;
        cudaGetDriverEntryPoint("cuTensorMapEncodeTiled", &fn, cudaEnableDefault, &q);
        enc = (EncodeFn)fn;
        cudaGetSymbolAddress(&scratch, g_scratch);
        cudaFuncSetAttribute(fused_kernel, cudaFuncAttributeMaxDynamicSharedMemorySize, SMEM_BYTES);
    }
    Maps maps;
    make_tile_map(enc, &maps.u, d_in[0]);
    make_tile_map(enc, &maps.out, d_out);
    make_map(enc, &maps.wg, d_in[9], FF, DM, 64, 32, CU_TENSOR_MAP_SWIZZLE_128B, CU_TENSOR_MAP_L2_PROMOTION_L2_128B);
    make_map(enc, &maps.wu, d_in[10], FF, DM, 64, 32, CU_TENSOR_MAP_SWIZZLE_128B, CU_TENSOR_MAP_L2_PROMOTION_L2_128B);
    make_map(enc, &maps.wd, d_in[11], DM, FF, 16, 224, CU_TENSOR_MAP_SWIZZLE_32B, WD_PROMO);
    Ptrs p;
    p.sc = (Scratch*)scratch;
    p.u = (const __nv_bfloat16*)d_in[0];
    p.logA = (const __nv_bfloat16*)d_in[1];
    p.Aim = (const __nv_bfloat16*)d_in[2];
    p.Cre = (const __nv_bfloat16*)d_in[3];
    p.Cim = (const __nv_bfloat16*)d_in[4];
    p.ldt = (const __nv_bfloat16*)d_in[5];
    p.dsk = (const __nv_bfloat16*)d_in[6];
    p.wr = (const __nv_bfloat16*)d_in[8];
    p.out = (__nv_bfloat16*)d_out;
    p.zero = 0;
    fused_kernel<<<NCTA, NTHR, SMEM_BYTES, cudaStreamPerThread>>>(p, maps);
}
```

```cpp
#include <cuda_runtime.h>
#include <cuda_bf16.h>
#include <cuda_fp16.h>
#include <cuda.h>
#include <stdint.h>

namespace {

constexpr int SEQ = 2048, DM = 1024, NMODE = 128, FF = 3584;
constexpr int NCTA = 128, NTHR = 512;
constexpr int GU_CTAS = 112;
constexpr int NREP = 4;

constexpr int OFF_XT = 0;
constexpr int OFF_RING = 65536;
constexpr int OFF_PRIV = OFF_RING + 65536;
constexpr int OFF_VT = OFF_PRIV + 65536;
constexpr int VT_PAD = 32, VT_PLANE = VT_PAD + 2048, VT_PITCH = 2 * VT_PLANE, ROW_PITCH = 2064;
constexpr int OFF_BAR = OFF_VT + 8 * VT_PITCH;
constexpr int OFF_MISC = OFF_BAR + 384;
constexpr int OFF_XCH = OFF_MISC + 112;
constexpr int SMEM_BYTES = OFF_XCH + 2048;
constexpr int OFF_LN = OFF_RING + 7 * 8192;
constexpr int OFF_ST = OFF_RING + 6 * 8192;
static_assert(SMEM_BYTES <= 232448, "shared memory");

constexpr int B_ROW = 0, B_XT = 4, B_V = 5, B_LN = 6, B_SFREE = 7, B_RECV = 8, B_RED = 10, B_UPD = 11, B_ST = 12, B_FREE = 20, B_FULL = 32, B_AUX = 44, NBAR = 48;

constexpr int T_DENSE = 60;
constexpr int T_PATCH = 2208;
constexpr int T_R2 = 2368;
constexpr int T_R3 = 3296;

constexpr int T_RED = 4032;
__device__ __forceinline__ bool slot_priv(int s) { return (uint32_t)(s - 6) < 4u; }
__device__ __forceinline__ uint32_t slot_off(int s) { return slot_priv(s) ? OFF_PRIV + 4096 + (s & 3) * 16384 : OFF_RING + (s < 6 ? s : s - 4) * 8192; }
__device__ __forceinline__ uint32_t tab_off(int w) { return OFF_PRIV + w * 8192 + (w & 1) * 4096; }

constexpr uint32_t SPIN_LIMIT = 1u << 20;
#define KG_UNROLL 4
constexpr int kKgUnroll = KG_UNROLL;
#define BB_UNROLL 2
constexpr int kBbUnroll = BB_UNROLL;
#define DENSE_UNROLL 1
constexpr int kDenseUnroll = DENSE_UNROLL;
#define ST_T0 2550
#define LN_PAUSE 0xf0
#define FEW_ST 0
#define FEW_H 0
#define ST_GAP 0
#define ST_PER 310
#define ST_PER2 300

struct Exchange {
    uint2 stat[SEQ];
    uint4 h[GU_CTAS * 32];
    uint32_t n_stat[4 * 32];
    uint32_t n_h[8 * 32];
};
struct Scratch {
    Exchange x[NREP];
    uint32_t epoch;
};
__device__ __align__(128) Scratch g_scratch;

struct Ptrs {
    Scratch* sc;
    const __nv_bfloat16 *logA, *Aim, *Cre, *Cim, *ldt, *dsk, *u, *wr;
    __nv_bfloat16* out;
    uint32_t zero;
};
struct Maps {
    CUtensorMap u, out, wg, wu, wd;
};

#define STAMP(i) do { } while (0)
#define KSTAMP(i) do { } while (0)
#define GSTAMP(i) do { } while (0)

__device__ __forceinline__ uint32_t s_u32(const void* p) { return (uint32_t)__cvta_generic_to_shared(p); }
__device__ __forceinline__ void mbar_init(uint32_t b, uint32_t n) {
    asm volatile("mbarrier.init.shared::cta.b64 [%0], %1;" ::"r"(b), "r"(n) : "memory");
}
__device__ __forceinline__ void mbar_expect_tx(uint32_t b, uint32_t bytes) {
    asm volatile("mbarrier.arrive.expect_tx.shared::cta.b64 _, [%0], %1;" ::"r"(b), "r"(bytes) : "memory");
}
__device__ __forceinline__ void mbar_arrive(uint32_t b) {
    asm volatile("mbarrier.arrive.shared::cta.b64 _, [%0];" ::"r"(b) : "memory");
}
__device__ __forceinline__ void mbar_arrive_n(uint32_t b, uint32_t n) {
    asm volatile("mbarrier.arrive.shared::cta.b64 _, [%0], %1;" ::"r"(b), "r"(n) : "memory");
}
__device__ __forceinline__ void mbar_arrive_peer(uint32_t b_cluster) {
    asm volatile("mbarrier.arrive.relaxed.cluster.shared::cluster.b64 _, [%0];" ::"r"(b_cluster) : "memory");
}
__device__ __forceinline__ void mbar_wait(uint32_t b, uint32_t parity) {
    asm volatile("{\n\t.reg .pred p;\n\t.reg .u32 c;\n\tmov.u32 c, 0;\n"
                 "W:\n\tmbarrier.try_wait.parity.shared::cta.b64 p, [%0], %1;\n\t@p bra D;\n\t"
                 "add.u32 c, c, 1;\n\tsetp.lt.u32 p, c, 1048576;\n\t@p bra W;\n\ttrap;\nD:\n\t}"
                 ::"r"(b), "r"(parity) : "memory");
}
__device__ __forceinline__ bool mbar_test(uint32_t b, uint32_t parity) {
    uint32_t ok;
    asm volatile("{ .reg .pred p; mbarrier.test_wait.parity.shared::cta.b64 p, [%1], %2; selp.u32 %0, 1, 0, p; }" : "=r"(ok) : "r"(b), "r"(parity) : "memory");
    return __all_sync(0xffffffffu, ok != 0);
}
__device__ __forceinline__ bool elect_one() {
    uint32_t p;
    asm volatile("{ .reg .pred P; elect.sync _|P, 0xffffffff; selp.u32 %0, 1, 0, P; }" : "=r"(p));
    return p != 0;
}
__device__ __forceinline__ uint32_t mapa(uint32_t a, uint32_t rank) {
    uint32_t r;
    asm("mapa.shared::cluster.u32 %0, %1, %2;" : "=r"(r) : "r"(a), "r"(rank));
    return r;
}
__device__ __forceinline__ void cluster_arrive() { asm volatile("barrier.cluster.arrive.relaxed.aligned;" ::: "memory"); }
__device__ __forceinline__ void cluster_wait() { asm volatile("barrier.cluster.wait.acquire.aligned;" ::: "memory"); }
__device__ __forceinline__ void tma_load_2d(uint32_t dst, const CUtensorMap* m, int c0, int c1, uint32_t bar) {
    asm volatile("cp.async.bulk.tensor.2d.shared::cluster.global.mbarrier::complete_tx::bytes [%0], [%1, {%3, %4}], [%2];"
                 ::"r"(dst), "l"(m), "r"(bar), "r"(c0), "r"(c1) : "memory");
}
__device__ __forceinline__ void tma_load_tile(uint32_t dst, const CUtensorMap* m, int c0, int c2, int c3, uint32_t bar) {
    asm volatile("cp.async.bulk.tensor.4d.shared::cluster.global.mbarrier::complete_tx::bytes.multicast::cluster [%0], [%1, {%3, %4, %5, %6}], [%2], %7;"
                 ::"r"(dst), "l"(m), "r"(bar), "r"(c0), "r"(0), "r"(c2), "r"(c3), "h"((uint16_t)3) : "memory");
}
__device__ __forceinline__ void tma_store_tile(const CUtensorMap* m, uint32_t src, int c0, int c2, int c3) {
    asm volatile("cp.async.bulk.tensor.4d.global.shared::cta.bulk_group [%0, {%2, %3, %4, %5}], [%1];"
                 ::"l"(m), "r"(src), "r"(c0), "r"(0), "r"(c2), "r"(c3) : "memory");
    asm volatile("cp.async.bulk.commit_group;" ::: "memory");
}
__device__ __forceinline__ void bulk_g2s(uint32_t dst, const void* src, uint32_t bytes, uint32_t bar) {
    asm volatile("cp.async.bulk.shared::cluster.global.mbarrier::complete_tx::bytes [%0], [%1], %2, [%3];"
                 ::"r"(dst), "l"(src), "r"(bytes), "r"(bar) : "memory");
}
__device__ __forceinline__ void cp_async16(uint32_t dst, const void* src) {
    asm volatile("cp.async.cg.shared.global [%0], [%1], 16;" ::"r"(dst), "l"(src) : "memory");
}
__device__ __forceinline__ void st_async128(uint32_t dst_cluster, uint32_t x, uint32_t y, uint32_t z, uint32_t w, uint32_t bar_cluster) {
    asm volatile("st.async.weak.shared::cluster.mbarrier::complete_tx::bytes.v4.b32 [%0], {%1,%2,%3,%4}, [%5];"
                 ::"r"(dst_cluster), "r"(x), "r"(y), "r"(z), "r"(w), "r"(bar_cluster) : "memory");
}
__device__ __forceinline__ void fence_async() { asm volatile("fence.proxy.async.shared::cta;" ::: "memory"); }
__device__ __forceinline__ void named_sync(int id, int n) { asm volatile("bar.sync %0, %1;" ::"r"(id), "r"(n) : "memory"); }

__device__ __forceinline__ void ldsm4(uint32_t* r, uint32_t a) {
    asm volatile("ldmatrix.sync.aligned.m8n8.x4.shared.b16 {%0,%1,%2,%3}, [%4];"
                 : "=r"(r[0]), "=r"(r[1]), "=r"(r[2]), "=r"(r[3]) : "r"(a));
}
__device__ __forceinline__ void ldsm4t(uint32_t* r, uint32_t a) {
    asm volatile("ldmatrix.sync.aligned.m8n8.x4.trans.shared.b16 {%0,%1,%2,%3}, [%4];"
                 : "=r"(r[0]), "=r"(r[1]), "=r"(r[2]), "=r"(r[3]) : "r"(a));
}
__device__ __forceinline__ void stsm4t(uint32_t a, uint32_t x, uint32_t y, uint32_t z, uint32_t w) {
    asm volatile("stmatrix.sync.aligned.m8n8.x4.trans.shared.b16 [%0], {%1,%2,%3,%4};"
                 ::"r"(a), "r"(x), "r"(y), "r"(z), "r"(w) : "memory");
}
__device__ __forceinline__ uint32_t lds32(uint32_t a) { uint32_t v; asm volatile("ld.shared.u32 %0, [%1];" : "=r"(v) : "r"(a)); return v; }
__device__ __forceinline__ float lds32f(uint32_t a) { float v; asm volatile("ld.shared.f32 %0, [%1];" : "=f"(v) : "r"(a)); return v; }
__device__ __forceinline__ uint2 lds64(uint32_t a) { uint2 v; asm volatile("ld.shared.v2.u32 {%0,%1}, [%2];" : "=r"(v.x), "=r"(v.y) : "r"(a)); return v; }
__device__ __forceinline__ uint4 lds128(uint32_t a) {
    uint4 v; asm volatile("ld.shared.v4.u32 {%0,%1,%2,%3}, [%4];" : "=r"(v.x), "=r"(v.y), "=r"(v.z), "=r"(v.w) : "r"(a)); return v;
}
__device__ __forceinline__ uint4 lds128v(uint32_t a) {
    uint4 v; asm volatile("ld.volatile.shared.v4.u32 {%0,%1,%2,%3}, [%4];" : "=r"(v.x), "=r"(v.y), "=r"(v.z), "=r"(v.w) : "r"(a)); return v;
}
__device__ __forceinline__ uint32_t or_xor(uint32_t a, uint32_t b, uint32_t c) {
    uint32_t r; asm("lop3.b32 %0, %1, %2, %3, 0xf6;" : "=r"(r) : "r"(a), "r"(b), "r"(c)); return r;
}
__device__ __forceinline__ float4 lds128f(uint32_t a) {
    float4 v; asm volatile("ld.shared.v4.f32 {%0,%1,%2,%3}, [%4];" : "=f"(v.x), "=f"(v.y), "=f"(v.z), "=f"(v.w) : "r"(a)); return v;
}
__device__ __forceinline__ void sts32(uint32_t a, uint32_t v) { asm volatile("st.shared.u32 [%0], %1;" ::"r"(a), "r"(v) : "memory"); }
__device__ __forceinline__ void sts32f(uint32_t a, float v) { asm volatile("st.shared.f32 [%0], %1;" ::"r"(a), "f"(v) : "memory"); }
__device__ __forceinline__ void sts64(uint32_t a, uint32_t x, uint32_t y) { asm volatile("st.shared.v2.u32 [%0], {%1,%2};" ::"r"(a), "r"(x), "r"(y) : "memory"); }
__device__ __forceinline__ void sts64f(uint32_t a, float x, float y) { asm volatile("st.shared.v2.f32 [%0], {%1,%2};" ::"r"(a), "f"(x), "f"(y) : "memory"); }
__device__ __forceinline__ void sts128(uint32_t a, uint32_t x, uint32_t y, uint32_t z, uint32_t w) {
    asm volatile("st.shared.v4.u32 [%0], {%1,%2,%3,%4};" ::"r"(a), "r"(x), "r"(y), "r"(z), "r"(w) : "memory");
}
__device__ __forceinline__ void sts128f(uint32_t a, const float* v) {
    asm volatile("st.shared.v4.f32 [%0], {%1,%2,%3,%4};" ::"r"(a), "f"(v[0]), "f"(v[1]), "f"(v[2]), "f"(v[3]) : "memory");
}
__device__ __forceinline__ uint4 ldg128(const void* p) {
    uint4 v; asm volatile("ld.global.nc.L1::no_allocate.v4.u32 {%0,%1,%2,%3}, [%4];" : "=r"(v.x), "=r"(v.y), "=r"(v.z), "=r"(v.w) : "l"(p)); return v;
}
__device__ __forceinline__ uint2 ldg64(const void* p) {
    uint2 v; asm volatile("ld.global.nc.L1::no_allocate.v2.u32 {%0,%1}, [%2];" : "=r"(v.x), "=r"(v.y) : "l"(p)); return v;
}
__device__ __forceinline__ uint32_t ldg32(const void* p) {
    uint32_t v; asm volatile("ld.global.nc.u32 %0, [%1];" : "=r"(v) : "l"(p)); return v;
}
__device__ __forceinline__ uint32_t ldg16(const void* p) {
    uint32_t v; asm volatile("ld.global.nc.u16 %0, [%1];" : "=r"(v) : "l"(p)); return v;
}
__device__ __forceinline__ uint4 ld_relaxed_128(const void* p) {
    uint4 v; asm volatile("ld.relaxed.gpu.global.v4.u32 {%0,%1,%2,%3}, [%4];" : "=r"(v.x), "=r"(v.y), "=r"(v.z), "=r"(v.w) : "l"(p) : "memory"); return v;
}
__device__ __forceinline__ void ld_relaxed_128_unless(uint4& q, const void* p, bool have) {
    asm volatile("{ .reg .pred p; setp.eq.u32 p, %5, 0; @p ld.relaxed.gpu.global.v4.u32 {%0,%1,%2,%3}, [%4]; }"
                 : "+r"(q.x), "+r"(q.y), "+r"(q.z), "+r"(q.w) : "l"(p), "r"((uint32_t)have) : "memory");
}
__device__ __forceinline__ uint2 ld_relaxed_64(const void* p) {
    uint2 v; asm volatile("ld.relaxed.gpu.global.v2.u32 {%0,%1}, [%2];" : "=r"(v.x), "=r"(v.y) : "l"(p) : "memory"); return v;
}
__device__ __forceinline__ uint32_t ld_relaxed_32(const void* p) {
    uint32_t v; asm volatile("ld.relaxed.gpu.global.u32 %0, [%1];" : "=r"(v) : "l"(p) : "memory"); return v;
}
__device__ __forceinline__ void st_relaxed_128(void* p, uint32_t x, uint32_t y, uint32_t z, uint32_t w) {
    asm volatile("st.relaxed.gpu.global.v4.u32 [%0], {%1,%2,%3,%4};" ::"l"(p), "r"(x), "r"(y), "r"(z), "r"(w) : "memory");
}
__device__ __forceinline__ void st_relaxed_64(void* p, uint32_t x, uint32_t y) {
    asm volatile("st.relaxed.gpu.global.v2.u32 [%0], {%1,%2};" ::"l"(p), "r"(x), "r"(y) : "memory");
}
__device__ __forceinline__ void st_relaxed_32(void* p, uint32_t v) {
    asm volatile("st.relaxed.gpu.global.u32 [%0], %1;" ::"l"(p), "r"(v) : "memory");
}
__device__ __forceinline__ void red_add(void* p, uint32_t v) { asm volatile("red.relaxed.gpu.global.add.u32 [%0], %1;" ::"l"(p), "r"(v) : "memory"); }
__device__ __forceinline__ uint32_t now_ns() { uint32_t t; asm volatile("mov.u32 %0, %%globaltimer_lo;" : "=r"(t) :: "memory"); return t; }
__device__ __forceinline__ void spin_guard(uint32_t& it) { if (++it > SPIN_LIMIT) __trap(); }
__device__ __forceinline__ void wait_count(const uint32_t* p, uint32_t target) {
#pragma unroll 1
    for (uint32_t it = 0; __any_sync(0xffffffffu, (int)(ld_relaxed_32(p) - target) < 0); spin_guard(it)) { }
}
__device__ __forceinline__ void mma_bf16(float* c, uint32_t a0, uint32_t a1, uint32_t a2, uint32_t a3, uint32_t b0, uint32_t b1) {
    asm("mma.sync.aligned.m16n8k16.row.col.f32.bf16.bf16.f32 {%0,%1,%2,%3}, {%4,%5,%6,%7}, {%8,%9}, {%0,%1,%2,%3};"
                 : "+f"(c[0]), "+f"(c[1]), "+f"(c[2]), "+f"(c[3]) : "r"(a0), "r"(a1), "r"(a2), "r"(a3), "r"(b0), "r"(b1));
}
__device__ __forceinline__ void mma_bf16_k8(float* c, uint32_t a0, uint32_t a1, uint32_t b0) {
    asm("mma.sync.aligned.m16n8k8.row.col.f32.bf16.bf16.f32 {%0,%1,%2,%3}, {%4,%5}, {%6}, {%0,%1,%2,%3};"
                 : "+f"(c[0]), "+f"(c[1]), "+f"(c[2]), "+f"(c[3]) : "r"(a0), "r"(a1), "r"(b0));
}
__device__ __forceinline__ void mma_v(float* c, const uint32_t* a, uint32_t b0, uint32_t b1) {
    asm volatile("mma.sync.aligned.m16n8k16.row.col.f32.bf16.bf16.f32 {%0,%1,%2,%3}, {%4,%5,%6,%7}, {%8,%9}, {%0,%1,%2,%3};"
                 : "+f"(c[0]), "+f"(c[1]), "+f"(c[2]), "+f"(c[3]) : "r"(a[0]), "r"(a[1]), "r"(a[2]), "r"(a[3]), "r"(b0), "r"(b1));
}
__device__ __forceinline__ void mma_bf16_z(float* c, uint32_t a0, uint32_t a1, uint32_t a2, uint32_t a3, uint32_t b0, uint32_t b1) {
    asm volatile("mma.sync.aligned.m16n8k16.row.col.f32.bf16.bf16.f32 {%0,%1,%2,%3}, {%4,%5,%6,%7}, {%8,%9}, {%10,%10,%10,%10};"
        : "=f"(c[0]), "=f"(c[1]), "=f"(c[2]), "=f"(c[3]) : "r"(a0), "r"(a1), "r"(a2), "r"(a3), "r"(b0), "r"(b1), "f"(0.f));
}
__device__ __forceinline__ void mma_f16(float* c, uint32_t a0, uint32_t a1, uint32_t a2, uint32_t a3, uint32_t b0, uint32_t b1) {
    asm("mma.sync.aligned.m16n8k16.row.col.f32.f16.f16.f32 {%0,%1,%2,%3}, {%4,%5,%6,%7}, {%8,%9}, {%0,%1,%2,%3};"
                 : "+f"(c[0]), "+f"(c[1]), "+f"(c[2]), "+f"(c[3]) : "r"(a0), "r"(a1), "r"(a2), "r"(a3), "r"(b0), "r"(b1));
}
__device__ __forceinline__ uint32_t pack_bf16(float lo, float hi) {
    uint32_t r; asm("cvt.rn.bf16x2.f32 %0, %1, %2;" : "=r"(r) : "f"(hi), "f"(lo)); return r;
}
__device__ __forceinline__ uint32_t pack_v(float lo, float hi) {
    uint32_t r; asm volatile("cvt.rn.bf16x2.f32 %0, %1, %2;" : "=r"(r) : "f"(hi), "f"(lo)); return r;
}
__device__ __forceinline__ uint32_t pack_w(float lo, float hi) {
    uint32_t r; asm volatile("cvt.rn.satfinite.bf16x2.f32 %0, %1, %2;" : "=r"(r) : "f"(hi), "f"(lo)); return r;
}
template <int N> __device__ __forceinline__ uint32_t after_all(const uint32_t (&f)[N][4], uint32_t zero) {
    uint32_t d[3] = {0, 0, 0};
#pragma unroll
    for (int i = 0; i < N; i++) d[i % 3] |= f[i][3];
    return (d[0] | d[1] | d[2]) & zero;
}
__device__ __forceinline__ void pin(uint32_t& x) { asm volatile("" : "+r"(x)); }
template <class T> __device__ __forceinline__ void pin(T*& x) { asm volatile("" : "+l"(x)); }
__device__ __forceinline__ uint32_t pack_f16(float lo, float hi) {
    uint32_t r; asm("cvt.rn.f16x2.f32 %0, %1, %2;" : "=r"(r) : "f"(hi), "f"(lo)); return r;
}
__device__ __forceinline__ float bf_lo(uint32_t v) { return __uint_as_float(v << 16); }
__device__ __forceinline__ float bf_hi(uint32_t v) { return __uint_as_float(v & 0xffff0000u); }
__device__ __forceinline__ float bf_round(float x) { return __uint_as_float(pack_bf16(0.f, x)); }
__device__ __forceinline__ uint32_t badd2(uint32_t a, uint32_t b) { uint32_t r; asm("add.rn.bf16x2 %0, %1, %2;" : "=r"(r) : "r"(a), "r"(b)); return r; }
__device__ __forceinline__ uint32_t bsub2_lo(uint32_t a, uint32_t b) {
    uint32_t r; asm("{ .reg .b16 m, h; .reg .b32 m2; mov.b32 {m, h}, %2; mov.b32 m2, {m, m}; sub.rn.bf16x2 %0, %1, m2; }" : "=r"(r) : "r"(a), "r"(b)); return r;
}
__device__ __forceinline__ uint32_t bmax2(uint32_t a, uint32_t b) { uint32_t r; asm("max.bf16x2 %0, %1, %2;" : "=r"(r) : "r"(a), "r"(b)); return r; }
__device__ __forceinline__ uint32_t normalize2(uint32_t x, uint32_t s0, uint32_t s1) {
    uint32_t r;
    asm("{ .reg .b16 m, h, l, k; .reg .b32 m2, h2, l2, d, t;\n\t"
        "mov.b32 {m, h}, %2; mov.b32 {l, k}, %3; mov.b32 m2, {m, m}; mov.b32 h2, {h, h}; mov.b32 l2, {l, l};\n\t"
        "sub.rn.bf16x2 d, %1, m2; mul.rn.bf16x2 t, d, l2; fma.rn.bf16x2 %0, d, h2, t; }" : "=r"(r) : "r"(x), "r"(s0), "r"(s1));
    return r;
}
__device__ __forceinline__ float rcpf(float x) { float r; asm("rcp.approx.ftz.f32 %0, %1;" : "=f"(r) : "f"(x)); return r; }
__device__ __forceinline__ float sqrtaf(float x) { float r; asm("sqrt.approx.ftz.f32 %0, %1;" : "=f"(r) : "f"(x)); return r; }
__device__ __forceinline__ float ex2f(float x) { float r; asm("ex2.approx.ftz.f32 %0, %1;" : "=f"(r) : "f"(x)); return r; }

__device__ __forceinline__ int tok_off(int t) { return ((t >> 3) & 1) * VT_PLANE + (t >> 4) * 16 + (t & 7) * 2; }

__device__ __forceinline__ uint32_t order_key(uint32_t b16) { return b16 ^ ((b16 & 0x8000u) ? 0xffffu : 0x8000u); }
__device__ __forceinline__ uint32_t unorder_key(uint32_t k16) { return k16 ^ ((k16 & 0x8000u) ? 0x8000u : 0xffffu); }

struct cplx { float r, i; };
struct hc { uint32_t r, i; };
template <bool CONJ> __device__ __forceinline__ cplx csq(cplx a) {
    float im;
    asm("{ .reg .f32 t; mul.ftz.f32 t, %1, %2; mul.ftz.f32 %0, t, 0f40000000; }" : "=f"(im) : "f"(CONJ ? -a.r : a.r), "f"(a.i));
    return {fmaf(a.r, a.r, -(a.i * a.i)), im};
}
__device__ __forceinline__ cplx cexpp(float a2, float ai) {
    float m = ex2f(a2), s, c;
    __sincosf(ai, &s, &c);
    return {m * c, m * s};
}
__device__ __forceinline__ __half2 as_h2(uint32_t x) { return *reinterpret_cast<__half2*>(&x); }
__device__ __forceinline__ uint32_t as_u(__half2 x) { return *reinterpret_cast<uint32_t*>(&x); }
__device__ __forceinline__ hc hmul(hc a, hc b) {
    return {as_u(__hfma2(as_h2(a.r), as_h2(b.r), __hneg2(__hmul2(as_h2(a.i), as_h2(b.i))))),
            as_u(__hfma2(as_h2(a.r), as_h2(b.i), __hmul2(as_h2(a.i), as_h2(b.r))))};
}
__device__ __forceinline__ hc hpack(cplx a, cplx b) { return {pack_f16(a.r, b.r), pack_f16(a.i, b.i)}; }
__device__ __forceinline__ void sts16(uint32_t a, uint32_t v) { asm volatile("st.shared.u16 [%0], %1;" ::"r"(a), "r"(v) : "memory"); }

struct KgenAddr {
    uint32_t l, h, m2, m3, m4, z, w, wz;
    __device__ __forceinline__ KgenAddr(uint32_t scr, int lane) {
        const int g = lane >> 2, t = lane & 3;
        const uint32_t rec = scr + t * 480;
        l = rec + 16 * g; h = rec + 128 + 8 * g; m2 = rec + 192 + 8 * (g & 1); m3 = rec + 208 + 4 * (g & 2); m4 = rec + 224 + 2 * (g & 4);
        z = scr + 7680 + 16 * t; w = scr + 240 * lane; wz = scr + 7680 + 8 * lane;
        pin(l); pin(h); pin(m2); pin(m3); pin(m4); pin(z); pin(w); pin(wz);
    }
    __device__ __forceinline__ uint32_t any() const { return (l | h | m2) | (m3 | m4 | z) | (w | wz); }
};
template <class Hook, class Hook2>
__device__ __forceinline__ void kgen(const KgenAddr& ad, uint32_t tab, int lane, uint2 la, uint2 aim, uint2 cre, uint2 cim, float dt, float skip, int dch, Hook main_done, Hook2 half_done) {
    const int g = lane >> 2, t = lane & 3;
    const float dt2 = 2.f * dt;
    const uint32_t am = bmax2(bmax2(cre.x & 0x7fff7fffu, cre.y & 0x7fff7fffu), bmax2(cim.x & 0x7fff7fffu, cim.y & 0x7fff7fffu));
    const float mx = dt2 * fmaxf(bf_lo(am), bf_hi(am));
    const uint32_t eb = min(max(__reduce_max_sync(0xffffffffu, __float_as_uint(mx)) >> 23, 1u), 252u);
    const float cscale = dt2 * __uint_as_float((253u - eb) << 23);
    const float scale_inv = __uint_as_float((eb + 1u) << 23);
    float k0 = (bf_lo(cre.x) + bf_hi(cre.x)) + (bf_lo(cre.y) + bf_hi(cre.y));
#pragma unroll
    for (int o = 16; o; o >>= 1) k0 += __shfl_xor_sync(0xffffffffu, k0, o);
    const float ndt = -1.4426950408889634f * dt;
    STAMP(40); KSTAMP(0);

    float acc[5][4];
#pragma unroll
    for (int i = 0; i < 5; i++) { acc[i][0] = acc[i][1] = acc[i][2] = acc[i][3] = 0.f; }

#pragma unroll kBbUnroll
    for (int bb = 0; bb < 2; bb++) {
        cplx z[2][11], cz[2];
#pragma unroll
        for (int e = 0; e < 2; e++) {
            const float lg = e ? bf_hi(la.x) : bf_lo(la.x), ai = (e ? bf_hi(aim.x) : bf_lo(aim.x)) * dt;
            const float cr = (e ? bf_hi(cre.x) : bf_lo(cre.x)) * cscale, ci = (e ? bf_hi(cim.x) : bf_lo(cim.x)) * cscale;
            const float a2 = bf_round(ex2f(lg * 1.4426950408889634f)) * ndt;
            z[e][0] = cexpp(a2, ai);
            z[e][5] = cexpp(a2 * 32.f, ai * -32.f);
#pragma unroll
            for (int i = 1; i < 11; i++) if (i != 5) z[e][i] = (i == 3 || i == 7) ? csq<true>(z[e][i - 1]) : csq<false>(z[e][i - 1]);
            cz[e] = {fmaf(cr, z[e][0].r, -(ci * z[e][0].i)), fmaf(cr, z[e][0].i, ci * z[e][0].r)};
        }
        la.x = la.y; aim.x = aim.y; cre.x = cre.y; cim.x = cim.y;
        const hc z1 = hpack(z[0][0], z[1][0]), z2 = hpack(z[0][1], z[1][1]), z4 = hpack(z[0][2], z[1][2]);
        hc L[8], H[8];
        L[1] = hpack(z[0][3], z[1][3]); L[2] = hpack(z[0][4], z[1][4]); L[4] = hpack(z[0][5], z[1][5]);
        const hc y64 = hpack(z[0][6], z[1][6]), z128 = hpack(z[0][7], z[1][7]), z256 = hpack(z[0][8], z[1][8]);
        const hc z512 = hpack(z[0][9], z[1][9]), z1024 = hpack(z[0][10], z[1][10]);
        H[0] = hpack(cz[0], cz[1]);
        H[1] = hmul(H[0], z1); H[2] = hmul(H[0], z2); H[3] = hmul(H[1], z2);
        L[3] = hmul(L[1], L[2]);
#pragma unroll
        for (int i = 0; i < 4; i++) { H[4 + i] = hmul(H[i], z4); if (i) L[4 + i] = hmul(L[i], L[4]); }
        __syncwarp();
        sts128(ad.w, 0x3c003c00u, y64.r, 0u, y64.i);
#pragma unroll
        for (int i = 1; i < 8; i++) { const hc q = hmul(L[i], y64); sts128(ad.w + 16 * i, L[i].r, q.r, L[i].i, q.i); }
#pragma unroll
        for (int i = 0; i < 4; i++) sts128(ad.w + 128 + 16 * i, H[2 * i].r, H[2 * i].i, H[2 * i + 1].r, H[2 * i + 1].i);
        {
            const hc a = hmul(z256, z1), b = hmul(z256, z128), c = hmul(z256, z2), d = hmul(z512, z4);
            sts128(ad.w + 192, a.r, a.i, b.r, b.i);
            sts128(ad.w + 208, c.r, c.i, z512.r, z512.i);
            sts128(ad.w + 224, d.r, d.i, z1024.r, z1024.i);
            sts64(ad.wz, z128.r, z128.i);
        }
        __syncwarp();
        KSTAMP(1 + 2 * bb);
#pragma unroll kKgUnroll
        for (int k2 = 0; k2 < 4; k2++) {
#pragma unroll
            for (uint32_t s = 0; s < 2; s++) {
                const uint32_t o = k2 * 1920 + s * 240;
                const uint4 l = lds128(ad.l + o);
                const uint2 h0 = lds64(ad.h + o), m2 = lds64(ad.m2 + o), m3 = lds64(ad.m3 + o), m4 = lds64(ad.m4 + o), mz = lds64(ad.z + k2 * 64 + s * 8);
                const hc H0 = {h0.x, h0.y};
                const hc H1 = hmul(H0, {mz.x, mz.y}), H2 = hmul(H0, {m2.x, m2.y}), H3 = hmul(H2, {m3.x, m3.y}), H4 = hmul(H3, {m4.x, m4.y});
                mma_f16(acc[0], l.x, l.y, l.z, l.w, H0.r, H0.i);
                mma_f16(acc[1], l.x, l.y, l.z, l.w, H1.r, H1.i);
                mma_f16(acc[2], l.x, l.y, l.z, l.w, H2.r, H2.i);
                mma_f16(acc[3], l.x, l.y, l.z, l.w, H3.r, H3.i);
                mma_f16(acc[4], l.x, l.y, l.z, l.w, H4.r, H4.i);
            }
        }
        KSTAMP(2 + 2 * bb);
        if (bb == 0) half_done();
    }
    __syncwarp();
    main_done();
    KSTAMP(5);
#pragma unroll
    for (int i = 0; i < 4; i++) sts128(tab + 2048 + 512 * i + 16 * lane, 0, 0, 0, 0);
    if (lane < 15) sts32(tab + 4 * lane, 0);
    __syncwarp();
    const uint32_t d0 = tab + T_DENSE + 4 + 8 * lane, src = (lane + 31) & 31;
    const uint32_t p0 = pack_bf16(fmaf(k0, dt2, skip), 0.f);
    uint32_t prev = p0;
#pragma unroll
    for (int i = 0; i < 4; i++) {
        const uint32_t pk = pack_bf16(acc[i >> 1][2 * (i & 1) + 1] * scale_inv, acc[i >> 1][2 * (i & 1)] * scale_inv);
        sts64(d0 + 256 * i, __byte_perm(pk, __shfl_sync(0xffffffffu, lane == 31 ? prev : pk, src), 0x5432), pk);
        prev = pk;
    }
    const uint32_t w0 = pack_bf16(acc[2][0] * scale_inv, acc[2][1] * scale_inv), w1 = pack_bf16(acc[2][2] * scale_inv, acc[2][3] * scale_inv);
    const uint32_t sa = (lane & 1) ? 0x5410u : 0x5454u, sb2 = (lane & 1) ? 0x1010u : 0x5410u;
#pragma unroll
    for (int hf = 0; hf < 2; hf++) {
        const uint32_t w = hf ? w1 : w0;
        const uint32_t pv = __shfl_sync(0xffffffffu, lane != 31 ? w : hf ? w0 : __byte_perm(prev, w1, 0x5410), src);
        sts64(d0 + 1024 + 256 * hf, __byte_perm(w, pv, sa), __byte_perm(w, pv, sb2));
        sts64(d0 + 1536 + 256 * hf, __byte_perm(w, pv, sa + 0x2222u), __byte_perm(w, pv, sb2 + 0x2222u));
    }
    const uint32_t d3 = tab + T_R2 + 160 + 320 * (t & 1) + 16 * (g >> 1) + 8 * (g & 1) + 4 * (t >> 1), d3n = d3 + (g >= 6 ? 32 : 0);
    const uint32_t d4 = tab + T_R3 + 80 + 160 * t + 4 * g, d4n = d4 + (g >= 6 ? 16 : 0);
    uint32_t p3;
#pragma unroll
    for (int hf = 0; hf < 2; hf++)
#pragma unroll
        for (int e = 0; e < 2; e++) {
            const float v3 = acc[3][2 * hf + e] * scale_inv;
            const uint32_t p4 = pack_bf16(acc[4][2 * hf + e] * scale_inv, 0.f);
            p3 = pack_bf16(v3, v3);
            sts16(d3 + 64 * hf + 160 * e, p3);
            sts16((hf ? d3n : d3) + 64 * hf + 160 * e + 18, p3);
            sts16(d4 + 32 * hf + 80 * e, p4);
            sts16((hf ? d4n : d4) + 32 * hf + 80 * e + 10, p4);
        }
    if (lane == 31) {
        const uint32_t k512 = __byte_perm(w1, 0, 0x3232);
        sts32(tab + T_DENSE, p0);
        sts64(tab + T_DENSE + 4 * 513, k512, k512); sts16(tab + T_DENSE + 4 * 515 + 2, k512);
        sts16(tab + T_PATCH + 4 * 17, p3); sts32(tab + T_PATCH + 4 * 18, p3); sts16(tab + T_PATCH + 4 * 19 + 2, p3);
    }
    __syncwarp();
}

__device__ __forceinline__ void load_toep(uint32_t* a, uint32_t p, uint32_t pz) {
    a[0] = lds32(p); a[1] = lds32(p + 32); a[2] = lds32(pz - 32); a[3] = lds32(pz);
}
#define YIELDS 2
#define YIELD_AT 2
#define DENSE_BLK 4
__device__ __forceinline__ void dense_step(float (&acc)[16][4], uint32_t (&R)[8][4], const uint32_t (&A)[4][4], uint32_t (&An)[4][4],
                                           uint32_t va, uint32_t vmin, uint32_t pn, uint32_t pz, uint32_t zero, int bit, uint32_t& junk) {
#pragma unroll
    for (int i0 = 0; i0 < 8; i0 += DENSE_BLK) {
#pragma unroll 1
        do {
#pragma unroll
            for (int i = i0; i < i0 + DENSE_BLK; i++) {
                const int ip = (i - DENSE_BLK) & 7;
                ldsm4(R[ip], ip == 0 ? max(va - 16, vmin) : va + ip * 128 - (i0 ? 16 : 0));
                if ((i & 1) == 0) load_toep(An[i >> 1], pn + (i >> 1) * 512, pz + (i >> 1) * 512);
#pragma unroll
                for (int ka = 0; ka < 4; ka++) {
                    mma_v(acc[i + ka], A[ka], R[i][0], R[i][1]);
                    if (i + 8 + ka < 16) mma_v(acc[i + 8 + ka], A[ka], R[i][2], R[i][3]);
                }
                if ((YIELDS >> (i - i0)) & 1) asm volatile("xor.b32 %0, %0, %1;" : "+r"(junk) : "r"(__float_as_uint(acc[i + YIELD_AT][0])));
            }
        } while (zero & (1u << (bit + i0)));
    }
}
struct DenseTaps {
    uint32_t A[4][4], E[4], F[4], e8[2], f8[2];
    __device__ __forceinline__ DenseTaps(uint32_t pb, uint32_t pz) {
        constexpr int PP = T_PATCH - T_DENSE + 56;
#pragma unroll
        for (int i = 0; i < 4; i++) load_toep(A[i], pb + 512 * i, pz + 512 * i);
        load_toep(E, pb + 2048, pz + 2048);
        load_toep(F, pb + PP, pz + PP);
        e8[0] = lds32(pz + 2048 + 32); e8[1] = lds32(pb + 2048 + 64);
        f8[0] = lds32(pz + PP + 32); f8[1] = lds32(pb + PP + 64);
    }
};
__device__ __forceinline__ uint32_t dense_phase(float (&acc)[16][4], uint32_t vrow, uint32_t pb, DenseTaps& tp, uint32_t zero, int lane) {
    uint32_t R[8][4], A1[4][4], junk = 0;
    const uint32_t vmin = vrow + ((lane >> 3) & 1) * VT_PLANE - 16 + zero;
    uint32_t va = vmin + 16 + (lane >> 4) * 1024 + (lane & 7) * 16, pz = pb + zero;
    {
        uint32_t H[3][4];
#pragma unroll
        for (int i = 0; i < 3; i++) ldsm4(H[i], vrow + VT_PLANE - 16 + lane * 16 + i * 512);
#pragma unroll
        for (int i = 0; i < 8; i++) ldsm4(R[i], va + i * 128);
#pragma unroll
        for (int i = 0; i < 12; i++) mma_bf16_k8(acc[i + 4], tp.e8[0], tp.e8[1], H[i >> 2][i & 3]);
#pragma unroll
        for (int i = 0; i < 8; i++) mma_bf16_k8(acc[i + 8], tp.f8[0], tp.f8[1], H[i >> 2][i & 3]);
#pragma unroll
        for (int i = 0; i < 12; i++) mma_v(acc[i + 4], tp.E, R[i & 7][2 * (i >> 3)], R[i & 7][2 * (i >> 3) + 1]);
#pragma unroll
        for (int i = 0; i < 8; i++) mma_v(acc[i + 8], tp.F, R[i][0], R[i][1]);
    }
#pragma unroll 1
    for (int rho = 0; rho < 8; rho += 2) {
        dense_step(acc, R, tp.A, A1, va, vmin, pb + 64, pz + 64, zero, 0, junk);
        dense_step(acc, R, A1, tp.A, va - 16, vmin, pb + 128, pz + 128, zero, 8, junk);
        pb += 128; pz += 128; va -= 32;
    }
    return junk & zero;
}
__device__ __forceinline__ uint32_t ones2(int c, int lo, int hi) {
    return (((uint32_t)(c - lo) <= (uint32_t)(hi - lo)) ? 0x3f80u : 0u) | (((uint32_t)(c + 1 - lo) <= (uint32_t)(hi - lo)) ? 0x3f800000u : 0u);
}
struct Boxes {
    uint32_t q[4], ha[2];
    __device__ __forceinline__ Boxes(uint32_t vrow, int lane, int O, int L1, int H1, int L2, int H2) {
        const int g = lane >> 2, t = lane & 3, d = 2 * t - g;
        q[0] = ones2(d, L1, H1); q[1] = ones2(d, L2, H2); q[2] = ones2(d + 8, L1, H1); q[3] = ones2(d + 8, L2, H2);
#pragma unroll
        for (int i = 0; i < 2; i++) { ha[i] = vrow + 16 * g + tok_off(O + 8 * i + 2 * t); pin(ha[i]); pin(q[i]); pin(q[2 + i]); }
    }
    __device__ __forceinline__ uint32_t any() const { return (q[0] | q[1] | q[2]) | (q[3] | ha[0] | ha[1]); }
    __device__ __forceinline__ void load(int j, uint32_t* v, uint32_t zero) const {
        const uint32_t o = j * 128;
        v[0] = lds32(ha[0] + o); v[1] = lds32(ha[1] + zero + o); v[2] = lds32(ha[1] + o);
        v[3] = lds32(ha[0] + zero + o + 16); v[4] = lds32(ha[0] + o + 16); v[5] = lds32(ha[1] + o + 16);
    }
    __device__ __forceinline__ void sums(const uint32_t* v, float* Z, float* X, float* Y) const {
        mma_bf16_z(Z, q[0], q[1], q[2], q[3], v[0], v[1]);
        mma_bf16_z(X, q[0], q[1], q[2], q[3], v[2], v[3]);
        mma_bf16_z(Y, q[0], q[1], q[2], q[3], v[4], v[5]);
    }
};
template <class After>
__device__ __forceinline__ void tail_phase(float (&acc)[16][4], const Boxes& b2, const Boxes& b3, uint32_t tp2, uint32_t tp3, uint32_t zero, After after) {
    uint2 tp[10];
    uint32_t v[6], a0[4], a1[4];
    float Z[4], X[4], Y[4];
    b2.load(0, v, zero);
#pragma unroll
    for (int i = 0; i < 5; i++) { const uint4 c = lds128(tp2 + 160 * i); tp[i] = make_uint2(c.x, c.y); tp[5 + i] = make_uint2(c.z, c.w); }
#pragma unroll
    for (int j = -1; j < 20; j++) {
        if (j < 19) {
            (j < 11 ? b2 : b3).sums(v, Z, X, Y);
            if (j < 10) b2.load(j + 2, v, zero); else if (j < 18) b3.load(j - 10, v, zero);
        }
        if (j >= 0 && j < 12) {
#pragma unroll
            for (int b = 0; b < 5; b++) if (j + 4 + b < 16) mma_v(acc[j + 4 + b], a1, tp[5 + b].x, tp[5 + b].y);
        }
        if (j < 11) { a1[0] = pack_v(Z[0], Z[1]); a1[1] = pack_w(X[0], X[1]); a1[2] = pack_v(Z[2], Z[3]); a1[3] = pack_w(X[2], X[3]); }
        if (j >= 0 && j < 12) {
#pragma unroll
            for (int b = 0; b < 5; b++) if (j + 4 + b < 16) mma_v(acc[j + 4 + b], a0, tp[b].x, tp[b].y);
            if (j >= 7 && j < 11) { tp[11 - j] = lds64(tp3 + 80 * (10 - j)); tp[16 - j] = lds64(tp3 + 80 * (14 - j)); }
        } else if (j >= 12) {
#pragma unroll
            for (int b = 0; b < 8; b++) if (j - 4 + b < 16) mma_v(acc[j - 4 + b], a0, tp[b < 4 ? b + 1 : b + 2].x, tp[b < 4 ? b + 1 : b + 2].y);
        }
        if (j < 11) { a0[0] = pack_v(X[0], X[1]); a0[1] = pack_v(Y[0], Y[1]); a0[2] = pack_v(X[2], X[3]); a0[3] = pack_v(Y[2], Y[3]); }
        else if (j < 19) { a0[0] = pack_v(X[0], X[1]); a0[1] = pack_v(Y[0], Y[1]); a0[2] = pack_v(Z[2], Z[3]); a0[3] = pack_v(X[2], X[3]); }
        after(j);
    }
}
template <int G>
__device__ __forceinline__ void emit(const float (&acc)[16][4], int h, uint32_t own, uint32_t peer, uint32_t bar, uint32_t bar_peer) {
#pragma unroll
    for (int o = 0; o < 2; o++)
#pragma unroll
        for (int hf = 0; hf < 2; hf++) {
            const int n = 8 * G + 4 * o;
            asm volatile("{ .reg .pred p; setp.eq.u32 p, %7, %8;\n\t@p st.shared.v4.u32 [%0], {%1,%2,%3,%4};\n\t"
                         "@!p st.async.weak.shared::cluster.mbarrier::complete_tx::bytes.v4.b32 [%5], {%1,%2,%3,%4}, [%6]; }"
                         ::"r"(own + G * 16384 + hf * 512), "r"(pack_bf16(acc[n][2 * hf], acc[n][2 * hf + 1])), "r"(pack_bf16(acc[n + 1][2 * hf], acc[n + 1][2 * hf + 1])),
                         "r"(pack_bf16(acc[n + 2][2 * hf], acc[n + 2][2 * hf + 1])), "r"(pack_bf16(acc[n + 3][2 * hf], acc[n + 3][2 * hf + 1])),
                         "r"(peer + G * 16384 + hf * 512), "r"(bar_peer + 8 * G), "r"(h), "r"(o) : "memory");
        }
    __syncwarp();
    if (elect_one()) mbar_arrive(bar + 8 * G);
}
__device__ __forceinline__ void finish(uint32_t src, uint32_t xa) {
    uint32_t s[4][4];
    uint4 x[4];
#pragma unroll
    for (int i = 0; i < 4; i++) {
        ldsm4t(s[i], (src ^ ((i & 1) << 5)) + (i >> 1) * 8192);
        x[i] = lds128((xa ^ ((i >> 1) << 4)) + (i & 1) * 256);
    }
#pragma unroll
    for (int i = 0; i < 4; i++)
        sts128((xa ^ ((i >> 1) << 4)) + (i & 1) * 256, badd2(x[i].x, s[i][0]), badd2(x[i].y, s[i][1]), badd2(x[i].z, s[i][2]), badd2(x[i].w, s[i][3]));
}

__device__ __noinline__ float centred_var(uint32_t rows, float mu, int lane) {
    float var = 0.f;
#pragma unroll 1
    for (int rr = 0; rr < 16; rr++) {
        const float c0 = __shfl_sync(0xffffffffu, mu, rr);
        float c = 0.f;
#pragma unroll 1
        for (int k = 0; k < 16; k++) {
            const uint32_t q = lds32(rows + rr * ROW_PITCH + k * 128 + lane * 4);
            const float d0 = bf_lo(q) - c0, d1 = bf_hi(q) - c0;
            c = fmaf(d0, d0, fmaf(d1, d1, c));
        }
#pragma unroll 1
        for (int o = 16; o; o >>= 1) c += __shfl_xor_sync(0xffffffffu, c, o);
        if ((lane & 15) == rr) var = c * (1.f / DM);
    }
    return var;
}
__device__ __noinline__ float centred_score(uint32_t rows, uint32_t wbuf, uint32_t s0, uint32_t s1, int lane) {
    float sc = 0.f;
#pragma unroll 1
    for (int rr = 0; rr < 16; rr++) {
        const uint32_t t0 = __shfl_sync(0xffffffffu, s0, rr), t1 = __shfl_sync(0xffffffffu, s1, rr);
        float c = 0.f;
#pragma unroll 1
        for (int k = 0; k < 16; k++) {
            const uint32_t xn = normalize2(lds32(rows + rr * ROW_PITCH + k * 128 + lane * 4), t0, t1);
            const uint32_t wq = lds32(wbuf + (k >> 2) * 1024 + (k & 3) * 128 + lane * 4);
            c = fmaf(bf_lo(xn), bf_lo(wq), fmaf(bf_hi(xn), bf_hi(wq), c));
        }
#pragma unroll 1
        for (int o = 16; o; o >>= 1) c += __shfl_xor_sync(0xffffffffu, c, o);
        if ((lane & 15) == rr) sc = c;
    }
    return sc;
}

__global__ void __cluster_dims__(2, 1, 1) __launch_bounds__(NTHR, 1)
fused_kernel(const __grid_constant__ Ptrs p, const __grid_constant__ Maps maps) {
    extern __shared__ __align__(1024) unsigned char smem[];
#define ROT 0
    const int tid = (threadIdx.x + ROT) & 511, lane = tid & 31, b = blockIdx.x;
    const int dch = 8 * b + (tid >> 5) - 4;
    uint2 la, aim, cre, cim;
    uint32_t ldt16, dsk16, epoch;
    uint4 wq;
    if ((uint32_t)(tid - 128) < 256u) {
        la = ldg64(p.logA + dch * NMODE + 4 * lane); aim = ldg64(p.Aim + dch * NMODE + 4 * lane);
        cre = ldg64(p.Cre + dch * NMODE + 4 * lane); cim = ldg64(p.Cim + dch * NMODE + 4 * lane);
        ldt16 = ldg16(p.ldt + dch); dsk16 = ldg16(p.dsk + dch);
    }
    if (tid < 128) { wq = ldg128(p.wr + 8 * tid); epoch = ld_relaxed_32(&p.sc->epoch); }
    const uint32_t sb = s_u32(smem);
    const int warp = __shfl_sync(0xffffffffu, tid >> 5, 0);
    const int h = b & 1, cl = b >> 1;
    const uint32_t bar0 = sb + OFF_BAR;
    const int m = lane >> 3, r = lane & 7, g = lane >> 2, t = lane & 3;
    const bool has_gu = b < GU_CTAS;
    if (warp == 4) { STAMP(0); GSTAMP(24); }

    if (warp >= 12) {
        asm volatile("setmaxnreg.dec.sync.aligned.u32 24;");
        const int a = warp - 12;
        uint32_t due = now_ns() + ST_T0 + (uint32_t)(128 * a + b) * ST_PER / 128;
        const bool el = elect_one();
        if (a == 1 && el) {
#pragma unroll
            for (int j = 0; j < 4; j++) mbar_init(bar0 + 8 * (B_ROW + j), 1);
            asm volatile("fence.mbarrier_init.release.cluster;" ::: "memory");
            fence_async();
#pragma unroll 1
            for (int j = 0; j < 4; j++) {
                mbar_expect_tx(bar0 + 8 * (B_ROW + j), 8192);
#pragma unroll
                for (int i = 0; i < 4; i++)
                    bulk_g2s(sb + OFF_VT + (4 * j + i) * ROW_PITCH, p.u + (size_t)(16 * b + 4 * j + i) * DM, 2048, bar0 + 8 * (B_ROW + j));
            }
        }
        if (a == 2 && el) {
#pragma unroll
            for (int i = B_XT; i < NBAR; i++) mbar_init(bar0 + 8 * i, i == B_SFREE ? 8 : i == B_UPD ? 4 : (i == B_RECV || i == B_RECV + 1) ? 9 : (i >= B_FREE + 6 && i < B_FREE + 10) ? 2 : 1);
            asm volatile("fence.mbarrier_init.release.cluster;" ::: "memory");
            fence_async();
            mbar_expect_tx(bar0 + 8 * B_XT, 65536);
            mbar_expect_tx(bar0 + 8 * B_RECV, 8192);
            mbar_expect_tx(bar0 + 8 * B_RECV + 8, 8192);
            mbar_expect_tx(bar0 + 8 * B_RED, 512);
        }
        if (a == 3 && el) {
#pragma unroll
            for (int i = 0; i < 5; i++) asm volatile("prefetch.tensormap [%0];" ::"l"(&maps.u + i) : "memory");
        }
        __syncwarp();
        cluster_arrive();
        cluster_wait();
        STAMP(18);
        mbar_wait(bar0 + 8 * (B_ROW + a), 0);
        if (el) {
#pragma unroll
            for (int i = 0; i < 4; i++)
                tma_load_tile(sb + OFF_XT + h * 32768 + a * 4096 + (i & 1) * 16384 + (i >> 1) * 2048, &maps.u, 16 * cl, 4 * a + (i & 2), 16 * (i & 1) + 8 * h, bar0 + 8 * B_XT);
        }
        if (el) {
#pragma unroll 1
            for (int k = has_gu ? 0 : 4; k < 6; k++) {
                const int i = 4 * k + a, s = k < 3 ? i : i - 12;
#pragma unroll 1
                for (int left; (left = (int)(due - now_ns())) > 0;) __nanosleep(left >> 1);
                due += k == 0 ? 4 * ST_PER + ST_GAP : k < 3 ? 4 * ST_PER : 4 * ST_PER2;
                const bool again = k >= 3 && has_gu;
                if (s >= 6 || again) mbar_wait(bar0 + 8 * (B_FREE + s), s >= 6 && again);
                const uint32_t dst = sb + slot_off(s), bar = bar0 + 8 * (B_FULL + s);
                if (k < 4) {
                    mbar_expect_tx(bar, 8192);
                    tma_load_2d(dst, &maps.wg, 64 * cl, 512 * h + 32 * i, bar);
                    tma_load_2d(dst + 4096, &maps.wu, 64 * cl, 512 * h + 32 * i, bar);
                } else {
                    mbar_expect_tx(bar, 7168);
                    tma_load_2d(dst, &maps.wd, 16 * cl, 1792 * h + 448 * a + 224 * (k & 1), bar);
                }
            }
            STAMP(19);
        }
    } else if (warp >= 4) {
        const int w = warp - 4;
        cluster_arrive();
        asm volatile("setmaxnreg.inc.sync.aligned.u32 168;");
        const uint32_t vrow = sb + OFF_VT + w * VT_PITCH + VT_PAD, tab = sb + tab_off(w);
        const uint32_t so = sb + OFF_XT + (8 * h + w) * 1024 + ((lane ^ ((w & 1) << 1)) << 4);
        uint32_t dst0 = so + (h ^ 1) * 32768;
        const uint32_t rb0 = bar0 + 8 * B_RECV, rb1 = mapa(rb0, h ^ 1);
        const uint32_t box = sb + OFF_XT + h * 32768 + w * 2048;
        uint32_t fs = sb + OFF_XT + (h ^ 1) * 32768 + (2 * m + (r & 1)) * 1024 + (w >> 2) * 512 + (((8 * (w & 3) + (r & 4) + ((r >> 1) & 1)) ^ ((r & 1) << 1)) << 4);
        uint32_t fx = box + (g >> 1) * 512 + (t >> 1) * 144 + (2 * (t & 1) + (g & 1)) * 32;
        uint32_t tpo = 80 + (g - 2 * t) * 8 - (g < 2 * t ? 16 : 0);
        uint32_t xa = sb + OFF_XT + (w & 2) * 16384 + (w >> 2) * 16384 + (w & 1) * 1024 + (g >> 1) * 2048 + (g & 1) * 128 + t * 32 + ((h ^ (g & 1)) << 4);
        uint32_t va = sb + OFF_VT + (2 * m + (r & 1)) * VT_PITCH + VT_PAD + (16 * w + (r >> 1)) * 16;
        uint32_t qa = sb + OFF_ST + 2048 * w + 128 * t + 16 * (g ^ (2 * t));
        pin(dst0); pin(fs); pin(fx); pin(tpo); pin(xa); pin(va); pin(qa);
        const Boxes b2(vrow, lane, -18, 5, 7, 0, 4), b3(vrow, lane, -20, 1, 7, 0, 8);
        const KgenAddr ka(sb + OFF_PRIV + w * 8192, lane);
        if (__any_sync(0xffffffffu, ((dst0 | fs) | (fx | tpo | xa) | (va | qa) | (b2.any() | b3.any() | ka.any())) & p.zero)) __trap();
        cluster_wait();
        pin(la.x); pin(la.y); pin(aim.x); pin(aim.y); pin(cre.x); pin(cre.y); pin(cim.x); pin(cim.y); pin(ldt16); pin(dsk16);
        kgen(ka, tab, lane, la, aim, cre, cim, bf_round(ex2f(bf_lo(ldt16) * 1.4426950408889634f)), 1.f + bf_lo(dsk16), dch, [&]() {
            STAMP(21);
            if (elect_one()) mbar_arrive(bar0 + 8 * (B_FREE + 6 + ((w >> 1) ^ 2)));
        }, [&]() {
            if ((LN_PAUSE >> w) & 1) mbar_wait(bar0 + 8 * B_LN, 0);
        });
        STAMP(1); KSTAMP(6);
        const uint32_t pb = tab + T_DENSE + (g - 2 * t) * 4;
        DenseTaps dt(pb, pb + p.zero);
        {
            uint4 q[4], x[8];
            mbar_wait(bar0 + 8 * B_XT, 0);
#pragma unroll
            for (int i = 0; i < 8; i++) x[i] = lds128(xa + (i & 1) * 8192 + (i >> 1) * 256);
            STAMP(47);
            mbar_wait(bar0 + 8 * (B_ST + w), 0);
#pragma unroll
            for (int n = 0; n < 4; n++) q[n] = lds128(qa + 512 * n);
            if (lane < 4) sts128(vrow - VT_PAD + (lane >> 1) * VT_PLANE + (lane & 1) * 16, 0, 0, 0, 0);
            STAMP(2); GSTAMP(28);
#pragma unroll
            for (int i = 0; i < 8; i++) {
                const uint32_t s0 = (i & 1) ? q[i >> 1].z : q[i >> 1].x, s1 = (i & 1) ? q[i >> 1].w : q[i >> 1].y;
                stsm4t(va + (i >> 1) * 64 + (i & 1) * VT_PLANE, normalize2(x[i].x, s0, s1), normalize2(x[i].y, s0, s1),
                       normalize2(x[i].z, s0, s1), normalize2(x[i].w, s0, s1));
            }
            named_sync(2, 256);
            if (elect_one()) {
                if (w < 3) mbar_arrive(bar0 + 8 * (w == 2 ? B_V : B_FREE + 10 + w));
            }
        }
        STAMP(3); KSTAMP(7);
        float acc[16][4];
#pragma unroll
        for (int i = 0; i < 16; i++) { acc[i][0] = acc[i][1] = acc[i][2] = acc[i][3] = 0.f; }
        tpo |= dense_phase(acc, vrow, pb, dt, p.zero, lane);
        STAMP(4); KSTAMP(8);
        const uint32_t dst1 = mapa(dst0 + (h ? 32768 : -32768), h ^ 1);
        tail_phase(acc, b2, b3, tab + T_R2 + 2 * tpo, tab + T_R3 + tpo, p.zero, [&](int j) {
            if (j == 3) {
                mbar_wait(bar0 + 8 * B_SFREE, 0);
                emit<0>(acc, h, dst0, dst1, rb0, rb1);
                STAMP(5);
            }
            if (j == 7) {
                mbar_wait(bar0 + 8 * B_RECV, 0);
                finish(fs, fx);
                fence_async();
                __syncwarp();
                if (elect_one()) tma_store_tile(&maps.out, box, 16 * cl, 2 * w, 8 * h);
                STAMP(20);
            }
        });
        emit<1>(acc, h, dst0, dst1, rb0, rb1);
        STAMP(30);
        mbar_wait(bar0 + 8 * (B_RECV + 1), 0);
        STAMP(6);
        finish(fs + 16384, fx + 16384);
        const bool ready = mbar_test(bar0 + 8 * B_UPD, 0);
        const bool el = elect_one();
#pragma unroll 1
        for (int pass = 0; pass < 2; pass++) {
            if ((pass != 0) == ready) {
                fence_async();
                __syncwarp();
                if (el) tma_store_tile(&maps.out, box + 16384, 16 * cl, 2 * w, 16 + 8 * h);
            } else {
                if (el) asm volatile("cp.async.bulk.wait_group 0;" ::: "memory");
                __syncwarp();
                mbar_wait(bar0 + 8 * B_UPD, 0);
                const int tok = 2047 - (int)(lds32(sb + OFF_MISC + 48 + 8 * g) & 2047);
                if ((((tok >> 6) & 8) | ((tok >> 1) & 7)) == 8 * h + w) {
                    const uint32_t xa = box + (tok >> 10) * 16384 + ((tok >> 6) & 7) * 256 + (tok & 1) * 128 + ((tok >> 4) & 3) * 32 + (((t >> 1) ^ (tok & 1)) << 4) + (t & 1) * 8;
                    const uint2 o0 = lds64(xa);
                    const float4 up = lds128f(sb + tab_off(g) + T_RED + 16 * t);
                    const uint2 o1 = make_uint2(badd2(o0.x, pack_bf16(up.x, up.y)), badd2(o0.y, pack_bf16(up.z, up.w)));
                    if (ready && tok >= 1024) sts64(xa, o1.x, o1.y);
                    else *reinterpret_cast<uint2*>(p.out + (size_t)tok * DM + 16 * cl + 4 * t) = o1;
                }
            }
        }
        if (el) asm volatile("cp.async.bulk.wait_group.read 0;" ::: "memory");
        STAMP(7);
    } else {
        const int a = warp;
        cluster_arrive();
        asm volatile("setmaxnreg.inc.sync.aligned.u32 152;");
        const uint32_t tag = __shfl_sync(0xffffffffu, epoch, 0) + 1u, misc = sb + OFF_MISC, abar = bar0 + 8 * (B_AUX + a);
        uint32_t aph = 0;
        const Exchange* in = &p.sc->x[cl & (NREP - 1)];
        uint2* pub = p.sc->x[m >> 1].stat + 16 * b + 2 * (r ^ (2 * (b & 3))) + (m & 1);
        uint32_t* cnt_s = &p.sc->x[t].n_stat[b & 96];
        pin(pub); pin(cnt_s);
        if (tid < 64) sts32(sb + OFF_XCH + 4 * tid, 0);
        const uint32_t wbuf = sb + OFF_LN + a * 1024, part = sb + OFF_LN + 4096;
        {
            sts128(wbuf + 16 * lane, wq.x, wq.y, wq.z, wq.w);
            sts128(wbuf + 512 + 16 * lane, 0x3f803f80u, 0x3f803f80u, 0x3f803f80u, 0x3f803f80u);
            float wsum = ((bf_lo(wq.x) + bf_hi(wq.x)) + (bf_lo(wq.y) + bf_hi(wq.y))) + ((bf_lo(wq.z) + bf_hi(wq.z)) + (bf_lo(wq.w) + bf_hi(wq.w)));
#pragma unroll
            for (int o = 16; o; o >>= 1) wsum += __shfl_xor_sync(0xffffffffu, wsum, o);
            sts32f(part + 1024 + 4 * a, wsum);
            uint32_t wf[4][4];
#pragma unroll
            for (int i = 0; i < 4; i++) ldsm4(wf[i], wbuf + ((uint32_t)(r - 1) < 2u ? 16 * (r - 1) : 512) + 32 * m + 128 * i);
            uint32_t ra = sb + OFF_VT + r * ROW_PITCH + 512 * a + 16 * m, pa = part + a * 256 + g * 16;
            cluster_wait();
            STAMP(22);
#pragma unroll 1
            for (int hf = 0; hf < 2; hf++) {
                mbar_wait(bar0 + 8 * B_ROW + 16 * hf, 0);
                mbar_wait(bar0 + 8 * B_ROW + 16 * hf + 8, 0);
                STAMP(23);
                uint32_t x[8][4];
                float cs[2][4], q[8][4];
#pragma unroll
                for (int i = 0; i < 40; i++) (i < 8 ? cs[i >> 2 & 1] : q[(i - 8) >> 2 & 7])[i & 3] = 0.f;
#pragma unroll
                for (int k = 0; k < 8; k++) ldsm4(x[k], ra + k * 64);
                const bool more = __any_sync(0xffffffffu, after_all(x, p.zero));
#pragma unroll 1
                do {
#pragma unroll
                    for (int k = 0; k < 8; k++) {
                        mma_v(cs[k & 1], x[k], wf[k >> 1][2 * (k & 1)], wf[k >> 1][2 * (k & 1) + 1]);
#pragma unroll
                        for (int i = 0; i < 4; i++) mma_bf16_k8(q[4 * (k & 1) + i], x[k][i & 2], x[k][i | 1], x[k][i]);
                    }
                } while (more);
                const float c2 = cs[0][2] + cs[1][2];
                if (t == 0) sts64f(pa, (cs[0][0] + cs[1][0]) + c2, cs[0][1] + cs[1][1]);
                if (t == 1) sts32f(pa + 12, c2);
                const float e0 = ((q[0][0] + q[2][0]) + (q[4][0] + q[6][0])) + ((q[1][2] + q[3][2]) + (q[5][2] + q[7][2]));
                const float e1 = ((q[0][1] + q[2][1]) + (q[4][1] + q[6][1])) + ((q[1][3] + q[3][3]) + (q[5][3] + q[7][3]));
                if (t == (g >> 1)) sts32f(pa + 8, (g & 1) ? e1 : e0);
                ra += 8 * ROW_PITCH; pa += 128;
            }
        }
        STAMP(31);
        named_sync(1, 128);
        if (a == 0) {
            const uint32_t pa = part + (lane & 15) * 16;
            const float4 p0 = lds128f(pa), p1 = lds128f(pa + 256), p2 = lds128f(pa + 512), p3 = lds128f(pa + 768), ws = lds128f(part + 1024);
            const float mu = ((p0.x + p1.x) + (p2.x + p3.x)) * (1.f / DM);
            float var = ((p0.z + p1.z) + (p2.z + p3.z)) * (1.f / DM) - mu * mu;
            const bool centred = __any_sync(0xffffffffu, !(mu * mu <= 4.f * var));
            if (centred) var = centred_var(sb + OFF_VT, mu, lane);
            const float ri = rcpf(bf_round(sqrtaf(bf_round(bf_round(var) + 1e-5f))));
            const uint32_t s0 = pack_bf16(mu, ri), s1 = (pack_bf16(ri - bf_hi(s0), 0.f) & 0xfffcu) | (tag & 3);
            float sc = ((((p0.y + p1.y) + (p2.y + p3.y)) + ((p0.w + p1.w) + (p2.w + p3.w))) - bf_lo(s0) * ((ws.x + ws.y) + (ws.z + ws.w))) * ri;
            if (centred) sc = centred_score(sb + OFF_VT, sb + OFF_LN, s0, s1, lane);
            const uint32_t sb16 = pack_bf16(0.f, sc);
            const uint32_t s2 = s1 | (sb16 ^ (((uint32_t)((int)sb16 >> 31) & 0x7fff0000u) | 0x80000000u));
            st_relaxed_64(pub, s0, s2);
            st_relaxed_64(pub + 2 * sizeof(Exchange) / 8, s0, s2);
            if (lane < NREP) red_add(cnt_s, 1);
            if (elect_one()) mbar_arrive(bar0 + 8 * B_LN);
            STAMP(9); GSTAMP(25);
        }
        const uint32_t slot0 = sb + OFF_RING + a * 8192, slot1 = sb + slot_off(4 + a), slot2 = sb + slot_off(8 + a), fbar = bar0 + 8 * (B_FULL + a);
        uint32_t mine = 0, row[2] = {0, 0};
        {
            uint32_t q[16];
            named_sync(1, 128);
            wait_count(&in->n_stat[32 * a], 32 * tag - FEW_ST);
            STAMP(41);
#pragma unroll 1
            for (uint32_t it = 0;; spin_guard(it)) {
                if (elect_one()) {
                    mbar_expect_tx(abar, 4096);
                    bulk_g2s(sb + OFF_ST + 4096 * a, in->stat + 512 * a, 4096, abar);
                }
                mbar_wait(abar, aph);
                aph ^= 1;
                uint32_t bad = 0;
#pragma unroll
                for (int n = 0; n < 8; n++) {
                    const uint4 u = lds128v(sb + OFF_ST + 4096 * a + 512 * n + 16 * lane);
                    q[2 * n] = u.y; q[2 * n + 1] = u.w;
                    bad = or_xor(bad, u.y, tag);
                }
                const bool ok = __all_sync(0xffffffffu, (bad & 3) == 0);
                asm volatile("{ .reg .pred p; setp.ne.u32 p, %1, 0; @p mbarrier.arrive.shared::cta.b64 _, [%0]; }" ::"r"(bar0 + 8 * B_ST + 16 * a + 8 * lane), "r"((uint32_t)(ok && lane < 2)) : "memory");
                if (ok) break;
            }
            STAMP(8);
            const uint32_t inv = 2047 - 512 * a - 16 * m - (r ^ (2 * m));
#pragma unroll
            for (int i = 0; i < 16; i++) asm("lop3.b32 %0, %0, %1, %2, 0x9b;" : "+r"(q[i]) : "r"(inv), "r"(0xffff0000u | (64 * (i >> 1) + 8 * (i & 1))));
            auto below = [&](uint32_t x) {
                uint32_t d[4];
#pragma unroll
                for (int i = 0; i < 16; i++) d[i & 3] = i < 4 ? x + q[i] : min(d[i & 3], x + q[i]);
                d[0] = min(min(d[0], d[1]), min(d[2], d[3]));
                return d[0] < x ? x - 1 - d[0] : 0u;
            };
            const uint32_t mx0 = ~min(min(min(min(q[0], q[1]), min(q[2], q[3])), min(min(q[4], q[5]), min(q[6], q[7]))),
                                      min(min(min(q[8], q[9]), min(q[10], q[11])), min(min(q[12], q[13]), min(q[14], q[15]))));
            const uint32_t gm = min(__reduce_max_sync(0xffffffffu, lane < 16 ? mx0 : 0u), __reduce_max_sync(0xffffffffu, lane < 16 ? 0u : mx0));
            if (lane == 0) sts32(misc + 16 + 4 * a, gm);
            named_sync(1, 128);
            STAMP(42);
            if (b == 0 && tid == 0) st_relaxed_32(&p.sc->epoch, tag);
            const uint4 t0 = lds128(misc + 16);
            uint32_t tau = min(min(t0.x, t0.y), min(t0.z, t0.w));
            uint32_t mx = mx0, cnt = 0, bal;
            const uint32_t list = sb + OFF_XCH + 64 * a;
#pragma unroll 1
            while ((bal = __ballot_sync(0xffffffffu, mx >= tau)) != 0) {
                const uint32_t pos = cnt + __popc(bal & ((1u << lane) - 1u));
                cnt += __popc(bal);
                if (cnt > 16) break;
                if (mx >= tau) sts32(list + 4 * pos, mx);
                mx = below(mx);
            }
            if (cnt > 16) {
                mx = mx0;
#pragma unroll 1
                for (int j = 0; j < 8; j++) {
                    const uint32_t top = __reduce_max_sync(0xffffffffu, mx), nx = below(mx);
                    if (mx == top) { sts32(list + 4 * j, mx); sts32(list + 32 + 4 * j, 0); mx = nx; }
                }
            }
            named_sync(1, 128);
            STAMP(43);
            const uint2 k = lds64(sb + OFF_XCH + 8 * lane);
            uint32_t hi = max(k.x, k.y), lo = min(k.x, k.y);
            mbar_wait(bar0 + 8 * B_V, 0);
#pragma unroll
            for (int j = 0; j < 8; j++) {
                const uint32_t top = __reduce_max_sync(0xffffffffu, hi);
                const bool won = hi == top;
                hi = won ? lo : hi;
                lo = won ? 0u : lo;
                if (g == j) mine = top;
                if (a == (j >> 1)) row[j & 1] = top;
            }
        }
        STAMP(11);
        const int tok = 2047 - (int)(mine & 2047);
        const uint32_t xs = sb + OFF_XT + (h ^ 1) * 32768;
        if (has_gu) {
            if (elect_one()) {
                mbar_expect_tx(abar, 2048);
#pragma unroll
                for (int j = 0; j < 2; j++) bulk_g2s(xs + (2 * a + j) * 1040, p.u + (size_t)(2047 - (row[j] & 2047)) * DM + 512 * h, 1024, abar);
            }
        }
        STAMP(44);
        const uint2 st = ld_relaxed_64(in->stat + (tok & ~15) + 2 * ((tok & 7) ^ ((tok >> 3) & 6)) + ((tok >> 3) & 1));
        if (a == 0 && t == 0) sts64(misc + 48 + 8 * g, mine, __float_as_uint(bf_hi(st.x) + bf_lo(st.y)));
        uint32_t xq[4][4];
        if (a == 0) STAMP(45);
        if (has_gu) {
            mbar_wait(abar, aph);
            aph ^= 1;
            STAMP(46);
            named_sync(1, 128);
#pragma unroll
            for (int j = 0; j < 4; j++) {
                ldsm4(xq[j], xs + r * 1040 + m * 16 + 64 * a + 256 * j);
#pragma unroll
                for (int i = 0; i < 4; i++) xq[j][i] = bsub2_lo(xq[j][i], st.x);
            }
        }
        __syncwarp();
        if (lane < 2) mbar_arrive_peer(mapa(bar0 + 8 * B_SFREE, lane) + (has_gu ? ((xq[0][0] | xq[1][0]) | (xq[2][0] | xq[3][0])) & p.zero : 0u));
        if (has_gu) {
            STAMP(12);
            float gacc[8][4];
#pragma unroll
            for (int i = 0; i < 8; i++) { gacc[i][0] = gacc[i][1] = gacc[i][2] = gacc[i][3] = 0.f; }
            uint4* pubh = &p.sc->x[a].h[b * 32 + lane];
            uint32_t* cnt_h = &p.sc->x[a].n_h[32 * (b / 14) + lane];
            pin(pubh); pin(cnt_h);
            if (elect_one()) mbar_expect_tx(abar, 512);
            uint32_t ko[8];
#pragma unroll
            for (int mt = 0; mt < 8; mt++) ko[mt] = (m & 1) * 4096 + (r + ((m >> 1) << 3)) * 128 + ((r ^ (4 * h) ^ mt) << 4);
#pragma unroll
            for (int c = 0; c < 4; c++) {
                if (c == 3) mbar_wait(bar0 + 8 * B_SFREE, 0);
                mbar_wait(fbar + 32 * (c % 3), c / 3);
                STAMP(36 + c);
                uint32_t af[16][4];
#pragma unroll
                for (int i = 0; i < 16; i++) ldsm4t(af[i], (c == 1 ? slot1 : c == 2 ? slot2 : slot0) + ko[i & 7] + (i >> 3) * 2048);
                __syncwarp();
                if (c < 3 && elect_one()) mbar_arrive_n(bar0 + 8 * (B_FREE + 4 * c + a), slot_priv(4 * c + a) ? 2 : 1);
                xq[c][0] |= after_all(af, p.zero);
#pragma unroll 1
                do {
#pragma unroll
                    for (int i = 0; i < 16; i++) mma_v(gacc[i & 7], af[i], xq[c][2 * (i >> 3)], xq[c][2 * (i >> 3) + 1]);
                } while (p.zero & (1u << c));
                STAMP(52 + c);
            }
            STAMP(13);
#pragma unroll
            for (int mt = 0; mt < 8; mt++) sts128f(slot0 + mt * 512 + lane * 16, gacc[mt]);
            named_sync(1, 128);
            const uint32_t base = sb + OFF_RING + 16 * tid;
            {
                const float4 p0 = lds128f(base + 2048), p1 = lds128f(base + 10240), p2 = lds128f(base + 18432), p3 = lds128f(base + 26624);
                st_async128(mapa(sb + OFF_XCH + 16 * tid, h ^ 1), __float_as_uint((p0.x + p1.x) + (p2.x + p3.x)), __float_as_uint((p0.y + p1.y) + (p2.y + p3.y)),
                            __float_as_uint((p0.z + p1.z) + (p2.z + p3.z)), __float_as_uint((p0.w + p1.w) + (p2.w + p3.w)), mapa(abar, h ^ 1));
            }
            STAMP(56);
            const float4 p0 = lds128f(base), p1 = lds128f(base + 8192), p2 = lds128f(base + 16384), p3 = lds128f(base + 24576);
            const float r0 = lds32f(misc + 52 + 16 * t), r1 = lds32f(misc + 60 + 16 * t);
            const float4 own = make_float4((p0.x + p1.x) + (p2.x + p3.x), (p0.y + p1.y) + (p2.y + p3.y), (p0.z + p1.z) + (p2.z + p3.z), (p0.w + p1.w) + (p2.w + p3.w));
            mbar_wait(abar, aph);
            aph ^= 1;
            STAMP(57);
            const float4 oth = lds128f(sb + OFF_XCH + 16 * tid);
            const float g0 = bf_round((own.x + oth.x) * r0), g1 = bf_round((own.y + oth.y) * r1);
            const float h0 = bf_round(g0 * rcpf(1.f + ex2f(-1.4426950408889634f * g0))) * bf_round((own.z + oth.z) * r0);
            const float h1 = bf_round(g1 * rcpf(1.f + ex2f(-1.4426950408889634f * g1))) * bf_round((own.w + oth.w) * r1);
            uint32_t hw;
            asm volatile("movmatrix.sync.aligned.m8n8.trans.b16 %0, %1;" : "=r"(hw) : "r"(pack_bf16(h0, h1)));
            sts32(sb + OFF_RING + 7168 + 16 * lane + 4 * a, hw);
            STAMP(58);
            named_sync(1, 128);
            const uint4 q = lds128(sb + OFF_RING + 7168 + 16 * lane);
            st_relaxed_128(pubh, q.x, q.y, q.z, (q.w & ~1u) | (tag & 1));
            if (lane == 0) red_add(cnt_h, 1);
            STAMP(14);
        }
        float dacc[4];
        {
            uint32_t wo = (r + ((m >> 1) << 3)) * 32 + (((m & 1) ^ (r >> 2)) << 4), af[14][4];
            pin(wo);
            float d[7][4];
#pragma unroll
            for (int i = 0; i < 7; i++) { d[i][0] = d[i][1] = d[i][2] = d[i][3] = 0.f; }
            mbar_wait(fbar + 32, has_gu);
#pragma unroll
            for (int j = 0; j < 14; j++) ldsm4t(af[j], slot1 + wo + j * 512);
            wait_count(&in->n_h[32 * (4 * h + a)], 14 * tag - FEW_H);
            STAMP(33);
            uint4 hq[14];
#pragma unroll 1
            for (uint32_t it = 0;; spin_guard(it)) {
                uint32_t bad = 0;
                if (elect_one()) {
                    mbar_expect_tx(abar, 7168);
                    bulk_g2s(slot0, &in->h[(56 * h + 14 * a) * 32], 7168, abar);
                }
                mbar_wait(abar, aph);
                aph ^= 1;
#pragma unroll
                for (int j = 0; j < 14; j++) { hq[j] = lds128(slot0 + 512 * j + 16 * lane); bad = or_xor(bad, hq[j].w, tag); }
                if (__all_sync(0xffffffffu, (bad & 1) == 0)) break;
            }
            STAMP(15);
#pragma unroll
            for (int s = 0; s < 2; s++) {
                if (s) {
                    mbar_wait(fbar + 64, has_gu);
#pragma unroll
                    for (int j = 0; j < 14; j++) ldsm4t(af[j], slot2 + wo + j * 512);
                }
                const bool more = __any_sync(0xffffffffu, after_all(af, p.zero));
#pragma unroll 1
                do {
#pragma unroll
                    for (int j = 0; j < 14; j++) {
                        const uint4 q = hq[7 * s + (j >> 1)];
                        mma_v(d[j % 7], af[j], (j & 1) ? q.z : q.x, (j & 1) ? q.w : q.y);
                    }
                } while (more);
            }
#pragma unroll
            for (int j = 0; j < 4; j++) dacc[j] = ((d[0][j] + d[1][j]) + (d[2][j] + d[3][j])) + ((d[4][j] + d[5][j]) + d[6][j]);
        }
        STAMP(16);
        {
            sts128f(slot0 + 7680 + lane * 16, dacc);
            named_sync(1, 128);
            const int tk = tid >> 4, col = tid & 15;
            const uint32_t base = sb + OFF_RING + 7680 + ((col & 7) * 4 + (tk >> 1)) * 16 + (((col >> 3) << 1) + (tk & 1)) * 4;
            const float y0 = (lds32f(base) + lds32f(base + 8192)) + (lds32f(base + 16384) + lds32f(base + 24576));
            const uint32_t red = sb + tab_off(tk) + T_RED + 4 * col, key = lds32(misc + 48 + 8 * tk);
            mbar_wait(bar0 + 8 * B_SFREE, 0);
            asm volatile("st.async.weak.shared::cluster.mbarrier::complete_tx::bytes.f32 [%0], %1, [%2];"
                         ::"r"(mapa(red, h ^ 1)), "f"(y0), "r"(mapa(bar0 + 8 * B_RED, h ^ 1)) : "memory");
            const float rv = __uint_as_float(unorder_key(key >> 16) << 16);
            const float sg = bf_round(rcpf(1.f + ex2f(-1.4426950408889634f * rv)));
            mbar_wait(bar0 + 8 * B_RED, 0);
            sts32f(red, bf_round(y0 + lds32f(red)) * sg);
            __syncwarp();
            if (elect_one()) mbar_arrive(bar0 + 8 * B_UPD);
        }
        STAMP(17); GSTAMP(29);
    }
}

typedef CUresult (*EncodeFn)(CUtensorMap*, CUtensorMapDataType, cuuint32_t, void*, const cuuint64_t*, const cuuint64_t*,
                             const cuuint32_t*, const cuuint32_t*, CUtensorMapInterleave, CUtensorMapSwizzle,
                             CUtensorMapL2promotion, CUtensorMapFloatOOBfill);

void make_map(EncodeFn enc, CUtensorMap* m, const void* ptr, uint64_t cols, uint64_t rows, uint32_t bc, uint32_t br,
              CUtensorMapSwizzle sw, CUtensorMapL2promotion pr) {
    cuuint64_t dims[2] = {cols, rows};
    cuuint64_t str[1] = {cols * 2};
    cuuint32_t box[2] = {bc, br};
    cuuint32_t es[2] = {1, 1};
    enc(m, CU_TENSOR_MAP_DATA_TYPE_BFLOAT16, 2, const_cast<void*>(ptr), dims, str, box, es, CU_TENSOR_MAP_INTERLEAVE_NONE, sw, pr,
        CU_TENSOR_MAP_FLOAT_OOB_FILL_NONE);
}
void make_tile_map(EncodeFn enc, CUtensorMap* m, const void* ptr) {
    cuuint64_t dims[4] = {DM, 4, 16, SEQ / 64};
    cuuint64_t str[3] = {16 * DM * 2, DM * 2, 64 * DM * 2};
    cuuint32_t box[4] = {16, 4, 2, 8};
    cuuint32_t es[4] = {1, 1, 1, 1};
    enc(m, CU_TENSOR_MAP_DATA_TYPE_BFLOAT16, 4, const_cast<void*>(ptr), dims, str, box, es, CU_TENSOR_MAP_INTERLEAVE_NONE,
        CU_TENSOR_MAP_SWIZZLE_32B, CU_TENSOR_MAP_L2_PROMOTION_NONE, CU_TENSOR_MAP_FLOAT_OOB_FILL_NONE);
}

}

#define WD_PROMO CU_TENSOR_MAP_L2_PROMOTION_L2_64B
extern "C" void kernel_launch(void* const* d_in, const int* in_sizes, int n_in, void* d_out, int out_size) {
    (void)in_sizes; (void)n_in; (void)out_size;
    static EncodeFn enc = nullptr;
    static void* scratch = nullptr;
    if (!enc) {
        void* fn = nullptr;
        cudaDriverEntryPointQueryResult q;
        cudaGetDriverEntryPoint("cuTensorMapEncodeTiled", &fn, cudaEnableDefault, &q);
        enc = (EncodeFn)fn;
        cudaGetSymbolAddress(&scratch, g_scratch);
        cudaFuncSetAttribute(fused_kernel, cudaFuncAttributeMaxDynamicSharedMemorySize, SMEM_BYTES);
    }
    Maps maps;
    make_tile_map(enc, &maps.u, d_in[0]);
    make_tile_map(enc, &maps.out, d_out);
    make_map(enc, &maps.wg, d_in[9], FF, DM, 64, 32, CU_TENSOR_MAP_SWIZZLE_128B, CU_TENSOR_MAP_L2_PROMOTION_L2_128B);
    make_map(enc, &maps.wu, d_in[10], FF, DM, 64, 32, CU_TENSOR_MAP_SWIZZLE_128B, CU_TENSOR_MAP_L2_PROMOTION_L2_128B);
    make_map(enc, &maps.wd, d_in[11], DM, FF, 16, 224, CU_TENSOR_MAP_SWIZZLE_32B, WD_PROMO);
    Ptrs p;
    p.sc = (Scratch*)scratch;
    p.u = (const __nv_bfloat16*)d_in[0];
    p.logA = (const __nv_bfloat16*)d_in[1];
    p.Aim = (const __nv_bfloat16*)d_in[2];
    p.Cre = (const __nv_bfloat16*)d_in[3];
    p.Cim = (const __nv_bfloat16*)d_in[4];
    p.ldt = (const __nv_bfloat16*)d_in[5];
    p.dsk = (const __nv_bfloat16*)d_in[6];
    p.wr = (const __nv_bfloat16*)d_in[8];
    p.out = (__nv_bfloat16*)d_out;
    p.zero = 0;
    fused_kernel<<<NCTA, NTHR, SMEM_BYTES, cudaStreamPerThread>>>(p, maps);
}
```

```cpp
#include <cuda_runtime.h>
#include <cuda_bf16.h>
#include <cuda_fp16.h>
#include <cuda.h>
#include <stdint.h>

namespace {

constexpr int SEQ = 2048, DM = 1024, NMODE = 128, FF = 3584;
constexpr int NCTA = 128, NTHR = 512;
constexpr int GU_CTAS = 112;
constexpr int NREP = 4;

constexpr int OFF_XT = 0;
constexpr int OFF_RING = 65536;
constexpr int OFF_PRIV = OFF_RING + 65536;
constexpr int OFF_VT = OFF_PRIV + 65536;
constexpr int VT_PAD = 32, VT_PLANE = VT_PAD + 2048, VT_PITCH = 2 * VT_PLANE, ROW_PITCH = 2064;
constexpr int OFF_BAR = OFF_VT + 8 * VT_PITCH;
constexpr int OFF_MISC = OFF_BAR + 384;
constexpr int OFF_XCH = OFF_MISC + 112;
constexpr int SMEM_BYTES = OFF_XCH + 2048;
constexpr int OFF_LN = OFF_RING + 7 * 8192;
constexpr int OFF_ST = OFF_RING + 6 * 8192;
static_assert(SMEM_BYTES <= 232448, "shared memory");

constexpr int B_ROW = 0, B_XT = 4, B_V = 5, B_LN = 6, B_SFREE = 7, B_RECV = 8, B_RED = 10, B_UPD = 11, B_ST = 12, B_XFREE = 16, B_FREE = 20, B_FULL = 32, B_AUX = 44, NBAR = 48;

constexpr int T_DENSE = 60;
constexpr int T_PATCH = 2208;
constexpr int T_R2 = 2368;
constexpr int T_R3 = 3296;

constexpr int T_RED = 4032;
__device__ __forceinline__ bool slot_priv(int s) { return (uint32_t)(s - 6) < 4u; }
__device__ __forceinline__ uint32_t slot_off(int s) { return slot_priv(s) ? OFF_PRIV + 4096 + (s & 3) * 16384 : OFF_RING + (s < 6 ? s : s - 4) * 8192; }
__device__ __forceinline__ uint32_t tab_off(int w) { return OFF_PRIV + w * 8192 + (w & 1) * 4096; }

constexpr uint32_t SPIN_LIMIT = 1u << 20;
#define KG_UNROLL 4
constexpr int kKgUnroll = KG_UNROLL;
#define BB_UNROLL 2
constexpr int kBbUnroll = BB_UNROLL;
#define DENSE_UNROLL 1
constexpr int kDenseUnroll = DENSE_UNROLL;
#define ST_T0 2600
#define LN_PAUSE 0xf0
#define FEW_ST 0
#define FEW_H 0
#define PERM 2
#define PERM_OFF 60
#define STORE_AT 12
#define ST_LATE 16
#define ST_GAP 0
#define ST_PER 290
#define ST_PER2 290

struct Exchange {
    uint2 stat[SEQ];
    uint4 h[GU_CTAS * 32];
    uint32_t n_stat[4 * 32];
    uint32_t n_h[8 * 32];
};
struct Scratch {
    Exchange x[NREP];
    uint32_t epoch;
};
__device__ __align__(128) Scratch g_scratch;

struct Ptrs {
    Scratch* sc;
    const __nv_bfloat16 *logA, *Aim, *Cre, *Cim, *ldt, *dsk, *u, *wr;
    __nv_bfloat16* out;
    uint32_t zero;
};
struct Maps {
    CUtensorMap u, out, wg, wu, wd;
};

#define STAMP(i) do { } while (0)
#define KSTAMP(i) do { } while (0)
#define GSTAMP(i) do { } while (0)

__device__ __forceinline__ uint32_t s_u32(const void* p) { return (uint32_t)__cvta_generic_to_shared(p); }
__device__ __forceinline__ void mbar_init(uint32_t b, uint32_t n) {
    asm volatile("mbarrier.init.shared::cta.b64 [%0], %1;" ::"r"(b), "r"(n) : "memory");
}
__device__ __forceinline__ void mbar_expect_tx(uint32_t b, uint32_t bytes) {
    asm volatile("mbarrier.arrive.expect_tx.shared::cta.b64 _, [%0], %1;" ::"r"(b), "r"(bytes) : "memory");
}
__device__ __forceinline__ void mbar_arrive(uint32_t b) {
    asm volatile("mbarrier.arrive.shared::cta.b64 _, [%0];" ::"r"(b) : "memory");
}
__device__ __forceinline__ void mbar_arrive_n(uint32_t b, uint32_t n) {
    asm volatile("mbarrier.arrive.shared::cta.b64 _, [%0], %1;" ::"r"(b), "r"(n) : "memory");
}
__device__ __forceinline__ void mbar_arrive_peer(uint32_t b_cluster) {
    asm volatile("mbarrier.arrive.relaxed.cluster.shared::cluster.b64 _, [%0];" ::"r"(b_cluster) : "memory");
}
__device__ __forceinline__ void mbar_wait(uint32_t b, uint32_t parity) {
    asm volatile("{\n\t.reg .pred p;\n\t.reg .u32 c;\n\tmov.u32 c, 0;\n"
                 "W:\n\tmbarrier.try_wait.parity.shared::cta.b64 p, [%0], %1;\n\t@p bra D;\n\t"
                 "add.u32 c, c, 1;\n\tsetp.lt.u32 p, c, 1048576;\n\t@p bra W;\n\ttrap;\nD:\n\t}"
                 ::"r"(b), "r"(parity) : "memory");
}
__device__ __forceinline__ bool mbar_test(uint32_t b, uint32_t parity) {
    uint32_t ok;
    asm volatile("{ .reg .pred p; mbarrier.test_wait.parity.shared::cta.b64 p, [%1], %2; selp.u32 %0, 1, 0, p; }" : "=r"(ok) : "r"(b), "r"(parity) : "memory");
    return __all_sync(0xffffffffu, ok != 0);
}
__device__ __forceinline__ bool elect_one() {
    uint32_t p;
    asm volatile("{ .reg .pred P; elect.sync _|P, 0xffffffff; selp.u32 %0, 1, 0, P; }" : "=r"(p));
    return p != 0;
}
__device__ __forceinline__ uint32_t mapa(uint32_t a, uint32_t rank) {
    uint32_t r;
    asm("mapa.shared::cluster.u32 %0, %1, %2;" : "=r"(r) : "r"(a), "r"(rank));
    return r;
}
__device__ __forceinline__ void cluster_arrive() { asm volatile("barrier.cluster.arrive.relaxed.aligned;" ::: "memory"); }
__device__ __forceinline__ void cluster_wait() { asm volatile("barrier.cluster.wait.acquire.aligned;" ::: "memory"); }
__device__ __forceinline__ void tma_load_2d(uint32_t dst, const CUtensorMap* m, int c0, int c1, uint32_t bar) {
    asm volatile("cp.async.bulk.tensor.2d.shared::cluster.global.mbarrier::complete_tx::bytes [%0], [%1, {%3, %4}], [%2];"
                 ::"r"(dst), "l"(m), "r"(bar), "r"(c0), "r"(c1) : "memory");
}
__device__ __forceinline__ void tma_load_perm(uint32_t dst, const CUtensorMap* m, int c0, int blk, uint32_t bar) {
    asm volatile("cp.async.bulk.tensor.5d.shared::cluster.global.mbarrier::complete_tx::bytes [%0], [%1, {%3, %4, %4, %4, %5}], [%2];"
                 ::"r"(dst), "l"(m), "r"(bar), "r"(c0), "r"(0), "r"(blk) : "memory");
}
__device__ __forceinline__ void tma_load_tile(uint32_t dst, const CUtensorMap* m, int c0, int c2, int c3, uint32_t bar) {
    asm volatile("cp.async.bulk.tensor.4d.shared::cluster.global.mbarrier::complete_tx::bytes.multicast::cluster [%0], [%1, {%3, %4, %5, %6}], [%2], %7;"
                 ::"r"(dst), "l"(m), "r"(bar), "r"(c0), "r"(0), "r"(c2), "r"(c3), "h"((uint16_t)3) : "memory");
}
__device__ __forceinline__ void tma_store_tile(const CUtensorMap* m, uint32_t src, int c0, int c2, int c3) {
    asm volatile("cp.async.bulk.tensor.4d.global.shared::cta.bulk_group [%0, {%2, %3, %4, %5}], [%1];"
                 ::"l"(m), "r"(src), "r"(c0), "r"(0), "r"(c2), "r"(c3) : "memory");
    asm volatile("cp.async.bulk.commit_group;" ::: "memory");
}
__device__ __forceinline__ void bulk_g2s(uint32_t dst, const void* src, uint32_t bytes, uint32_t bar) {
    asm volatile("cp.async.bulk.shared::cluster.global.mbarrier::complete_tx::bytes [%0], [%1], %2, [%3];"
                 ::"r"(dst), "l"(src), "r"(bytes), "r"(bar) : "memory");
}
__device__ __forceinline__ void cp_async16(uint32_t dst, const void* src) {
    asm volatile("cp.async.cg.shared.global [%0], [%1], 16;" ::"r"(dst), "l"(src) : "memory");
}
__device__ __forceinline__ void st_async128(uint32_t dst_cluster, uint32_t x, uint32_t y, uint32_t z, uint32_t w, uint32_t bar_cluster) {
    asm volatile("st.async.weak.shared::cluster.mbarrier::complete_tx::bytes.v4.b32 [%0], {%1,%2,%3,%4}, [%5];"
                 ::"r"(dst_cluster), "r"(x), "r"(y), "r"(z), "r"(w), "r"(bar_cluster) : "memory");
}
__device__ __forceinline__ void fence_async() { asm volatile("fence.proxy.async.shared::cta;" ::: "memory"); }
__device__ __forceinline__ void named_sync(int id, int n) { asm volatile("bar.sync %0, %1;" ::"r"(id), "r"(n) : "memory"); }

__device__ __forceinline__ void ldsm4(uint32_t* r, uint32_t a) {
    asm volatile("ldmatrix.sync.aligned.m8n8.x4.shared.b16 {%0,%1,%2,%3}, [%4];"
                 : "=r"(r[0]), "=r"(r[1]), "=r"(r[2]), "=r"(r[3]) : "r"(a));
}
__device__ __forceinline__ void ldsm4t(uint32_t* r, uint32_t a) {
    asm volatile("ldmatrix.sync.aligned.m8n8.x4.trans.shared.b16 {%0,%1,%2,%3}, [%4];"
                 : "=r"(r[0]), "=r"(r[1]), "=r"(r[2]), "=r"(r[3]) : "r"(a));
}
__device__ __forceinline__ void stsm4t(uint32_t a, uint32_t x, uint32_t y, uint32_t z, uint32_t w) {
    asm volatile("stmatrix.sync.aligned.m8n8.x4.trans.shared.b16 [%0], {%1,%2,%3,%4};"
                 ::"r"(a), "r"(x), "r"(y), "r"(z), "r"(w) : "memory");
}
__device__ __forceinline__ uint32_t lds32(uint32_t a) { uint32_t v; asm volatile("ld.shared.u32 %0, [%1];" : "=r"(v) : "r"(a)); return v; }
__device__ __forceinline__ float lds32f(uint32_t a) { float v; asm volatile("ld.shared.f32 %0, [%1];" : "=f"(v) : "r"(a)); return v; }
__device__ __forceinline__ uint2 lds64(uint32_t a) { uint2 v; asm volatile("ld.shared.v2.u32 {%0,%1}, [%2];" : "=r"(v.x), "=r"(v.y) : "r"(a)); return v; }
__device__ __forceinline__ uint4 lds128(uint32_t a) {
    uint4 v; asm volatile("ld.shared.v4.u32 {%0,%1,%2,%3}, [%4];" : "=r"(v.x), "=r"(v.y), "=r"(v.z), "=r"(v.w) : "r"(a)); return v;
}
__device__ __forceinline__ uint4 lds128v(uint32_t a) {
    uint4 v; asm volatile("ld.volatile.shared.v4.u32 {%0,%1,%2,%3}, [%4];" : "=r"(v.x), "=r"(v.y), "=r"(v.z), "=r"(v.w) : "r"(a)); return v;
}
__device__ __forceinline__ uint32_t or_xor(uint32_t a, uint32_t b, uint32_t c) {
    uint32_t r; asm("lop3.b32 %0, %1, %2, %3, 0xf6;" : "=r"(r) : "r"(a), "r"(b), "r"(c)); return r;
}
__device__ __forceinline__ float4 lds128f(uint32_t a) {
    float4 v; asm volatile("ld.shared.v4.f32 {%0,%1,%2,%3}, [%4];" : "=f"(v.x), "=f"(v.y), "=f"(v.z), "=f"(v.w) : "r"(a)); return v;
}
__device__ __forceinline__ void sts32(uint32_t a, uint32_t v) { asm volatile("st.shared.u32 [%0], %1;" ::"r"(a), "r"(v) : "memory"); }
__device__ __forceinline__ void sts32f(uint32_t a, float v) { asm volatile("st.shared.f32 [%0], %1;" ::"r"(a), "f"(v) : "memory"); }
__device__ __forceinline__ void sts64(uint32_t a, uint32_t x, uint32_t y) { asm volatile("st.shared.v2.u32 [%0], {%1,%2};" ::"r"(a), "r"(x), "r"(y) : "memory"); }
__device__ __forceinline__ void sts64f(uint32_t a, float x, float y) { asm volatile("st.shared.v2.f32 [%0], {%1,%2};" ::"r"(a), "f"(x), "f"(y) : "memory"); }
__device__ __forceinline__ void sts128(uint32_t a, uint32_t x, uint32_t y, uint32_t z, uint32_t w) {
    asm volatile("st.shared.v4.u32 [%0], {%1,%2,%3,%4};" ::"r"(a), "r"(x), "r"(y), "r"(z), "r"(w) : "memory");
}
__device__ __forceinline__ void sts128f(uint32_t a, const float* v) {
    asm volatile("st.shared.v4.f32 [%0], {%1,%2,%3,%4};" ::"r"(a), "f"(v[0]), "f"(v[1]), "f"(v[2]), "f"(v[3]) : "memory");
}
__device__ __forceinline__ uint4 ldg128(const void* p) {
    uint4 v; asm volatile("ld.global.nc.L1::no_allocate.v4.u32 {%0,%1,%2,%3}, [%4];" : "=r"(v.x), "=r"(v.y), "=r"(v.z), "=r"(v.w) : "l"(p)); return v;
}
__device__ __forceinline__ uint2 ldg64(const void* p) {
    uint2 v; asm volatile("ld.global.nc.L1::no_allocate.v2.u32 {%0,%1}, [%2];" : "=r"(v.x), "=r"(v.y) : "l"(p)); return v;
}
__device__ __forceinline__ uint32_t ldg32(const void* p) {
    uint32_t v; asm volatile("ld.global.nc.u32 %0, [%1];" : "=r"(v) : "l"(p)); return v;
}
__device__ __forceinline__ uint32_t ldg16(const void* p) {
    uint32_t v; asm volatile("ld.global.nc.u16 %0, [%1];" : "=r"(v) : "l"(p)); return v;
}
__device__ __forceinline__ uint4 ld_relaxed_128(const void* p) {
    uint4 v; asm volatile("ld.relaxed.gpu.global.v4.u32 {%0,%1,%2,%3}, [%4];" : "=r"(v.x), "=r"(v.y), "=r"(v.z), "=r"(v.w) : "l"(p) : "memory"); return v;
}
__device__ __forceinline__ void ld_relaxed_128_unless(uint4& q, const void* p, bool have) {
    asm volatile("{ .reg .pred p; setp.eq.u32 p, %5, 0; @p ld.relaxed.gpu.global.v4.u32 {%0,%1,%2,%3}, [%4]; }"
                 : "+r"(q.x), "+r"(q.y), "+r"(q.z), "+r"(q.w) : "l"(p), "r"((uint32_t)have) : "memory");
}
__device__ __forceinline__ uint2 ld_relaxed_64(const void* p) {
    uint2 v; asm volatile("ld.relaxed.gpu.global.v2.u32 {%0,%1}, [%2];" : "=r"(v.x), "=r"(v.y) : "l"(p) : "memory"); return v;
}
__device__ __forceinline__ uint32_t ld_relaxed_32(const void* p) {
    uint32_t v; asm volatile("ld.relaxed.gpu.global.u32 %0, [%1];" : "=r"(v) : "l"(p) : "memory"); return v;
}
__device__ __forceinline__ void st_relaxed_128(void* p, uint32_t x, uint32_t y, uint32_t z, uint32_t w) {
    asm volatile("st.relaxed.gpu.global.v4.u32 [%0], {%1,%2,%3,%4};" ::"l"(p), "r"(x), "r"(y), "r"(z), "r"(w) : "memory");
}
__device__ __forceinline__ void st_relaxed_64(void* p, uint32_t x, uint32_t y) {
    asm volatile("st.relaxed.gpu.global.v2.u32 [%0], {%1,%2};" ::"l"(p), "r"(x), "r"(y) : "memory");
}
__device__ __forceinline__ void st_relaxed_32(void* p, uint32_t v) {
    asm volatile("st.relaxed.gpu.global.u32 [%0], %1;" ::"l"(p), "r"(v) : "memory");
}
__device__ __forceinline__ void red_add(void* p, uint32_t v) { asm volatile("red.relaxed.gpu.global.add.u32 [%0], %1;" ::"l"(p), "r"(v) : "memory"); }
__device__ __forceinline__ uint32_t now_ns() { uint32_t t; asm volatile("mov.u32 %0, %%globaltimer_lo;" : "=r"(t) :: "memory"); return t; }
__device__ __forceinline__ void spin_guard(uint32_t& it) { if (++it > SPIN_LIMIT) __trap(); }
__device__ __forceinline__ void wait_count(const uint32_t* p, uint32_t target) {
#pragma unroll 1
    for (uint32_t it = 0; __any_sync(0xffffffffu, (int)(ld_relaxed_32(p) - target) < 0); spin_guard(it)) { }
}
__device__ __forceinline__ void mma_bf16(float* c, uint32_t a0, uint32_t a1, uint32_t a2, uint32_t a3, uint32_t b0, uint32_t b1) {
    asm("mma.sync.aligned.m16n8k16.row.col.f32.bf16.bf16.f32 {%0,%1,%2,%3}, {%4,%5,%6,%7}, {%8,%9}, {%0,%1,%2,%3};"
                 : "+f"(c[0]), "+f"(c[1]), "+f"(c[2]), "+f"(c[3]) : "r"(a0), "r"(a1), "r"(a2), "r"(a3), "r"(b0), "r"(b1));
}
__device__ __forceinline__ void mma_bf16_k8(float* c, uint32_t a0, uint32_t a1, uint32_t b0) {
    asm("mma.sync.aligned.m16n8k8.row.col.f32.bf16.bf16.f32 {%0,%1,%2,%3}, {%4,%5}, {%6}, {%0,%1,%2,%3};"
                 : "+f"(c[0]), "+f"(c[1]), "+f"(c[2]), "+f"(c[3]) : "r"(a0), "r"(a1), "r"(b0));
}
__device__ __forceinline__ void mma_v(float* c, const uint32_t* a, uint32_t b0, uint32_t b1) {
    asm volatile("mma.sync.aligned.m16n8k16.row.col.f32.bf16.bf16.f32 {%0,%1,%2,%3}, {%4,%5,%6,%7}, {%8,%9}, {%0,%1,%2,%3};"
                 : "+f"(c[0]), "+f"(c[1]), "+f"(c[2]), "+f"(c[3]) : "r"(a[0]), "r"(a[1]), "r"(a[2]), "r"(a[3]), "r"(b0), "r"(b1));
}
__device__ __forceinline__ void mma_bf16_z(float* c, uint32_t a0, uint32_t a1, uint32_t a2, uint32_t a3, uint32_t b0, uint32_t b1) {
    asm volatile("mma.sync.aligned.m16n8k16.row.col.f32.bf16.bf16.f32 {%0,%1,%2,%3}, {%4,%5,%6,%7}, {%8,%9}, {%10,%10,%10,%10};"
        : "=f"(c[0]), "=f"(c[1]), "=f"(c[2]), "=f"(c[3]) : "r"(a0), "r"(a1), "r"(a2), "r"(a3), "r"(b0), "r"(b1), "f"(0.f));
}
__device__ __forceinline__ void mma_f16(float* c, uint32_t a0, uint32_t a1, uint32_t a2, uint32_t a3, uint32_t b0, uint32_t b1) {
    asm("mma.sync.aligned.m16n8k16.row.col.f32.f16.f16.f32 {%0,%1,%2,%3}, {%4,%5,%6,%7}, {%8,%9}, {%0,%1,%2,%3};"
                 : "+f"(c[0]), "+f"(c[1]), "+f"(c[2]), "+f"(c[3]) : "r"(a0), "r"(a1), "r"(a2), "r"(a3), "r"(b0), "r"(b1));
}
__device__ __forceinline__ uint32_t pack_bf16(float lo, float hi) {
    uint32_t r; asm("cvt.rn.bf16x2.f32 %0, %1, %2;" : "=r"(r) : "f"(hi), "f"(lo)); return r;
}
__device__ __forceinline__ uint32_t pack_v(float lo, float hi) {
    uint32_t r; asm volatile("cvt.rn.bf16x2.f32 %0, %1, %2;" : "=r"(r) : "f"(hi), "f"(lo)); return r;
}
__device__ __forceinline__ uint32_t pack_w(float lo, float hi) {
    uint32_t r; asm volatile("cvt.rn.satfinite.bf16x2.f32 %0, %1, %2;" : "=r"(r) : "f"(hi), "f"(lo)); return r;
}
template <int N> __device__ __forceinline__ uint32_t after_all(const uint32_t (&f)[N][4], uint32_t zero) {
    uint32_t d[3] = {0, 0, 0};
#pragma unroll
    for (int i = 0; i < N; i++) d[i % 3] |= f[i][3];
    return (d[0] | d[1] | d[2]) & zero;
}
__device__ __forceinline__ void pin(uint32_t& x) { asm volatile("" : "+r"(x)); }
template <class T> __device__ __forceinline__ void pin(T*& x) { asm volatile("" : "+l"(x)); }
__device__ __forceinline__ uint32_t pack_f16(float lo, float hi) {
    uint32_t r; asm("cvt.rn.f16x2.f32 %0, %1, %2;" : "=r"(r) : "f"(hi), "f"(lo)); return r;
}
__device__ __forceinline__ float bf_lo(uint32_t v) { return __uint_as_float(v << 16); }
__device__ __forceinline__ float bf_hi(uint32_t v) { return __uint_as_float(v & 0xffff0000u); }
__device__ __forceinline__ float bf_round(float x) { return __uint_as_float(pack_bf16(0.f, x)); }
__device__ __forceinline__ uint32_t badd2(uint32_t a, uint32_t b) { uint32_t r; asm("add.rn.bf16x2 %0, %1, %2;" : "=r"(r) : "r"(a), "r"(b)); return r; }
__device__ __forceinline__ uint32_t bsub2_lo(uint32_t a, uint32_t b) {
    uint32_t r; asm("{ .reg .b16 m, h; .reg .b32 m2; mov.b32 {m, h}, %2; mov.b32 m2, {m, m}; sub.rn.bf16x2 %0, %1, m2; }" : "=r"(r) : "r"(a), "r"(b)); return r;
}
__device__ __forceinline__ uint32_t bmax2(uint32_t a, uint32_t b) { uint32_t r; asm("max.bf16x2 %0, %1, %2;" : "=r"(r) : "r"(a), "r"(b)); return r; }
__device__ __forceinline__ uint32_t normalize2(uint32_t x, uint32_t s0, uint32_t s1) {
    uint32_t r;
    asm("{ .reg .b16 m, h, l, k; .reg .b32 m2, h2, l2, d, t;\n\t"
        "mov.b32 {m, h}, %2; mov.b32 {l, k}, %3; mov.b32 m2, {m, m}; mov.b32 h2, {h, h}; mov.b32 l2, {l, l};\n\t"
        "sub.rn.bf16x2 d, %1, m2; mul.rn.bf16x2 t, d, l2; fma.rn.bf16x2 %0, d, h2, t; }" : "=r"(r) : "r"(x), "r"(s0), "r"(s1));
    return r;
}
__device__ __forceinline__ float rcpf(float x) { float r; asm("rcp.approx.ftz.f32 %0, %1;" : "=f"(r) : "f"(x)); return r; }
__device__ __forceinline__ float sqrtaf(float x) { float r; asm("sqrt.approx.ftz.f32 %0, %1;" : "=f"(r) : "f"(x)); return r; }
__device__ __forceinline__ float ex2f(float x) { float r; asm("ex2.approx.ftz.f32 %0, %1;" : "=f"(r) : "f"(x)); return r; }

__device__ __forceinline__ int tok_off(int t) { return ((t >> 3) & 1) * VT_PLANE + (t >> 4) * 16 + (t & 7) * 2; }

__device__ __forceinline__ uint32_t order_key(uint32_t b16) { return b16 ^ ((b16 & 0x8000u) ? 0xffffu : 0x8000u); }
__device__ __forceinline__ uint32_t unorder_key(uint32_t k16) { return k16 ^ ((k16 & 0x8000u) ? 0x8000u : 0xffffu); }

struct cplx { float r, i; };
struct hc { uint32_t r, i; };
template <bool CONJ> __device__ __forceinline__ cplx csq(cplx a) {
    float im;
    asm("{ .reg .f32 t; mul.ftz.f32 t, %1, %2; mul.ftz.f32 %0, t, 0f40000000; }" : "=f"(im) : "f"(CONJ ? -a.r : a.r), "f"(a.i));
    return {fmaf(a.r, a.r, -(a.i * a.i)), im};
}
__device__ __forceinline__ cplx cexpp(float a2, float ai) {
    float m = ex2f(a2), s, c;
    __sincosf(ai, &s, &c);
    return {m * c, m * s};
}
__device__ __forceinline__ __half2 as_h2(uint32_t x) { return *reinterpret_cast<__half2*>(&x); }
__device__ __forceinline__ uint32_t as_u(__half2 x) { return *reinterpret_cast<uint32_t*>(&x); }
__device__ __forceinline__ hc hmul(hc a, hc b) {
    return {as_u(__hfma2(as_h2(a.r), as_h2(b.r), __hneg2(__hmul2(as_h2(a.i), as_h2(b.i))))),
            as_u(__hfma2(as_h2(a.r), as_h2(b.i), __hmul2(as_h2(a.i), as_h2(b.r))))};
}
__device__ __forceinline__ hc hpack(cplx a, cplx b) { return {pack_f16(a.r, b.r), pack_f16(a.i, b.i)}; }
__device__ __forceinline__ void sts16(uint32_t a, uint32_t v) { asm volatile("st.shared.u16 [%0], %1;" ::"r"(a), "r"(v) : "memory"); }

struct KgenAddr {
    uint32_t l, h, m2, m3, m4, z, w, wz;
    __device__ __forceinline__ KgenAddr(uint32_t scr, int lane) {
        const int g = lane >> 2, t = lane & 3;
        const uint32_t rec = scr + t * 480;
        l = rec + 16 * g; h = rec + 128 + 8 * g; m2 = rec + 192 + 8 * (g & 1); m3 = rec + 208 + 4 * (g & 2); m4 = rec + 224 + 2 * (g & 4);
        z = scr + 7680 + 16 * t; w = scr + 240 * lane; wz = scr + 7680 + 8 * lane;
        pin(l); pin(h); pin(m2); pin(m3); pin(m4); pin(z); pin(w); pin(wz);
    }
    __device__ __forceinline__ uint32_t any() const { return (l | h | m2) | (m3 | m4 | z) | (w | wz); }
};
template <class Hook, class Hook2>
__device__ __forceinline__ void kgen(const KgenAddr& ad, uint32_t tab, int lane, uint2 la, uint2 aim, uint2 cre, uint2 cim, float dt, float skip, int dch, Hook main_done, Hook2 half_done) {
    const int g = lane >> 2, t = lane & 3;
    const float dt2 = 2.f * dt;
    const uint32_t am = bmax2(bmax2(cre.x & 0x7fff7fffu, cre.y & 0x7fff7fffu), bmax2(cim.x & 0x7fff7fffu, cim.y & 0x7fff7fffu));
    const float mx = dt2 * fmaxf(bf_lo(am), bf_hi(am));
    const uint32_t eb = min(max(__reduce_max_sync(0xffffffffu, __float_as_uint(mx)) >> 23, 1u), 252u);
    const float cscale = dt2 * __uint_as_float((253u - eb) << 23);
    const float scale_inv = __uint_as_float((eb + 1u) << 23);
    float k0 = (bf_lo(cre.x) + bf_hi(cre.x)) + (bf_lo(cre.y) + bf_hi(cre.y));
#pragma unroll
    for (int o = 16; o; o >>= 1) k0 += __shfl_xor_sync(0xffffffffu, k0, o);
    const float ndt = -1.4426950408889634f * dt;
    STAMP(40); KSTAMP(0);

    float acc[5][4];
#pragma unroll
    for (int i = 0; i < 5; i++) { acc[i][0] = acc[i][1] = acc[i][2] = acc[i][3] = 0.f; }

#pragma unroll kBbUnroll
    for (int bb = 0; bb < 2; bb++) {
        cplx z[2][11], cz[2];
#pragma unroll
        for (int e = 0; e < 2; e++) {
            const float lg = e ? bf_hi(la.x) : bf_lo(la.x), ai = (e ? bf_hi(aim.x) : bf_lo(aim.x)) * dt;
            const float cr = (e ? bf_hi(cre.x) : bf_lo(cre.x)) * cscale, ci = (e ? bf_hi(cim.x) : bf_lo(cim.x)) * cscale;
            const float a2 = bf_round(ex2f(lg * 1.4426950408889634f)) * ndt;
            z[e][0] = cexpp(a2, ai);
            z[e][5] = cexpp(a2 * 32.f, ai * -32.f);
#pragma unroll
            for (int i = 1; i < 11; i++) if (i != 5) z[e][i] = (i == 3 || i == 7) ? csq<true>(z[e][i - 1]) : csq<false>(z[e][i - 1]);
            cz[e] = {fmaf(cr, z[e][0].r, -(ci * z[e][0].i)), fmaf(cr, z[e][0].i, ci * z[e][0].r)};
        }
        la.x = la.y; aim.x = aim.y; cre.x = cre.y; cim.x = cim.y;
        const hc z1 = hpack(z[0][0], z[1][0]), z2 = hpack(z[0][1], z[1][1]), z4 = hpack(z[0][2], z[1][2]);
        hc L[8], H[8];
        L[1] = hpack(z[0][3], z[1][3]); L[2] = hpack(z[0][4], z[1][4]); L[4] = hpack(z[0][5], z[1][5]);
        const hc y64 = hpack(z[0][6], z[1][6]), z128 = hpack(z[0][7], z[1][7]), z256 = hpack(z[0][8], z[1][8]);
        const hc z512 = hpack(z[0][9], z[1][9]), z1024 = hpack(z[0][10], z[1][10]);
        H[0] = hpack(cz[0], cz[1]);
        H[1] = hmul(H[0], z1); H[2] = hmul(H[0], z2); H[3] = hmul(H[1], z2);
        L[3] = hmul(L[1], L[2]);
#pragma unroll
        for (int i = 0; i < 4; i++) { H[4 + i] = hmul(H[i], z4); if (i) L[4 + i] = hmul(L[i], L[4]); }
        __syncwarp();
        sts128(ad.w, 0x3c003c00u, y64.r, 0u, y64.i);
#pragma unroll
        for (int i = 1; i < 8; i++) { const hc q = hmul(L[i], y64); sts128(ad.w + 16 * i, L[i].r, q.r, L[i].i, q.i); }
#pragma unroll
        for (int i = 0; i < 4; i++) sts128(ad.w + 128 + 16 * i, H[2 * i].r, H[2 * i].i, H[2 * i + 1].r, H[2 * i + 1].i);
        {
            const hc a = hmul(z256, z1), b = hmul(z256, z128), c = hmul(z256, z2), d = hmul(z512, z4);
            sts128(ad.w + 192, a.r, a.i, b.r, b.i);
            sts128(ad.w + 208, c.r, c.i, z512.r, z512.i);
            sts128(ad.w + 224, d.r, d.i, z1024.r, z1024.i);
            sts64(ad.wz, z128.r, z128.i);
        }
        __syncwarp();
        KSTAMP(1 + 2 * bb);
#pragma unroll kKgUnroll
        for (int k2 = 0; k2 < 4; k2++) {
#pragma unroll
            for (uint32_t s = 0; s < 2; s++) {
                const uint32_t o = k2 * 1920 + s * 240;
                const uint4 l = lds128(ad.l + o);
                const uint2 h0 = lds64(ad.h + o), m2 = lds64(ad.m2 + o), m3 = lds64(ad.m3 + o), m4 = lds64(ad.m4 + o), mz = lds64(ad.z + k2 * 64 + s * 8);
                const hc H0 = {h0.x, h0.y};
                const hc H1 = hmul(H0, {mz.x, mz.y}), H2 = hmul(H0, {m2.x, m2.y}), H3 = hmul(H2, {m3.x, m3.y}), H4 = hmul(H3, {m4.x, m4.y});
                mma_f16(acc[0], l.x, l.y, l.z, l.w, H0.r, H0.i);
                mma_f16(acc[1], l.x, l.y, l.z, l.w, H1.r, H1.i);
                mma_f16(acc[2], l.x, l.y, l.z, l.w, H2.r, H2.i);
                mma_f16(acc[3], l.x, l.y, l.z, l.w, H3.r, H3.i);
                mma_f16(acc[4], l.x, l.y, l.z, l.w, H4.r, H4.i);
            }
        }
        KSTAMP(2 + 2 * bb);
        if (bb == 0) half_done();
    }
    __syncwarp();
    main_done();
    KSTAMP(5);
#pragma unroll
    for (int i = 0; i < 4; i++) sts128(tab + 2048 + 512 * i + 16 * lane, 0, 0, 0, 0);
    if (lane < 15) sts32(tab + 4 * lane, 0);
    __syncwarp();
    const uint32_t d0 = tab + T_DENSE + 4 + 8 * lane, src = (lane + 31) & 31;
    const uint32_t p0 = pack_bf16(fmaf(k0, dt2, skip), 0.f);
    uint32_t prev = p0;
#pragma unroll
    for (int i = 0; i < 4; i++) {
        const uint32_t pk = pack_bf16(acc[i >> 1][2 * (i & 1) + 1] * scale_inv, acc[i >> 1][2 * (i & 1)] * scale_inv);
        sts64(d0 + 256 * i, __byte_perm(pk, __shfl_sync(0xffffffffu, lane == 31 ? prev : pk, src), 0x5432), pk);
        prev = pk;
    }
    const uint32_t w0 = pack_bf16(acc[2][0] * scale_inv, acc[2][1] * scale_inv), w1 = pack_bf16(acc[2][2] * scale_inv, acc[2][3] * scale_inv);
    const uint32_t sa = (lane & 1) ? 0x5410u : 0x5454u, sb2 = (lane & 1) ? 0x1010u : 0x5410u;
#pragma unroll
    for (int hf = 0; hf < 2; hf++) {
        const uint32_t w = hf ? w1 : w0;
        const uint32_t pv = __shfl_sync(0xffffffffu, lane != 31 ? w : hf ? w0 : __byte_perm(prev, w1, 0x5410), src);
        sts64(d0 + 1024 + 256 * hf, __byte_perm(w, pv, sa), __byte_perm(w, pv, sb2));
        sts64(d0 + 1536 + 256 * hf, __byte_perm(w, pv, sa + 0x2222u), __byte_perm(w, pv, sb2 + 0x2222u));
    }
    const uint32_t d3 = tab + T_R2 + 160 + 320 * (t & 1) + 16 * (g >> 1) + 8 * (g & 1) + 4 * (t >> 1), d3n = d3 + (g >= 6 ? 32 : 0);
    const uint32_t d4 = tab + T_R3 + 80 + 160 * t + 4 * g, d4n = d4 + (g >= 6 ? 16 : 0);
    uint32_t p3;
#pragma unroll
    for (int hf = 0; hf < 2; hf++)
#pragma unroll
        for (int e = 0; e < 2; e++) {
            const float v3 = acc[3][2 * hf + e] * scale_inv;
            const uint32_t p4 = pack_bf16(acc[4][2 * hf + e] * scale_inv, 0.f);
            p3 = pack_bf16(v3, v3);
            sts16(d3 + 64 * hf + 160 * e, p3);
            sts16((hf ? d3n : d3) + 64 * hf + 160 * e + 18, p3);
            sts16(d4 + 32 * hf + 80 * e, p4);
            sts16((hf ? d4n : d4) + 32 * hf + 80 * e + 10, p4);
        }
    if (lane == 31) {
        const uint32_t k512 = __byte_perm(w1, 0, 0x3232);
        sts32(tab + T_DENSE, p0);
        sts64(tab + T_DENSE + 4 * 513, k512, k512); sts16(tab + T_DENSE + 4 * 515 + 2, k512);
        sts16(tab + T_PATCH + 4 * 17, p3); sts32(tab + T_PATCH + 4 * 18, p3); sts16(tab + T_PATCH + 4 * 19 + 2, p3);
    }
    __syncwarp();
}

__device__ __forceinline__ void load_toep(uint32_t* a, uint32_t p, uint32_t pz) {
    a[0] = lds32(p); a[1] = lds32(p + 32); a[2] = lds32(pz - 32); a[3] = lds32(pz);
}
#define YIELDS 2
#define YIELD_AT 2
#define DENSE_BLK 4
__device__ __forceinline__ void dense_step(float (&acc)[16][4], uint32_t (&R)[8][4], const uint32_t (&A)[4][4], uint32_t (&An)[4][4],
                                           uint32_t va, uint32_t vmin, uint32_t pn, uint32_t pz, uint32_t zero, int bit, uint32_t& junk) {
#pragma unroll
    for (int i0 = 0; i0 < 8; i0 += DENSE_BLK) {
#pragma unroll 1
        do {
#pragma unroll
            for (int i = i0; i < i0 + DENSE_BLK; i++) {
                const int ip = (i - DENSE_BLK) & 7;
                ldsm4(R[ip], ip == 0 ? max(va - 16, vmin) : va + ip * 128 - (i0 ? 16 : 0));
                if ((i & 1) == 0) load_toep(An[i >> 1], pn + (i >> 1) * 512, pz + (i >> 1) * 512);
#pragma unroll
                for (int ka = 0; ka < 4; ka++) {
                    mma_v(acc[i + ka], A[ka], R[i][0], R[i][1]);
                    if (i + 8 + ka < 16) mma_v(acc[i + 8 + ka], A[ka], R[i][2], R[i][3]);
                }
                if ((YIELDS >> (i - i0)) & 1) asm volatile("xor.b32 %0, %0, %1;" : "+r"(junk) : "r"(__float_as_uint(acc[i + YIELD_AT][0])));
            }
        } while (zero & (1u << (bit + i0)));
    }
}
struct DenseTaps {
    uint32_t A[4][4], E[4], F[4], G[4];
    __device__ __forceinline__ DenseTaps(uint32_t pb, uint32_t pz) {
        constexpr int PP = T_PATCH - T_DENSE + 56;
#pragma unroll
        for (int i = 0; i < 4; i++) load_toep(A[i], pb + 512 * i, pz + 512 * i);
        load_toep(E, pb + 2048, pz + 2048);
        load_toep(F, pb + PP, pz + PP);
        G[0] = lds32(pz + 2048 + 32); G[1] = lds32(pb + 2048 + 64); G[2] = lds32(pz + PP + 32); G[3] = lds32(pb + PP + 64);
    }
};
__device__ __forceinline__ uint32_t dense_phase(float (&acc)[16][4], uint32_t vrow, uint32_t pb, DenseTaps& tp, uint32_t zero, int lane) {
    uint32_t R[8][4], A1[4][4], junk = 0;
    const uint32_t vmin = vrow + ((lane >> 3) & 1) * VT_PLANE - 16 + zero;
    uint32_t va = vmin + 16 + (lane >> 4) * 1024 + (lane & 7) * 16, pz = pb + zero;
    {
        uint32_t H[4][4];
#pragma unroll
        for (int i = 0; i < 4; i++) ldsm4(H[i], vrow + VT_PLANE + 496 - ((lane >> 3) & 1) * 512 + (lane >> 4) * 128 + (lane & 7) * 16 + i * 256);
#pragma unroll
        for (int i = 0; i < 8; i++) ldsm4(R[i], va + i * 128);
#pragma unroll
        for (int i = 0; i < 4; i++) mma_bf16_k8(acc[i + 4], tp.G[0], tp.G[1], H[i >> 1][2 * (i & 1) + 1]);
#pragma unroll
        for (int i = 0; i < 8; i++) mma_v(acc[i + 8], tp.G, H[i >> 1][2 * (i & 1)], H[i >> 1][2 * (i & 1) + 1]);
#pragma unroll
        for (int i = 0; i < 12; i++) mma_v(acc[i + 4], tp.E, R[i & 7][2 * (i >> 3)], R[i & 7][2 * (i >> 3) + 1]);
#pragma unroll
        for (int i = 0; i < 8; i++) mma_v(acc[i + 8], tp.F, R[i][0], R[i][1]);
    }
#pragma unroll 1
    for (int rho = 0; rho < 8; rho += 2) {
        dense_step(acc, R, tp.A, A1, va, vmin, pb + 64, pz + 64, zero, 0, junk);
        dense_step(acc, R, A1, tp.A, va - 16, vmin, pb + 128, pz + 128, zero, 8, junk);
        pb += 128; pz += 128; va -= 32;
    }
    return junk & zero;
}
__device__ __forceinline__ uint32_t ones2(int c, int lo, int hi) {
    return (((uint32_t)(c - lo) <= (uint32_t)(hi - lo)) ? 0x3f80u : 0u) | (((uint32_t)(c + 1 - lo) <= (uint32_t)(hi - lo)) ? 0x3f800000u : 0u);
}
struct Boxes {
    uint32_t q[4], ha[2];
    __device__ __forceinline__ Boxes(uint32_t vrow, int lane, int O, int L1, int H1, int L2, int H2) {
        const int g = lane >> 2, t = lane & 3, d = 2 * t - g;
        q[0] = ones2(d, L1, H1); q[1] = ones2(d, L2, H2); q[2] = ones2(d + 8, L1, H1); q[3] = ones2(d + 8, L2, H2);
#pragma unroll
        for (int i = 0; i < 2; i++) { ha[i] = vrow + 16 * g + tok_off(O + 8 * i + 2 * t); pin(ha[i]); pin(q[i]); pin(q[2 + i]); }
    }
    __device__ __forceinline__ uint32_t any() const { return (q[0] | q[1] | q[2]) | (q[3] | ha[0] | ha[1]); }
    __device__ __forceinline__ void load(int j, uint32_t* v, uint32_t zero) const {
        const uint32_t o = j * 128;
        v[0] = lds32(ha[0] + o); v[1] = lds32(ha[1] + zero + o); v[2] = lds32(ha[1] + o);
        v[3] = lds32(ha[0] + zero + o + 16); v[4] = lds32(ha[0] + o + 16); v[5] = lds32(ha[1] + o + 16);
    }
    __device__ __forceinline__ void sums(const uint32_t* v, float* Z, float* X, float* Y) const {
        mma_bf16_z(Z, q[0], q[1], q[2], q[3], v[0], v[1]);
        mma_bf16_z(X, q[0], q[1], q[2], q[3], v[2], v[3]);
        mma_bf16_z(Y, q[0], q[1], q[2], q[3], v[4], v[5]);
    }
};
template <class After>
__device__ __forceinline__ void tail_phase(float (&acc)[16][4], const Boxes& b2, const Boxes& b3, uint32_t tp2, uint32_t tp3, uint32_t zero, After after) {
    uint2 tp[10];
    uint32_t v[6], a0[4], a1[4];
    float Z[4], X[4], Y[4];
    b2.load(0, v, zero);
#pragma unroll
    for (int i = 0; i < 5; i++) { const uint4 c = lds128(tp2 + 160 * i); tp[i] = make_uint2(c.x, c.y); tp[5 + i] = make_uint2(c.z, c.w); }
#pragma unroll
    for (int j = -1; j < 20; j++) {
        if (j < 19) {
            (j < 11 ? b2 : b3).sums(v, Z, X, Y);
            if (j < 10) b2.load(j + 2, v, zero); else if (j < 18) b3.load(j - 10, v, zero);
        }
        if (j >= 0 && j < 12) {
#pragma unroll
            for (int b = 0; b < 5; b++) if (j + 4 + b < 16) mma_v(acc[j + 4 + b], a1, tp[5 + b].x, tp[5 + b].y);
        }
        if (j < 11) { a1[0] = pack_v(Z[0], Z[1]); a1[1] = pack_w(X[0], X[1]); a1[2] = pack_v(Z[2], Z[3]); a1[3] = pack_w(X[2], X[3]); }
        if (j >= 0 && j < 12) {
#pragma unroll
            for (int b = 0; b < 5; b++) if (j + 4 + b < 16) mma_v(acc[j + 4 + b], a0, tp[b].x, tp[b].y);
            if (j >= 7 && j < 11) { tp[11 - j] = lds64(tp3 + 80 * (10 - j)); tp[16 - j] = lds64(tp3 + 80 * (14 - j)); }
        } else if (j >= 12) {
#pragma unroll
            for (int b = 0; b < 8; b++) if (j - 4 + b < 16) mma_v(acc[j - 4 + b], a0, tp[b < 4 ? b + 1 : b + 2].x, tp[b < 4 ? b + 1 : b + 2].y);
        }
        if (j < 11) { a0[0] = pack_v(X[0], X[1]); a0[1] = pack_v(Y[0], Y[1]); a0[2] = pack_v(X[2], X[3]); a0[3] = pack_v(Y[2], Y[3]); }
        else if (j < 19) { a0[0] = pack_v(X[0], X[1]); a0[1] = pack_v(Y[0], Y[1]); a0[2] = pack_v(Z[2], Z[3]); a0[3] = pack_v(X[2], X[3]); }
        after(j);
    }
}
template <int G>
__device__ __forceinline__ void emit(const float (&acc)[16][4], int h, uint32_t own, uint32_t peer, uint32_t bar, uint32_t bar_peer) {
#pragma unroll
    for (int o = 0; o < 2; o++)
#pragma unroll
        for (int hf = 0; hf < 2; hf++) {
            const int n = 8 * G + 4 * o;
            asm volatile("{ .reg .pred p; setp.eq.u32 p, %7, %8;\n\t@p st.shared.v4.u32 [%0], {%1,%2,%3,%4};\n\t"
                         "@!p st.async.weak.shared::cluster.mbarrier::complete_tx::bytes.v4.b32 [%5], {%1,%2,%3,%4}, [%6]; }"
                         ::"r"(own + G * 16384 + hf * 512), "r"(pack_bf16(acc[n][2 * hf], acc[n][2 * hf + 1])), "r"(pack_bf16(acc[n + 1][2 * hf], acc[n + 1][2 * hf + 1])),
                         "r"(pack_bf16(acc[n + 2][2 * hf], acc[n + 2][2 * hf + 1])), "r"(pack_bf16(acc[n + 3][2 * hf], acc[n + 3][2 * hf + 1])),
                         "r"(peer + G * 16384 + hf * 512), "r"(bar_peer + 8 * G), "r"(h), "r"(o) : "memory");
        }
    __syncwarp();
    if (elect_one()) mbar_arrive(bar + 8 * G);
}
__device__ __forceinline__ void finish(uint32_t src, uint32_t xa) {
    uint32_t s[4][4];
    uint4 x[4];
#pragma unroll
    for (int i = 0; i < 4; i++) {
        ldsm4t(s[i], (src ^ ((i & 1) << 5)) + (i >> 1) * 8192);
        x[i] = lds128((xa ^ ((i >> 1) << 4)) + (i & 1) * 256);
    }
#pragma unroll
    for (int i = 0; i < 4; i++)
        sts128((xa ^ ((i >> 1) << 4)) + (i & 1) * 256, badd2(x[i].x, s[i][0]), badd2(x[i].y, s[i][1]), badd2(x[i].z, s[i][2]), badd2(x[i].w, s[i][3]));
}

__device__ __noinline__ float centred_var(uint32_t rows, float mu, int lane) {
    float var = 0.f;
#pragma unroll 1
    for (int rr = 0; rr < 16; rr++) {
        const float c0 = __shfl_sync(0xffffffffu, mu, rr);
        float c = 0.f;
#pragma unroll 1
        for (int k = 0; k < 16; k++) {
            const uint32_t q = lds32(rows + rr * ROW_PITCH + k * 128 + lane * 4);
            const float d0 = bf_lo(q) - c0, d1 = bf_hi(q) - c0;
            c = fmaf(d0, d0, fmaf(d1, d1, c));
        }
#pragma unroll 1
        for (int o = 16; o; o >>= 1) c += __shfl_xor_sync(0xffffffffu, c, o);
        if ((lane & 15) == rr) var = c * (1.f / DM);
    }
    return var;
}
__device__ __noinline__ float centred_score(uint32_t rows, uint32_t wbuf, uint32_t s0, uint32_t s1, int lane) {
    float sc = 0.f;
#pragma unroll 1
    for (int rr = 0; rr < 16; rr++) {
        const uint32_t t0 = __shfl_sync(0xffffffffu, s0, rr), t1 = __shfl_sync(0xffffffffu, s1, rr);
        float c = 0.f;
#pragma unroll 1
        for (int k = 0; k < 16; k++) {
            const uint32_t xn = normalize2(lds32(rows + rr * ROW_PITCH + k * 128 + lane * 4), t0, t1);
            const uint32_t wq = lds32(wbuf + (k >> 2) * 1024 + (k & 3) * 128 + lane * 4);
            c = fmaf(bf_lo(xn), bf_lo(wq), fmaf(bf_hi(xn), bf_hi(wq), c));
        }
#pragma unroll 1
        for (int o = 16; o; o >>= 1) c += __shfl_xor_sync(0xffffffffu, c, o);
        if ((lane & 15) == rr) sc = c;
    }
    return sc;
}

__global__ void __cluster_dims__(2, 1, 1) __launch_bounds__(NTHR, 1)
fused_kernel(const __grid_constant__ Ptrs p, const __grid_constant__ Maps maps) {
    extern __shared__ __align__(1024) unsigned char smem[];
    const int tid = threadIdx.x, lane = tid & 31;
    const int c_ = ((blockIdx.x >> 1) + PERM_OFF) & 63, b = 2 * ((c_ & 32) | ((c_ & 7) << 2) | ((c_ >> 3) & 3)) + (blockIdx.x & 1);
    const int dch = 8 * b + (tid >> 5) - 4;
    uint2 la, aim, cre, cim;
    uint32_t ldt16, dsk16, epoch;
    uint4 wq;
    if ((uint32_t)(tid - 128) < 256u) {
        la = ldg64(p.logA + dch * NMODE + 4 * lane); aim = ldg64(p.Aim + dch * NMODE + 4 * lane);
        cre = ldg64(p.Cre + dch * NMODE + 4 * lane); cim = ldg64(p.Cim + dch * NMODE + 4 * lane);
        ldt16 = ldg16(p.ldt + dch); dsk16 = ldg16(p.dsk + dch);
    }
    if (tid < 128) { wq = ldg128(p.wr + 8 * tid); epoch = ld_relaxed_32(&p.sc->epoch); }
    const uint32_t sb = s_u32(smem);
    const int warp = __shfl_sync(0xffffffffu, tid >> 5, 0);
    const int h = b & 1, cl = b >> 1;
    const uint32_t bar0 = sb + OFF_BAR;
    const int m = lane >> 3, r = lane & 7, g = lane >> 2, t = lane & 3;
    const bool has_gu = b < GU_CTAS;
    if (warp == 4) { STAMP(0); GSTAMP(24); }

    if (warp >= 12) {
        asm volatile("setmaxnreg.dec.sync.aligned.u32 24;");
        const int a = warp - 12;
        uint32_t due = now_ns() + ST_T0 + (uint32_t)(128 * a + b) * ST_PER / 128 + (has_gu ? 0 : ST_LATE * (12 * ST_PER + 4 * ST_PER2) / 16);
        const bool el = elect_one();
        if (a == 1 && el) {
#pragma unroll
            for (int j = 0; j < 4; j++) mbar_init(bar0 + 8 * (B_ROW + j), 1);
            asm volatile("fence.mbarrier_init.release.cluster;" ::: "memory");
            fence_async();
#pragma unroll 1
            for (int j = 0; j < 4; j++) {
                mbar_expect_tx(bar0 + 8 * (B_ROW + j), 8192);
#pragma unroll
                for (int i = 0; i < 4; i++)
                    bulk_g2s(sb + OFF_VT + (4 * j + i) * ROW_PITCH, p.u + (size_t)(16 * b + 4 * j + i) * DM, 2048, bar0 + 8 * (B_ROW + j));
            }
        }
        if (a == 2 && el) {
#pragma unroll
            for (int i = B_XT; i < NBAR; i++) mbar_init(bar0 + 8 * i, (i == B_V || i == B_SFREE || i == B_XFREE) ? 8 : (i == B_RECV || i == B_RECV + 1) ? 9 : (i == B_UPD || (i >= B_FREE && i < B_FULL)) ? 4 : 1);
            asm volatile("fence.mbarrier_init.release.cluster;" ::: "memory");
            fence_async();
            mbar_expect_tx(bar0 + 8 * B_XT, 65536);
            mbar_expect_tx(bar0 + 8 * B_RECV, 8192);
            mbar_expect_tx(bar0 + 8 * B_RECV + 8, 8192);
            mbar_expect_tx(bar0 + 8 * B_RED, 512);
        }
        if (a == 3 && el) {
#pragma unroll
            for (int i = 0; i < 5; i++) asm volatile("prefetch.tensormap [%0];" ::"l"(&maps.u + i) : "memory");
        }
        __syncwarp();
        cluster_arrive();
        cluster_wait();
        STAMP(18);
        mbar_wait(bar0 + 8 * (B_ROW + a), 0);
        if (el) {
#pragma unroll
            for (int i = 0; i < 4; i++)
                tma_load_tile(sb + OFF_XT + h * 32768 + a * 4096 + (i & 1) * 16384 + (i >> 1) * 2048, &maps.u, 16 * cl, 4 * a + (i & 2), 16 * (i & 1) + 8 * h, bar0 + 8 * B_XT);
        }
        if (el) {
#pragma unroll 1
            for (int k = has_gu ? 0 : 4; k < 6; k++) {
                const int i = 4 * k + a, s = k < 3 ? i : i - 12;
#pragma unroll 1
                for (int left; (left = (int)(due - now_ns())) > 0;) __nanosleep(left >> 1);
                due += k == 0 ? 4 * ST_PER + ST_GAP : k < 3 ? 4 * ST_PER : 4 * ST_PER2;
                const bool again = k >= 3 && has_gu;
                if (s >= 6 || again) mbar_wait(bar0 + 8 * (s < 10 || again ? B_FREE + s : B_V), slot_priv(s) && again);
                const uint32_t dst = sb + slot_off(s), bar = bar0 + 8 * (B_FULL + s);
                if (k < 4) {
                    mbar_expect_tx(bar, 8192);
                    tma_load_2d(dst, &maps.wg, 64 * cl, 512 * h + 32 * i, bar);
                    tma_load_2d(dst + 4096, &maps.wu, 64 * cl, 512 * h + 32 * i, bar);
                } else {
                    mbar_expect_tx(bar, 7168);
                    tma_load_perm(dst, &maps.wd, 16 * cl, 56 * h + 14 * a + 7 * (k & 1), bar);
                }
            }
            STAMP(19);
        }
    } else if (warp >= 4) {
        const int w = warp - 4;
        cluster_arrive();
        asm volatile("setmaxnreg.inc.sync.aligned.u32 168;");
        const uint32_t vrow = sb + OFF_VT + w * VT_PITCH + VT_PAD, tab = sb + tab_off(w);
        const uint32_t so = sb + OFF_XT + (8 * h + w) * 1024 + ((lane ^ ((w & 1) << 1)) << 4);
        uint32_t dst0 = so + (h ^ 1) * 32768;
        const uint32_t rb0 = bar0 + 8 * B_RECV, rb1 = mapa(rb0, h ^ 1);
        const uint32_t box = sb + OFF_XT + h * 32768 + w * 2048;
        uint32_t fs = sb + OFF_XT + (h ^ 1) * 32768 + (2 * m + (r & 1)) * 1024 + (w >> 2) * 512 + (((8 * (w & 3) + (r & 4) + ((r >> 1) & 1)) ^ ((r & 1) << 1)) << 4);
        uint32_t fx = box + (g >> 1) * 512 + (t >> 1) * 144 + (2 * (t & 1) + (g & 1)) * 32;
        uint32_t tpo = 80 + (g - 2 * t) * 8 - (g < 2 * t ? 16 : 0);
        uint32_t xa = sb + OFF_XT + (w & 2) * 16384 + (w >> 2) * 16384 + (w & 1) * 1024 + (g >> 1) * 2048 + (g & 1) * 128 + t * 32 + ((h ^ (g & 1)) << 4);
        uint32_t va = sb + OFF_VT + (2 * m + (r & 1)) * VT_PITCH + VT_PAD + (16 * w + (r >> 1)) * 16;
        uint32_t qa = sb + OFF_ST + 2048 * w + 128 * t + 16 * (g ^ (2 * t));
        pin(dst0); pin(fs); pin(fx); pin(tpo); pin(xa); pin(va); pin(qa);
        const Boxes b2(vrow, lane, -18, 5, 7, 0, 4), b3(vrow, lane, -20, 1, 7, 0, 8);
        const KgenAddr ka(sb + OFF_PRIV + w * 8192, lane);
        if (__any_sync(0xffffffffu, ((dst0 | fs) | (fx | tpo | xa) | (va | qa) | (b2.any() | b3.any() | ka.any())) & p.zero)) __trap();
        cluster_wait();
        pin(la.x); pin(la.y); pin(aim.x); pin(aim.y); pin(cre.x); pin(cre.y); pin(cim.x); pin(cim.y); pin(ldt16); pin(dsk16);
        uint4 x[8];
        auto load_x = [&]() {
            mbar_wait(bar0 + 8 * B_XT, 0);
#pragma unroll
            for (int i = 0; i < 8; i++) x[i] = lds128(xa + (i & 1) * 8192 + (i >> 1) * 256);
        };
        kgen(ka, tab, lane, la, aim, cre, cim, bf_round(ex2f(bf_lo(ldt16) * 1.4426950408889634f)), 1.f + bf_lo(dsk16), dch, [&]() {
            STAMP(21);
            if (elect_one()) mbar_arrive_n(bar0 + 8 * (B_FREE + 6 + ((w >> 1) ^ 2)), 2);
        }, [&]() {
            if ((LN_PAUSE >> w) & 1) mbar_wait(bar0 + 8 * B_LN, 0);
        });
        STAMP(1); KSTAMP(6);
        const uint32_t pb = tab + T_DENSE + (g - 2 * t) * 4;
        {
            load_x();
            STAMP(47);
            mbar_wait(bar0 + 8 * (B_ST + (w >> 1)), 0);
            uint4 q[4];
#pragma unroll
            for (int n = 0; n < 4; n++) q[n] = lds128(qa + 512 * n);
            if (lane < 4) sts128(vrow - VT_PAD + (lane >> 1) * VT_PLANE + (lane & 1) * 16, 0, 0, 0, 0);
            STAMP(2); GSTAMP(28);
#pragma unroll
            for (int i = 0; i < 8; i++) {
                const uint32_t s0 = (i & 1) ? q[i >> 1].z : q[i >> 1].x, s1 = (i & 1) ? q[i >> 1].w : q[i >> 1].y;
                stsm4t(va + (i >> 1) * 64 + (i & 1) * VT_PLANE, normalize2(x[i].x, s0, s1), normalize2(x[i].y, s0, s1),
                       normalize2(x[i].z, s0, s1), normalize2(x[i].w, s0, s1));
            }
            __syncwarp();
            if (elect_one()) mbar_arrive(bar0 + 8 * B_V);
        }
        DenseTaps dt(pb, pb + p.zero);
        mbar_wait(bar0 + 8 * B_V, 0);
        STAMP(3); KSTAMP(7);
        float acc[16][4];
#pragma unroll
        for (int i = 0; i < 16; i++) { acc[i][0] = acc[i][1] = acc[i][2] = acc[i][3] = 0.f; }
        tpo |= dense_phase(acc, vrow, pb, dt, p.zero, lane);
        STAMP(4); KSTAMP(8);
        const uint32_t dst1 = mapa(dst0 + (h ? 32768 : -32768), h ^ 1);
        tail_phase(acc, b2, b3, tab + T_R2 + 2 * tpo, tab + T_R3 + tpo, p.zero, [&](int j) {
            if (j == 3) {
                mbar_wait(bar0 + 8 * B_SFREE, 0);
                emit<0>(acc, h, dst0, dst1, rb0, rb1);
                STAMP(5);
            }
            if (j == STORE_AT) {
                mbar_wait(bar0 + 8 * B_XFREE, 0);
                mbar_wait(bar0 + 8 * B_RECV, 0);
                finish(fs, fx);
                fence_async();
                __syncwarp();
                if (elect_one()) tma_store_tile(&maps.out, box, 16 * cl, 2 * w, 8 * h);
                STAMP(20);
            }
        });
        emit<1>(acc, h, dst0, dst1, rb0, rb1);
        STAMP(30);
        const int tok = 2047 - (int)(lds32(sb + OFF_MISC + 48 + 8 * g) & 2047);
        const bool mine = (((tok >> 6) & 8) | ((tok >> 1) & 7)) == 8 * h + w;
        const bool any = __any_sync(0xffffffffu, mine), late = __any_sync(0xffffffffu, mine && tok >= 1024);
        const uint32_t ta = box + (tok >> 10) * 16384 + ((tok >> 6) & 7) * 256 + (tok & 1) * 128 + ((tok >> 4) & 3) * 32 + (((t >> 1) ^ (tok & 1)) << 4) + (t & 1) * 8;
        const bool el = elect_one();
        mbar_wait(bar0 + 8 * (B_RECV + 1), 0);
        STAMP(6);
        finish(fs + 16384, fx + 16384);
#pragma unroll 1
        for (int pass = 0; pass < 2; pass++) {
            if ((pass != 0) == late) {
                fence_async();
                __syncwarp();
                if (el) tma_store_tile(&maps.out, box + 16384, 16 * cl, 2 * w, 16 + 8 * h);
            } else if (any) {
                if (el) {
                    if (late) asm volatile("cp.async.bulk.wait_group 0;" ::: "memory");
                    else asm volatile("cp.async.bulk.wait_group 1;" ::: "memory");
                }
                __syncwarp();
                const uint2 o0 = lds64(ta);
                mbar_wait(bar0 + 8 * B_UPD, 0);
                const float4 up = lds128f(sb + tab_off(g) + T_RED + 16 * t);
                const uint2 o1 = make_uint2(badd2(o0.x, pack_bf16(up.x, up.y)), badd2(o0.y, pack_bf16(up.z, up.w)));
                if (mine) {
                    if (tok >= 1024) sts64(ta, o1.x, o1.y);
                    else *reinterpret_cast<uint2*>(p.out + (size_t)tok * DM + 16 * cl + 4 * t) = o1;
                }
            }
        }
        if (el) asm volatile("cp.async.bulk.wait_group.read 0;" ::: "memory");
        STAMP(7);
    } else {
        const int a = warp;
        cluster_arrive();
        asm volatile("setmaxnreg.inc.sync.aligned.u32 152;");
        const uint32_t tag = __shfl_sync(0xffffffffu, epoch, 0) + 1u, misc = sb + OFF_MISC, abar = bar0 + 8 * (B_AUX + a);
        uint32_t aph = 0;
        const Exchange* in = &p.sc->x[cl & (NREP - 1)];
        uint2* pub = p.sc->x[m >> 1].stat + 16 * b + 2 * (r ^ (2 * (b & 3))) + (m & 1);
        uint32_t* cnt_s = &p.sc->x[t].n_stat[b & 96];
        pin(pub); pin(cnt_s);
        if (tid < 64) sts32(sb + OFF_XCH + 4 * tid, 0);
        const uint32_t wbuf = sb + OFF_LN + a * 1024, part = sb + OFF_LN + 4096;
        {
            sts128(wbuf + 16 * lane, wq.x, wq.y, wq.z, wq.w);
            sts128(wbuf + 512 + 16 * lane, 0x3f803f80u, 0x3f803f80u, 0x3f803f80u, 0x3f803f80u);
            float wsum = ((bf_lo(wq.x) + bf_hi(wq.x)) + (bf_lo(wq.y) + bf_hi(wq.y))) + ((bf_lo(wq.z) + bf_hi(wq.z)) + (bf_lo(wq.w) + bf_hi(wq.w)));
#pragma unroll
            for (int o = 16; o; o >>= 1) wsum += __shfl_xor_sync(0xffffffffu, wsum, o);
            sts32f(part + 1024 + 4 * a, wsum);
            uint32_t wf[4][4];
#pragma unroll
            for (int i = 0; i < 4; i++) ldsm4(wf[i], wbuf + ((uint32_t)(r - 1) < 2u ? 16 * (r - 1) : 512) + 32 * m + 128 * i);
            uint32_t ra = sb + OFF_VT + r * ROW_PITCH + 512 * a + 16 * m, pa = part + a * 256 + g * 16;
            cluster_wait();
            STAMP(22);
#pragma unroll 1
            for (int hf = 0; hf < 2; hf++) {
                mbar_wait(bar0 + 8 * B_ROW + 16 * hf, 0);
                mbar_wait(bar0 + 8 * B_ROW + 16 * hf + 8, 0);
                STAMP(23);
                uint32_t x[8][4];
                float cs[2][4], q[8][4];
#pragma unroll
                for (int i = 0; i < 40; i++) (i < 8 ? cs[i >> 2 & 1] : q[(i - 8) >> 2 & 7])[i & 3] = 0.f;
#pragma unroll
                for (int k = 0; k < 8; k++) ldsm4(x[k], ra + k * 64);
                const bool more = __any_sync(0xffffffffu, after_all(x, p.zero));
#pragma unroll 1
                do {
#pragma unroll
                    for (int k = 0; k < 8; k++) {
                        mma_v(cs[k & 1], x[k], wf[k >> 1][2 * (k & 1)], wf[k >> 1][2 * (k & 1) + 1]);
#pragma unroll
                        for (int i = 0; i < 4; i++) mma_bf16_k8(q[4 * (k & 1) + i], x[k][i & 2], x[k][i | 1], x[k][i]);
                    }
                } while (more);
                const float c2 = cs[0][2] + cs[1][2];
                if (t == 0) sts64f(pa, (cs[0][0] + cs[1][0]) + c2, cs[0][1] + cs[1][1]);
                if (t == 1) sts32f(pa + 12, c2);
                const float e0 = ((q[0][0] + q[2][0]) + (q[4][0] + q[6][0])) + ((q[1][2] + q[3][2]) + (q[5][2] + q[7][2]));
                const float e1 = ((q[0][1] + q[2][1]) + (q[4][1] + q[6][1])) + ((q[1][3] + q[3][3]) + (q[5][3] + q[7][3]));
                if (t == (g >> 1)) sts32f(pa + 8, (g & 1) ? e1 : e0);
                ra += 8 * ROW_PITCH; pa += 128;
            }
        }
        STAMP(31);
        named_sync(1, 128);
        if (a == 0) {
            const uint32_t pa = part + (lane & 15) * 16;
            const float4 p0 = lds128f(pa), p1 = lds128f(pa + 256), p2 = lds128f(pa + 512), p3 = lds128f(pa + 768), ws = lds128f(part + 1024);
            const float mu = ((p0.x + p1.x) + (p2.x + p3.x)) * (1.f / DM);
            float var = ((p0.z + p1.z) + (p2.z + p3.z)) * (1.f / DM) - mu * mu;
            const bool centred = __any_sync(0xffffffffu, !(mu * mu <= 4.f * var));
            if (centred) var = centred_var(sb + OFF_VT, mu, lane);
            const float ri = rcpf(bf_round(sqrtaf(bf_round(bf_round(var) + 1e-5f))));
            const uint32_t s0 = pack_bf16(mu, ri), s1 = (pack_bf16(ri - bf_hi(s0), 0.f) & 0xfffcu) | (tag & 3);
            float sc = ((((p0.y + p1.y) + (p2.y + p3.y)) + ((p0.w + p1.w) + (p2.w + p3.w))) - bf_lo(s0) * ((ws.x + ws.y) + (ws.z + ws.w))) * ri;
            if (centred) sc = centred_score(sb + OFF_VT, sb + OFF_LN, s0, s1, lane);
            const uint32_t sb16 = pack_bf16(0.f, sc);
            const uint32_t s2 = s1 | (sb16 ^ (((uint32_t)((int)sb16 >> 31) & 0x7fff0000u) | 0x80000000u));
            st_relaxed_64(pub, s0, s2);
            st_relaxed_64(pub + 2 * sizeof(Exchange) / 8, s0, s2);
            if (lane < NREP) red_add(cnt_s, 1);
            if (elect_one()) mbar_arrive(bar0 + 8 * B_LN);
            STAMP(9); GSTAMP(25);
        }
        const uint32_t slot0 = sb + OFF_RING + a * 8192, slot1 = sb + slot_off(4 + a), slot2 = sb + slot_off(8 + a), fbar = bar0 + 8 * (B_FULL + a);
        uint32_t mine = 0, row[2] = {0, 0};
        {
            uint32_t q[16];
            named_sync(1, 128);
            wait_count(&in->n_stat[32 * a], 32 * tag - FEW_ST);
            STAMP(41);
#pragma unroll 1
            for (uint32_t it = 0;; spin_guard(it)) {
                if (elect_one()) {
                    mbar_expect_tx(abar, 4096);
                    bulk_g2s(sb + OFF_ST + 4096 * a, in->stat + 512 * a, 4096, abar);
                }
                mbar_wait(abar, aph);
                aph ^= 1;
                uint32_t bad = 0;
#pragma unroll
                for (int n = 0; n < 8; n++) {
                    const uint4 u = lds128v(sb + OFF_ST + 4096 * a + 512 * n + 16 * lane);
                    q[2 * n] = u.y; q[2 * n + 1] = u.w;
                    bad = or_xor(bad, u.y, tag);
                }
                const bool ok = __all_sync(0xffffffffu, (bad & 3) == 0);
                asm volatile("{ .reg .pred p; setp.ne.u32 p, %1, 0; @p mbarrier.arrive.shared::cta.b64 _, [%0]; }" ::"r"(bar0 + 8 * (B_ST + a)), "r"((uint32_t)(ok && lane == 0)) : "memory");
                if (ok) break;
            }
            STAMP(8);
            const uint32_t inv = 2047 - 512 * a - 16 * m - (r ^ (2 * m));
#pragma unroll
            for (int i = 0; i < 16; i++) asm("lop3.b32 %0, %0, %1, %2, 0x9b;" : "+r"(q[i]) : "r"(inv), "r"(0xffff0000u | (64 * (i >> 1) + 8 * (i & 1))));
            auto below = [&](uint32_t x) {
                uint32_t d[4];
#pragma unroll
                for (int i = 0; i < 16; i++) d[i & 3] = i < 4 ? x + q[i] : min(d[i & 3], x + q[i]);
                d[0] = min(min(d[0], d[1]), min(d[2], d[3]));
                return d[0] < x ? x - 1 - d[0] : 0u;
            };
            const uint32_t mx0 = ~min(min(min(min(q[0], q[1]), min(q[2], q[3])), min(min(q[4], q[5]), min(q[6], q[7]))),
                                      min(min(min(q[8], q[9]), min(q[10], q[11])), min(min(q[12], q[13]), min(q[14], q[15]))));
            const uint32_t gm = min(__reduce_max_sync(0xffffffffu, lane < 16 ? mx0 : 0u), __reduce_max_sync(0xffffffffu, lane < 16 ? 0u : mx0));
            if (lane == 0) sts32(misc + 16 + 4 * a, gm);
            named_sync(1, 128);
            STAMP(42);
            if (b == 0 && tid == 0) st_relaxed_32(&p.sc->epoch, tag);
            const uint4 t0 = lds128(misc + 16);
            uint32_t tau = min(min(t0.x, t0.y), min(t0.z, t0.w));
            uint32_t mx = mx0, cnt = 0, bal;
            const uint32_t list = sb + OFF_XCH + 64 * a;
#pragma unroll 1
            while ((bal = __ballot_sync(0xffffffffu, mx >= tau)) != 0) {
                const uint32_t pos = cnt + __popc(bal & ((1u << lane) - 1u));
                cnt += __popc(bal);
                if (cnt > 16) break;
                if (mx >= tau) sts32(list + 4 * pos, mx);
                mx = below(mx);
            }
            if (cnt > 16) {
                mx = mx0;
#pragma unroll 1
                for (int j = 0; j < 8; j++) {
                    const uint32_t top = __reduce_max_sync(0xffffffffu, mx), nx = below(mx);
                    if (mx == top) { sts32(list + 4 * j, mx); sts32(list + 32 + 4 * j, 0); mx = nx; }
                }
            }
            named_sync(1, 128);
            STAMP(43);
            const uint2 k = lds64(sb + OFF_XCH + 8 * lane);
            uint32_t hi = max(k.x, k.y), lo = min(k.x, k.y);
            mbar_wait(bar0 + 8 * B_V, 0);
#pragma unroll
            for (int j = 0; j < 8; j++) {
                const uint32_t top = __reduce_max_sync(0xffffffffu, hi);
                const bool won = hi == top;
                hi = won ? lo : hi;
                lo = won ? 0u : lo;
                if (g == j) mine = top;
                if (a == (j >> 1)) row[j & 1] = top;
            }
        }
        STAMP(11);
        const int tok = 2047 - (int)(mine & 2047);
        const uint32_t xs = sb + OFF_XT + (h ^ 1) * 32768 + 16384;
        if (has_gu) {
            if (elect_one()) {
                mbar_expect_tx(abar, 2048);
#pragma unroll
                for (int j = 0; j < 2; j++) bulk_g2s(xs + (2 * a + j) * 1040, p.u + (size_t)(2047 - (row[j] & 2047)) * DM + 512 * h, 1024, abar);
            }
        }
        STAMP(44);
        const uint2 st = ld_relaxed_64(in->stat + (tok & ~15) + 2 * ((tok & 7) ^ ((tok >> 3) & 6)) + ((tok >> 3) & 1));
        if (a == 0 && t == 0) sts64(misc + 48 + 8 * g, mine, __float_as_uint(bf_hi(st.x) + bf_lo(st.y)));
        if (a == 0) STAMP(45);
        if (has_gu) {
            const uint32_t mean = __shfl_sync(0xffffffffu, st.x, 8 * a + 4 * (lane >> 4)), xr = xs + (2 * a + (lane >> 4)) * 1040 + 16 * (lane & 15);
            mbar_wait(abar, aph);
            aph ^= 1;
            STAMP(46);
            uint4 x[4];
#pragma unroll
            for (int j = 0; j < 4; j++) x[j] = lds128(xr + 256 * j);
#pragma unroll
            for (int j = 0; j < 4; j++) sts128(xr + 256 * j, bsub2_lo(x[j].x, mean), bsub2_lo(x[j].y, mean), bsub2_lo(x[j].z, mean), bsub2_lo(x[j].w, mean));
            if (elect_one()) mbar_expect_tx(abar, 512);
            named_sync(1, 128);
        }
        if (lane < (has_gu ? 2 : 4)) mbar_arrive_peer(mapa(bar0 + 8 * (lane & 2 ? B_XFREE : B_SFREE), lane & 1));
        if (has_gu) {
            STAMP(12);
            float gacc[8][4];
#pragma unroll
            for (int i = 0; i < 8; i++) { gacc[i][0] = gacc[i][1] = gacc[i][2] = gacc[i][3] = 0.f; }
            uint32_t* pubh = reinterpret_cast<uint32_t*>(&p.sc->x[0].h[b * 32 + 8 * a + (g ^ (2 * a))]) + t;
            uint32_t* cnt_h = &p.sc->x[t].n_h[32 * (b / 14)];
            uint32_t ko = sb + (m & 1) * 4096 + (r + ((m >> 1) << 3)) * 128 + ((r ^ (4 * h) ^ a) << 4), kp = ko ^ 64, xb = xs + r * 1040 + m * 16;
            uint32_t xch = sb + OFF_XCH + 16 * tid, tagm = t == 3 ? 1u : 0u;
            pin(pubh); pin(cnt_h); pin(ko); pin(kp); pin(xb); pin(xch); pin(tagm);
            const float r0 = lds32f(misc + 52 + 16 * t), r1 = lds32f(misc + 60 + 16 * t);
#pragma unroll
            for (int c = 0; c < 4; c++) {
                uint32_t af[20][4];
#pragma unroll
                for (int j = 0; j < 4; j++) ldsm4(af[16 + j], xb + 256 * c + 64 * j);
                if (c == 3) {
                    __syncwarp();
                    if (lane < 2) mbar_arrive_peer(mapa(bar0 + 8 * B_XFREE, lane) + ((af[16][0] | af[17][0] | af[18][0] | af[19][0]) & p.zero));
                    mbar_wait(bar0 + 8 * B_SFREE, 0);
                }
#pragma unroll
                for (int j = 0; j < 4; j++) {
                    mbar_wait(bar0 + 8 * (B_FULL + 4 * (c % 3) + j), c / 3);
#pragma unroll
                    for (int i = 0; i < 4; i++) ldsm4t(af[8 * (i >> 1) + 2 * j + (i & 1)], ((i & 1) ? kp : ko) + slot_off(4 * (c % 3) + j) + (i >> 1) * 2048);
                }
                STAMP(36 + c);
                __syncwarp();
                if (c < 3 && lane < 4) mbar_arrive(bar0 + 8 * (B_FREE + 4 * c + lane));
                const bool more = __any_sync(0xffffffffu, (af[6][3] | af[7][3] | af[14][3] | af[15][3]) & p.zero);
#pragma unroll 1
                do {
#pragma unroll
                    for (int i = 0; i < 16; i++) mma_v(gacc[i & 7], af[i], af[16 + ((i >> 1) & 3)][2 * (i >> 3)], af[16 + ((i >> 1) & 3)][2 * (i >> 3) + 1]);
                } while (more);
                STAMP(52 + c);
            }
            STAMP(13);
            float own[4], oth[4];
#pragma unroll
            for (int j = 0; j < 4; j++) oth[j] = (gacc[1][j] + gacc[3][j]) + (gacc[5][j] + gacc[7][j]);
            st_async128(mapa(xch, h ^ 1), __float_as_uint(oth[0]), __float_as_uint(oth[1]), __float_as_uint(oth[2]), __float_as_uint(oth[3]), mapa(abar, h ^ 1));
            STAMP(56);
#pragma unroll
            for (int j = 0; j < 4; j++) own[j] = ((gacc[0][j] + gacc[2][j]) + (gacc[4][j] + gacc[6][j])) * ((j & 1) ? r1 : r0);
            mbar_wait(abar, aph);
            aph ^= 1;
            STAMP(57);
            const float4 o4 = lds128f(xch);
            const float g0 = bf_round(fmaf(o4.x, r0, own[0])), g1 = bf_round(fmaf(o4.y, r1, own[1]));
            const float h0 = bf_round(g0 * rcpf(1.f + ex2f(-1.4426950408889634f * g0))) * bf_round(fmaf(o4.z, r0, own[2]));
            const float h1 = bf_round(g1 * rcpf(1.f + ex2f(-1.4426950408889634f * g1))) * bf_round(fmaf(o4.w, r1, own[3]));
            uint32_t hw;
            asm volatile("movmatrix.sync.aligned.m8n8.trans.b16 %0, %1;" : "=r"(hw) : "r"(pack_bf16(h0, h1)));
            hw = (hw & ~tagm) | (tag & tagm);
#pragma unroll
            for (int j = 0; j < NREP; j++) st_relaxed_32(pubh + j * (sizeof(Exchange) / 4), hw);
            if (lane < NREP) red_add(cnt_h, 1);
            named_sync(1, 128);
            STAMP(14);
        }
        float dacc[4];
        {
            uint32_t wo = (r + ((m >> 1) << 3)) * 32 + (((m & 1) ^ (r >> 2)) << 4), af[14][4];
            pin(wo);
            float d[7][4];
#pragma unroll
            for (int i = 0; i < 7; i++) { d[i][0] = d[i][1] = d[i][2] = d[i][3] = 0.f; }
            auto first_half = [&]() {
                mbar_wait(fbar + 32, has_gu);
#pragma unroll
                for (int j = 0; j < 14; j++) ldsm4t(af[j], slot1 + wo + j * 512);
            };
            auto fetch = [&]() {
                if (elect_one()) {
                    mbar_expect_tx(abar, 7168);
                    bulk_g2s(slot0, &in->h[(56 * h + 14 * a) * 32], 7168, abar);
                }
            };
            wait_count(&in->n_h[32 * (4 * h + a)], 56 * tag - FEW_H);
            STAMP(33);
            fetch();
            first_half();
            uint4 hq[14];
#pragma unroll 1
            for (uint32_t it = 0;; spin_guard(it)) {
                mbar_wait(abar, aph);
                aph ^= 1;
                uint32_t bad = 0;
#pragma unroll
                for (int j = 0; j < 14; j++) { hq[j] = lds128(slot0 + 512 * j + 128 * t + 16 * (g ^ (2 * t))); bad = or_xor(bad, hq[j].w, tag); }
                if (__all_sync(0xffffffffu, (bad & 1) == 0)) break;
                fetch();
            }
            STAMP(15);
#pragma unroll
            for (int s = 0; s < 2; s++) {
                if (s) {
                    mbar_wait(fbar + 64, has_gu);
#pragma unroll
                    for (int j = 0; j < 14; j++) ldsm4t(af[j], slot2 + wo + j * 512);
                }
                const bool more = __any_sync(0xffffffffu, after_all(af, p.zero));
#pragma unroll 1
                do {
#pragma unroll
                    for (int j = 0; j < 14; j++) {
                        const uint4 q = hq[7 * s + (j >> 1)];
                        mma_v(d[j % 7], af[j], (j & 1) ? q.z : q.x, (j & 1) ? q.w : q.y);
                    }
                } while (more);
            }
#pragma unroll
            for (int j = 0; j < 4; j++) dacc[j] = ((d[0][j] + d[1][j]) + (d[2][j] + d[3][j])) + ((d[4][j] + d[5][j]) + d[6][j]);
        }
        STAMP(16);
        {
            sts128f(slot0 + 7680 + lane * 16, dacc);
            named_sync(1, 128);
            const int tk = tid >> 4, col = tid & 15;
            const uint32_t base = sb + OFF_RING + 7680 + ((col & 7) * 4 + (tk >> 1)) * 16 + (((col >> 3) << 1) + (tk & 1)) * 4;
            const float y0 = (lds32f(base) + lds32f(base + 8192)) + (lds32f(base + 16384) + lds32f(base + 24576));
            const uint32_t red = sb + tab_off(tk) + T_RED + 4 * col, key = lds32(misc + 48 + 8 * tk);
            mbar_wait(bar0 + 8 * B_SFREE, 0);
            asm volatile("st.async.weak.shared::cluster.mbarrier::complete_tx::bytes.f32 [%0], %1, [%2];"
                         ::"r"(mapa(red, h ^ 1)), "f"(y0), "r"(mapa(bar0 + 8 * B_RED, h ^ 1)) : "memory");
            const float rv = __uint_as_float(unorder_key(key >> 16) << 16);
            const float sg = bf_round(rcpf(1.f + ex2f(-1.4426950408889634f * rv)));
            mbar_wait(bar0 + 8 * B_RED, 0);
            sts32f(red, bf_round(y0 + lds32f(red)) * sg);
            __syncwarp();
            if (elect_one()) mbar_arrive(bar0 + 8 * B_UPD);
        }
        STAMP(17); GSTAMP(29);
    }
}

typedef CUresult (*EncodeFn)(CUtensorMap*, CUtensorMapDataType, cuuint32_t, void*, const cuuint64_t*, const cuuint64_t*,
                             const cuuint32_t*, const cuuint32_t*, CUtensorMapInterleave, CUtensorMapSwizzle,
                             CUtensorMapL2promotion, CUtensorMapFloatOOBfill);

void make_map(EncodeFn enc, CUtensorMap* m, const void* ptr, uint64_t cols, uint64_t rows, uint32_t bc, uint32_t br,
              CUtensorMapSwizzle sw, CUtensorMapL2promotion pr) {
    cuuint64_t dims[2] = {cols, rows};
    cuuint64_t str[1] = {cols * 2};
    cuuint32_t box[2] = {bc, br};
    cuuint32_t es[2] = {1, 1};
    enc(m, CU_TENSOR_MAP_DATA_TYPE_BFLOAT16, 2, const_cast<void*>(ptr), dims, str, box, es, CU_TENSOR_MAP_INTERLEAVE_NONE, sw, pr,
        CU_TENSOR_MAP_FLOAT_OOB_FILL_NONE);
}
void make_perm_map(EncodeFn enc, CUtensorMap* m, const void* ptr, CUtensorMapL2promotion pr) {
    cuuint64_t dims[5] = {DM, 2, 4, 4, FF / 32};
    cuuint64_t str[4] = {DM * 2, 8 * DM * 2, 2 * DM * 2, 32 * DM * 2};
    cuuint32_t box[5] = {16, 2, 4, 4, 7};
    cuuint32_t es[5] = {1, 1, 1, 1, 1};
    enc(m, CU_TENSOR_MAP_DATA_TYPE_BFLOAT16, 5, const_cast<void*>(ptr), dims, str, box, es, CU_TENSOR_MAP_INTERLEAVE_NONE,
        CU_TENSOR_MAP_SWIZZLE_32B, pr, CU_TENSOR_MAP_FLOAT_OOB_FILL_NONE);
}
void make_tile_map(EncodeFn enc, CUtensorMap* m, const void* ptr) {
    cuuint64_t dims[4] = {DM, 4, 16, SEQ / 64};
    cuuint64_t str[3] = {16 * DM * 2, DM * 2, 64 * DM * 2};
    cuuint32_t box[4] = {16, 4, 2, 8};
    cuuint32_t es[4] = {1, 1, 1, 1};
    enc(m, CU_TENSOR_MAP_DATA_TYPE_BFLOAT16, 4, const_cast<void*>(ptr), dims, str, box, es, CU_TENSOR_MAP_INTERLEAVE_NONE,
        CU_TENSOR_MAP_SWIZZLE_32B, CU_TENSOR_MAP_L2_PROMOTION_NONE, CU_TENSOR_MAP_FLOAT_OOB_FILL_NONE);
}

}

#define WD_PROMO CU_TENSOR_MAP_L2_PROMOTION_L2_64B
extern "C" void kernel_launch(void* const* d_in, const int* in_sizes, int n_in, void* d_out, int out_size) {
    (void)in_sizes; (void)n_in; (void)out_size;
    static EncodeFn enc = nullptr;
    static void* scratch = nullptr;
    if (!enc) {
        void* fn = nullptr;
        cudaDriverEntryPointQueryResult q;
        cudaGetDriverEntryPoint("cuTensorMapEncodeTiled", &fn, cudaEnableDefault, &q);
        enc = (EncodeFn)fn;
        cudaGetSymbolAddress(&scratch, g_scratch);
        cudaFuncSetAttribute(fused_kernel, cudaFuncAttributeMaxDynamicSharedMemorySize, SMEM_BYTES);
    }
    Maps maps;
    make_tile_map(enc, &maps.u, d_in[0]);
    make_tile_map(enc, &maps.out, d_out);
    make_map(enc, &maps.wg, d_in[9], FF, DM, 64, 32, CU_TENSOR_MAP_SWIZZLE_128B, CU_TENSOR_MAP_L2_PROMOTION_L2_128B);
    make_map(enc, &maps.wu, d_in[10], FF, DM, 64, 32, CU_TENSOR_MAP_SWIZZLE_128B, CU_TENSOR_MAP_L2_PROMOTION_L2_128B);
    make_perm_map(enc, &maps.wd, d_in[11], WD_PROMO);
    Ptrs p;
    p.sc = (Scratch*)scratch;
    p.u = (const __nv_bfloat16*)d_in[0];
    p.logA = (const __nv_bfloat16*)d_in[1];
    p.Aim = (const __nv_bfloat16*)d_in[2];
    p.Cre = (const __nv_bfloat16*)d_in[3];
    p.Cim = (const __nv_bfloat16*)d_in[4];
    p.ldt = (const __nv_bfloat16*)d_in[5];
    p.dsk = (const __nv_bfloat16*)d_in[6];
    p.wr = (const __nv_bfloat16*)d_in[8];
    p.out = (__nv_bfloat16*)d_out;
    p.zero = 0;
    fused_kernel<<<NCTA, NTHR, SMEM_BYTES, cudaStreamPerThread>>>(p, maps);
}
```

```cpp
#include <cuda_runtime.h>
#include <cuda_bf16.h>
#include <cuda_fp16.h>
#include <cuda.h>
#include <stdint.h>

namespace {

constexpr int SEQ = 2048, DM = 1024, NMODE = 128, FF = 3584;
constexpr int NCTA = 128, NTHR = 512;
constexpr int GU_CTAS = 112;
constexpr int NREP = 4;

constexpr int OFF_XT = 0;
constexpr int OFF_RING = 65536;
constexpr int OFF_PRIV = OFF_RING + 65536;
constexpr int OFF_VT = OFF_PRIV + 65536;
constexpr int VT_PAD = 32, VT_PLANE = VT_PAD + 2048, VT_PITCH = 2 * VT_PLANE, ROW_PITCH = 2064;
constexpr int OFF_BAR = OFF_VT + 8 * VT_PITCH;
constexpr int OFF_MISC = OFF_BAR + 384;
constexpr int OFF_XCH = OFF_MISC + 112;
constexpr int SMEM_BYTES = OFF_XCH + 2048;
constexpr int OFF_LN = OFF_RING + 7 * 8192;
constexpr int OFF_ST = OFF_RING + 6 * 8192;
static_assert(SMEM_BYTES <= 232448, "shared memory");

constexpr int B_ROW = 0, B_XT = 4, B_V = 5, B_LN = 6, B_SFREE = 7, B_RECV = 8, B_RED = 10, B_UPD = 11, B_ST = 12, B_XFREE = 16, B_FREE = 20, B_FULL = 32, B_AUX = 44, NBAR = 48;

constexpr int T_DENSE = 60;
constexpr int T_PATCH = 2208;
constexpr int T_R2 = 2368;
constexpr int T_R3 = 3296;

constexpr int T_RED = 4032;
__device__ __forceinline__ bool slot_priv(int s) { return (uint32_t)(s - 6) < 4u; }
__device__ __forceinline__ uint32_t slot_off(int s) { return slot_priv(s) ? OFF_PRIV + 4096 + (s & 3) * 16384 : OFF_RING + (s < 6 ? s : s - 4) * 8192; }
__device__ __forceinline__ uint32_t tab_off(int w) { return OFF_PRIV + w * 8192 + (w & 1) * 4096; }

constexpr uint32_t SPIN_LIMIT = 1u << 20;
#define KG_UNROLL 4
constexpr int kKgUnroll = KG_UNROLL;
#define BB_UNROLL 2
constexpr int kBbUnroll = BB_UNROLL;
#define DENSE_UNROLL 1
constexpr int kDenseUnroll = DENSE_UNROLL;
#define ST_T0 2400
#define LN_PAUSE 0xf0
#define FEW_ST 0
#define FEW_H 0
#define PERM 2
#define PERM_OFF 60
#define STORE_AT 12
#define ST_LATE 16
#define ST_GAP 0
#define ST_PER 308
#define ST_PER2 335

struct Exchange {
    uint2 stat[SEQ];
    uint4 h[GU_CTAS * 32];
    uint32_t n_stat[4 * 32];
    uint32_t n_h[8 * 32];
};
struct Scratch {
    Exchange x[NREP];
    uint32_t epoch;
};
__device__ __align__(128) Scratch g_scratch;

struct Ptrs {
    Scratch* sc;
    const __nv_bfloat16 *logA, *Aim, *Cre, *Cim, *ldt, *dsk, *u, *wr;
    __nv_bfloat16* out;
    uint32_t zero;
};
struct Maps {
    CUtensorMap u, out, wg, wu, wd;
};

#define STAMP(i) do { } while (0)
#define KSTAMP(i) do { } while (0)
#define GSTAMP(i) do { } while (0)

__device__ __forceinline__ uint32_t s_u32(const void* p) { return (uint32_t)__cvta_generic_to_shared(p); }
__device__ __forceinline__ void mbar_init(uint32_t b, uint32_t n) {
    asm volatile("mbarrier.init.shared::cta.b64 [%0], %1;" ::"r"(b), "r"(n) : "memory");
}
__device__ __forceinline__ void mbar_expect_tx(uint32_t b, uint32_t bytes) {
    asm volatile("mbarrier.arrive.expect_tx.shared::cta.b64 _, [%0], %1;" ::"r"(b), "r"(bytes) : "memory");
}
__device__ __forceinline__ void mbar_arrive(uint32_t b) {
    asm volatile("mbarrier.arrive.shared::cta.b64 _, [%0];" ::"r"(b) : "memory");
}
__device__ __forceinline__ void mbar_arrive_n(uint32_t b, uint32_t n) {
    asm volatile("mbarrier.arrive.shared::cta.b64 _, [%0], %1;" ::"r"(b), "r"(n) : "memory");
}
__device__ __forceinline__ void mbar_arrive_peer(uint32_t b_cluster) {
    asm volatile("mbarrier.arrive.relaxed.cluster.shared::cluster.b64 _, [%0];" ::"r"(b_cluster) : "memory");
}
__device__ __forceinline__ void mbar_wait(uint32_t b, uint32_t parity) {
    asm volatile("{\n\t.reg .pred p;\n\t.reg .u32 c;\n\tmov.u32 c, 0;\n"
                 "W:\n\tmbarrier.try_wait.parity.shared::cta.b64 p, [%0], %1;\n\t@p bra D;\n\t"
                 "add.u32 c, c, 1;\n\tsetp.lt.u32 p, c, 1048576;\n\t@p bra W;\n\ttrap;\nD:\n\t}"
                 ::"r"(b), "r"(parity) : "memory");
}
__device__ __forceinline__ bool mbar_test(uint32_t b, uint32_t parity) {
    uint32_t ok;
    asm volatile("{ .reg .pred p; mbarrier.test_wait.parity.shared::cta.b64 p, [%1], %2; selp.u32 %0, 1, 0, p; }" : "=r"(ok) : "r"(b), "r"(parity) : "memory");
    return __all_sync(0xffffffffu, ok != 0);
}
__device__ __forceinline__ bool elect_one() {
    uint32_t p;
    asm volatile("{ .reg .pred P; elect.sync _|P, 0xffffffff; selp.u32 %0, 1, 0, P; }" : "=r"(p));
    return p != 0;
}
__device__ __forceinline__ uint32_t mapa(uint32_t a, uint32_t rank) {
    uint32_t r;
    asm("mapa.shared::cluster.u32 %0, %1, %2;" : "=r"(r) : "r"(a), "r"(rank));
    return r;
}
__device__ __forceinline__ void cluster_arrive() { asm volatile("barrier.cluster.arrive.relaxed.aligned;" ::: "memory"); }
__device__ __forceinline__ void cluster_wait() { asm volatile("barrier.cluster.wait.acquire.aligned;" ::: "memory"); }
__device__ __forceinline__ void tma_load_2d(uint32_t dst, const CUtensorMap* m, int c0, int c1, uint32_t bar) {
    asm volatile("cp.async.bulk.tensor.2d.shared::cluster.global.mbarrier::complete_tx::bytes [%0], [%1, {%3, %4}], [%2];"
                 ::"r"(dst), "l"(m), "r"(bar), "r"(c0), "r"(c1) : "memory");
}
__device__ __forceinline__ void tma_load_perm(uint32_t dst, const CUtensorMap* m, int c0, int blk, uint32_t bar) {
    asm volatile("cp.async.bulk.tensor.5d.shared::cluster.global.mbarrier::complete_tx::bytes [%0], [%1, {%3, %4, %4, %4, %5}], [%2];"
                 ::"r"(dst), "l"(m), "r"(bar), "r"(c0), "r"(0), "r"(blk) : "memory");
}
__device__ __forceinline__ void tma_load_tile(uint32_t dst, const CUtensorMap* m, int c0, int c2, int c3, uint32_t bar) {
    asm volatile("cp.async.bulk.tensor.4d.shared::cluster.global.mbarrier::complete_tx::bytes.multicast::cluster [%0], [%1, {%3, %4, %5, %6}], [%2], %7;"
                 ::"r"(dst), "l"(m), "r"(bar), "r"(c0), "r"(0), "r"(c2), "r"(c3), "h"((uint16_t)3) : "memory");
}
__device__ __forceinline__ void tma_store_tile(const CUtensorMap* m, uint32_t src, int c0, int c2, int c3) {
    asm volatile("cp.async.bulk.tensor.4d.global.shared::cta.bulk_group [%0, {%2, %3, %4, %5}], [%1];"
                 ::"l"(m), "r"(src), "r"(c0), "r"(0), "r"(c2), "r"(c3) : "memory");
    asm volatile("cp.async.bulk.commit_group;" ::: "memory");
}
__device__ __forceinline__ void bulk_g2s(uint32_t dst, const void* src, uint32_t bytes, uint32_t bar) {
    asm volatile("cp.async.bulk.shared::cluster.global.mbarrier::complete_tx::bytes [%0], [%1], %2, [%3];"
                 ::"r"(dst), "l"(src), "r"(bytes), "r"(bar) : "memory");
}
__device__ __forceinline__ void cp_async16(uint32_t dst, const void* src) {
    asm volatile("cp.async.cg.shared.global [%0], [%1], 16;" ::"r"(dst), "l"(src) : "memory");
}
__device__ __forceinline__ void st_async128(uint32_t dst_cluster, uint32_t x, uint32_t y, uint32_t z, uint32_t w, uint32_t bar_cluster) {
    asm volatile("st.async.weak.shared::cluster.mbarrier::complete_tx::bytes.v4.b32 [%0], {%1,%2,%3,%4}, [%5];"
                 ::"r"(dst_cluster), "r"(x), "r"(y), "r"(z), "r"(w), "r"(bar_cluster) : "memory");
}
__device__ __forceinline__ void fence_async() { asm volatile("fence.proxy.async.shared::cta;" ::: "memory"); }
__device__ __forceinline__ void named_sync(int id, int n) { asm volatile("bar.sync %0, %1;" ::"r"(id), "r"(n) : "memory"); }

__device__ __forceinline__ void ldsm4(uint32_t* r, uint32_t a) {
    asm volatile("ldmatrix.sync.aligned.m8n8.x4.shared.b16 {%0,%1,%2,%3}, [%4];"
                 : "=r"(r[0]), "=r"(r[1]), "=r"(r[2]), "=r"(r[3]) : "r"(a));
}
__device__ __forceinline__ void ldsm4t(uint32_t* r, uint32_t a) {
    asm volatile("ldmatrix.sync.aligned.m8n8.x4.trans.shared.b16 {%0,%1,%2,%3}, [%4];"
                 : "=r"(r[0]), "=r"(r[1]), "=r"(r[2]), "=r"(r[3]) : "r"(a));
}
__device__ __forceinline__ void stsm4t(uint32_t a, uint32_t x, uint32_t y, uint32_t z, uint32_t w) {
    asm volatile("stmatrix.sync.aligned.m8n8.x4.trans.shared.b16 [%0], {%1,%2,%3,%4};"
                 ::"r"(a), "r"(x), "r"(y), "r"(z), "r"(w) : "memory");
}
__device__ __forceinline__ uint32_t lds32(uint32_t a) { uint32_t v; asm volatile("ld.shared.u32 %0, [%1];" : "=r"(v) : "r"(a)); return v; }
__device__ __forceinline__ float lds32f(uint32_t a) { float v; asm volatile("ld.shared.f32 %0, [%1];" : "=f"(v) : "r"(a)); return v; }
__device__ __forceinline__ uint2 lds64(uint32_t a) { uint2 v; asm volatile("ld.shared.v2.u32 {%0,%1}, [%2];" : "=r"(v.x), "=r"(v.y) : "r"(a)); return v; }
__device__ __forceinline__ uint4 lds128(uint32_t a) {
    uint4 v; asm volatile("ld.shared.v4.u32 {%0,%1,%2,%3}, [%4];" : "=r"(v.x), "=r"(v.y), "=r"(v.z), "=r"(v.w) : "r"(a)); return v;
}
__device__ __forceinline__ uint4 lds128v(uint32_t a) {
    uint4 v; asm volatile("ld.volatile.shared.v4.u32 {%0,%1,%2,%3}, [%4];" : "=r"(v.x), "=r"(v.y), "=r"(v.z), "=r"(v.w) : "r"(a)); return v;
}
__device__ __forceinline__ uint32_t or_xor(uint32_t a, uint32_t b, uint32_t c) {
    uint32_t r; asm("lop3.b32 %0, %1, %2, %3, 0xf6;" : "=r"(r) : "r"(a), "r"(b), "r"(c)); return r;
}
__device__ __forceinline__ float4 lds128f(uint32_t a) {
    float4 v; asm volatile("ld.shared.v4.f32 {%0,%1,%2,%3}, [%4];" : "=f"(v.x), "=f"(v.y), "=f"(v.z), "=f"(v.w) : "r"(a)); return v;
}
__device__ __forceinline__ void sts32(uint32_t a, uint32_t v) { asm volatile("st.shared.u32 [%0], %1;" ::"r"(a), "r"(v) : "memory"); }
__device__ __forceinline__ void sts32f(uint32_t a, float v) { asm volatile("st.shared.f32 [%0], %1;" ::"r"(a), "f"(v) : "memory"); }
__device__ __forceinline__ void sts64(uint32_t a, uint32_t x, uint32_t y) { asm volatile("st.shared.v2.u32 [%0], {%1,%2};" ::"r"(a), "r"(x), "r"(y) : "memory"); }
__device__ __forceinline__ void sts64f(uint32_t a, float x, float y) { asm volatile("st.shared.v2.f32 [%0], {%1,%2};" ::"r"(a), "f"(x), "f"(y) : "memory"); }
__device__ __forceinline__ void sts128(uint32_t a, uint32_t x, uint32_t y, uint32_t z, uint32_t w) {
    asm volatile("st.shared.v4.u32 [%0], {%1,%2,%3,%4};" ::"r"(a), "r"(x), "r"(y), "r"(z), "r"(w) : "memory");
}
__device__ __forceinline__ void sts128f(uint32_t a, const float* v) {
    asm volatile("st.shared.v4.f32 [%0], {%1,%2,%3,%4};" ::"r"(a), "f"(v[0]), "f"(v[1]), "f"(v[2]), "f"(v[3]) : "memory");
}
__device__ __forceinline__ uint4 ldg128(const void* p) {
    uint4 v; asm volatile("ld.global.nc.L1::no_allocate.v4.u32 {%0,%1,%2,%3}, [%4];" : "=r"(v.x), "=r"(v.y), "=r"(v.z), "=r"(v.w) : "l"(p)); return v;
}
__device__ __forceinline__ uint2 ldg64(const void* p) {
    uint2 v; asm volatile("ld.global.nc.L1::no_allocate.v2.u32 {%0,%1}, [%2];" : "=r"(v.x), "=r"(v.y) : "l"(p)); return v;
}
__device__ __forceinline__ uint32_t ldg32(const void* p) {
    uint32_t v; asm volatile("ld.global.nc.u32 %0, [%1];" : "=r"(v) : "l"(p)); return v;
}
__device__ __forceinline__ uint32_t ldg16(const void* p) {
    uint32_t v; asm volatile("ld.global.nc.u16 %0, [%1];" : "=r"(v) : "l"(p)); return v;
}
__device__ __forceinline__ uint4 ld_relaxed_128(const void* p) {
    uint4 v; asm volatile("ld.relaxed.gpu.global.v4.u32 {%0,%1,%2,%3}, [%4];" : "=r"(v.x), "=r"(v.y), "=r"(v.z), "=r"(v.w) : "l"(p) : "memory"); return v;
}
__device__ __forceinline__ void ld_relaxed_128_unless(uint4& q, const void* p, bool have) {
    asm volatile("{ .reg .pred p; setp.eq.u32 p, %5, 0; @p ld.relaxed.gpu.global.v4.u32 {%0,%1,%2,%3}, [%4]; }"
                 : "+r"(q.x), "+r"(q.y), "+r"(q.z), "+r"(q.w) : "l"(p), "r"((uint32_t)have) : "memory");
}
__device__ __forceinline__ uint2 ld_relaxed_64(const void* p) {
    uint2 v; asm volatile("ld.relaxed.gpu.global.v2.u32 {%0,%1}, [%2];" : "=r"(v.x), "=r"(v.y) : "l"(p) : "memory"); return v;
}
__device__ __forceinline__ uint32_t ld_relaxed_32(const void* p) {
    uint32_t v; asm volatile("ld.relaxed.gpu.global.u32 %0, [%1];" : "=r"(v) : "l"(p) : "memory"); return v;
}
__device__ __forceinline__ void st_relaxed_128(void* p, uint32_t x, uint32_t y, uint32_t z, uint32_t w) {
    asm volatile("st.relaxed.gpu.global.v4.u32 [%0], {%1,%2,%3,%4};" ::"l"(p), "r"(x), "r"(y), "r"(z), "r"(w) : "memory");
}
__device__ __forceinline__ void st_relaxed_64(void* p, uint32_t x, uint32_t y) {
    asm volatile("st.relaxed.gpu.global.v2.u32 [%0], {%1,%2};" ::"l"(p), "r"(x), "r"(y) : "memory");
}
__device__ __forceinline__ void st_relaxed_32(void* p, uint32_t v) {
    asm volatile("st.relaxed.gpu.global.u32 [%0], %1;" ::"l"(p), "r"(v) : "memory");
}
__device__ __forceinline__ void red_add(void* p, uint32_t v) { asm volatile("red.relaxed.gpu.global.add.u32 [%0], %1;" ::"l"(p), "r"(v) : "memory"); }
__device__ __forceinline__ uint32_t now_ns() { uint32_t t; asm volatile("mov.u32 %0, %%globaltimer_lo;" : "=r"(t) :: "memory"); return t; }
__device__ __forceinline__ void spin_guard(uint32_t& it) { if (++it > SPIN_LIMIT) __trap(); }
__device__ __forceinline__ void wait_count(const uint32_t* p, uint32_t target) {
#pragma unroll 1
    for (uint32_t it = 0; __any_sync(0xffffffffu, (int)(ld_relaxed_32(p) - target) < 0); spin_guard(it)) { }
}
__device__ __forceinline__ void mma_bf16(float* c, uint32_t a0, uint32_t a1, uint32_t a2, uint32_t a3, uint32_t b0, uint32_t b1) {
    asm("mma.sync.aligned.m16n8k16.row.col.f32.bf16.bf16.f32 {%0,%1,%2,%3}, {%4,%5,%6,%7}, {%8,%9}, {%0,%1,%2,%3};"
                 : "+f"(c[0]), "+f"(c[1]), "+f"(c[2]), "+f"(c[3]) : "r"(a0), "r"(a1), "r"(a2), "r"(a3), "r"(b0), "r"(b1));
}
__device__ __forceinline__ void mma_bf16_k8(float* c, uint32_t a0, uint32_t a1, uint32_t b0) {
    asm("mma.sync.aligned.m16n8k8.row.col.f32.bf16.bf16.f32 {%0,%1,%2,%3}, {%4,%5}, {%6}, {%0,%1,%2,%3};"
                 : "+f"(c[0]), "+f"(c[1]), "+f"(c[2]), "+f"(c[3]) : "r"(a0), "r"(a1), "r"(b0));
}
__device__ __forceinline__ void mma_v(float* c, const uint32_t* a, uint32_t b0, uint32_t b1) {
    asm volatile("mma.sync.aligned.m16n8k16.row.col.f32.bf16.bf16.f32 {%0,%1,%2,%3}, {%4,%5,%6,%7}, {%8,%9}, {%0,%1,%2,%3};"
                 : "+f"(c[0]), "+f"(c[1]), "+f"(c[2]), "+f"(c[3]) : "r"(a[0]), "r"(a[1]), "r"(a[2]), "r"(a[3]), "r"(b0), "r"(b1));
}
__device__ __forceinline__ void mma_bf16_z(float* c, uint32_t a0, uint32_t a1, uint32_t a2, uint32_t a3, uint32_t b0, uint32_t b1) {
    asm volatile("mma.sync.aligned.m16n8k16.row.col.f32.bf16.bf16.f32 {%0,%1,%2,%3}, {%4,%5,%6,%7}, {%8,%9}, {%10,%10,%10,%10};"
        : "=f"(c[0]), "=f"(c[1]), "=f"(c[2]), "=f"(c[3]) : "r"(a0), "r"(a1), "r"(a2), "r"(a3), "r"(b0), "r"(b1), "f"(0.f));
}
__device__ __forceinline__ void mma_f16(float* c, uint32_t a0, uint32_t a1, uint32_t a2, uint32_t a3, uint32_t b0, uint32_t b1) {
    asm("mma.sync.aligned.m16n8k16.row.col.f32.f16.f16.f32 {%0,%1,%2,%3}, {%4,%5,%6,%7}, {%8,%9}, {%0,%1,%2,%3};"
                 : "+f"(c[0]), "+f"(c[1]), "+f"(c[2]), "+f"(c[3]) : "r"(a0), "r"(a1), "r"(a2), "r"(a3), "r"(b0), "r"(b1));
}
__device__ __forceinline__ uint32_t pack_bf16(float lo, float hi) {
    uint32_t r; asm("cvt.rn.bf16x2.f32 %0, %1, %2;" : "=r"(r) : "f"(hi), "f"(lo)); return r;
}
__device__ __forceinline__ uint32_t pack_v(float lo, float hi) {
    uint32_t r; asm volatile("cvt.rn.bf16x2.f32 %0, %1, %2;" : "=r"(r) : "f"(hi), "f"(lo)); return r;
}
__device__ __forceinline__ uint32_t pack_w(float lo, float hi) {
    uint32_t r; asm volatile("cvt.rn.satfinite.bf16x2.f32 %0, %1, %2;" : "=r"(r) : "f"(hi), "f"(lo)); return r;
}
template <int N> __device__ __forceinline__ uint32_t after_all(const uint32_t (&f)[N][4], uint32_t zero) {
    uint32_t d[3] = {0, 0, 0};
#pragma unroll
    for (int i = 0; i < N; i++) d[i % 3] |= f[i][3];
    return (d[0] | d[1] | d[2]) & zero;
}
__device__ __forceinline__ void pin(uint32_t& x) { asm volatile("" : "+r"(x)); }
template <class T> __device__ __forceinline__ void pin(T*& x) { asm volatile("" : "+l"(x)); }
__device__ __forceinline__ uint32_t pack_f16(float lo, float hi) {
    uint32_t r; asm("cvt.rn.f16x2.f32 %0, %1, %2;" : "=r"(r) : "f"(hi), "f"(lo)); return r;
}
__device__ __forceinline__ float bf_lo(uint32_t v) { return __uint_as_float(v << 16); }
__device__ __forceinline__ float bf_hi(uint32_t v) { return __uint_as_float(v & 0xffff0000u); }
__device__ __forceinline__ float bf_round(float x) { return __uint_as_float(pack_bf16(0.f, x)); }
__device__ __forceinline__ uint32_t badd2(uint32_t a, uint32_t b) { uint32_t r; asm("add.rn.bf16x2 %0, %1, %2;" : "=r"(r) : "r"(a), "r"(b)); return r; }
__device__ __forceinline__ uint32_t bsub2_lo(uint32_t a, uint32_t b) {
    uint32_t r; asm("{ .reg .b16 m, h; .reg .b32 m2; mov.b32 {m, h}, %2; mov.b32 m2, {m, m}; sub.rn.bf16x2 %0, %1, m2; }" : "=r"(r) : "r"(a), "r"(b)); return r;
}
__device__ __forceinline__ uint32_t bmax2(uint32_t a, uint32_t b) { uint32_t r; asm("max.bf16x2 %0, %1, %2;" : "=r"(r) : "r"(a), "r"(b)); return r; }
__device__ __forceinline__ uint32_t normalize2(uint32_t x, uint32_t s0, uint32_t s1) {
    uint32_t r;
    asm("{ .reg .b16 m, h, l, k; .reg .b32 m2, h2, l2, d, t;\n\t"
        "mov.b32 {m, h}, %2; mov.b32 {l, k}, %3; mov.b32 m2, {m, m}; mov.b32 h2, {h, h}; mov.b32 l2, {l, l};\n\t"
        "sub.rn.bf16x2 d, %1, m2; mul.rn.bf16x2 t, d, l2; fma.rn.bf16x2 %0, d, h2, t; }" : "=r"(r) : "r"(x), "r"(s0), "r"(s1));
    return r;
}
__device__ __forceinline__ float rcpf(float x) { float r; asm("rcp.approx.ftz.f32 %0, %1;" : "=f"(r) : "f"(x)); return r; }
__device__ __forceinline__ float sqrtaf(float x) { float r; asm("sqrt.approx.ftz.f32 %0, %1;" : "=f"(r) : "f"(x)); return r; }
__device__ __forceinline__ float ex2f(float x) { float r; asm("ex2.approx.ftz.f32 %0, %1;" : "=f"(r) : "f"(x)); return r; }

__device__ __forceinline__ int tok_off(int t) { return ((t >> 3) & 1) * VT_PLANE + (t >> 4) * 16 + (t & 7) * 2; }

__device__ __forceinline__ uint32_t order_key(uint32_t b16) { return b16 ^ ((b16 & 0x8000u) ? 0xffffu : 0x8000u); }
__device__ __forceinline__ uint32_t unorder_key(uint32_t k16) { return k16 ^ ((k16 & 0x8000u) ? 0x8000u : 0xffffu); }

struct cplx { float r, i; };
struct hc { uint32_t r, i; };
template <bool CONJ> __device__ __forceinline__ cplx csq(cplx a) {
    float im;
    asm("{ .reg .f32 t; mul.ftz.f32 t, %1, %2; mul.ftz.f32 %0, t, 0f40000000; }" : "=f"(im) : "f"(CONJ ? -a.r : a.r), "f"(a.i));
    return {fmaf(a.r, a.r, -(a.i * a.i)), im};
}
__device__ __forceinline__ cplx cexpp(float a2, float ai) {
    float m = ex2f(a2), s, c;
    __sincosf(ai, &s, &c);
    return {m * c, m * s};
}
__device__ __forceinline__ __half2 as_h2(uint32_t x) { return *reinterpret_cast<__half2*>(&x); }
__device__ __forceinline__ uint32_t as_u(__half2 x) { return *reinterpret_cast<uint32_t*>(&x); }
__device__ __forceinline__ hc hmul(hc a, hc b) {
    return {as_u(__hfma2(as_h2(a.r), as_h2(b.r), __hneg2(__hmul2(as_h2(a.i), as_h2(b.i))))),
            as_u(__hfma2(as_h2(a.r), as_h2(b.i), __hmul2(as_h2(a.i), as_h2(b.r))))};
}
__device__ __forceinline__ hc hpack(cplx a, cplx b) { return {pack_f16(a.r, b.r), pack_f16(a.i, b.i)}; }
__device__ __forceinline__ void sts16(uint32_t a, uint32_t v) { asm volatile("st.shared.u16 [%0], %1;" ::"r"(a), "r"(v) : "memory"); }

struct KgenAddr {
    uint32_t l, h, m2, m3, m4, z, w, wz;
    __device__ __forceinline__ KgenAddr(uint32_t scr, int lane) {
        const int g = lane >> 2, t = lane & 3;
        const uint32_t rec = scr + t * 480;
        l = rec + 16 * g; h = rec + 128 + 8 * g; m2 = rec + 192 + 8 * (g & 1); m3 = rec + 208 + 4 * (g & 2); m4 = rec + 224 + 2 * (g & 4);
        z = scr + 7680 + 16 * t; w = scr + 240 * lane; wz = scr + 7680 + 8 * lane;
        pin(l); pin(h); pin(m2); pin(m3); pin(m4); pin(z); pin(w); pin(wz);
    }
    __device__ __forceinline__ uint32_t any() const { return (l | h | m2) | (m3 | m4 | z) | (w | wz); }
};
template <class Hook, class Hook2>
__device__ __forceinline__ void kgen(const KgenAddr& ad, uint32_t tab, int lane, uint2 la, uint2 aim, uint2 cre, uint2 cim, float dt, float skip, int dch, Hook main_done, Hook2 half_done) {
    const int g = lane >> 2, t = lane & 3;
    const float dt2 = 2.f * dt;
    const uint32_t am = bmax2(bmax2(cre.x & 0x7fff7fffu, cre.y & 0x7fff7fffu), bmax2(cim.x & 0x7fff7fffu, cim.y & 0x7fff7fffu));
    const float mx = dt2 * fmaxf(bf_lo(am), bf_hi(am));
    const uint32_t eb = min(max(__reduce_max_sync(0xffffffffu, __float_as_uint(mx)) >> 23, 1u), 252u);
    const float cscale = dt2 * __uint_as_float((253u - eb) << 23);
    const float scale_inv = __uint_as_float((eb + 1u) << 23);
    float k0 = (bf_lo(cre.x) + bf_hi(cre.x)) + (bf_lo(cre.y) + bf_hi(cre.y));
#pragma unroll
    for (int o = 16; o; o >>= 1) k0 += __shfl_xor_sync(0xffffffffu, k0, o);
    const float ndt = -1.4426950408889634f * dt;
    STAMP(40); KSTAMP(0);

    float acc[5][4];
#pragma unroll
    for (int i = 0; i < 5; i++) { acc[i][0] = acc[i][1] = acc[i][2] = acc[i][3] = 0.f; }

#pragma unroll kBbUnroll
    for (int bb = 0; bb < 2; bb++) {
        cplx z[2][11], cz[2];
#pragma unroll
        for (int e = 0; e < 2; e++) {
            const float lg = e ? bf_hi(la.x) : bf_lo(la.x), ai = (e ? bf_hi(aim.x) : bf_lo(aim.x)) * dt;
            const float cr = (e ? bf_hi(cre.x) : bf_lo(cre.x)) * cscale, ci = (e ? bf_hi(cim.x) : bf_lo(cim.x)) * cscale;
            const float a2 = bf_round(ex2f(lg * 1.4426950408889634f)) * ndt;
            z[e][0] = cexpp(a2, ai);
            z[e][5] = cexpp(a2 * 32.f, ai * -32.f);
#pragma unroll
            for (int i = 1; i < 11; i++) if (i != 5) z[e][i] = (i == 3 || i == 7) ? csq<true>(z[e][i - 1]) : csq<false>(z[e][i - 1]);
            cz[e] = {fmaf(cr, z[e][0].r, -(ci * z[e][0].i)), fmaf(cr, z[e][0].i, ci * z[e][0].r)};
        }
        la.x = la.y; aim.x = aim.y; cre.x = cre.y; cim.x = cim.y;
        const hc z1 = hpack(z[0][0], z[1][0]), z2 = hpack(z[0][1], z[1][1]), z4 = hpack(z[0][2], z[1][2]);
        hc L[8], H[8];
        L[1] = hpack(z[0][3], z[1][3]); L[2] = hpack(z[0][4], z[1][4]); L[4] = hpack(z[0][5], z[1][5]);
        const hc y64 = hpack(z[0][6], z[1][6]), z128 = hpack(z[0][7], z[1][7]), z256 = hpack(z[0][8], z[1][8]);
        const hc z512 = hpack(z[0][9], z[1][9]), z1024 = hpack(z[0][10], z[1][10]);
        H[0] = hpack(cz[0], cz[1]);
        H[1] = hmul(H[0], z1); H[2] = hmul(H[0], z2); H[3] = hmul(H[1], z2);
        L[3] = hmul(L[1], L[2]);
#pragma unroll
        for (int i = 0; i < 4; i++) { H[4 + i] = hmul(H[i], z4); if (i) L[4 + i] = hmul(L[i], L[4]); }
        __syncwarp();
        sts128(ad.w, 0x3c003c00u, y64.r, 0u, y64.i);
#pragma unroll
        for (int i = 1; i < 8; i++) { const hc q = hmul(L[i], y64); sts128(ad.w + 16 * i, L[i].r, q.r, L[i].i, q.i); }
#pragma unroll
        for (int i = 0; i < 4; i++) sts128(ad.w + 128 + 16 * i, H[2 * i].r, H[2 * i].i, H[2 * i + 1].r, H[2 * i + 1].i);
        {
            const hc a = hmul(z256, z1), b = hmul(z256, z128), c = hmul(z256, z2), d = hmul(z512, z4);
            sts128(ad.w + 192, a.r, a.i, b.r, b.i);
            sts128(ad.w + 208, c.r, c.i, z512.r, z512.i);
            sts128(ad.w + 224, d.r, d.i, z1024.r, z1024.i);
            sts64(ad.wz, z128.r, z128.i);
        }
        __syncwarp();
        KSTAMP(1 + 2 * bb);
#pragma unroll kKgUnroll
        for (int k2 = 0; k2 < 4; k2++) {
#pragma unroll
            for (uint32_t s = 0; s < 2; s++) {
                const uint32_t o = k2 * 1920 + s * 240;
                const uint4 l = lds128(ad.l + o);
                const uint2 h0 = lds64(ad.h + o), m2 = lds64(ad.m2 + o), m3 = lds64(ad.m3 + o), m4 = lds64(ad.m4 + o), mz = lds64(ad.z + k2 * 64 + s * 8);
                const hc H0 = {h0.x, h0.y};
                const hc H1 = hmul(H0, {mz.x, mz.y}), H2 = hmul(H0, {m2.x, m2.y}), H3 = hmul(H2, {m3.x, m3.y}), H4 = hmul(H3, {m4.x, m4.y});
                mma_f16(acc[0], l.x, l.y, l.z, l.w, H0.r, H0.i);
                mma_f16(acc[1], l.x, l.y, l.z, l.w, H1.r, H1.i);
                mma_f16(acc[2], l.x, l.y, l.z, l.w, H2.r, H2.i);
                mma_f16(acc[3], l.x, l.y, l.z, l.w, H3.r, H3.i);
                mma_f16(acc[4], l.x, l.y, l.z, l.w, H4.r, H4.i);
            }
        }
        KSTAMP(2 + 2 * bb);
        if (bb == 0) half_done();
    }
    __syncwarp();
    main_done();
    KSTAMP(5);
#pragma unroll
    for (int i = 0; i < 4; i++) sts128(tab + 2048 + 512 * i + 16 * lane, 0, 0, 0, 0);
    if (lane < 15) sts32(tab + 4 * lane, 0);
    __syncwarp();
    const uint32_t d0 = tab + T_DENSE + 4 + 8 * lane, src = (lane + 31) & 31;
    const uint32_t p0 = pack_bf16(fmaf(k0, dt2, skip), 0.f);
    uint32_t prev = p0;
#pragma unroll
    for (int i = 0; i < 4; i++) {
        const uint32_t pk = pack_bf16(acc[i >> 1][2 * (i & 1) + 1] * scale_inv, acc[i >> 1][2 * (i & 1)] * scale_inv);
        sts64(d0 + 256 * i, __byte_perm(pk, __shfl_sync(0xffffffffu, lane == 31 ? prev : pk, src), 0x5432), pk);
        prev = pk;
    }
    const uint32_t w0 = pack_bf16(acc[2][0] * scale_inv, acc[2][1] * scale_inv), w1 = pack_bf16(acc[2][2] * scale_inv, acc[2][3] * scale_inv);
    const uint32_t sa = (lane & 1) ? 0x5410u : 0x5454u, sb2 = (lane & 1) ? 0x1010u : 0x5410u;
#pragma unroll
    for (int hf = 0; hf < 2; hf++) {
        const uint32_t w = hf ? w1 : w0;
        const uint32_t pv = __shfl_sync(0xffffffffu, lane != 31 ? w : hf ? w0 : __byte_perm(prev, w1, 0x5410), src);
        sts64(d0 + 1024 + 256 * hf, __byte_perm(w, pv, sa), __byte_perm(w, pv, sb2));
        sts64(d0 + 1536 + 256 * hf, __byte_perm(w, pv, sa + 0x2222u), __byte_perm(w, pv, sb2 + 0x2222u));
    }
    const uint32_t d3 = tab + T_R2 + 160 + 320 * (t & 1) + 16 * (g >> 1) + 8 * (g & 1) + 4 * (t >> 1), d3n = d3 + (g >= 6 ? 32 : 0);
    const uint32_t d4 = tab + T_R3 + 80 + 160 * t + 4 * g, d4n = d4 + (g >= 6 ? 16 : 0);
    uint32_t p3;
#pragma unroll
    for (int hf = 0; hf < 2; hf++)
#pragma unroll
        for (int e = 0; e < 2; e++) {
            const float v3 = acc[3][2 * hf + e] * scale_inv;
            const uint32_t p4 = pack_bf16(acc[4][2 * hf + e] * scale_inv, 0.f);
            p3 = pack_bf16(v3, v3);
            sts16(d3 + 64 * hf + 160 * e, p3);
            sts16((hf ? d3n : d3) + 64 * hf + 160 * e + 18, p3);
            sts16(d4 + 32 * hf + 80 * e, p4);
            sts16((hf ? d4n : d4) + 32 * hf + 80 * e + 10, p4);
        }
    if (lane == 31) {
        const uint32_t k512 = __byte_perm(w1, 0, 0x3232);
        sts32(tab + T_DENSE, p0);
        sts64(tab + T_DENSE + 4 * 513, k512, k512); sts16(tab + T_DENSE + 4 * 515 + 2, k512);
        sts16(tab + T_PATCH + 4 * 17, p3); sts32(tab + T_PATCH + 4 * 18, p3); sts16(tab + T_PATCH + 4 * 19 + 2, p3);
    }
    __syncwarp();
}

__device__ __forceinline__ void load_toep(uint32_t* a, uint32_t p, uint32_t pz) {
    a[0] = lds32(p); a[1] = lds32(p + 32); a[2] = lds32(pz - 32); a[3] = lds32(pz);
}
#define YIELDS 2
#define YIELD_AT 2
#define DENSE_BLK 4
__device__ __forceinline__ void dense_step(float (&acc)[16][4], uint32_t (&R)[8][4], const uint32_t (&A)[4][4], uint32_t (&An)[4][4],
                                           uint32_t va, uint32_t vmin, uint32_t pn, uint32_t pz, uint32_t zero, int bit, uint32_t& junk) {
#pragma unroll
    for (int i0 = 0; i0 < 8; i0 += DENSE_BLK) {
#pragma unroll 1
        do {
#pragma unroll
            for (int i = i0; i < i0 + DENSE_BLK; i++) {
                const int ip = (i - DENSE_BLK) & 7;
                ldsm4(R[ip], ip == 0 ? max(va - 16, vmin) : va + ip * 128 - (i0 ? 16 : 0));
                if ((i & 1) == 0) load_toep(An[i >> 1], pn + (i >> 1) * 512, pz + (i >> 1) * 512);
#pragma unroll
                for (int ka = 0; ka < 4; ka++) {
                    mma_v(acc[i + ka], A[ka], R[i][0], R[i][1]);
                    if (i + 8 + ka < 16) mma_v(acc[i + 8 + ka], A[ka], R[i][2], R[i][3]);
                }
                if ((YIELDS >> (i - i0)) & 1) asm volatile("xor.b32 %0, %0, %1;" : "+r"(junk) : "r"(__float_as_uint(acc[i + YIELD_AT][0])));
            }
        } while (zero & (1u << (bit + i0)));
    }
}
struct DenseTaps {
    uint32_t A[4][4], E[4], F[4], G[4];
    __device__ __forceinline__ DenseTaps(uint32_t pb, uint32_t pz) {
        constexpr int PP = T_PATCH - T_DENSE + 56;
#pragma unroll
        for (int i = 0; i < 4; i++) load_toep(A[i], pb + 512 * i, pz + 512 * i);
        load_toep(E, pb + 2048, pz + 2048);
        load_toep(F, pb + PP, pz + PP);
        G[0] = lds32(pz + 2048 + 32); G[1] = lds32(pb + 2048 + 64); G[2] = lds32(pz + PP + 32); G[3] = lds32(pb + PP + 64);
    }
};
__device__ __forceinline__ uint32_t dense_phase(float (&acc)[16][4], uint32_t vrow, uint32_t pb, DenseTaps& tp, uint32_t zero, int lane) {
    uint32_t R[8][4], A1[4][4], junk = 0;
    const uint32_t vmin = vrow + ((lane >> 3) & 1) * VT_PLANE - 16 + zero;
    uint32_t va = vmin + 16 + (lane >> 4) * 1024 + (lane & 7) * 16, pz = pb + zero;
    {
        uint32_t H[4][4];
#pragma unroll
        for (int i = 0; i < 4; i++) ldsm4(H[i], vrow + VT_PLANE + 496 - ((lane >> 3) & 1) * 512 + (lane >> 4) * 128 + (lane & 7) * 16 + i * 256);
#pragma unroll
        for (int i = 0; i < 8; i++) ldsm4(R[i], va + i * 128);
#pragma unroll
        for (int i = 0; i < 4; i++) mma_bf16_k8(acc[i + 4], tp.G[0], tp.G[1], H[i >> 1][2 * (i & 1) + 1]);
#pragma unroll
        for (int i = 0; i < 8; i++) mma_v(acc[i + 8], tp.G, H[i >> 1][2 * (i & 1)], H[i >> 1][2 * (i & 1) + 1]);
#pragma unroll
        for (int i = 0; i < 12; i++) mma_v(acc[i + 4], tp.E, R[i & 7][2 * (i >> 3)], R[i & 7][2 * (i >> 3) + 1]);
#pragma unroll
        for (int i = 0; i < 8; i++) mma_v(acc[i + 8], tp.F, R[i][0], R[i][1]);
    }
#pragma unroll 1
    for (int rho = 0; rho < 8; rho += 2) {
        dense_step(acc, R, tp.A, A1, va, vmin, pb + 64, pz + 64, zero, 0, junk);
        dense_step(acc, R, A1, tp.A, va - 16, vmin, pb + 128, pz + 128, zero, 8, junk);
        pb += 128; pz += 128; va -= 32;
    }
    return junk & zero;
}
__device__ __forceinline__ uint32_t ones2(int c, int lo, int hi) {
    return (((uint32_t)(c - lo) <= (uint32_t)(hi - lo)) ? 0x3f80u : 0u) | (((uint32_t)(c + 1 - lo) <= (uint32_t)(hi - lo)) ? 0x3f800000u : 0u);
}
struct Boxes {
    uint32_t q[4], ha[2];
    __device__ __forceinline__ Boxes(uint32_t vrow, int lane, int O, int L1, int H1, int L2, int H2) {
        const int g = lane >> 2, t = lane & 3, d = 2 * t - g;
        q[0] = ones2(d, L1, H1); q[1] = ones2(d, L2, H2); q[2] = ones2(d + 8, L1, H1); q[3] = ones2(d + 8, L2, H2);
#pragma unroll
        for (int i = 0; i < 2; i++) { ha[i] = vrow + 16 * g + tok_off(O + 8 * i + 2 * t); pin(ha[i]); pin(q[i]); pin(q[2 + i]); }
    }
    __device__ __forceinline__ uint32_t any() const { return (q[0] | q[1] | q[2]) | (q[3] | ha[0] | ha[1]); }
    __device__ __forceinline__ void load(int j, uint32_t* v, uint32_t zero) const {
        const uint32_t o = j * 128;
        v[0] = lds32(ha[0] + o); v[1] = lds32(ha[1] + zero + o); v[2] = lds32(ha[1] + o);
        v[3] = lds32(ha[0] + zero + o + 16); v[4] = lds32(ha[0] + o + 16); v[5] = lds32(ha[1] + o + 16);
    }
    __device__ __forceinline__ void sums(const uint32_t* v, float* Z, float* X, float* Y) const {
        mma_bf16_z(Z, q[0], q[1], q[2], q[3], v[0], v[1]);
        mma_bf16_z(X, q[0], q[1], q[2], q[3], v[2], v[3]);
        mma_bf16_z(Y, q[0], q[1], q[2], q[3], v[4], v[5]);
    }
};
template <class After>
__device__ __forceinline__ void tail_phase(float (&acc)[16][4], const Boxes& b2, const Boxes& b3, uint32_t tp2, uint32_t tp3, uint32_t zero, After after) {
    uint2 tp[10];
    uint32_t v[6], a0[4], a1[4];
    float Z[4], X[4], Y[4];
    b2.load(0, v, zero);
#pragma unroll
    for (int i = 0; i < 5; i++) { const uint4 c = lds128(tp2 + 160 * i); tp[i] = make_uint2(c.x, c.y); tp[5 + i] = make_uint2(c.z, c.w); }
#pragma unroll
    for (int j = -1; j < 20; j++) {
        if (j < 19) {
            (j < 11 ? b2 : b3).sums(v, Z, X, Y);
            if (j < 10) b2.load(j + 2, v, zero); else if (j < 18) b3.load(j - 10, v, zero);
        }
        if (j >= 0 && j < 12) {
#pragma unroll
            for (int b = 0; b < 5; b++) if (j + 4 + b < 16) mma_v(acc[j + 4 + b], a1, tp[5 + b].x, tp[5 + b].y);
        }
        if (j < 11) { a1[0] = pack_v(Z[0], Z[1]); a1[1] = pack_w(X[0], X[1]); a1[2] = pack_v(Z[2], Z[3]); a1[3] = pack_w(X[2], X[3]); }
        if (j >= 0 && j < 12) {
#pragma unroll
            for (int b = 0; b < 5; b++) if (j + 4 + b < 16) mma_v(acc[j + 4 + b], a0, tp[b].x, tp[b].y);
            if (j >= 7 && j < 11) { tp[11 - j] = lds64(tp3 + 80 * (10 - j)); tp[16 - j] = lds64(tp3 + 80 * (14 - j)); }
        } else if (j >= 12) {
#pragma unroll
            for (int b = 0; b < 8; b++) if (j - 4 + b < 16) mma_v(acc[j - 4 + b], a0, tp[b < 4 ? b + 1 : b + 2].x, tp[b < 4 ? b + 1 : b + 2].y);
        }
        if (j < 11) { a0[0] = pack_v(X[0], X[1]); a0[1] = pack_v(Y[0], Y[1]); a0[2] = pack_v(X[2], X[3]); a0[3] = pack_v(Y[2], Y[3]); }
        else if (j < 19) { a0[0] = pack_v(X[0], X[1]); a0[1] = pack_v(Y[0], Y[1]); a0[2] = pack_v(Z[2], Z[3]); a0[3] = pack_v(X[2], X[3]); }
        after(j);
    }
}
template <int G>
__device__ __forceinline__ void emit(const float (&acc)[16][4], int h, uint32_t own, uint32_t peer, uint32_t bar, uint32_t bar_peer) {
#pragma unroll
    for (int o = 0; o < 2; o++)
#pragma unroll
        for (int hf = 0; hf < 2; hf++) {
            const int n = 8 * G + 4 * o;
            asm volatile("{ .reg .pred p; setp.eq.u32 p, %7, %8;\n\t@p st.shared.v4.u32 [%0], {%1,%2,%3,%4};\n\t"
                         "@!p st.async.weak.shared::cluster.mbarrier::complete_tx::bytes.v4.b32 [%5], {%1,%2,%3,%4}, [%6]; }"
                         ::"r"(own + G * 16384 + hf * 512), "r"(pack_bf16(acc[n][2 * hf], acc[n][2 * hf + 1])), "r"(pack_bf16(acc[n + 1][2 * hf], acc[n + 1][2 * hf + 1])),
                         "r"(pack_bf16(acc[n + 2][2 * hf], acc[n + 2][2 * hf + 1])), "r"(pack_bf16(acc[n + 3][2 * hf], acc[n + 3][2 * hf + 1])),
                         "r"(peer + G * 16384 + hf * 512), "r"(bar_peer + 8 * G), "r"(h), "r"(o) : "memory");
        }
    __syncwarp();
    if (elect_one()) mbar_arrive(bar + 8 * G);
}
__device__ __forceinline__ void finish(uint32_t src, uint32_t xa) {
    uint32_t s[4][4];
    uint4 x[4];
#pragma unroll
    for (int i = 0; i < 4; i++) {
        ldsm4t(s[i], (src ^ ((i & 1) << 5)) + (i >> 1) * 8192);
        x[i] = lds128((xa ^ ((i >> 1) << 4)) + (i & 1) * 256);
    }
#pragma unroll
    for (int i = 0; i < 4; i++)
        sts128((xa ^ ((i >> 1) << 4)) + (i & 1) * 256, badd2(x[i].x, s[i][0]), badd2(x[i].y, s[i][1]), badd2(x[i].z, s[i][2]), badd2(x[i].w, s[i][3]));
}

__device__ __noinline__ float centred_var(uint32_t rows, float mu, int lane) {
    float var = 0.f;
#pragma unroll 1
    for (int rr = 0; rr < 16; rr++) {
        const float c0 = __shfl_sync(0xffffffffu, mu, rr);
        float c = 0.f;
#pragma unroll 1
        for (int k = 0; k < 16; k++) {
            const uint32_t q = lds32(rows + rr * ROW_PITCH + k * 128 + lane * 4);
            const float d0 = bf_lo(q) - c0, d1 = bf_hi(q) - c0;
            c = fmaf(d0, d0, fmaf(d1, d1, c));
        }
#pragma unroll 1
        for (int o = 16; o; o >>= 1) c += __shfl_xor_sync(0xffffffffu, c, o);
        if ((lane & 15) == rr) var = c * (1.f / DM);
    }
    return var;
}
__device__ __noinline__ float centred_score(uint32_t rows, uint32_t wbuf, uint32_t s0, uint32_t s1, int lane) {
    float sc = 0.f;
#pragma unroll 1
    for (int rr = 0; rr < 16; rr++) {
        const uint32_t t0 = __shfl_sync(0xffffffffu, s0, rr), t1 = __shfl_sync(0xffffffffu, s1, rr);
        float c = 0.f;
#pragma unroll 1
        for (int k = 0; k < 16; k++) {
            const uint32_t xn = normalize2(lds32(rows + rr * ROW_PITCH + k * 128 + lane * 4), t0, t1);
            const uint32_t wq = lds32(wbuf + (k >> 2) * 1024 + (k & 3) * 128 + lane * 4);
            c = fmaf(bf_lo(xn), bf_lo(wq), fmaf(bf_hi(xn), bf_hi(wq), c));
        }
#pragma unroll 1
        for (int o = 16; o; o >>= 1) c += __shfl_xor_sync(0xffffffffu, c, o);
        if ((lane & 15) == rr) sc = c;
    }
    return sc;
}

__global__ void __cluster_dims__(2, 1, 1) __launch_bounds__(NTHR, 1)
fused_kernel(const __grid_constant__ Ptrs p, const __grid_constant__ Maps maps) {
    extern __shared__ __align__(1024) unsigned char smem[];
    const int tid = threadIdx.x, lane = tid & 31;
    const int c_ = ((blockIdx.x >> 1) + PERM_OFF) & 63, b = 2 * ((c_ & 32) | ((c_ & 7) << 2) | ((c_ >> 3) & 3)) + (blockIdx.x & 1);
    const int dch = 8 * b + (tid >> 5) - 4;
    uint2 la, aim, cre, cim;
    uint32_t ldt16, dsk16, epoch;
    uint4 wq;
    if ((uint32_t)(tid - 128) < 256u) {
        la = ldg64(p.logA + dch * NMODE + 4 * lane); aim = ldg64(p.Aim + dch * NMODE + 4 * lane);
        cre = ldg64(p.Cre + dch * NMODE + 4 * lane); cim = ldg64(p.Cim + dch * NMODE + 4 * lane);
        ldt16 = ldg16(p.ldt + dch); dsk16 = ldg16(p.dsk + dch);
    }
    if (tid < 128) { wq = ldg128(p.wr + 8 * tid); epoch = ld_relaxed_32(&p.sc->epoch); }
    const uint32_t sb = s_u32(smem);
    const int warp = __shfl_sync(0xffffffffu, tid >> 5, 0);
    const int h = b & 1, cl = b >> 1;
    const uint32_t bar0 = sb + OFF_BAR;
    const int m = lane >> 3, r = lane & 7, g = lane >> 2, t = lane & 3;
    const bool has_gu = b < GU_CTAS;
    if (warp == 4) { STAMP(0); GSTAMP(24); }

    if (warp >= 12) {
        asm volatile("setmaxnreg.dec.sync.aligned.u32 24;");
        const int a = warp - 12;
        uint32_t due = now_ns() + ST_T0 + (uint32_t)(128 * a + b) * ST_PER / 128 + (has_gu ? 0 : ST_LATE * (12 * ST_PER + 4 * ST_PER2) / 16);
        const bool el = elect_one();
        if (a == 1 && el) {
#pragma unroll
            for (int j = 0; j < 4; j++) mbar_init(bar0 + 8 * (B_ROW + j), 1);
            asm volatile("fence.mbarrier_init.release.cluster;" ::: "memory");
            fence_async();
#pragma unroll 1
            for (int j = 0; j < 4; j++) {
                mbar_expect_tx(bar0 + 8 * (B_ROW + j), 8192);
#pragma unroll
                for (int i = 0; i < 4; i++)
                    bulk_g2s(sb + OFF_VT + (4 * j + i) * ROW_PITCH, p.u + (size_t)(16 * b + 4 * j + i) * DM, 2048, bar0 + 8 * (B_ROW + j));
            }
        }
        if (a == 2 && el) {
#pragma unroll
            for (int i = B_XT; i < NBAR; i++) mbar_init(bar0 + 8 * i, (i == B_V || i == B_SFREE || i == B_XFREE) ? 8 : (i == B_RECV || i == B_RECV + 1) ? 9 : i == B_RED ? 5 : (i == B_UPD || (i >= B_FREE && i < B_FULL)) ? 4 : 1);
            asm volatile("fence.mbarrier_init.release.cluster;" ::: "memory");
            fence_async();
            mbar_expect_tx(bar0 + 8 * B_XT, 65536);
            mbar_expect_tx(bar0 + 8 * B_RECV, 8192);
            mbar_expect_tx(bar0 + 8 * B_RECV + 8, 8192);
            mbar_expect_tx(bar0 + 8 * B_RED, 2048);
        }
        if (a == 3 && el) {
#pragma unroll
            for (int i = 0; i < 5; i++) asm volatile("prefetch.tensormap [%0];" ::"l"(&maps.u + i) : "memory");
        }
        __syncwarp();
        cluster_arrive();
        cluster_wait();
        STAMP(18);
        mbar_wait(bar0 + 8 * (B_ROW + a), 0);
        if (el) {
#pragma unroll
            for (int i = 0; i < 4; i++)
                tma_load_tile(sb + OFF_XT + h * 32768 + a * 4096 + (i & 1) * 16384 + (i >> 1) * 2048, &maps.u, 16 * cl, 4 * a + (i & 2), 16 * (i & 1) + 8 * h, bar0 + 8 * B_XT);
        }
        if (el) {
#pragma unroll 1
            for (int k = has_gu ? 0 : 4; k < 6; k++) {
                const int i = 4 * k + a, s = k < 3 ? i : i - 12;
#pragma unroll 1
                for (int left; (left = (int)(due - now_ns())) > 0;) __nanosleep(left >> 1);
                due += k == 0 ? 4 * ST_PER + ST_GAP : k < 3 ? 4 * ST_PER : 4 * ST_PER2;
                const bool again = k >= 3 && has_gu;
                if (s >= 6 || again) mbar_wait(bar0 + 8 * (s < 10 || again ? B_FREE + s : B_V), slot_priv(s) && again);
                const uint32_t dst = sb + slot_off(s), bar = bar0 + 8 * (B_FULL + s);
                if (k < 4) {
                    mbar_expect_tx(bar, 8192);
                    tma_load_2d(dst, &maps.wg, 64 * cl, 512 * h + 32 * i, bar);
                    tma_load_2d(dst + 4096, &maps.wu, 64 * cl, 512 * h + 32 * i, bar);
                } else {
                    mbar_expect_tx(bar, 7168);
                    tma_load_perm(dst, &maps.wd, 16 * cl, 56 * h + 14 * a + 7 * (k & 1), bar);
                }
            }
            STAMP(19);
        }
    } else if (warp >= 4) {
        const int w = warp - 4;
        cluster_arrive();
        asm volatile("setmaxnreg.inc.sync.aligned.u32 168;");
        const uint32_t vrow = sb + OFF_VT + w * VT_PITCH + VT_PAD, tab = sb + tab_off(w);
        const uint32_t so = sb + OFF_XT + (8 * h + w) * 1024 + ((lane ^ ((w & 1) << 1)) << 4);
        uint32_t dst0 = so + (h ^ 1) * 32768;
        const uint32_t rb0 = bar0 + 8 * B_RECV, rb1 = mapa(rb0, h ^ 1);
        const uint32_t box = sb + OFF_XT + h * 32768 + w * 2048;
        uint32_t fs = sb + OFF_XT + (h ^ 1) * 32768 + (2 * m + (r & 1)) * 1024 + (w >> 2) * 512 + (((8 * (w & 3) + (r & 4) + ((r >> 1) & 1)) ^ ((r & 1) << 1)) << 4);
        uint32_t fx = box + (g >> 1) * 512 + (t >> 1) * 144 + (2 * (t & 1) + (g & 1)) * 32;
        uint32_t tpo = 80 + (g - 2 * t) * 8 - (g < 2 * t ? 16 : 0);
        uint32_t xa = sb + OFF_XT + (w & 2) * 16384 + (w >> 2) * 16384 + (w & 1) * 1024 + (g >> 1) * 2048 + (g & 1) * 128 + t * 32 + ((h ^ (g & 1)) << 4);
        uint32_t va = sb + OFF_VT + (2 * m + (r & 1)) * VT_PITCH + VT_PAD + (16 * w + (r >> 1)) * 16;
        uint32_t qa = sb + OFF_ST + 2048 * w + 128 * t + 16 * (g ^ (2 * t));
        pin(dst0); pin(fs); pin(fx); pin(tpo); pin(xa); pin(va); pin(qa);
        const Boxes b2(vrow, lane, -18, 5, 7, 0, 4), b3(vrow, lane, -20, 1, 7, 0, 8);
        const KgenAddr ka(sb + OFF_PRIV + w * 8192, lane);
        if (__any_sync(0xffffffffu, ((dst0 | fs) | (fx | tpo | xa) | (va | qa) | (b2.any() | b3.any() | ka.any())) & p.zero)) __trap();
        cluster_wait();
        pin(la.x); pin(la.y); pin(aim.x); pin(aim.y); pin(cre.x); pin(cre.y); pin(cim.x); pin(cim.y); pin(ldt16); pin(dsk16);
        uint4 x[8];
        auto load_x = [&]() {
            mbar_wait(bar0 + 8 * B_XT, 0);
#pragma unroll
            for (int i = 0; i < 8; i++) x[i] = lds128(xa + (i & 1) * 8192 + (i >> 1) * 256);
        };
        kgen(ka, tab, lane, la, aim, cre, cim, bf_round(ex2f(bf_lo(ldt16) * 1.4426950408889634f)), 1.f + bf_lo(dsk16), dch, [&]() {
            STAMP(21);
            if (elect_one()) mbar_arrive_n(bar0 + 8 * (B_FREE + 6 + ((w >> 1) ^ 2)), 2);
        }, [&]() {
            if ((LN_PAUSE >> w) & 1) mbar_wait(bar0 + 8 * B_LN, 0);
        });
        STAMP(1); KSTAMP(6);
        const uint32_t pb = tab + T_DENSE + (g - 2 * t) * 4;
        {
            load_x();
            STAMP(47);
            mbar_wait(bar0 + 8 * (B_ST + (w >> 1)), 0);
            uint4 q[4];
#pragma unroll
            for (int n = 0; n < 4; n++) q[n] = lds128(qa + 512 * n);
            if (lane < 4) sts128(vrow - VT_PAD + (lane >> 1) * VT_PLANE + (lane & 1) * 16, 0, 0, 0, 0);
            STAMP(2); GSTAMP(28);
#pragma unroll
            for (int i = 0; i < 8; i++) {
                const uint32_t s0 = (i & 1) ? q[i >> 1].z : q[i >> 1].x, s1 = (i & 1) ? q[i >> 1].w : q[i >> 1].y;
                stsm4t(va + (i >> 1) * 64 + (i & 1) * VT_PLANE, normalize2(x[i].x, s0, s1), normalize2(x[i].y, s0, s1),
                       normalize2(x[i].z, s0, s1), normalize2(x[i].w, s0, s1));
            }
            __syncwarp();
            if (elect_one()) mbar_arrive(bar0 + 8 * B_V);
        }
        DenseTaps dt(pb, pb + p.zero);
        mbar_wait(bar0 + 8 * B_V, 0);
        STAMP(3); KSTAMP(7);
        float acc[16][4];
#pragma unroll
        for (int i = 0; i < 16; i++) { acc[i][0] = acc[i][1] = acc[i][2] = acc[i][3] = 0.f; }
        tpo |= dense_phase(acc, vrow, pb, dt, p.zero, lane);
        STAMP(4); KSTAMP(8);
        const uint32_t dst1 = mapa(dst0 + (h ? 32768 : -32768), h ^ 1);
        tail_phase(acc, b2, b3, tab + T_R2 + 2 * tpo, tab + T_R3 + tpo, p.zero, [&](int j) {
            if (j == 3) {
                mbar_wait(bar0 + 8 * B_SFREE, 0);
                emit<0>(acc, h, dst0, dst1, rb0, rb1);
                STAMP(5);
            }
            if (j == STORE_AT) {
                mbar_wait(bar0 + 8 * B_XFREE, 0);
                mbar_wait(bar0 + 8 * B_RECV, 0);
                finish(fs, fx);
                fence_async();
                __syncwarp();
                if (elect_one()) tma_store_tile(&maps.out, box, 16 * cl, 2 * w, 8 * h);
                STAMP(20);
            }
        });
        emit<1>(acc, h, dst0, dst1, rb0, rb1);
        STAMP(30);
        const int tok = 2047 - (int)(lds32(sb + OFF_MISC + 48 + 8 * g) & 2047);
        const bool mine = (((tok >> 6) & 8) | ((tok >> 1) & 7)) == 8 * h + w;
        const bool any = __any_sync(0xffffffffu, mine), late = __any_sync(0xffffffffu, mine && tok >= 1024);
        const uint32_t ta = box + (tok >> 10) * 16384 + ((tok >> 6) & 7) * 256 + (tok & 1) * 128 + ((tok >> 4) & 3) * 32 + (((t >> 1) ^ (tok & 1)) << 4) + (t & 1) * 8;
        const bool el = elect_one();
        mbar_wait(bar0 + 8 * (B_RECV + 1), 0);
        STAMP(6);
        finish(fs + 16384, fx + 16384);
#pragma unroll 1
        for (int pass = 0; pass < 2; pass++) {
            if ((pass != 0) == late) {
                fence_async();
                __syncwarp();
                if (el) tma_store_tile(&maps.out, box + 16384, 16 * cl, 2 * w, 16 + 8 * h);
            } else if (any) {
                if (el) {
                    if (late) asm volatile("cp.async.bulk.wait_group 0;" ::: "memory");
                    else asm volatile("cp.async.bulk.wait_group 1;" ::: "memory");
                }
                __syncwarp();
                const uint2 o0 = lds64(ta);
                mbar_wait(bar0 + 8 * B_UPD, 0);
                const float4 up = lds128f(sb + tab_off(g) + T_RED + 16 * t);
                const uint2 o1 = make_uint2(badd2(o0.x, pack_bf16(up.x, up.y)), badd2(o0.y, pack_bf16(up.z, up.w)));
                if (mine) {
                    if (tok >= 1024) sts64(ta, o1.x, o1.y);
                    else *reinterpret_cast<uint2*>(p.out + (size_t)tok * DM + 16 * cl + 4 * t) = o1;
                }
            }
        }
        if (el) asm volatile("cp.async.bulk.wait_group.read 0;" ::: "memory");
        STAMP(7);
    } else {
        const int a = warp;
        cluster_arrive();
        asm volatile("setmaxnreg.inc.sync.aligned.u32 152;");
        const uint32_t tag = __shfl_sync(0xffffffffu, epoch, 0) + 1u, misc = sb + OFF_MISC, abar = bar0 + 8 * (B_AUX + a);
        uint32_t aph = 0;
        const Exchange* in = &p.sc->x[cl & (NREP - 1)];
        uint2* pub = p.sc->x[m >> 1].stat + 16 * b + 2 * (r ^ (2 * (b & 3))) + (m & 1);
        uint32_t* cnt_s = &p.sc->x[t].n_stat[b & 96];
        pin(pub); pin(cnt_s);
        if (tid < 64) sts32(sb + OFF_XCH + 4 * tid, 0);
        const uint32_t wbuf = sb + OFF_LN + a * 1024, part = sb + OFF_LN + 4096;
        {
            sts128(wbuf + 16 * lane, wq.x, wq.y, wq.z, wq.w);
            sts128(wbuf + 512 + 16 * lane, 0x3f803f80u, 0x3f803f80u, 0x3f803f80u, 0x3f803f80u);
            float wsum = ((bf_lo(wq.x) + bf_hi(wq.x)) + (bf_lo(wq.y) + bf_hi(wq.y))) + ((bf_lo(wq.z) + bf_hi(wq.z)) + (bf_lo(wq.w) + bf_hi(wq.w)));
#pragma unroll
            for (int o = 16; o; o >>= 1) wsum += __shfl_xor_sync(0xffffffffu, wsum, o);
            sts32f(part + 1024 + 4 * a, wsum);
            uint32_t wf[4][4];
#pragma unroll
            for (int i = 0; i < 4; i++) ldsm4(wf[i], wbuf + ((uint32_t)(r - 1) < 2u ? 16 * (r - 1) : 512) + 32 * m + 128 * i);
            uint32_t ra = sb + OFF_VT + r * ROW_PITCH + 512 * a + 16 * m, pa = part + a * 256 + g * 16;
            cluster_wait();
            STAMP(22);
#pragma unroll 1
            for (int hf = 0; hf < 2; hf++) {
                mbar_wait(bar0 + 8 * B_ROW + 16 * hf, 0);
                mbar_wait(bar0 + 8 * B_ROW + 16 * hf + 8, 0);
                STAMP(23);
                uint32_t x[8][4];
                float cs[2][4], q[8][4];
#pragma unroll
                for (int i = 0; i < 40; i++) (i < 8 ? cs[i >> 2 & 1] : q[(i - 8) >> 2 & 7])[i & 3] = 0.f;
#pragma unroll
                for (int k = 0; k < 8; k++) ldsm4(x[k], ra + k * 64);
                const bool more = __any_sync(0xffffffffu, after_all(x, p.zero));
#pragma unroll 1
                do {
#pragma unroll
                    for (int k = 0; k < 8; k++) {
                        mma_v(cs[k & 1], x[k], wf[k >> 1][2 * (k & 1)], wf[k >> 1][2 * (k & 1) + 1]);
#pragma unroll
                        for (int i = 0; i < 4; i++) mma_bf16_k8(q[4 * (k & 1) + i], x[k][i & 2], x[k][i | 1], x[k][i]);
                    }
                } while (more);
                const float c2 = cs[0][2] + cs[1][2];
                if (t == 0) sts64f(pa, (cs[0][0] + cs[1][0]) + c2, cs[0][1] + cs[1][1]);
                if (t == 1) sts32f(pa + 12, c2);
                const float e0 = ((q[0][0] + q[2][0]) + (q[4][0] + q[6][0])) + ((q[1][2] + q[3][2]) + (q[5][2] + q[7][2]));
                const float e1 = ((q[0][1] + q[2][1]) + (q[4][1] + q[6][1])) + ((q[1][3] + q[3][3]) + (q[5][3] + q[7][3]));
                if (t == (g >> 1)) sts32f(pa + 8, (g & 1) ? e1 : e0);
                ra += 8 * ROW_PITCH; pa += 128;
            }
        }
        STAMP(31);
        named_sync(1, 128);
        if (a == 0) {
            const uint32_t pa = part + (lane & 15) * 16;
            const float4 p0 = lds128f(pa), p1 = lds128f(pa + 256), p2 = lds128f(pa + 512), p3 = lds128f(pa + 768), ws = lds128f(part + 1024);
            const float mu = ((p0.x + p1.x) + (p2.x + p3.x)) * (1.f / DM);
            float var = ((p0.z + p1.z) + (p2.z + p3.z)) * (1.f / DM) - mu * mu;
            const bool centred = __any_sync(0xffffffffu, !(mu * mu <= 4.f * var));
            if (centred) var = centred_var(sb + OFF_VT, mu, lane);
            const float ri = rcpf(bf_round(sqrtaf(bf_round(bf_round(var) + 1e-5f))));
            const uint32_t s0 = pack_bf16(mu, ri), s1 = (pack_bf16(ri - bf_hi(s0), 0.f) & 0xfffcu) | (tag & 3);
            float sc = ((((p0.y + p1.y) + (p2.y + p3.y)) + ((p0.w + p1.w) + (p2.w + p3.w))) - bf_lo(s0) * ((ws.x + ws.y) + (ws.z + ws.w))) * ri;
            if (centred) sc = centred_score(sb + OFF_VT, sb + OFF_LN, s0, s1, lane);
            const uint32_t sb16 = pack_bf16(0.f, sc);
            const uint32_t s2 = s1 | (sb16 ^ (((uint32_t)((int)sb16 >> 31) & 0x7fff0000u) | 0x80000000u));
            st_relaxed_64(pub, s0, s2);
            st_relaxed_64(pub + 2 * sizeof(Exchange) / 8, s0, s2);
            if (lane < NREP) red_add(cnt_s, 1);
            if (elect_one()) mbar_arrive(bar0 + 8 * B_LN);
            STAMP(9); GSTAMP(25);
        }
        const uint32_t slot0 = sb + OFF_RING + a * 8192, slot1 = sb + slot_off(4 + a), slot2 = sb + slot_off(8 + a), fbar = bar0 + 8 * (B_FULL + a);
        uint32_t mine = 0, row[2] = {0, 0};
        {
            uint32_t q[16];
            named_sync(1, 128);
            wait_count(&in->n_stat[32 * a], 32 * tag - FEW_ST);
            STAMP(41);
#pragma unroll 1
            for (uint32_t it = 0;; spin_guard(it)) {
                if (elect_one()) {
                    mbar_expect_tx(abar, 4096);
                    bulk_g2s(sb + OFF_ST + 4096 * a, in->stat + 512 * a, 4096, abar);
                }
                mbar_wait(abar, aph);
                aph ^= 1;
                uint32_t bad = 0;
#pragma unroll
                for (int n = 0; n < 8; n++) {
                    const uint4 u = lds128v(sb + OFF_ST + 4096 * a + 512 * n + 16 * lane);
                    q[2 * n] = u.y; q[2 * n + 1] = u.w;
                    bad = or_xor(bad, u.y, tag);
                }
                const bool ok = __all_sync(0xffffffffu, (bad & 3) == 0);
                asm volatile("{ .reg .pred p; setp.ne.u32 p, %1, 0; @p mbarrier.arrive.shared::cta.b64 _, [%0]; }" ::"r"(bar0 + 8 * (B_ST + a)), "r"((uint32_t)(ok && lane == 0)) : "memory");
                if (ok) break;
            }
            STAMP(8);
            const uint32_t inv = 2047 - 512 * a - 16 * m - (r ^ (2 * m));
#pragma unroll
            for (int i = 0; i < 16; i++) asm("lop3.b32 %0, %0, %1, %2, 0x9b;" : "+r"(q[i]) : "r"(inv), "r"(0xffff0000u | (64 * (i >> 1) + 8 * (i & 1))));
            auto below = [&](uint32_t x) {
                uint32_t d[4];
#pragma unroll
                for (int i = 0; i < 16; i++) d[i & 3] = i < 4 ? x + q[i] : min(d[i & 3], x + q[i]);
                d[0] = min(min(d[0], d[1]), min(d[2], d[3]));
                return d[0] < x ? x - 1 - d[0] : 0u;
            };
            const uint32_t mx0 = ~min(min(min(min(q[0], q[1]), min(q[2], q[3])), min(min(q[4], q[5]), min(q[6], q[7]))),
                                      min(min(min(q[8], q[9]), min(q[10], q[11])), min(min(q[12], q[13]), min(q[14], q[15]))));
            const uint32_t gm = min(__reduce_max_sync(0xffffffffu, lane < 16 ? mx0 : 0u), __reduce_max_sync(0xffffffffu, lane < 16 ? 0u : mx0));
            if (lane == 0) sts32(misc + 16 + 4 * a, gm);
            named_sync(1, 128);
            STAMP(42);
            if (b == 0 && tid == 0) st_relaxed_32(&p.sc->epoch, tag);
            const uint4 t0 = lds128(misc + 16);
            uint32_t tau = min(min(t0.x, t0.y), min(t0.z, t0.w));
            uint32_t mx = mx0, cnt = 0, bal;
            const uint32_t list = sb + OFF_XCH + 64 * a;
#pragma unroll 1
            while ((bal = __ballot_sync(0xffffffffu, mx >= tau)) != 0) {
                const uint32_t pos = cnt + __popc(bal & ((1u << lane) - 1u));
                cnt += __popc(bal);
                if (cnt > 16) break;
                if (mx >= tau) sts32(list + 4 * pos, mx);
                mx = below(mx);
            }
            if (cnt > 16) {
                mx = mx0;
#pragma unroll 1
                for (int j = 0; j < 8; j++) {
                    const uint32_t top = __reduce_max_sync(0xffffffffu, mx), nx = below(mx);
                    if (mx == top) { sts32(list + 4 * j, mx); sts32(list + 32 + 4 * j, 0); mx = nx; }
                }
            }
            named_sync(1, 128);
            STAMP(43);
            const uint2 k = lds64(sb + OFF_XCH + 8 * lane);
            uint32_t hi = max(k.x, k.y), lo = min(k.x, k.y);
            mbar_wait(bar0 + 8 * B_V, 0);
#pragma unroll
            for (int j = 0; j < 8; j++) {
                const uint32_t top = __reduce_max_sync(0xffffffffu, hi);
                const bool won = hi == top;
                hi = won ? lo : hi;
                lo = won ? 0u : lo;
                if (g == j) mine = top;
                if (a == (j >> 1)) row[j & 1] = top;
            }
        }
        STAMP(11);
        const int tok = 2047 - (int)(mine & 2047);
        const uint32_t xs = sb + OFF_XT + (h ^ 1) * 32768 + 16384;
        if (has_gu) {
            if (elect_one()) {
                mbar_expect_tx(abar, 2048);
#pragma unroll
                for (int j = 0; j < 2; j++) bulk_g2s(xs + (2 * a + j) * 1040, p.u + (size_t)(2047 - (row[j] & 2047)) * DM + 512 * h, 1024, abar);
            }
        }
        STAMP(44);
        const uint2 st = ld_relaxed_64(in->stat + (tok & ~15) + 2 * ((tok & 7) ^ ((tok >> 3) & 6)) + ((tok >> 3) & 1));
        if (a == 0 && t == 0) sts64(misc + 48 + 8 * g, mine, __float_as_uint(bf_hi(st.x) + bf_lo(st.y)));
        if (a == 0) STAMP(45);
        if (has_gu) {
            const uint32_t mean = __shfl_sync(0xffffffffu, st.x, 8 * a + 4 * (lane >> 4)), xr = xs + (2 * a + (lane >> 4)) * 1040 + 16 * (lane & 15);
            mbar_wait(abar, aph);
            aph ^= 1;
            STAMP(46);
            uint4 x[4];
#pragma unroll
            for (int j = 0; j < 4; j++) x[j] = lds128(xr + 256 * j);
#pragma unroll
            for (int j = 0; j < 4; j++) sts128(xr + 256 * j, bsub2_lo(x[j].x, mean), bsub2_lo(x[j].y, mean), bsub2_lo(x[j].z, mean), bsub2_lo(x[j].w, mean));
            if (elect_one()) mbar_expect_tx(abar, 512);
            named_sync(1, 128);
        }
        if (lane < (has_gu ? 2 : 4)) mbar_arrive_peer(mapa(bar0 + 8 * (lane & 2 ? B_XFREE : B_SFREE), lane & 1));
        if (has_gu) {
            STAMP(12);
            float gacc[8][4];
#pragma unroll
            for (int i = 0; i < 8; i++) { gacc[i][0] = gacc[i][1] = gacc[i][2] = gacc[i][3] = 0.f; }
            uint32_t* pubh = reinterpret_cast<uint32_t*>(&p.sc->x[0].h[b * 32 + 8 * a + (g ^ (2 * a))]) + t;
            uint32_t* cnt_h = &p.sc->x[t].n_h[32 * (b / 14)];
            uint32_t ko = sb + (m & 1) * 4096 + (r + ((m >> 1) << 3)) * 128 + ((r ^ (4 * h) ^ a) << 4), kp = ko ^ 64, xb = xs + r * 1040 + m * 16;
            uint32_t xch = sb + OFF_XCH + 16 * tid, tagm = t == 3 ? 1u : 0u;
            pin(pubh); pin(cnt_h); pin(ko); pin(kp); pin(xb); pin(xch); pin(tagm);
            const float r0 = lds32f(misc + 52 + 16 * t), r1 = lds32f(misc + 60 + 16 * t);
#pragma unroll
            for (int c = 0; c < 4; c++) {
                uint32_t af[20][4];
#pragma unroll
                for (int j = 0; j < 4; j++) ldsm4(af[16 + j], xb + 256 * c + 64 * j);
                if (c == 3) mbar_wait(bar0 + 8 * B_SFREE, 0);
#pragma unroll
                for (int j = 0; j < 4; j++) {
                    mbar_wait(bar0 + 8 * (B_FULL + 4 * (c % 3) + j), c / 3);
#pragma unroll
                    for (int i = 0; i < 4; i++) ldsm4t(af[8 * (i >> 1) + 2 * j + (i & 1)], ((i & 1) ? kp : ko) + slot_off(4 * (c % 3) + j) + (i >> 1) * 2048);
                }
                STAMP(36 + c);
                __syncwarp();
                if (c < 3 && lane < 4) mbar_arrive(bar0 + 8 * (B_FREE + 4 * c + lane));
                const bool more = __any_sync(0xffffffffu, (af[6][3] | af[7][3] | af[14][3] | af[15][3]) & p.zero);
#pragma unroll 1
                do {
#pragma unroll
                    for (int i = 0; i < 16; i++) mma_v(gacc[i & 7], af[i], af[16 + ((i >> 1) & 3)][2 * (i >> 3)], af[16 + ((i >> 1) & 3)][2 * (i >> 3) + 1]);
                } while (more);
                STAMP(52 + c);
            }
            STAMP(13);
            float own[4], oth[4];
#pragma unroll
            for (int j = 0; j < 4; j++) oth[j] = (gacc[1][j] + gacc[3][j]) + (gacc[5][j] + gacc[7][j]);
            st_async128(mapa(xch, h ^ 1), __float_as_uint(oth[0]), __float_as_uint(oth[1]), __float_as_uint(oth[2]), __float_as_uint(oth[3]), mapa(abar, h ^ 1));
            STAMP(56);
#pragma unroll
            for (int j = 0; j < 4; j++) own[j] = ((gacc[0][j] + gacc[2][j]) + (gacc[4][j] + gacc[6][j])) * ((j & 1) ? r1 : r0);
            mbar_wait(abar, aph);
            aph ^= 1;
            STAMP(57);
            const float4 o4 = lds128f(xch);
            const float g0 = bf_round(fmaf(o4.x, r0, own[0])), g1 = bf_round(fmaf(o4.y, r1, own[1]));
            const float h0 = bf_round(g0 * rcpf(1.f + ex2f(-1.4426950408889634f * g0))) * bf_round(fmaf(o4.z, r0, own[2]));
            const float h1 = bf_round(g1 * rcpf(1.f + ex2f(-1.4426950408889634f * g1))) * bf_round(fmaf(o4.w, r1, own[3]));
            uint32_t hw;
            asm volatile("movmatrix.sync.aligned.m8n8.trans.b16 %0, %1;" : "=r"(hw) : "r"(pack_bf16(h0, h1)));
            hw = (hw & ~tagm) | (tag & tagm);
#pragma unroll
            for (int j = 0; j < NREP; j++) st_relaxed_32(pubh + j * (sizeof(Exchange) / 4), hw);
            if (lane < NREP) red_add(cnt_h, 1);
            if (lane < 2) mbar_arrive_peer(mapa(bar0 + 8 * B_XFREE, lane));
            named_sync(1, 128);
            STAMP(14);
        }
        float dacc[4];
        const int tk = ((tid >> 1) & 6) | (tid & 1);
        uint32_t ro = 4 * tid, red = sb + tab_off(tk) + T_RED + 4 * ((tid >> 4) + 4 * (tid & 2));
        if (!has_gu) named_sync(1, 128);
        const float sg = bf_round(rcpf(1.f + ex2f(-1.4426950408889634f * __uint_as_float(unorder_key(lds32(misc + 48 + 8 * tk) >> 16) << 16))));
        pin(ro); pin(red);
        mbar_wait(bar0 + 8 * B_XFREE, 0);
        {
            uint32_t wo = (r + ((m >> 1) << 3)) * 32 + (((m & 1) ^ (r >> 2)) << 4), af[14][4];
            pin(wo);
            float d[7][4];
#pragma unroll
            for (int i = 0; i < 7; i++) { d[i][0] = d[i][1] = d[i][2] = d[i][3] = 0.f; }
            auto first_half = [&]() {
                mbar_wait(fbar + 32, has_gu);
#pragma unroll
                for (int j = 0; j < 14; j++) ldsm4t(af[j], slot1 + wo + j * 512);
            };
            auto fetch = [&]() {
                if (elect_one()) {
                    mbar_expect_tx(abar, 7168);
                    bulk_g2s(slot0, &in->h[(56 * h + 14 * a) * 32], 7168, abar);
                }
            };
            wait_count(&in->n_h[32 * (4 * h + a)], 56 * tag - FEW_H);
            STAMP(33);
            fetch();
            first_half();
            uint4 hq[14];
#pragma unroll 1
            for (uint32_t it = 0;; spin_guard(it)) {
                mbar_wait(abar, aph);
                aph ^= 1;
                uint32_t bad = 0;
#pragma unroll
                for (int j = 0; j < 14; j++) { hq[j] = lds128(slot0 + 512 * j + 128 * t + 16 * (g ^ (2 * t))); bad = or_xor(bad, hq[j].w, tag); }
                if (__all_sync(0xffffffffu, (bad & 1) == 0)) break;
                fetch();
            }
            STAMP(15);
#pragma unroll
            for (int s = 0; s < 2; s++) {
                if (s) {
                    mbar_wait(fbar + 64, has_gu);
#pragma unroll
                    for (int j = 0; j < 14; j++) ldsm4t(af[j], slot2 + wo + j * 512);
                }
                const bool more = __any_sync(0xffffffffu, after_all(af, p.zero));
#pragma unroll 1
                do {
#pragma unroll
                    for (int j = 0; j < 14; j++) {
                        const uint4 q = hq[7 * s + (j >> 1)];
                        mma_v(d[j % 7], af[j], (j & 1) ? q.z : q.x, (j & 1) ? q.w : q.y);
                    }
                } while (more);
            }
#pragma unroll
            for (int j = 0; j < 4; j++) dacc[j] = ((d[0][j] + d[1][j]) + (d[2][j] + d[3][j])) + ((d[4][j] + d[5][j]) + d[6][j]);
        }
        STAMP(16);
        {
            st_async128(mapa(sb + OFF_XCH + 16 * tid, h ^ 1), __float_as_uint(dacc[0]), __float_as_uint(dacc[1]), __float_as_uint(dacc[2]), __float_as_uint(dacc[3]),
                        mapa(bar0 + 8 * B_RED, h ^ 1));
            sts128f(slot0 + 7680 + lane * 16, dacc);
            __syncwarp();
            if (elect_one()) mbar_arrive(bar0 + 8 * B_RED);
            mbar_wait(bar0 + 8 * B_RED, 0);
            const uint32_t b0 = sb + OFF_RING + 7680 + ro, b1 = sb + OFF_XCH + ro;
            const float y = ((lds32f(b0) + lds32f(b0 + 8192)) + (lds32f(b0 + 16384) + lds32f(b0 + 24576))) +
                            ((lds32f(b1) + lds32f(b1 + 512)) + (lds32f(b1 + 1024) + lds32f(b1 + 1536)));
            sts32f(red, bf_round(y) * sg);
            __syncwarp();
            if (elect_one()) mbar_arrive(bar0 + 8 * B_UPD);
        }
        STAMP(17); GSTAMP(29);
    }
}

typedef CUresult (*EncodeFn)(CUtensorMap*, CUtensorMapDataType, cuuint32_t, void*, const cuuint64_t*, const cuuint64_t*,
                             const cuuint32_t*, const cuuint32_t*, CUtensorMapInterleave, CUtensorMapSwizzle,
                             CUtensorMapL2promotion, CUtensorMapFloatOOBfill);

void make_map(EncodeFn enc, CUtensorMap* m, const void* ptr, uint64_t cols, uint64_t rows, uint32_t bc, uint32_t br,
              CUtensorMapSwizzle sw, CUtensorMapL2promotion pr) {
    cuuint64_t dims[2] = {cols, rows};
    cuuint64_t str[1] = {cols * 2};
    cuuint32_t box[2] = {bc, br};
    cuuint32_t es[2] = {1, 1};
    enc(m, CU_TENSOR_MAP_DATA_TYPE_BFLOAT16, 2, const_cast<void*>(ptr), dims, str, box, es, CU_TENSOR_MAP_INTERLEAVE_NONE, sw, pr,
        CU_TENSOR_MAP_FLOAT_OOB_FILL_NONE);
}
void make_perm_map(EncodeFn enc, CUtensorMap* m, const void* ptr, CUtensorMapL2promotion pr) {
    cuuint64_t dims[5] = {DM, 2, 4, 4, FF / 32};
    cuuint64_t str[4] = {DM * 2, 8 * DM * 2, 2 * DM * 2, 32 * DM * 2};
    cuuint32_t box[5] = {16, 2, 4, 4, 7};
    cuuint32_t es[5] = {1, 1, 1, 1, 1};
    enc(m, CU_TENSOR_MAP_DATA_TYPE_BFLOAT16, 5, const_cast<void*>(ptr), dims, str, box, es, CU_TENSOR_MAP_INTERLEAVE_NONE,
        CU_TENSOR_MAP_SWIZZLE_32B, pr, CU_TENSOR_MAP_FLOAT_OOB_FILL_NONE);
}
void make_tile_map(EncodeFn enc, CUtensorMap* m, const void* ptr) {
    cuuint64_t dims[4] = {DM, 4, 16, SEQ / 64};
    cuuint64_t str[3] = {16 * DM * 2, DM * 2, 64 * DM * 2};
    cuuint32_t box[4] = {16, 4, 2, 8};
    cuuint32_t es[4] = {1, 1, 1, 1};
    enc(m, CU_TENSOR_MAP_DATA_TYPE_BFLOAT16, 4, const_cast<void*>(ptr), dims, str, box, es, CU_TENSOR_MAP_INTERLEAVE_NONE,
        CU_TENSOR_MAP_SWIZZLE_32B, CU_TENSOR_MAP_L2_PROMOTION_NONE, CU_TENSOR_MAP_FLOAT_OOB_FILL_NONE);
}

}

#define WD_PROMO CU_TENSOR_MAP_L2_PROMOTION_L2_64B
extern "C" void kernel_launch(void* const* d_in, const int* in_sizes, int n_in, void* d_out, int out_size) {
    (void)in_sizes; (void)n_in; (void)out_size;
    static EncodeFn enc = nullptr;
    static void* scratch = nullptr;
    if (!enc) {
        void* fn = nullptr;
        cudaDriverEntryPointQueryResult q;
        cudaGetDriverEntryPoint("cuTensorMapEncodeTiled", &fn, cudaEnableDefault, &q);
        enc = (EncodeFn)fn;
        cudaGetSymbolAddress(&scratch, g_scratch);
        cudaFuncSetAttribute(fused_kernel, cudaFuncAttributeMaxDynamicSharedMemorySize, SMEM_BYTES);
    }
    Maps maps;
    make_tile_map(enc, &maps.u, d_in[0]);
    make_tile_map(enc, &maps.out, d_out);
    make_map(enc, &maps.wg, d_in[9], FF, DM, 64, 32, CU_TENSOR_MAP_SWIZZLE_128B, CU_TENSOR_MAP_L2_PROMOTION_L2_128B);
    make_map(enc, &maps.wu, d_in[10], FF, DM, 64, 32, CU_TENSOR_MAP_SWIZZLE_128B, CU_TENSOR_MAP_L2_PROMOTION_L2_128B);
    make_perm_map(enc, &maps.wd, d_in[11], WD_PROMO);
    Ptrs p;
    p.sc = (Scratch*)scratch;
    p.u = (const __nv_bfloat16*)d_in[0];
    p.logA = (const __nv_bfloat16*)d_in[1];
    p.Aim = (const __nv_bfloat16*)d_in[2];
    p.Cre = (const __nv_bfloat16*)d_in[3];
    p.Cim = (const __nv_bfloat16*)d_in[4];
    p.ldt = (const __nv_bfloat16*)d_in[5];
    p.dsk = (const __nv_bfloat16*)d_in[6];
    p.wr = (const __nv_bfloat16*)d_in[8];
    p.out = (__nv_bfloat16*)d_out;
    p.zero = 0;
    fused_kernel<<<NCTA, NTHR, SMEM_BYTES, cudaStreamPerThread>>>(p, maps);
}
```

```cpp
#include <cuda_runtime.h>
#include <cuda_bf16.h>
#include <cuda_fp16.h>
#include <cuda.h>
#include <stdint.h>

namespace {

constexpr int SEQ = 2048, DM = 1024, NMODE = 128, FF = 3584;
constexpr int NCTA = 128, NTHR = 512;
constexpr int GU_CTAS = 112;
constexpr int NREP = 4;

constexpr int OFF_XT = 0;
constexpr int OFF_RING = 65536;
constexpr int OFF_PRIV = OFF_RING + 65536;
constexpr int OFF_VT = OFF_PRIV + 65536;
constexpr int VT_PAD = 32, VT_PLANE = VT_PAD + 2048, VT_PITCH = 2 * VT_PLANE, ROW_PITCH = 2064;
constexpr int OFF_BAR = OFF_VT + 8 * VT_PITCH;
constexpr int OFF_MISC = OFF_BAR + 384;
constexpr int OFF_XCH = OFF_MISC + 112;
constexpr int SMEM_BYTES = OFF_XCH + 2048;
constexpr int OFF_LN = OFF_RING + 7 * 8192;
constexpr int OFF_ST = OFF_RING + 6 * 8192;
static_assert(SMEM_BYTES <= 232448, "shared memory");

constexpr int B_ROW = 0, B_XT = 4, B_V = 5, B_LN = 6, B_SFREE = 7, B_RECV = 8, B_RED = 10, B_UPD = 11, B_ST = 12, B_XFREE = 16, B_FREE = 20, B_FULL = 32, B_AUX = 44, NBAR = 48;

constexpr int T_DENSE = 60;
constexpr int T_PATCH = 2208;
constexpr int T_R2 = 2368;
constexpr int T_R3 = 3296;

constexpr int T_RED = 4032;
__device__ __forceinline__ bool slot_priv(int s) { return (uint32_t)(s - 6) < 4u; }
__device__ __forceinline__ uint32_t slot_off(int s) { return slot_priv(s) ? OFF_PRIV + 4096 + (s & 3) * 16384 : OFF_RING + (s < 6 ? s : s - 4) * 8192; }
__device__ __forceinline__ uint32_t tab_off(int w) { return OFF_PRIV + w * 8192 + (w & 1) * 4096; }

constexpr uint32_t SPIN_LIMIT = 1u << 20;
#define KG_UNROLL 4
constexpr int kKgUnroll = KG_UNROLL;
#define BB_UNROLL 2
constexpr int kBbUnroll = BB_UNROLL;
#define DENSE_UNROLL 1
constexpr int kDenseUnroll = DENSE_UNROLL;
#define ST_T0 2400
#define LN_PAUSE 0xf0
#define FEW_ST 0
#define FEW_H 0
#define PERM 2
#define PERM_OFF 60
#define STORE_AT 12
#define ST_LATE 16
#define ST_GAP 0
#define ST_PER 308
#define ST_PER2 335

struct Exchange {
    uint2 stat[SEQ];
    uint4 h[GU_CTAS * 32];
    uint32_t n_stat[4 * 32];
    uint32_t n_h[8 * 32];
};
struct Scratch {
    Exchange x[NREP];
    uint32_t epoch;
};
__device__ __align__(128) Scratch g_scratch;

struct Ptrs {
    const __nv_bfloat16 *logA, *Aim, *Cre, *Cim, *ldt, *u;
    const __nv_bfloat16 *dsk, *wr;
    Scratch* sc;
    __nv_bfloat16* out;
    uint32_t zero;
};
struct Maps {
    CUtensorMap u, out, wg, wu, wd;
};

#define STAMP(i) do { } while (0)
#define KSTAMP(i) do { } while (0)
#define GSTAMP(i) do { } while (0)

__device__ __forceinline__ uint32_t s_u32(const void* p) { return (uint32_t)__cvta_generic_to_shared(p); }
__device__ __forceinline__ void mbar_init(uint32_t b, uint32_t n) {
    asm volatile("mbarrier.init.shared::cta.b64 [%0], %1;" ::"r"(b), "r"(n) : "memory");
}
__device__ __forceinline__ void mbar_expect_tx(uint32_t b, uint32_t bytes) {
    asm volatile("mbarrier.arrive.expect_tx.shared::cta.b64 _, [%0], %1;" ::"r"(b), "r"(bytes) : "memory");
}
__device__ __forceinline__ void mbar_arrive(uint32_t b) {
    asm volatile("mbarrier.arrive.shared::cta.b64 _, [%0];" ::"r"(b) : "memory");
}
__device__ __forceinline__ void mbar_arrive_n(uint32_t b, uint32_t n) {
    asm volatile("mbarrier.arrive.shared::cta.b64 _, [%0], %1;" ::"r"(b), "r"(n) : "memory");
}
__device__ __forceinline__ void mbar_arrive_peer(uint32_t b_cluster) {
    asm volatile("mbarrier.arrive.relaxed.cluster.shared::cluster.b64 _, [%0];" ::"r"(b_cluster) : "memory");
}
__device__ __forceinline__ void mbar_wait(uint32_t b, uint32_t parity) {
    asm volatile("{\n\t.reg .pred p;\n\t.reg .u32 c;\n\tmov.u32 c, 0;\n"
                 "W:\n\tmbarrier.try_wait.parity.shared::cta.b64 p, [%0], %1;\n\t@p bra D;\n\t"
                 "add.u32 c, c, 1;\n\tsetp.lt.u32 p, c, 1048576;\n\t@p bra W;\n\ttrap;\nD:\n\t}"
                 ::"r"(b), "r"(parity) : "memory");
}
__device__ __forceinline__ bool mbar_test(uint32_t b, uint32_t parity) {
    uint32_t ok;
    asm volatile("{ .reg .pred p; mbarrier.test_wait.parity.shared::cta.b64 p, [%1], %2; selp.u32 %0, 1, 0, p; }" : "=r"(ok) : "r"(b), "r"(parity) : "memory");
    return __all_sync(0xffffffffu, ok != 0);
}
__device__ __forceinline__ bool elect_one() {
    uint32_t p;
    asm volatile("{ .reg .pred P; elect.sync _|P, 0xffffffff; selp.u32 %0, 1, 0, P; }" : "=r"(p));
    return p != 0;
}
__device__ __forceinline__ uint32_t mapa(uint32_t a, uint32_t rank) {
    uint32_t r;
    asm("mapa.shared::cluster.u32 %0, %1, %2;" : "=r"(r) : "r"(a), "r"(rank));
    return r;
}
__device__ __forceinline__ void cluster_arrive() { asm volatile("barrier.cluster.arrive.relaxed.aligned;" ::: "memory"); }
__device__ __forceinline__ void cluster_wait() { asm volatile("barrier.cluster.wait.acquire.aligned;" ::: "memory"); }
__device__ __forceinline__ void tma_load_2d(uint32_t dst, const CUtensorMap* m, int c0, int c1, uint32_t bar) {
    asm volatile("cp.async.bulk.tensor.2d.shared::cluster.global.mbarrier::complete_tx::bytes [%0], [%1, {%3, %4}], [%2];"
                 ::"r"(dst), "l"(m), "r"(bar), "r"(c0), "r"(c1) : "memory");
}
__device__ __forceinline__ void tma_load_perm(uint32_t dst, const CUtensorMap* m, int c0, int blk, uint32_t bar) {
    asm volatile("cp.async.bulk.tensor.5d.shared::cluster.global.mbarrier::complete_tx::bytes [%0], [%1, {%3, %4, %4, %4, %5}], [%2];"
                 ::"r"(dst), "l"(m), "r"(bar), "r"(c0), "r"(0), "r"(blk) : "memory");
}
__device__ __forceinline__ void tma_load_tile(uint32_t dst, const CUtensorMap* m, int c0, int c2, int c3, uint32_t bar) {
    asm volatile("cp.async.bulk.tensor.4d.shared::cluster.global.mbarrier::complete_tx::bytes.multicast::cluster [%0], [%1, {%3, %4, %5, %6}], [%2], %7;"
                 ::"r"(dst), "l"(m), "r"(bar), "r"(c0), "r"(0), "r"(c2), "r"(c3), "h"((uint16_t)3) : "memory");
}
__device__ __forceinline__ void tma_store_tile(const CUtensorMap* m, uint32_t src, int c0, int c2, int c3) {
    asm volatile("cp.async.bulk.tensor.4d.global.shared::cta.bulk_group [%0, {%2, %3, %4, %5}], [%1];"
                 ::"l"(m), "r"(src), "r"(c0), "r"(0), "r"(c2), "r"(c3) : "memory");
    asm volatile("cp.async.bulk.commit_group;" ::: "memory");
}
__device__ __forceinline__ void bulk_g2s(uint32_t dst, const void* src, uint32_t bytes, uint32_t bar) {
    asm volatile("cp.async.bulk.shared::cluster.global.mbarrier::complete_tx::bytes [%0], [%1], %2, [%3];"
                 ::"r"(dst), "l"(src), "r"(bytes), "r"(bar) : "memory");
}
__device__ __forceinline__ void cp_async16(uint32_t dst, const void* src) {
    asm volatile("cp.async.cg.shared.global [%0], [%1], 16;" ::"r"(dst), "l"(src) : "memory");
}
__device__ __forceinline__ void st_async128(uint32_t dst_cluster, uint32_t x, uint32_t y, uint32_t z, uint32_t w, uint32_t bar_cluster) {
    asm volatile("st.async.weak.shared::cluster.mbarrier::complete_tx::bytes.v4.b32 [%0], {%1,%2,%3,%4}, [%5];"
                 ::"r"(dst_cluster), "r"(x), "r"(y), "r"(z), "r"(w), "r"(bar_cluster) : "memory");
}
__device__ __forceinline__ void fence_async() { asm volatile("fence.proxy.async.shared::cta;" ::: "memory"); }
__device__ __forceinline__ void named_sync(int id, int n) { asm volatile("bar.sync %0, %1;" ::"r"(id), "r"(n) : "memory"); }

__device__ __forceinline__ void ldsm4(uint32_t* r, uint32_t a) {
    asm volatile("ldmatrix.sync.aligned.m8n8.x4.shared.b16 {%0,%1,%2,%3}, [%4];"
                 : "=r"(r[0]), "=r"(r[1]), "=r"(r[2]), "=r"(r[3]) : "r"(a));
}
__device__ __forceinline__ void ldsm4t(uint32_t* r, uint32_t a) {
    asm volatile("ldmatrix.sync.aligned.m8n8.x4.trans.shared.b16 {%0,%1,%2,%3}, [%4];"
                 : "=r"(r[0]), "=r"(r[1]), "=r"(r[2]), "=r"(r[3]) : "r"(a));
}
__device__ __forceinline__ void stsm4t(uint32_t a, uint32_t x, uint32_t y, uint32_t z, uint32_t w) {
    asm volatile("stmatrix.sync.aligned.m8n8.x4.trans.shared.b16 [%0], {%1,%2,%3,%4};"
                 ::"r"(a), "r"(x), "r"(y), "r"(z), "r"(w) : "memory");
}
__device__ __forceinline__ uint32_t lds32(uint32_t a) { uint32_t v; asm volatile("ld.shared.u32 %0, [%1];" : "=r"(v) : "r"(a)); return v; }
__device__ __forceinline__ float lds32f(uint32_t a) { float v; asm volatile("ld.shared.f32 %0, [%1];" : "=f"(v) : "r"(a)); return v; }
__device__ __forceinline__ uint2 lds64(uint32_t a) { uint2 v; asm volatile("ld.shared.v2.u32 {%0,%1}, [%2];" : "=r"(v.x), "=r"(v.y) : "r"(a)); return v; }
__device__ __forceinline__ uint4 lds128(uint32_t a) {
    uint4 v; asm volatile("ld.shared.v4.u32 {%0,%1,%2,%3}, [%4];" : "=r"(v.x), "=r"(v.y), "=r"(v.z), "=r"(v.w) : "r"(a)); return v;
}
__device__ __forceinline__ uint4 lds128v(uint32_t a) {
    uint4 v; asm volatile("ld.volatile.shared.v4.u32 {%0,%1,%2,%3}, [%4];" : "=r"(v.x), "=r"(v.y), "=r"(v.z), "=r"(v.w) : "r"(a)); return v;
}
__device__ __forceinline__ uint32_t or_xor(uint32_t a, uint32_t b, uint32_t c) {
    uint32_t r; asm("lop3.b32 %0, %1, %2, %3, 0xf6;" : "=r"(r) : "r"(a), "r"(b), "r"(c)); return r;
}
__device__ __forceinline__ float4 lds128f(uint32_t a) {
    float4 v; asm volatile("ld.shared.v4.f32 {%0,%1,%2,%3}, [%4];" : "=f"(v.x), "=f"(v.y), "=f"(v.z), "=f"(v.w) : "r"(a)); return v;
}
__device__ __forceinline__ void sts32(uint32_t a, uint32_t v) { asm volatile("st.shared.u32 [%0], %1;" ::"r"(a), "r"(v) : "memory"); }
__device__ __forceinline__ void sts32f(uint32_t a, float v) { asm volatile("st.shared.f32 [%0], %1;" ::"r"(a), "f"(v) : "memory"); }
__device__ __forceinline__ void sts64(uint32_t a, uint32_t x, uint32_t y) { asm volatile("st.shared.v2.u32 [%0], {%1,%2};" ::"r"(a), "r"(x), "r"(y) : "memory"); }
__device__ __forceinline__ void sts64f(uint32_t a, float x, float y) { asm volatile("st.shared.v2.f32 [%0], {%1,%2};" ::"r"(a), "f"(x), "f"(y) : "memory"); }
__device__ __forceinline__ void sts128(uint32_t a, uint32_t x, uint32_t y, uint32_t z, uint32_t w) {
    asm volatile("st.shared.v4.u32 [%0], {%1,%2,%3,%4};" ::"r"(a), "r"(x), "r"(y), "r"(z), "r"(w) : "memory");
}
__device__ __forceinline__ void sts128f(uint32_t a, const float* v) {
    asm volatile("st.shared.v4.f32 [%0], {%1,%2,%3,%4};" ::"r"(a), "f"(v[0]), "f"(v[1]), "f"(v[2]), "f"(v[3]) : "memory");
}
__device__ __forceinline__ uint4 ldg128(const void* p) {
    uint4 v; asm volatile("ld.global.nc.L1::no_allocate.v4.u32 {%0,%1,%2,%3}, [%4];" : "=r"(v.x), "=r"(v.y), "=r"(v.z), "=r"(v.w) : "l"(p)); return v;
}
__device__ __forceinline__ uint2 ldg64(const void* p) {
    uint2 v; asm volatile("ld.global.nc.L1::no_allocate.v2.u32 {%0,%1}, [%2];" : "=r"(v.x), "=r"(v.y) : "l"(p)); return v;
}
__device__ __forceinline__ uint32_t ldg32(const void* p) {
    uint32_t v; asm volatile("ld.global.nc.u32 %0, [%1];" : "=r"(v) : "l"(p)); return v;
}
__device__ __forceinline__ uint32_t ldg16(const void* p) {
    uint32_t v; asm volatile("ld.global.nc.u16 %0, [%1];" : "=r"(v) : "l"(p)); return v;
}
__device__ __forceinline__ uint4 ld_relaxed_128(const void* p) {
    uint4 v; asm volatile("ld.relaxed.gpu.global.v4.u32 {%0,%1,%2,%3}, [%4];" : "=r"(v.x), "=r"(v.y), "=r"(v.z), "=r"(v.w) : "l"(p) : "memory"); return v;
}
__device__ __forceinline__ void ld_relaxed_128_unless(uint4& q, const void* p, bool have) {
    asm volatile("{ .reg .pred p; setp.eq.u32 p, %5, 0; @p ld.relaxed.gpu.global.v4.u32 {%0,%1,%2,%3}, [%4]; }"
                 : "+r"(q.x), "+r"(q.y), "+r"(q.z), "+r"(q.w) : "l"(p), "r"((uint32_t)have) : "memory");
}
__device__ __forceinline__ uint2 ld_relaxed_64(const void* p) {
    uint2 v; asm volatile("ld.relaxed.gpu.global.v2.u32 {%0,%1}, [%2];" : "=r"(v.x), "=r"(v.y) : "l"(p) : "memory"); return v;
}
__device__ __forceinline__ uint32_t ld_relaxed_32(const void* p) {
    uint32_t v; asm volatile("ld.relaxed.gpu.global.u32 %0, [%1];" : "=r"(v) : "l"(p) : "memory"); return v;
}
__device__ __forceinline__ void st_relaxed_128(void* p, uint32_t x, uint32_t y, uint32_t z, uint32_t w) {
    asm volatile("st.relaxed.gpu.global.v4.u32 [%0], {%1,%2,%3,%4};" ::"l"(p), "r"(x), "r"(y), "r"(z), "r"(w) : "memory");
}
__device__ __forceinline__ void st_relaxed_64(void* p, uint32_t x, uint32_t y) {
    asm volatile("st.relaxed.gpu.global.v2.u32 [%0], {%1,%2};" ::"l"(p), "r"(x), "r"(y) : "memory");
}
__device__ __forceinline__ void st_relaxed_32(void* p, uint32_t v) {
    asm volatile("st.relaxed.gpu.global.u32 [%0], %1;" ::"l"(p), "r"(v) : "memory");
}
__device__ __forceinline__ void red_add(void* p, uint32_t v) { asm volatile("red.relaxed.gpu.global.add.u32 [%0], %1;" ::"l"(p), "r"(v) : "memory"); }
__device__ __forceinline__ uint32_t now_ns() { uint32_t t; asm volatile("mov.u32 %0, %%globaltimer_lo;" : "=r"(t) :: "memory"); return t; }
__device__ __forceinline__ void spin_guard(uint32_t& it) { if (++it > SPIN_LIMIT) __trap(); }
__device__ __forceinline__ void wait_count(const uint32_t* p, uint32_t target) {
#pragma unroll 1
    for (uint32_t it = 0; __any_sync(0xffffffffu, (int)(ld_relaxed_32(p) - target) < 0); spin_guard(it)) { }
}
__device__ __forceinline__ void mma_bf16(float* c, uint32_t a0, uint32_t a1, uint32_t a2, uint32_t a3, uint32_t b0, uint32_t b1) {
    asm("mma.sync.aligned.m16n8k16.row.col.f32.bf16.bf16.f32 {%0,%1,%2,%3}, {%4,%5,%6,%7}, {%8,%9}, {%0,%1,%2,%3};"
                 : "+f"(c[0]), "+f"(c[1]), "+f"(c[2]), "+f"(c[3]) : "r"(a0), "r"(a1), "r"(a2), "r"(a3), "r"(b0), "r"(b1));
}
__device__ __forceinline__ void mma_bf16_k8(float* c, uint32_t a0, uint32_t a1, uint32_t b0) {
    asm("mma.sync.aligned.m16n8k8.row.col.f32.bf16.bf16.f32 {%0,%1,%2,%3}, {%4,%5}, {%6}, {%0,%1,%2,%3};"
                 : "+f"(c[0]), "+f"(c[1]), "+f"(c[2]), "+f"(c[3]) : "r"(a0), "r"(a1), "r"(b0));
}
__device__ __forceinline__ void mma_v(float* c, const uint32_t* a, uint32_t b0, uint32_t b1) {
    asm volatile("mma.sync.aligned.m16n8k16.row.col.f32.bf16.bf16.f32 {%0,%1,%2,%3}, {%4,%5,%6,%7}, {%8,%9}, {%0,%1,%2,%3};"
                 : "+f"(c[0]), "+f"(c[1]), "+f"(c[2]), "+f"(c[3]) : "r"(a[0]), "r"(a[1]), "r"(a[2]), "r"(a[3]), "r"(b0), "r"(b1));
}
__device__ __forceinline__ void mma_bf16_z(float* c, uint32_t a0, uint32_t a1, uint32_t a2, uint32_t a3, uint32_t b0, uint32_t b1) {
    asm volatile("mma.sync.aligned.m16n8k16.row.col.f32.bf16.bf16.f32 {%0,%1,%2,%3}, {%4,%5,%6,%7}, {%8,%9}, {%10,%10,%10,%10};"
        : "=f"(c[0]), "=f"(c[1]), "=f"(c[2]), "=f"(c[3]) : "r"(a0), "r"(a1), "r"(a2), "r"(a3), "r"(b0), "r"(b1), "f"(0.f));
}
__device__ __forceinline__ void mma_f16(float* c, uint32_t a0, uint32_t a1, uint32_t a2, uint32_t a3, uint32_t b0, uint32_t b1) {
    asm("mma.sync.aligned.m16n8k16.row.col.f32.f16.f16.f32 {%0,%1,%2,%3}, {%4,%5,%6,%7}, {%8,%9}, {%0,%1,%2,%3};"
                 : "+f"(c[0]), "+f"(c[1]), "+f"(c[2]), "+f"(c[3]) : "r"(a0), "r"(a1), "r"(a2), "r"(a3), "r"(b0), "r"(b1));
}
__device__ __forceinline__ uint32_t pack_bf16(float lo, float hi) {
    uint32_t r; asm("cvt.rn.bf16x2.f32 %0, %1, %2;" : "=r"(r) : "f"(hi), "f"(lo)); return r;
}
__device__ __forceinline__ uint32_t pack_v(float lo, float hi) {
    uint32_t r; asm volatile("cvt.rn.bf16x2.f32 %0, %1, %2;" : "=r"(r) : "f"(hi), "f"(lo)); return r;
}
__device__ __forceinline__ uint32_t pack_w(float lo, float hi) {
    uint32_t r; asm volatile("cvt.rn.satfinite.bf16x2.f32 %0, %1, %2;" : "=r"(r) : "f"(hi), "f"(lo)); return r;
}
template <int N> __device__ __forceinline__ uint32_t after_all(const uint32_t (&f)[N][4], uint32_t zero) {
    uint32_t d[3] = {0, 0, 0};
#pragma unroll
    for (int i = 0; i < N; i++) d[i % 3] |= f[i][3];
    return (d[0] | d[1] | d[2]) & zero;
}
__device__ __forceinline__ void pin(uint32_t& x) { asm volatile("" : "+r"(x)); }
template <class T> __device__ __forceinline__ void pin(T*& x) { asm volatile("" : "+l"(x)); }
__device__ __forceinline__ uint32_t pack_f16(float lo, float hi) {
    uint32_t r; asm("cvt.rn.f16x2.f32 %0, %1, %2;" : "=r"(r) : "f"(hi), "f"(lo)); return r;
}
__device__ __forceinline__ float bf_lo(uint32_t v) { return __uint_as_float(v << 16); }
__device__ __forceinline__ float bf_hi(uint32_t v) { return __uint_as_float(v & 0xffff0000u); }
__device__ __forceinline__ float bf_round(float x) { return __uint_as_float(pack_bf16(0.f, x)); }
__device__ __forceinline__ uint32_t badd2(uint32_t a, uint32_t b) { uint32_t r; asm("add.rn.bf16x2 %0, %1, %2;" : "=r"(r) : "r"(a), "r"(b)); return r; }
__device__ __forceinline__ uint32_t bsub2_lo(uint32_t a, uint32_t b) {
    uint32_t r; asm("{ .reg .b16 m, h; .reg .b32 m2; mov.b32 {m, h}, %2; mov.b32 m2, {m, m}; sub.rn.bf16x2 %0, %1, m2; }" : "=r"(r) : "r"(a), "r"(b)); return r;
}
__device__ __forceinline__ uint32_t bmax2(uint32_t a, uint32_t b) { uint32_t r; asm("max.bf16x2 %0, %1, %2;" : "=r"(r) : "r"(a), "r"(b)); return r; }
__device__ __forceinline__ uint32_t normalize2(uint32_t x, uint32_t s0, uint32_t s1) {
    uint32_t r;
    asm("{ .reg .b16 m, h, l, k; .reg .b32 m2, h2, l2, d, t;\n\t"
        "mov.b32 {m, h}, %2; mov.b32 {l, k}, %3; mov.b32 m2, {m, m}; mov.b32 h2, {h, h}; mov.b32 l2, {l, l};\n\t"
        "sub.rn.bf16x2 d, %1, m2; mul.rn.bf16x2 t, d, l2; fma.rn.bf16x2 %0, d, h2, t; }" : "=r"(r) : "r"(x), "r"(s0), "r"(s1));
    return r;
}
__device__ __forceinline__ float rcpf(float x) { float r; asm("rcp.approx.ftz.f32 %0, %1;" : "=f"(r) : "f"(x)); return r; }
__device__ __forceinline__ float sqrtaf(float x) { float r; asm("sqrt.approx.ftz.f32 %0, %1;" : "=f"(r) : "f"(x)); return r; }
__device__ __forceinline__ float ex2f(float x) { float r; asm("ex2.approx.ftz.f32 %0, %1;" : "=f"(r) : "f"(x)); return r; }

__device__ __forceinline__ int tok_off(int t) { return ((t >> 3) & 1) * VT_PLANE + (t >> 4) * 16 + (t & 7) * 2; }

__device__ __forceinline__ uint32_t order_key(uint32_t b16) { return b16 ^ ((b16 & 0x8000u) ? 0xffffu : 0x8000u); }
__device__ __forceinline__ uint32_t unorder_key(uint32_t k16) { return k16 ^ ((k16 & 0x8000u) ? 0x8000u : 0xffffu); }

struct cplx { float r, i; };
struct hc { uint32_t r, i; };
template <bool CONJ> __device__ __forceinline__ cplx csq(cplx a) {
    float im;
    asm("{ .reg .f32 t; mul.ftz.f32 t, %1, %2; mul.ftz.f32 %0, t, 0f40000000; }" : "=f"(im) : "f"(CONJ ? -a.r : a.r), "f"(a.i));
    return {fmaf(a.r, a.r, -(a.i * a.i)), im};
}
__device__ __forceinline__ cplx cexpp(float a2, float ai) {
    float m = ex2f(a2), s, c;
    __sincosf(ai, &s, &c);
    return {m * c, m * s};
}
__device__ __forceinline__ __half2 as_h2(uint32_t x) { return *reinterpret_cast<__half2*>(&x); }
__device__ __forceinline__ uint32_t as_u(__half2 x) { return *reinterpret_cast<uint32_t*>(&x); }
__device__ __forceinline__ hc hmul(hc a, hc b) {
    return {as_u(__hfma2(as_h2(a.r), as_h2(b.r), __hneg2(__hmul2(as_h2(a.i), as_h2(b.i))))),
            as_u(__hfma2(as_h2(a.r), as_h2(b.i), __hmul2(as_h2(a.i), as_h2(b.r))))};
}
__device__ __forceinline__ hc hpack(cplx a, cplx b) { return {pack_f16(a.r, b.r), pack_f16(a.i, b.i)}; }
__device__ __forceinline__ void sts16(uint32_t a, uint32_t v) { asm volatile("st.shared.u16 [%0], %1;" ::"r"(a), "r"(v) : "memory"); }

struct KgenAddr {
    uint32_t l, h, m2, m3, m4, z, w, wz;
    __device__ __forceinline__ KgenAddr(uint32_t scr, int lane) {
        const int g = lane >> 2, t = lane & 3;
        const uint32_t rec = scr + t * 480;
        l = rec + 16 * g; h = rec + 128 + 8 * g; m2 = rec + 192 + 8 * (g & 1); m3 = rec + 208 + 4 * (g & 2); m4 = rec + 224 + 2 * (g & 4);
        z = scr + 7680 + 16 * t; w = scr + 240 * lane; wz = scr + 7680 + 8 * lane;
        pin(l); pin(h); pin(m2); pin(m3); pin(m4); pin(z); pin(w); pin(wz);
    }
    __device__ __forceinline__ uint32_t any() const { return (l | h | m2) | (m3 | m4 | z) | (w | wz); }
};
template <class Hook, class Hook2>
__device__ __forceinline__ void kgen(const KgenAddr& ad, uint32_t tab, int lane, uint2 la, uint2 aim, uint2 cre, uint2 cim, float dt, float skip, int dch, Hook main_done, Hook2 half_done) {
    const int g = lane >> 2, t = lane & 3;
    const float dt2 = 2.f * dt;
    const uint32_t am = bmax2(bmax2(cre.x & 0x7fff7fffu, cre.y & 0x7fff7fffu), bmax2(cim.x & 0x7fff7fffu, cim.y & 0x7fff7fffu));
    const float mx = dt2 * fmaxf(bf_lo(am), bf_hi(am));
    const uint32_t eb = min(max(__reduce_max_sync(0xffffffffu, __float_as_uint(mx)) >> 23, 1u), 252u);
    const float cscale = dt2 * __uint_as_float((253u - eb) << 23);
    const float scale_inv = __uint_as_float((eb + 1u) << 23);
    float k0 = (bf_lo(cre.x) + bf_hi(cre.x)) + (bf_lo(cre.y) + bf_hi(cre.y));
#pragma unroll
    for (int o = 16; o; o >>= 1) k0 += __shfl_xor_sync(0xffffffffu, k0, o);
    const float ndt = -1.4426950408889634f * dt;
    STAMP(40); KSTAMP(0);

    float acc[5][4];
#pragma unroll
    for (int i = 0; i < 5; i++) { acc[i][0] = acc[i][1] = acc[i][2] = acc[i][3] = 0.f; }

#pragma unroll kBbUnroll
    for (int bb = 0; bb < 2; bb++) {
        cplx z[2][11], cz[2];
#pragma unroll
        for (int e = 0; e < 2; e++) {
            const float lg = e ? bf_hi(la.x) : bf_lo(la.x), ai = (e ? bf_hi(aim.x) : bf_lo(aim.x)) * dt;
            const float cr = (e ? bf_hi(cre.x) : bf_lo(cre.x)) * cscale, ci = (e ? bf_hi(cim.x) : bf_lo(cim.x)) * cscale;
            const float a2 = bf_round(ex2f(lg * 1.4426950408889634f)) * ndt;
            z[e][0] = cexpp(a2, ai);
            z[e][5] = cexpp(a2 * 32.f, ai * -32.f);
#pragma unroll
            for (int i = 1; i < 11; i++) if (i != 5) z[e][i] = (i == 3 || i == 7) ? csq<true>(z[e][i - 1]) : csq<false>(z[e][i - 1]);
            cz[e] = {fmaf(cr, z[e][0].r, -(ci * z[e][0].i)), fmaf(cr, z[e][0].i, ci * z[e][0].r)};
        }
        la.x = la.y; aim.x = aim.y; cre.x = cre.y; cim.x = cim.y;
        const hc z1 = hpack(z[0][0], z[1][0]), z2 = hpack(z[0][1], z[1][1]), z4 = hpack(z[0][2], z[1][2]);
        hc L[8], H[8];
        L[1] = hpack(z[0][3], z[1][3]); L[2] = hpack(z[0][4], z[1][4]); L[4] = hpack(z[0][5], z[1][5]);
        const hc y64 = hpack(z[0][6], z[1][6]), z128 = hpack(z[0][7], z[1][7]), z256 = hpack(z[0][8], z[1][8]);
        const hc z512 = hpack(z[0][9], z[1][9]), z1024 = hpack(z[0][10], z[1][10]);
        H[0] = hpack(cz[0], cz[1]);
        H[1] = hmul(H[0], z1); H[2] = hmul(H[0], z2); H[3] = hmul(H[1], z2);
        L[3] = hmul(L[1], L[2]);
#pragma unroll
        for (int i = 0; i < 4; i++) { H[4 + i] = hmul(H[i], z4); if (i) L[4 + i] = hmul(L[i], L[4]); }
        __syncwarp();
        sts128(ad.w, 0x3c003c00u, y64.r, 0u, y64.i);
#pragma unroll
        for (int i = 1; i < 8; i++) { const hc q = hmul(L[i], y64); sts128(ad.w + 16 * i, L[i].r, q.r, L[i].i, q.i); }
#pragma unroll
        for (int i = 0; i < 4; i++) sts128(ad.w + 128 + 16 * i, H[2 * i].r, H[2 * i].i, H[2 * i + 1].r, H[2 * i + 1].i);
        {
            const hc a = hmul(z256, z1), b = hmul(z256, z128), c = hmul(z256, z2), d = hmul(z512, z4);
            sts128(ad.w + 192, a.r, a.i, b.r, b.i);
            sts128(ad.w + 208, c.r, c.i, z512.r, z512.i);
            sts128(ad.w + 224, d.r, d.i, z1024.r, z1024.i);
            sts64(ad.wz, z128.r, z128.i);
        }
        __syncwarp();
        KSTAMP(1 + 2 * bb);
#pragma unroll kKgUnroll
        for (int k2 = 0; k2 < 4; k2++) {
#pragma unroll
            for (uint32_t s = 0; s < 2; s++) {
                const uint32_t o = k2 * 1920 + s * 240;
                const uint4 l = lds128(ad.l + o);
                const uint2 h0 = lds64(ad.h + o), m2 = lds64(ad.m2 + o), m3 = lds64(ad.m3 + o), m4 = lds64(ad.m4 + o), mz = lds64(ad.z + k2 * 64 + s * 8);
                const hc H0 = {h0.x, h0.y};
                const hc H1 = hmul(H0, {mz.x, mz.y}), H2 = hmul(H0, {m2.x, m2.y}), H3 = hmul(H2, {m3.x, m3.y}), H4 = hmul(H3, {m4.x, m4.y});
                mma_f16(acc[0], l.x, l.y, l.z, l.w, H0.r, H0.i);
                mma_f16(acc[1], l.x, l.y, l.z, l.w, H1.r, H1.i);
                mma_f16(acc[2], l.x, l.y, l.z, l.w, H2.r, H2.i);
                mma_f16(acc[3], l.x, l.y, l.z, l.w, H3.r, H3.i);
                mma_f16(acc[4], l.x, l.y, l.z, l.w, H4.r, H4.i);
            }
        }
        KSTAMP(2 + 2 * bb);
        if (bb == 0) half_done();
    }
    __syncwarp();
    main_done();
    KSTAMP(5);
#pragma unroll
    for (int i = 0; i < 4; i++) sts128(tab + 2048 + 512 * i + 16 * lane, 0, 0, 0, 0);
    if (lane < 15) sts32(tab + 4 * lane, 0);
    __syncwarp();
    const uint32_t d0 = tab + T_DENSE + 4 + 8 * lane, src = (lane + 31) & 31;
    const uint32_t p0 = pack_bf16(fmaf(k0, dt2, skip), 0.f);
    uint32_t prev = p0;
#pragma unroll
    for (int i = 0; i < 4; i++) {
        const uint32_t pk = pack_bf16(acc[i >> 1][2 * (i & 1) + 1] * scale_inv, acc[i >> 1][2 * (i & 1)] * scale_inv);
        sts64(d0 + 256 * i, __byte_perm(pk, __shfl_sync(0xffffffffu, lane == 31 ? prev : pk, src), 0x5432), pk);
        prev = pk;
    }
    const uint32_t w0 = pack_bf16(acc[2][0] * scale_inv, acc[2][1] * scale_inv), w1 = pack_bf16(acc[2][2] * scale_inv, acc[2][3] * scale_inv);
    const uint32_t sa = (lane & 1) ? 0x5410u : 0x5454u, sb2 = (lane & 1) ? 0x1010u : 0x5410u;
#pragma unroll
    for (int hf = 0; hf < 2; hf++) {
        const uint32_t w = hf ? w1 : w0;
        const uint32_t pv = __shfl_sync(0xffffffffu, lane != 31 ? w : hf ? w0 : __byte_perm(prev, w1, 0x5410), src);
        sts64(d0 + 1024 + 256 * hf, __byte_perm(w, pv, sa), __byte_perm(w, pv, sb2));
        sts64(d0 + 1536 + 256 * hf, __byte_perm(w, pv, sa + 0x2222u), __byte_perm(w, pv, sb2 + 0x2222u));
    }
    const uint32_t d3 = tab + T_R2 + 160 + 320 * (t & 1) + 16 * (g >> 1) + 8 * (g & 1) + 4 * (t >> 1), d3n = d3 + (g >= 6 ? 32 : 0);
    const uint32_t d4 = tab + T_R3 + 80 + 160 * t + 4 * g, d4n = d4 + (g >= 6 ? 16 : 0);
    uint32_t p3;
#pragma unroll
    for (int hf = 0; hf < 2; hf++)
#pragma unroll
        for (int e = 0; e < 2; e++) {
            const float v3 = acc[3][2 * hf + e] * scale_inv;
            const uint32_t p4 = pack_bf16(acc[4][2 * hf + e] * scale_inv, 0.f);
            p3 = pack_bf16(v3, v3);
            sts16(d3 + 64 * hf + 160 * e, p3);
            sts16((hf ? d3n : d3) + 64 * hf + 160 * e + 18, p3);
            sts16(d4 + 32 * hf + 80 * e, p4);
            sts16((hf ? d4n : d4) + 32 * hf + 80 * e + 10, p4);
        }
    if (lane == 31) {
        const uint32_t k512 = __byte_perm(w1, 0, 0x3232);
        sts32(tab + T_DENSE, p0);
        sts64(tab + T_DENSE + 4 * 513, k512, k512); sts16(tab + T_DENSE + 4 * 515 + 2, k512);
        sts16(tab + T_PATCH + 4 * 17, p3); sts32(tab + T_PATCH + 4 * 18, p3); sts16(tab + T_PATCH + 4 * 19 + 2, p3);
    }
    __syncwarp();
}

__device__ __forceinline__ void load_toep(uint32_t* a, uint32_t p, uint32_t pz) {
    a[0] = lds32(p); a[1] = lds32(p + 32); a[2] = lds32(pz - 32); a[3] = lds32(pz);
}
#define YIELDS 2
#define YIELD_AT 2
#define DENSE_BLK 4
__device__ __forceinline__ void dense_step(float (&acc)[16][4], uint32_t (&R)[8][4], const uint32_t (&A)[4][4], uint32_t (&An)[4][4],
                                           uint32_t va, uint32_t vmin, uint32_t pn, uint32_t pz, uint32_t zero, int bit, uint32_t& junk) {
#pragma unroll
    for (int i0 = 0; i0 < 8; i0 += DENSE_BLK) {
#pragma unroll 1
        do {
#pragma unroll
            for (int i = i0; i < i0 + DENSE_BLK; i++) {
                const int ip = (i - DENSE_BLK) & 7;
                ldsm4(R[ip], ip == 0 ? max(va - 16, vmin) : va + ip * 128 - (i0 ? 16 : 0));
                if ((i & 1) == 0) load_toep(An[i >> 1], pn + (i >> 1) * 512, pz + (i >> 1) * 512);
#pragma unroll
                for (int ka = 0; ka < 4; ka++) {
                    mma_v(acc[i + ka], A[ka], R[i][0], R[i][1]);
                    if (i + 8 + ka < 16) mma_v(acc[i + 8 + ka], A[ka], R[i][2], R[i][3]);
                }
                if ((YIELDS >> (i - i0)) & 1) asm volatile("xor.b32 %0, %0, %1;" : "+r"(junk) : "r"(__float_as_uint(acc[i + YIELD_AT][0])));
            }
        } while (zero & (1u << (bit + i0)));
    }
}
struct DenseTaps {
    uint32_t A[4][4], E[4], F[4], G[4];
    __device__ __forceinline__ DenseTaps(uint32_t pb, uint32_t pz) {
        constexpr int PP = T_PATCH - T_DENSE + 56;
#pragma unroll
        for (int i = 0; i < 4; i++) load_toep(A[i], pb + 512 * i, pz + 512 * i);
        load_toep(E, pb + 2048, pz + 2048);
        load_toep(F, pb + PP, pz + PP);
        G[0] = lds32(pz + 2048 + 32); G[1] = lds32(pb + 2048 + 64); G[2] = lds32(pz + PP + 32); G[3] = lds32(pb + PP + 64);
    }
};
__device__ __forceinline__ uint32_t dense_phase(float (&acc)[16][4], uint32_t vrow, uint32_t pb, DenseTaps& tp, uint32_t zero, int lane) {
    uint32_t R[8][4], A1[4][4], junk = 0;
    const uint32_t vmin = vrow + ((lane >> 3) & 1) * VT_PLANE - 16 + zero;
    uint32_t va = vmin + 16 + (lane >> 4) * 1024 + (lane & 7) * 16, pz = pb + zero;
    {
        uint32_t H[4][4];
#pragma unroll
        for (int i = 0; i < 4; i++) ldsm4(H[i], vrow + VT_PLANE + 496 - ((lane >> 3) & 1) * 512 + (lane >> 4) * 128 + (lane & 7) * 16 + i * 256);
#pragma unroll
        for (int i = 0; i < 8; i++) ldsm4(R[i], va + i * 128);
#pragma unroll
        for (int i = 0; i < 4; i++) mma_bf16_k8(acc[i + 4], tp.G[0], tp.G[1], H[i >> 1][2 * (i & 1) + 1]);
#pragma unroll
        for (int i = 0; i < 8; i++) mma_v(acc[i + 8], tp.G, H[i >> 1][2 * (i & 1)], H[i >> 1][2 * (i & 1) + 1]);
#pragma unroll
        for (int i = 0; i < 12; i++) mma_v(acc[i + 4], tp.E, R[i & 7][2 * (i >> 3)], R[i & 7][2 * (i >> 3) + 1]);
#pragma unroll
        for (int i = 0; i < 8; i++) mma_v(acc[i + 8], tp.F, R[i][0], R[i][1]);
    }
#pragma unroll 1
    for (int rho = 0; rho < 8; rho += 2) {
        dense_step(acc, R, tp.A, A1, va, vmin, pb + 64, pz + 64, zero, 0, junk);
        dense_step(acc, R, A1, tp.A, va - 16, vmin, pb + 128, pz + 128, zero, 8, junk);
        pb += 128; pz += 128; va -= 32;
    }
    return junk & zero;
}
__device__ __forceinline__ uint32_t ones2(int c, int lo, int hi) {
    return (((uint32_t)(c - lo) <= (uint32_t)(hi - lo)) ? 0x3f80u : 0u) | (((uint32_t)(c + 1 - lo) <= (uint32_t)(hi - lo)) ? 0x3f800000u : 0u);
}
struct Boxes {
    uint32_t q[4], ha[2];
    __device__ __forceinline__ Boxes(uint32_t vrow, int lane, int O, int L1, int H1, int L2, int H2) {
        const int g = lane >> 2, t = lane & 3, d = 2 * t - g;
        q[0] = ones2(d, L1, H1); q[1] = ones2(d, L2, H2); q[2] = ones2(d + 8, L1, H1); q[3] = ones2(d + 8, L2, H2);
#pragma unroll
        for (int i = 0; i < 2; i++) { ha[i] = vrow + 16 * g + tok_off(O + 8 * i + 2 * t); pin(ha[i]); pin(q[i]); pin(q[2 + i]); }
    }
    __device__ __forceinline__ uint32_t any() const { return (q[0] | q[1] | q[2]) | (q[3] | ha[0] | ha[1]); }
    __device__ __forceinline__ void load(int j, uint32_t* v, uint32_t zero) const {
        const uint32_t o = j * 128;
        v[0] = lds32(ha[0] + o); v[1] = lds32(ha[1] + zero + o); v[2] = lds32(ha[1] + o);
        v[3] = lds32(ha[0] + zero + o + 16); v[4] = lds32(ha[0] + o + 16); v[5] = lds32(ha[1] + o + 16);
    }
    __device__ __forceinline__ void sums(const uint32_t* v, float* Z, float* X, float* Y) const {
        mma_bf16_z(Z, q[0], q[1], q[2], q[3], v[0], v[1]);
        mma_bf16_z(X, q[0], q[1], q[2], q[3], v[2], v[3]);
        mma_bf16_z(Y, q[0], q[1], q[2], q[3], v[4], v[5]);
    }
};
template <class After>
__device__ __forceinline__ void tail_phase(float (&acc)[16][4], const Boxes& b2, const Boxes& b3, uint32_t tp2, uint32_t tp3, uint32_t zero, After after) {
    uint2 tp[10];
    uint32_t v[6], a0[4], a1[4];
    float Z[4], X[4], Y[4];
    b2.load(0, v, zero);
#pragma unroll
    for (int i = 0; i < 5; i++) { const uint4 c = lds128(tp2 + 160 * i); tp[i] = make_uint2(c.x, c.y); tp[5 + i] = make_uint2(c.z, c.w); }
#pragma unroll
    for (int j = -1; j < 20; j++) {
        if (j < 19) {
            (j < 11 ? b2 : b3).sums(v, Z, X, Y);
            if (j < 10) b2.load(j + 2, v, zero); else if (j < 18) b3.load(j - 10, v, zero);
        }
        if (j >= 0 && j < 12) {
#pragma unroll
            for (int b = 0; b < 5; b++) if (j + 4 + b < 16) mma_v(acc[j + 4 + b], a1, tp[5 + b].x, tp[5 + b].y);
        }
        if (j < 11) { a1[0] = pack_v(Z[0], Z[1]); a1[1] = pack_w(X[0], X[1]); a1[2] = pack_v(Z[2], Z[3]); a1[3] = pack_w(X[2], X[3]); }
        if (j >= 0 && j < 12) {
#pragma unroll
            for (int b = 0; b < 5; b++) if (j + 4 + b < 16) mma_v(acc[j + 4 + b], a0, tp[b].x, tp[b].y);
            if (j >= 7 && j < 11) { tp[11 - j] = lds64(tp3 + 80 * (10 - j)); tp[16 - j] = lds64(tp3 + 80 * (14 - j)); }
        } else if (j >= 12) {
#pragma unroll
            for (int b = 0; b < 8; b++) if (j - 4 + b < 16) mma_v(acc[j - 4 + b], a0, tp[b < 4 ? b + 1 : b + 2].x, tp[b < 4 ? b + 1 : b + 2].y);
        }
        if (j < 11) { a0[0] = pack_v(X[0], X[1]); a0[1] = pack_v(Y[0], Y[1]); a0[2] = pack_v(X[2], X[3]); a0[3] = pack_v(Y[2], Y[3]); }
        else if (j < 19) { a0[0] = pack_v(X[0], X[1]); a0[1] = pack_v(Y[0], Y[1]); a0[2] = pack_v(Z[2], Z[3]); a0[3] = pack_v(X[2], X[3]); }
        after(j);
    }
}
template <int G>
__device__ __forceinline__ void emit(const float (&acc)[16][4], int h, uint32_t own, uint32_t peer, uint32_t bar, uint32_t bar_peer) {
#pragma unroll
    for (int o = 0; o < 2; o++)
#pragma unroll
        for (int hf = 0; hf < 2; hf++) {
            const int n = 8 * G + 4 * o;
            asm volatile("{ .reg .pred p; setp.eq.u32 p, %7, %8;\n\t@p st.shared.v4.u32 [%0], {%1,%2,%3,%4};\n\t"
                         "@!p st.async.weak.shared::cluster.mbarrier::complete_tx::bytes.v4.b32 [%5], {%1,%2,%3,%4}, [%6]; }"
                         ::"r"(own + G * 16384 + hf * 512), "r"(pack_bf16(acc[n][2 * hf], acc[n][2 * hf + 1])), "r"(pack_bf16(acc[n + 1][2 * hf], acc[n + 1][2 * hf + 1])),
                         "r"(pack_bf16(acc[n + 2][2 * hf], acc[n + 2][2 * hf + 1])), "r"(pack_bf16(acc[n + 3][2 * hf], acc[n + 3][2 * hf + 1])),
                         "r"(peer + G * 16384 + hf * 512), "r"(bar_peer + 8 * G), "r"(h), "r"(o) : "memory");
        }
    __syncwarp();
    if (elect_one()) mbar_arrive(bar + 8 * G);
}
__device__ __forceinline__ void finish(uint32_t src, uint32_t xa) {
    uint32_t s[4][4];
    uint4 x[4];
#pragma unroll
    for (int i = 0; i < 4; i++) {
        ldsm4t(s[i], (src ^ ((i & 1) << 5)) + (i >> 1) * 8192);
        x[i] = lds128((xa ^ ((i >> 1) << 4)) + (i & 1) * 256);
    }
#pragma unroll
    for (int i = 0; i < 4; i++)
        sts128((xa ^ ((i >> 1) << 4)) + (i & 1) * 256, badd2(x[i].x, s[i][0]), badd2(x[i].y, s[i][1]), badd2(x[i].z, s[i][2]), badd2(x[i].w, s[i][3]));
}

__device__ __noinline__ float centred_var(uint32_t rows, float mu, int lane) {
    float var = 0.f;
#pragma unroll 1
    for (int rr = 0; rr < 16; rr++) {
        const float c0 = __shfl_sync(0xffffffffu, mu, rr);
        float c = 0.f;
#pragma unroll 1
        for (int k = 0; k < 16; k++) {
            const uint32_t q = lds32(rows + rr * ROW_PITCH + k * 128 + lane * 4);
            const float d0 = bf_lo(q) - c0, d1 = bf_hi(q) - c0;
            c = fmaf(d0, d0, fmaf(d1, d1, c));
        }
#pragma unroll 1
        for (int o = 16; o; o >>= 1) c += __shfl_xor_sync(0xffffffffu, c, o);
        if ((lane & 15) == rr) var = c * (1.f / DM);
    }
    return var;
}
__device__ __noinline__ float centred_score(uint32_t rows, uint32_t wbuf, uint32_t s0, uint32_t s1, int lane) {
    float sc = 0.f;
#pragma unroll 1
    for (int rr = 0; rr < 16; rr++) {
        const uint32_t t0 = __shfl_sync(0xffffffffu, s0, rr), t1 = __shfl_sync(0xffffffffu, s1, rr);
        float c = 0.f;
#pragma unroll 1
        for (int k = 0; k < 16; k++) {
            const uint32_t xn = normalize2(lds32(rows + rr * ROW_PITCH + k * 128 + lane * 4), t0, t1);
            const uint32_t wq = lds32(wbuf + (k >> 2) * 1024 + (k & 3) * 128 + lane * 4);
            c = fmaf(bf_lo(xn), bf_lo(wq), fmaf(bf_hi(xn), bf_hi(wq), c));
        }
#pragma unroll 1
        for (int o = 16; o; o >>= 1) c += __shfl_xor_sync(0xffffffffu, c, o);
        if ((lane & 15) == rr) sc = c;
    }
    return sc;
}

__device__ __forceinline__ void issue_rows(const __nv_bfloat16* u, uint32_t sb, int b) {
    if (elect_one()) {
        const uint32_t bar = sb + OFF_BAR + 8 * B_ROW;
#pragma unroll
        for (int j = 0; j < 4; j++) mbar_init(bar + 8 * j, 1);
        asm volatile("fence.mbarrier_init.release.cluster;" ::: "memory");
        fence_async();
#pragma unroll 1
        for (int j = 0; j < 4; j++) {
            mbar_expect_tx(bar + 8 * j, 8192);
#pragma unroll
            for (int i = 0; i < 4; i++) bulk_g2s(sb + OFF_VT + (4 * j + i) * ROW_PITCH, u + (size_t)(16 * b + 4 * j + i) * DM, 2048, bar + 8 * j);
        }
    }
    __syncwarp();
}

__global__ void __cluster_dims__(2, 1, 1) __launch_bounds__(NTHR, 1)
fused_kernel(const __grid_constant__ Ptrs p, const __grid_constant__ Maps maps) {
    extern __shared__ __align__(1024) unsigned char smem[];
    const int tid = threadIdx.x, lane = tid & 31;
    const int c_ = ((blockIdx.x >> 1) + PERM_OFF) & 63, b = 2 * ((c_ & 32) | ((c_ & 7) << 2) | ((c_ >> 3) & 3)) + (blockIdx.x & 1);
    const int dch = 8 * b + (tid >> 5) - 4;
    uint2 la, aim, cre, cim;
    uint32_t ldt16;
    if ((uint32_t)(tid - 128) < 256u) {
        la = ldg64(p.logA + dch * NMODE + 4 * lane); aim = ldg64(p.Aim + dch * NMODE + 4 * lane);
        cre = ldg64(p.Cre + dch * NMODE + 4 * lane); cim = ldg64(p.Cim + dch * NMODE + 4 * lane);
        ldt16 = ldg16(p.ldt + dch);
    }
    const uint32_t sb = s_u32(smem), bar0 = sb + OFF_BAR;
    const int warp = __shfl_sync(0xffffffffu, tid >> 5, 0);
    const int h = b & 1, cl = b >> 1;
    const int m = lane >> 3, r = lane & 7, g = lane >> 2, t = lane & 3;
    const bool has_gu = b < GU_CTAS;
    if (warp == 4) { STAMP(0); GSTAMP(24); }

    if (warp >= 12) {
        asm volatile("setmaxnreg.dec.sync.aligned.u32 24;");
        const int a = warp - 12;
        uint32_t due = now_ns() + ST_T0 + (uint32_t)(128 * a + b) * ST_PER / 128 + (has_gu ? 0 : ST_LATE * (12 * ST_PER + 4 * ST_PER2) / 16);
        const bool el = elect_one();
        if (a == 1) issue_rows(p.u, sb, b);
        if (a == 2 && el) {
#pragma unroll
            for (int i = B_XT; i < NBAR; i++) mbar_init(bar0 + 8 * i, (i == B_V || i == B_SFREE || i == B_XFREE) ? 8 : (i == B_RECV || i == B_RECV + 1) ? 9 : i == B_RED ? 5 : (i == B_UPD || (i >= B_FREE && i < B_FULL)) ? 4 : 1);
            asm volatile("fence.mbarrier_init.release.cluster;" ::: "memory");
            fence_async();
            mbar_expect_tx(bar0 + 8 * B_XT, 65536);
            mbar_expect_tx(bar0 + 8 * B_RECV, 8192);
            mbar_expect_tx(bar0 + 8 * B_RECV + 8, 8192);
            mbar_expect_tx(bar0 + 8 * B_RED, 2048);
        }
        if (a == 3 && el) {
#pragma unroll
            for (int i = 0; i < 5; i++) asm volatile("prefetch.tensormap [%0];" ::"l"(&maps.u + i) : "memory");
        }
        __syncwarp();
        cluster_arrive();
        cluster_wait();
        STAMP(18);
        mbar_wait(bar0 + 8 * (B_ROW + a), 0);
        if (el) {
#pragma unroll
            for (int i = 0; i < 4; i++)
                tma_load_tile(sb + OFF_XT + h * 32768 + a * 4096 + (i & 1) * 16384 + (i >> 1) * 2048, &maps.u, 16 * cl, 4 * a + (i & 2), 16 * (i & 1) + 8 * h, bar0 + 8 * B_XT);
        }
        if (el) {
#pragma unroll 1
            for (int k = has_gu ? 0 : 4; k < 6; k++) {
                const int i = 4 * k + a, s = k < 3 ? i : i - 12;
#pragma unroll 1
                for (int left; (left = (int)(due - now_ns())) > 0;) __nanosleep(left >> 1);
                due += k == 0 ? 4 * ST_PER + ST_GAP : k < 3 ? 4 * ST_PER : 4 * ST_PER2;
                const bool again = k >= 3 && has_gu;
                if (s >= 6 || again) mbar_wait(bar0 + 8 * (s < 10 || again ? B_FREE + s : B_V), slot_priv(s) && again);
                const uint32_t dst = sb + slot_off(s), bar = bar0 + 8 * (B_FULL + s);
                if (k < 4) {
                    mbar_expect_tx(bar, 8192);
                    tma_load_2d(dst, &maps.wg, 64 * cl, 512 * h + 32 * i, bar);
                    tma_load_2d(dst + 4096, &maps.wu, 64 * cl, 512 * h + 32 * i, bar);
                } else {
                    mbar_expect_tx(bar, 7168);
                    tma_load_perm(dst, &maps.wd, 16 * cl, 56 * h + 14 * a + 7 * (k & 1), bar);
                }
            }
            STAMP(19);
        }
    } else if (warp >= 4) {
        const int w = warp - 4;
        uint32_t dsk16 = ldg16(p.dsk + dch);
        cluster_arrive();
        asm volatile("setmaxnreg.inc.sync.aligned.u32 168;");
        const uint32_t vrow = sb + OFF_VT + w * VT_PITCH + VT_PAD, tab = sb + tab_off(w);
        const uint32_t so = sb + OFF_XT + (8 * h + w) * 1024 + ((lane ^ ((w & 1) << 1)) << 4);
        uint32_t dst0 = so + (h ^ 1) * 32768;
        const uint32_t rb0 = bar0 + 8 * B_RECV, rb1 = mapa(rb0, h ^ 1);
        const uint32_t box = sb + OFF_XT + h * 32768 + w * 2048;
        uint32_t fs = sb + OFF_XT + (h ^ 1) * 32768 + (2 * m + (r & 1)) * 1024 + (w >> 2) * 512 + (((8 * (w & 3) + (r & 4) + ((r >> 1) & 1)) ^ ((r & 1) << 1)) << 4);
        uint32_t fx = box + (g >> 1) * 512 + (t >> 1) * 144 + (2 * (t & 1) + (g & 1)) * 32;
        uint32_t tpo = 80 + (g - 2 * t) * 8 - (g < 2 * t ? 16 : 0);
        uint32_t xa = sb + OFF_XT + (w & 2) * 16384 + (w >> 2) * 16384 + (w & 1) * 1024 + (g >> 1) * 2048 + (g & 1) * 128 + t * 32 + ((h ^ (g & 1)) << 4);
        uint32_t va = sb + OFF_VT + (2 * m + (r & 1)) * VT_PITCH + VT_PAD + (16 * w + (r >> 1)) * 16;
        uint32_t qa = sb + OFF_ST + 2048 * w + 128 * t + 16 * (g ^ (2 * t));
        pin(dst0); pin(fs); pin(fx); pin(tpo); pin(xa); pin(va); pin(qa);
        const Boxes b2(vrow, lane, -18, 5, 7, 0, 4), b3(vrow, lane, -20, 1, 7, 0, 8);
        const KgenAddr ka(sb + OFF_PRIV + w * 8192, lane);
        if (__any_sync(0xffffffffu, ((dst0 | fs) | (fx | tpo | xa) | (va | qa) | (b2.any() | b3.any() | ka.any())) & p.zero)) __trap();
        cluster_wait();
        pin(la.x); pin(la.y); pin(aim.x); pin(aim.y); pin(cre.x); pin(cre.y); pin(cim.x); pin(cim.y); pin(ldt16); pin(dsk16);
        uint4 x[8];
        auto load_x = [&]() {
            mbar_wait(bar0 + 8 * B_XT, 0);
#pragma unroll
            for (int i = 0; i < 8; i++) x[i] = lds128(xa + (i & 1) * 8192 + (i >> 1) * 256);
        };
        kgen(ka, tab, lane, la, aim, cre, cim, bf_round(ex2f(bf_lo(ldt16) * 1.4426950408889634f)), 1.f + bf_lo(dsk16), dch, [&]() {
            STAMP(21);
            if (elect_one()) mbar_arrive_n(bar0 + 8 * (B_FREE + 6 + ((w >> 1) ^ 2)), 2);
        }, [&]() {
            if ((LN_PAUSE >> w) & 1) mbar_wait(bar0 + 8 * B_LN, 0);
        });
        STAMP(1); KSTAMP(6);
        const uint32_t pb = tab + T_DENSE + (g - 2 * t) * 4;
        {
            load_x();
            STAMP(47);
            mbar_wait(bar0 + 8 * (B_ST + (w >> 1)), 0);
            uint4 q[4];
#pragma unroll
            for (int n = 0; n < 4; n++) q[n] = lds128(qa + 512 * n);
            if (lane < 4) sts128(vrow - VT_PAD + (lane >> 1) * VT_PLANE + (lane & 1) * 16, 0, 0, 0, 0);
            STAMP(2); GSTAMP(28);
#pragma unroll
            for (int i = 0; i < 8; i++) {
                const uint32_t s0 = (i & 1) ? q[i >> 1].z : q[i >> 1].x, s1 = (i & 1) ? q[i >> 1].w : q[i >> 1].y;
                stsm4t(va + (i >> 1) * 64 + (i & 1) * VT_PLANE, normalize2(x[i].x, s0, s1), normalize2(x[i].y, s0, s1),
                       normalize2(x[i].z, s0, s1), normalize2(x[i].w, s0, s1));
            }
            __syncwarp();
            if (elect_one()) mbar_arrive(bar0 + 8 * B_V);
        }
        DenseTaps dt(pb, pb + p.zero);
        mbar_wait(bar0 + 8 * B_V, 0);
        STAMP(3); KSTAMP(7);
        float acc[16][4];
#pragma unroll
        for (int i = 0; i < 16; i++) { acc[i][0] = acc[i][1] = acc[i][2] = acc[i][3] = 0.f; }
        tpo |= dense_phase(acc, vrow, pb, dt, p.zero, lane);
        STAMP(4); KSTAMP(8);
        const uint32_t dst1 = mapa(dst0 + (h ? 32768 : -32768), h ^ 1);
        tail_phase(acc, b2, b3, tab + T_R2 + 2 * tpo, tab + T_R3 + tpo, p.zero, [&](int j) {
            if (j == 3) {
                mbar_wait(bar0 + 8 * B_SFREE, 0);
                emit<0>(acc, h, dst0, dst1, rb0, rb1);
                STAMP(5);
            }
            if (j == STORE_AT) {
                mbar_wait(bar0 + 8 * B_XFREE, 0);
                mbar_wait(bar0 + 8 * B_RECV, 0);
                finish(fs, fx);
                fence_async();
                __syncwarp();
                if (elect_one()) tma_store_tile(&maps.out, box, 16 * cl, 2 * w, 8 * h);
                STAMP(20);
            }
        });
        emit<1>(acc, h, dst0, dst1, rb0, rb1);
        STAMP(30);
        const int tok = 2047 - (int)(lds32(sb + OFF_MISC + 48 + 8 * g) & 2047);
        const bool mine = (((tok >> 6) & 8) | ((tok >> 1) & 7)) == 8 * h + w;
        const bool any = __any_sync(0xffffffffu, mine), late = __any_sync(0xffffffffu, mine && tok >= 1024);
        const uint32_t ta = box + (tok >> 10) * 16384 + ((tok >> 6) & 7) * 256 + (tok & 1) * 128 + ((tok >> 4) & 3) * 32 + (((t >> 1) ^ (tok & 1)) << 4) + (t & 1) * 8;
        const bool el = elect_one();
        mbar_wait(bar0 + 8 * (B_RECV + 1), 0);
        STAMP(6);
        finish(fs + 16384, fx + 16384);
#pragma unroll 1
        for (int pass = 0; pass < 2; pass++) {
            if ((pass != 0) == late) {
                fence_async();
                __syncwarp();
                if (el) tma_store_tile(&maps.out, box + 16384, 16 * cl, 2 * w, 16 + 8 * h);
            } else if (any) {
                if (el) {
                    if (late) asm volatile("cp.async.bulk.wait_group 0;" ::: "memory");
                    else asm volatile("cp.async.bulk.wait_group 1;" ::: "memory");
                }
                __syncwarp();
                const uint2 o0 = lds64(ta);
                mbar_wait(bar0 + 8 * B_UPD, 0);
                const float4 up = lds128f(sb + tab_off(g) + T_RED + 16 * t);
                const uint2 o1 = make_uint2(badd2(o0.x, pack_bf16(up.x, up.y)), badd2(o0.y, pack_bf16(up.z, up.w)));
                if (mine) {
                    if (tok >= 1024) sts64(ta, o1.x, o1.y);
                    else *reinterpret_cast<uint2*>(p.out + (size_t)tok * DM + 16 * cl + 4 * t) = o1;
                }
            }
        }
        if (el) asm volatile("cp.async.bulk.wait_group.read 0;" ::: "memory");
        STAMP(7);
    } else {
        const int a = warp;
        const uint4 wq = ldg128(p.wr + 8 * tid);
        const uint32_t epoch = ld_relaxed_32(&p.sc->epoch);
        cluster_arrive();
        asm volatile("setmaxnreg.inc.sync.aligned.u32 152;");
        const uint32_t tag = __shfl_sync(0xffffffffu, epoch, 0) + 1u, misc = sb + OFF_MISC, abar = bar0 + 8 * (B_AUX + a);
        uint32_t aph = 0;
        const Exchange* in = &p.sc->x[cl & (NREP - 1)];
        uint2* pub = p.sc->x[m >> 1].stat + 16 * b + 2 * (r ^ (2 * (b & 3))) + (m & 1);
        uint32_t* cnt_s = &p.sc->x[t].n_stat[b & 96];
        pin(pub); pin(cnt_s);
        if (tid < 64) sts32(sb + OFF_XCH + 4 * tid, 0);
        const uint32_t wbuf = sb + OFF_LN + a * 1024, part = sb + OFF_LN + 4096;
        {
            sts128(wbuf + 16 * lane, wq.x, wq.y, wq.z, wq.w);
            sts128(wbuf + 512 + 16 * lane, 0x3f803f80u, 0x3f803f80u, 0x3f803f80u, 0x3f803f80u);
            float wsum = ((bf_lo(wq.x) + bf_hi(wq.x)) + (bf_lo(wq.y) + bf_hi(wq.y))) + ((bf_lo(wq.z) + bf_hi(wq.z)) + (bf_lo(wq.w) + bf_hi(wq.w)));
#pragma unroll
            for (int o = 16; o; o >>= 1) wsum += __shfl_xor_sync(0xffffffffu, wsum, o);
            sts32f(part + 1024 + 4 * a, wsum);
            uint32_t wf[4][4];
#pragma unroll
            for (int i = 0; i < 4; i++) ldsm4(wf[i], wbuf + ((uint32_t)(r - 1) < 2u ? 16 * (r - 1) : 512) + 32 * m + 128 * i);
            uint32_t ra = sb + OFF_VT + r * ROW_PITCH + 512 * a + 16 * m, pa = part + a * 256 + g * 16;
            cluster_wait();
            STAMP(22);
#pragma unroll 1
            for (int hf = 0; hf < 2; hf++) {
                mbar_wait(bar0 + 8 * B_ROW + 16 * hf, 0);
                mbar_wait(bar0 + 8 * B_ROW + 16 * hf + 8, 0);
                STAMP(23);
                uint32_t x[8][4];
                float cs[2][4], q[8][4];
#pragma unroll
                for (int i = 0; i < 40; i++) (i < 8 ? cs[i >> 2 & 1] : q[(i - 8) >> 2 & 7])[i & 3] = 0.f;
#pragma unroll
                for (int k = 0; k < 8; k++) ldsm4(x[k], ra + k * 64);
                const bool more = __any_sync(0xffffffffu, after_all(x, p.zero));
#pragma unroll 1
                do {
#pragma unroll
                    for (int k = 0; k < 8; k++) {
                        mma_v(cs[k & 1], x[k], wf[k >> 1][2 * (k & 1)], wf[k >> 1][2 * (k & 1) + 1]);
#pragma unroll
                        for (int i = 0; i < 4; i++) mma_bf16_k8(q[4 * (k & 1) + i], x[k][i & 2], x[k][i | 1], x[k][i]);
                    }
                } while (more);
                const float c2 = cs[0][2] + cs[1][2];
                if (t == 0) sts64f(pa, (cs[0][0] + cs[1][0]) + c2, cs[0][1] + cs[1][1]);
                if (t == 1) sts32f(pa + 12, c2);
                const float e0 = ((q[0][0] + q[2][0]) + (q[4][0] + q[6][0])) + ((q[1][2] + q[3][2]) + (q[5][2] + q[7][2]));
                const float e1 = ((q[0][1] + q[2][1]) + (q[4][1] + q[6][1])) + ((q[1][3] + q[3][3]) + (q[5][3] + q[7][3]));
                if (t == (g >> 1)) sts32f(pa + 8, (g & 1) ? e1 : e0);
                ra += 8 * ROW_PITCH; pa += 128;
            }
        }
        STAMP(31);
        named_sync(1, 128);
        if (a == 0) {
            const uint32_t pa = part + (lane & 15) * 16;
            const float4 p0 = lds128f(pa), p1 = lds128f(pa + 256), p2 = lds128f(pa + 512), p3 = lds128f(pa + 768), ws = lds128f(part + 1024);
            const float mu = ((p0.x + p1.x) + (p2.x + p3.x)) * (1.f / DM);
            float var = ((p0.z + p1.z) + (p2.z + p3.z)) * (1.f / DM) - mu * mu;
            const bool centred = __any_sync(0xffffffffu, !(mu * mu <= 4.f * var));
            if (centred) var = centred_var(sb + OFF_VT, mu, lane);
            const float ri = rcpf(bf_round(sqrtaf(bf_round(bf_round(var) + 1e-5f))));
            const uint32_t s0 = pack_bf16(mu, ri), s1 = (pack_bf16(ri - bf_hi(s0), 0.f) & 0xfffcu) | (tag & 3);
            float sc = ((((p0.y + p1.y) + (p2.y + p3.y)) + ((p0.w + p1.w) + (p2.w + p3.w))) - bf_lo(s0) * ((ws.x + ws.y) + (ws.z + ws.w))) * ri;
            if (centred) sc = centred_score(sb + OFF_VT, sb + OFF_LN, s0, s1, lane);
            const uint32_t sb16 = pack_bf16(0.f, sc);
            const uint32_t s2 = s1 | (sb16 ^ (((uint32_t)((int)sb16 >> 31) & 0x7fff0000u) | 0x80000000u));
            st_relaxed_64(pub, s0, s2);
            st_relaxed_64(pub + 2 * sizeof(Exchange) / 8, s0, s2);
            if (lane < NREP) red_add(cnt_s, 1);
            if (elect_one()) mbar_arrive(bar0 + 8 * B_LN);
            STAMP(9); GSTAMP(25);
        }
        const uint32_t slot0 = sb + OFF_RING + a * 8192, slot1 = sb + slot_off(4 + a), slot2 = sb + slot_off(8 + a), fbar = bar0 + 8 * (B_FULL + a);
        uint32_t mine = 0, row[2] = {0, 0};
        {
            uint32_t q[16];
            named_sync(1, 128);
            wait_count(&in->n_stat[32 * a], 32 * tag - FEW_ST);
            STAMP(41);
#pragma unroll 1
            for (uint32_t it = 0;; spin_guard(it)) {
                if (elect_one()) {
                    mbar_expect_tx(abar, 4096);
                    bulk_g2s(sb + OFF_ST + 4096 * a, in->stat + 512 * a, 4096, abar);
                }
                mbar_wait(abar, aph);
                aph ^= 1;
                uint32_t bad = 0;
#pragma unroll
                for (int n = 0; n < 8; n++) {
                    const uint4 u = lds128v(sb + OFF_ST + 4096 * a + 512 * n + 16 * lane);
                    q[2 * n] = u.y; q[2 * n + 1] = u.w;
                    bad = or_xor(bad, u.y, tag);
                }
                const bool ok = __all_sync(0xffffffffu, (bad & 3) == 0);
                asm volatile("{ .reg .pred p; setp.ne.u32 p, %1, 0; @p mbarrier.arrive.shared::cta.b64 _, [%0]; }" ::"r"(bar0 + 8 * (B_ST + a)), "r"((uint32_t)(ok && lane == 0)) : "memory");
                if (ok) break;
            }
            STAMP(8);
            const uint32_t inv = 2047 - 512 * a - 16 * m - (r ^ (2 * m));
#pragma unroll
            for (int i = 0; i < 16; i++) asm("lop3.b32 %0, %0, %1, %2, 0x9b;" : "+r"(q[i]) : "r"(inv), "r"(0xffff0000u | (64 * (i >> 1) + 8 * (i & 1))));
            auto below = [&](uint32_t x) {
                uint32_t d[4];
#pragma unroll
                for (int i = 0; i < 16; i++) d[i & 3] = i < 4 ? x + q[i] : min(d[i & 3], x + q[i]);
                d[0] = min(min(d[0], d[1]), min(d[2], d[3]));
                return d[0] < x ? x - 1 - d[0] : 0u;
            };
            const uint32_t mx0 = ~min(min(min(min(q[0], q[1]), min(q[2], q[3])), min(min(q[4], q[5]), min(q[6], q[7]))),
                                      min(min(min(q[8], q[9]), min(q[10], q[11])), min(min(q[12], q[13]), min(q[14], q[15]))));
            const uint32_t gm = min(__reduce_max_sync(0xffffffffu, lane < 16 ? mx0 : 0u), __reduce_max_sync(0xffffffffu, lane < 16 ? 0u : mx0));
            if (lane == 0) sts32(misc + 16 + 4 * a, gm);
            named_sync(1, 128);
            STAMP(42);
            if (b == 0 && tid == 0) st_relaxed_32(&p.sc->epoch, tag);
            const uint4 t0 = lds128(misc + 16);
            uint32_t tau = min(min(t0.x, t0.y), min(t0.z, t0.w));
            uint32_t mx = mx0, cnt = 0, bal;
            const uint32_t list = sb + OFF_XCH + 64 * a;
#pragma unroll 1
            while ((bal = __ballot_sync(0xffffffffu, mx >= tau)) != 0) {
                const uint32_t pos = cnt + __popc(bal & ((1u << lane) - 1u));
                cnt += __popc(bal);
                if (cnt > 16) break;
                if (mx >= tau) sts32(list + 4 * pos, mx);
                mx = below(mx);
            }
            if (cnt > 16) {
                mx = mx0;
#pragma unroll 1
                for (int j = 0; j < 8; j++) {
                    const uint32_t top = __reduce_max_sync(0xffffffffu, mx), nx = below(mx);
                    if (mx == top) { sts32(list + 4 * j, mx); sts32(list + 32 + 4 * j, 0); mx = nx; }
                }
            }
            named_sync(1, 128);
            STAMP(43);
            const uint2 k = lds64(sb + OFF_XCH + 8 * lane);
            uint32_t hi = max(k.x, k.y), lo = min(k.x, k.y);
            mbar_wait(bar0 + 8 * B_V, 0);
#pragma unroll
            for (int j = 0; j < 8; j++) {
                const uint32_t top = __reduce_max_sync(0xffffffffu, hi);
                const bool won = hi == top;
                hi = won ? lo : hi;
                lo = won ? 0u : lo;
                if (g == j) mine = top;
                if (a == (j >> 1)) row[j & 1] = top;
            }
        }
        STAMP(11);
        const int tok = 2047 - (int)(mine & 2047);
        const uint32_t xs = sb + OFF_XT + (h ^ 1) * 32768 + 16384;
        if (has_gu) {
            if (elect_one()) {
                mbar_expect_tx(abar, 2048);
#pragma unroll
                for (int j = 0; j < 2; j++) bulk_g2s(xs + (2 * a + j) * 1040, p.u + (size_t)(2047 - (row[j] & 2047)) * DM + 512 * h, 1024, abar);
            }
        }
        STAMP(44);
        const uint2 st = ld_relaxed_64(in->stat + (tok & ~15) + 2 * ((tok & 7) ^ ((tok >> 3) & 6)) + ((tok >> 3) & 1));
        if (a == 0 && t == 0) sts64(misc + 48 + 8 * g, mine, __float_as_uint(bf_hi(st.x) + bf_lo(st.y)));
        if (a == 0) STAMP(45);
        if (has_gu) {
            const uint32_t mean = __shfl_sync(0xffffffffu, st.x, 8 * a + 4 * (lane >> 4)), xr = xs + (2 * a + (lane >> 4)) * 1040 + 16 * (lane & 15);
            mbar_wait(abar, aph);
            aph ^= 1;
            STAMP(46);
            uint4 x[4];
#pragma unroll
            for (int j = 0; j < 4; j++) x[j] = lds128(xr + 256 * j);
#pragma unroll
            for (int j = 0; j < 4; j++) sts128(xr + 256 * j, bsub2_lo(x[j].x, mean), bsub2_lo(x[j].y, mean), bsub2_lo(x[j].z, mean), bsub2_lo(x[j].w, mean));
            if (elect_one()) mbar_expect_tx(abar, 512);
            named_sync(1, 128);
        }
        if (lane < (has_gu ? 2 : 4)) mbar_arrive_peer(mapa(bar0 + 8 * (lane & 2 ? B_XFREE : B_SFREE), lane & 1));
        if (has_gu) {
            STAMP(12);
            float gacc[8][4];
#pragma unroll
            for (int i = 0; i < 8; i++) { gacc[i][0] = gacc[i][1] = gacc[i][2] = gacc[i][3] = 0.f; }
            uint32_t* pubh = reinterpret_cast<uint32_t*>(&p.sc->x[0].h[b * 32 + 8 * a + (g ^ (2 * a))]) + t;
            uint32_t* cnt_h = &p.sc->x[t].n_h[32 * (b / 14)];
            uint32_t ko = sb + (m & 1) * 4096 + (r + ((m >> 1) << 3)) * 128 + ((r ^ (4 * h) ^ a) << 4), kp = ko ^ 64, xb = xs + r * 1040 + m * 16;
            uint32_t xch = sb + OFF_XCH + 16 * tid, tagm = t == 3 ? 1u : 0u;
            pin(pubh); pin(cnt_h); pin(ko); pin(kp); pin(xb); pin(xch); pin(tagm);
            const float r0 = lds32f(misc + 52 + 16 * t), r1 = lds32f(misc + 60 + 16 * t);
#pragma unroll
            for (int c = 0; c < 4; c++) {
                uint32_t af[20][4];
#pragma unroll
                for (int j = 0; j < 4; j++) ldsm4(af[16 + j], xb + 256 * c + 64 * j);
                if (c == 3) mbar_wait(bar0 + 8 * B_SFREE, 0);
#pragma unroll
                for (int j = 0; j < 4; j++) {
                    mbar_wait(bar0 + 8 * (B_FULL + 4 * (c % 3) + j), c / 3);
#pragma unroll
                    for (int i = 0; i < 4; i++) ldsm4t(af[8 * (i >> 1) + 2 * j + (i & 1)], ((i & 1) ? kp : ko) + slot_off(4 * (c % 3) + j) + (i >> 1) * 2048);
                }
                STAMP(36 + c);
                __syncwarp();
                if (c < 3 && lane < 4) mbar_arrive(bar0 + 8 * (B_FREE + 4 * c + lane));
                const bool more = __any_sync(0xffffffffu, (af[6][3] | af[7][3] | af[14][3] | af[15][3]) & p.zero);
#pragma unroll 1
                do {
#pragma unroll
                    for (int i = 0; i < 16; i++) mma_v(gacc[i & 7], af[i], af[16 + ((i >> 1) & 3)][2 * (i >> 3)], af[16 + ((i >> 1) & 3)][2 * (i >> 3) + 1]);
                } while (more);
                STAMP(52 + c);
            }
            STAMP(13);
            float own[4], oth[4];
#pragma unroll
            for (int j = 0; j < 4; j++) oth[j] = (gacc[1][j] + gacc[3][j]) + (gacc[5][j] + gacc[7][j]);
            st_async128(mapa(xch, h ^ 1), __float_as_uint(oth[0]), __float_as_uint(oth[1]), __float_as_uint(oth[2]), __float_as_uint(oth[3]), mapa(abar, h ^ 1));
            STAMP(56);
#pragma unroll
            for (int j = 0; j < 4; j++) own[j] = ((gacc[0][j] + gacc[2][j]) + (gacc[4][j] + gacc[6][j])) * ((j & 1) ? r1 : r0);
            mbar_wait(abar, aph);
            aph ^= 1;
            STAMP(57);
            const float4 o4 = lds128f(xch);
            const float g0 = bf_round(fmaf(o4.x, r0, own[0])), g1 = bf_round(fmaf(o4.y, r1, own[1]));
            const float h0 = bf_round(g0 * rcpf(1.f + ex2f(-1.4426950408889634f * g0))) * bf_round(fmaf(o4.z, r0, own[2]));
            const float h1 = bf_round(g1 * rcpf(1.f + ex2f(-1.4426950408889634f * g1))) * bf_round(fmaf(o4.w, r1, own[3]));
            uint32_t hw;
            asm volatile("movmatrix.sync.aligned.m8n8.trans.b16 %0, %1;" : "=r"(hw) : "r"(pack_bf16(h0, h1)));
            hw = (hw & ~tagm) | (tag & tagm);
#pragma unroll
            for (int j = 0; j < NREP; j++) st_relaxed_32(pubh + j * (sizeof(Exchange) / 4), hw);
            if (lane < NREP) red_add(cnt_h, 1);
            if (lane < 2) mbar_arrive_peer(mapa(bar0 + 8 * B_XFREE, lane));
            named_sync(1, 128);
            STAMP(14);
        }
        float dacc[4];
        const int tk = ((tid >> 1) & 6) | (tid & 1);
        uint32_t ro = 4 * tid, red = sb + tab_off(tk) + T_RED + 4 * ((tid >> 4) + 4 * (tid & 2));
        if (!has_gu) named_sync(1, 128);
        const float sg = bf_round(rcpf(1.f + ex2f(-1.4426950408889634f * __uint_as_float(unorder_key(lds32(misc + 48 + 8 * tk) >> 16) << 16))));
        pin(ro); pin(red);
        mbar_wait(bar0 + 8 * B_XFREE, 0);
        {
            uint32_t wo = (r + ((m >> 1) << 3)) * 32 + (((m & 1) ^ (r >> 2)) << 4), af[14][4];
            pin(wo);
            float d[7][4];
#pragma unroll
            for (int i = 0; i < 7; i++) { d[i][0] = d[i][1] = d[i][2] = d[i][3] = 0.f; }
            auto first_half = [&]() {
                mbar_wait(fbar + 32, has_gu);
#pragma unroll
                for (int j = 0; j < 14; j++) ldsm4t(af[j], slot1 + wo + j * 512);
            };
            auto fetch = [&]() {
                if (elect_one()) {
                    mbar_expect_tx(abar, 7168);
                    bulk_g2s(slot0, &in->h[(56 * h + 14 * a) * 32], 7168, abar);
                }
            };
            wait_count(&in->n_h[32 * (4 * h + a)], 56 * tag - FEW_H);
            STAMP(33);
            fetch();
            first_half();
            uint4 hq[14];
#pragma unroll 1
            for (uint32_t it = 0;; spin_guard(it)) {
                mbar_wait(abar, aph);
                aph ^= 1;
                uint32_t bad = 0;
#pragma unroll
                for (int j = 0; j < 14; j++) { hq[j] = lds128(slot0 + 512 * j + 128 * t + 16 * (g ^ (2 * t))); bad = or_xor(bad, hq[j].w, tag); }
                if (__all_sync(0xffffffffu, (bad & 1) == 0)) break;
                fetch();
            }
            STAMP(15);
#pragma unroll
            for (int s = 0; s < 2; s++) {
                if (s) {
                    mbar_wait(fbar + 64, has_gu);
#pragma unroll
                    for (int j = 0; j < 14; j++) ldsm4t(af[j], slot2 + wo + j * 512);
                }
                const bool more = __any_sync(0xffffffffu, after_all(af, p.zero));
#pragma unroll 1
                do {
#pragma unroll
                    for (int j = 0; j < 14; j++) {
                        const uint4 q = hq[7 * s + (j >> 1)];
                        mma_v(d[j % 7], af[j], (j & 1) ? q.z : q.x, (j & 1) ? q.w : q.y);
                    }
                } while (more);
            }
#pragma unroll
            for (int j = 0; j < 4; j++) dacc[j] = ((d[0][j] + d[1][j]) + (d[2][j] + d[3][j])) + ((d[4][j] + d[5][j]) + d[6][j]);
        }
        STAMP(16);
        {
            st_async128(mapa(sb + OFF_XCH + 16 * tid, h ^ 1), __float_as_uint(dacc[0]), __float_as_uint(dacc[1]), __float_as_uint(dacc[2]), __float_as_uint(dacc[3]),
                        mapa(bar0 + 8 * B_RED, h ^ 1));
            sts128f(slot0 + 7680 + lane * 16, dacc);
            __syncwarp();
            if (elect_one()) mbar_arrive(bar0 + 8 * B_RED);
            mbar_wait(bar0 + 8 * B_RED, 0);
            const uint32_t b0 = sb + OFF_RING + 7680 + ro, b1 = sb + OFF_XCH + ro;
            const float y = ((lds32f(b0) + lds32f(b0 + 8192)) + (lds32f(b0 + 16384) + lds32f(b0 + 24576))) +
                            ((lds32f(b1) + lds32f(b1 + 512)) + (lds32f(b1 + 1024) + lds32f(b1 + 1536)));
            sts32f(red, bf_round(y) * sg);
            __syncwarp();
            if (elect_one()) mbar_arrive(bar0 + 8 * B_UPD);
        }
        STAMP(17); GSTAMP(29);
    }
}

typedef CUresult (*EncodeFn)(CUtensorMap*, CUtensorMapDataType, cuuint32_t, void*, const cuuint64_t*, const cuuint64_t*,
                             const cuuint32_t*, const cuuint32_t*, CUtensorMapInterleave, CUtensorMapSwizzle,
                             CUtensorMapL2promotion, CUtensorMapFloatOOBfill);

void make_map(EncodeFn enc, CUtensorMap* m, const void* ptr, uint64_t cols, uint64_t rows, uint32_t bc, uint32_t br,
              CUtensorMapSwizzle sw, CUtensorMapL2promotion pr) {
    cuuint64_t dims[2] = {cols, rows};
    cuuint64_t str[1] = {cols * 2};
    cuuint32_t box[2] = {bc, br};
    cuuint32_t es[2] = {1, 1};
    enc(m, CU_TENSOR_MAP_DATA_TYPE_BFLOAT16, 2, const_cast<void*>(ptr), dims, str, box, es, CU_TENSOR_MAP_INTERLEAVE_NONE, sw, pr,
        CU_TENSOR_MAP_FLOAT_OOB_FILL_NONE);
}
void make_perm_map(EncodeFn enc, CUtensorMap* m, const void* ptr, CUtensorMapL2promotion pr) {
    cuuint64_t dims[5] = {DM, 2, 4, 4, FF / 32};
    cuuint64_t str[4] = {DM * 2, 8 * DM * 2, 2 * DM * 2, 32 * DM * 2};
    cuuint32_t box[5] = {16, 2, 4, 4, 7};
    cuuint32_t es[5] = {1, 1, 1, 1, 1};
    enc(m, CU_TENSOR_MAP_DATA_TYPE_BFLOAT16, 5, const_cast<void*>(ptr), dims, str, box, es, CU_TENSOR_MAP_INTERLEAVE_NONE,
        CU_TENSOR_MAP_SWIZZLE_32B, pr, CU_TENSOR_MAP_FLOAT_OOB_FILL_NONE);
}
void make_tile_map(EncodeFn enc, CUtensorMap* m, const void* ptr) {
    cuuint64_t dims[4] = {DM, 4, 16, SEQ / 64};
    cuuint64_t str[3] = {16 * DM * 2, DM * 2, 64 * DM * 2};
    cuuint32_t box[4] = {16, 4, 2, 8};
    cuuint32_t es[4] = {1, 1, 1, 1};
    enc(m, CU_TENSOR_MAP_DATA_TYPE_BFLOAT16, 4, const_cast<void*>(ptr), dims, str, box, es, CU_TENSOR_MAP_INTERLEAVE_NONE,
        CU_TENSOR_MAP_SWIZZLE_32B, CU_TENSOR_MAP_L2_PROMOTION_NONE, CU_TENSOR_MAP_FLOAT_OOB_FILL_NONE);
}

}

#define WD_PROMO CU_TENSOR_MAP_L2_PROMOTION_L2_64B
extern "C" void kernel_launch(void* const* d_in, const int* in_sizes, int n_in, void* d_out, int out_size) {
    (void)in_sizes; (void)n_in; (void)out_size;
    static EncodeFn enc = nullptr;
    static void* scratch = nullptr;
    if (!enc) {
        void* fn = nullptr;
        cudaDriverEntryPointQueryResult q;
        cudaGetDriverEntryPoint("cuTensorMapEncodeTiled", &fn, cudaEnableDefault, &q);
        enc = (EncodeFn)fn;
        cudaGetSymbolAddress(&scratch, g_scratch);
        cudaFuncSetAttribute(fused_kernel, cudaFuncAttributeMaxDynamicSharedMemorySize, SMEM_BYTES);
    }
    Maps maps;
    make_tile_map(enc, &maps.u, d_in[0]);
    make_tile_map(enc, &maps.out, d_out);
    make_map(enc, &maps.wg, d_in[9], FF, DM, 64, 32, CU_TENSOR_MAP_SWIZZLE_128B, CU_TENSOR_MAP_L2_PROMOTION_L2_128B);
    make_map(enc, &maps.wu, d_in[10], FF, DM, 64, 32, CU_TENSOR_MAP_SWIZZLE_128B, CU_TENSOR_MAP_L2_PROMOTION_L2_128B);
    make_perm_map(enc, &maps.wd, d_in[11], WD_PROMO);
    Ptrs p;
    p.sc = (Scratch*)scratch;
    p.u = (const __nv_bfloat16*)d_in[0];
    p.logA = (const __nv_bfloat16*)d_in[1];
    p.Aim = (const __nv_bfloat16*)d_in[2];
    p.Cre = (const __nv_bfloat16*)d_in[3];
    p.Cim = (const __nv_bfloat16*)d_in[4];
    p.ldt = (const __nv_bfloat16*)d_in[5];
    p.dsk = (const __nv_bfloat16*)d_in[6];
    p.wr = (const __nv_bfloat16*)d_in[8];
    p.out = (__nv_bfloat16*)d_out;
    p.zero = 0;
    fused_kernel<<<NCTA, NTHR, SMEM_BYTES, cudaStreamPerThread>>>(p, maps);
}
```

```cpp
#include <cuda_runtime.h>
#include <cuda_bf16.h>
#include <cuda_fp16.h>
#include <cuda.h>
#include <stdint.h>

namespace {

constexpr int SEQ = 2048, DM = 1024, NMODE = 128, FF = 3584;
constexpr int NCTA = 128, NTHR = 512;
constexpr int GU_CTAS = 112;
constexpr int NREP = 4;

constexpr int OFF_XT = 0;
constexpr int OFF_RING = 65536;
constexpr int OFF_PRIV = OFF_RING + 65536;
constexpr int OFF_VT = OFF_PRIV + 65536;
constexpr int VT_PAD = 32, VT_PLANE = VT_PAD + 2048, VT_PITCH = 2 * VT_PLANE, ROW_PITCH = 2064;
constexpr int OFF_BAR = OFF_VT + 8 * VT_PITCH;
constexpr int OFF_MISC = OFF_BAR + 384;
constexpr int OFF_XCH = OFF_MISC + 112;
constexpr int SMEM_BYTES = OFF_XCH + 2048;
constexpr int OFF_LN = OFF_RING + 7 * 8192;
constexpr int OFF_ST = OFF_RING + 6 * 8192;
static_assert(SMEM_BYTES <= 232448, "shared memory");

constexpr int B_ROW = 0, B_XT = 4, B_V = 5, B_LN = 6, B_SFREE = 7, B_RECV = 8, B_RED = 10, B_UPD = 11, B_ST = 12, B_XFREE = 16, B_OWN = 17, B_FREE = 20, B_FULL = 32, B_AUX = 44, NBAR = 48;

constexpr int T_DENSE = 60;
constexpr int T_PATCH = 2208;
constexpr int T_R2 = 2368;
constexpr int T_R3 = 3296;

constexpr int T_RED = 4032;
__device__ __forceinline__ bool slot_priv(int s) { return (uint32_t)(s - 6) < 4u; }
__device__ __forceinline__ uint32_t slot_off(int s) { return slot_priv(s) ? OFF_PRIV + 4096 + (s & 3) * 16384 : OFF_RING + (s < 6 ? s : s - 4) * 8192; }
__device__ __forceinline__ uint32_t tab_off(int w) { return OFF_PRIV + w * 8192 + (w & 1) * 4096; }

constexpr uint32_t SPIN_LIMIT = 1u << 20;
#define KG_UNROLL 4
constexpr int kKgUnroll = KG_UNROLL;
#define BB_UNROLL 2
constexpr int kBbUnroll = BB_UNROLL;
#define DENSE_UNROLL 1
constexpr int kDenseUnroll = DENSE_UNROLL;
#define ST_T0 2250
#define LN_PAUSE 0xf0
#define FEW_ST 8
#define FEW_H 8
#define PERM 2
#define PERM_OFF 60
#define STORE_AT 12
#define ST_LATE 16
#define ST_GAP 0
#define ST_PER 308
#define ST_PER2 335

struct Exchange {
    uint2 stat[SEQ];
    uint4 h[GU_CTAS * 32];
    uint32_t n_stat[4 * 32];
    uint32_t n_h[8 * 32];
};
struct Scratch {
    Exchange x[NREP];
    uint32_t epoch;
};
__device__ __align__(128) Scratch g_scratch;

struct Ptrs {
    const __nv_bfloat16 *logA, *Aim, *Cre, *Cim, *ldt, *u;
    const __nv_bfloat16 *dsk, *wr;
    Scratch* sc;
    __nv_bfloat16* out;
    uint32_t zero;
};
struct Maps {
    CUtensorMap u, out, wg, wu, wd;
};

#define STAMP(i) do { } while (0)
#define KSTAMP(i) do { } while (0)
#define GSTAMP(i) do { } while (0)

__device__ __forceinline__ uint32_t s_u32(const void* p) { return (uint32_t)__cvta_generic_to_shared(p); }
__device__ __forceinline__ void mbar_init(uint32_t b, uint32_t n) {
    asm volatile("mbarrier.init.shared::cta.b64 [%0], %1;" ::"r"(b), "r"(n) : "memory");
}
__device__ __forceinline__ void mbar_expect_tx(uint32_t b, uint32_t bytes) {
    asm volatile("mbarrier.arrive.expect_tx.shared::cta.b64 _, [%0], %1;" ::"r"(b), "r"(bytes) : "memory");
}
__device__ __forceinline__ void mbar_arrive(uint32_t b) {
    asm volatile("mbarrier.arrive.shared::cta.b64 _, [%0];" ::"r"(b) : "memory");
}
__device__ __forceinline__ void mbar_arrive_n(uint32_t b, uint32_t n) {
    asm volatile("mbarrier.arrive.shared::cta.b64 _, [%0], %1;" ::"r"(b), "r"(n) : "memory");
}
__device__ __forceinline__ void mbar_arrive_peer(uint32_t b_cluster) {
    asm volatile("mbarrier.arrive.relaxed.cluster.shared::cluster.b64 _, [%0];" ::"r"(b_cluster) : "memory");
}
__device__ __forceinline__ void mbar_wait(uint32_t b, uint32_t parity) {
    asm volatile("{\n\t.reg .pred p;\n\t.reg .u32 c;\n\tmov.u32 c, 0;\n"
                 "W:\n\tmbarrier.try_wait.parity.shared::cta.b64 p, [%0], %1;\n\t@p bra D;\n\t"
                 "add.u32 c, c, 1;\n\tsetp.lt.u32 p, c, 1048576;\n\t@p bra W;\n\ttrap;\nD:\n\t}"
                 ::"r"(b), "r"(parity) : "memory");
}
__device__ __forceinline__ bool mbar_test(uint32_t b, uint32_t parity) {
    uint32_t ok;
    asm volatile("{ .reg .pred p; mbarrier.test_wait.parity.shared::cta.b64 p, [%1], %2; selp.u32 %0, 1, 0, p; }" : "=r"(ok) : "r"(b), "r"(parity) : "memory");
    return __all_sync(0xffffffffu, ok != 0);
}
__device__ __forceinline__ bool elect_one() {
    uint32_t p;
    asm volatile("{ .reg .pred P; elect.sync _|P, 0xffffffff; selp.u32 %0, 1, 0, P; }" : "=r"(p));
    return p != 0;
}
__device__ __forceinline__ uint32_t mapa(uint32_t a, uint32_t rank) {
    uint32_t r;
    asm("mapa.shared::cluster.u32 %0, %1, %2;" : "=r"(r) : "r"(a), "r"(rank));
    return r;
}
__device__ __forceinline__ void cluster_arrive() { asm volatile("barrier.cluster.arrive.relaxed.aligned;" ::: "memory"); }
__device__ __forceinline__ void cluster_wait() { asm volatile("barrier.cluster.wait.acquire.aligned;" ::: "memory"); }
__device__ __forceinline__ void tma_load_2d(uint32_t dst, const CUtensorMap* m, int c0, int c1, uint32_t bar) {
    asm volatile("cp.async.bulk.tensor.2d.shared::cluster.global.mbarrier::complete_tx::bytes [%0], [%1, {%3, %4}], [%2];"
                 ::"r"(dst), "l"(m), "r"(bar), "r"(c0), "r"(c1) : "memory");
}
__device__ __forceinline__ void tma_load_perm(uint32_t dst, const CUtensorMap* m, int c0, int blk, uint32_t bar) {
    asm volatile("cp.async.bulk.tensor.5d.shared::cluster.global.mbarrier::complete_tx::bytes [%0], [%1, {%3, %4, %4, %4, %5}], [%2];"
                 ::"r"(dst), "l"(m), "r"(bar), "r"(c0), "r"(0), "r"(blk) : "memory");
}
__device__ __forceinline__ void tma_load_tile(uint32_t dst, const CUtensorMap* m, int c0, int c2, int c3, uint32_t bar) {
    asm volatile("cp.async.bulk.tensor.4d.shared::cluster.global.mbarrier::complete_tx::bytes.multicast::cluster [%0], [%1, {%3, %4, %5, %6}], [%2], %7;"
                 ::"r"(dst), "l"(m), "r"(bar), "r"(c0), "r"(0), "r"(c2), "r"(c3), "h"((uint16_t)3) : "memory");
}
__device__ __forceinline__ void tma_store_tile(const CUtensorMap* m, uint32_t src, int c0, int c2, int c3) {
    asm volatile("cp.async.bulk.tensor.4d.global.shared::cta.bulk_group [%0, {%2, %3, %4, %5}], [%1];"
                 ::"l"(m), "r"(src), "r"(c0), "r"(0), "r"(c2), "r"(c3) : "memory");
    asm volatile("cp.async.bulk.commit_group;" ::: "memory");
}
__device__ __forceinline__ void bulk_g2s(uint32_t dst, const void* src, uint32_t bytes, uint32_t bar) {
    asm volatile("cp.async.bulk.shared::cluster.global.mbarrier::complete_tx::bytes [%0], [%1], %2, [%3];"
                 ::"r"(dst), "l"(src), "r"(bytes), "r"(bar) : "memory");
}
__device__ __forceinline__ void cp_async16(uint32_t dst, const void* src) {
    asm volatile("cp.async.cg.shared.global [%0], [%1], 16;" ::"r"(dst), "l"(src) : "memory");
}
__device__ __forceinline__ void st_async128(uint32_t dst_cluster, uint32_t x, uint32_t y, uint32_t z, uint32_t w, uint32_t bar_cluster) {
    asm volatile("st.async.weak.shared::cluster.mbarrier::complete_tx::bytes.v4.b32 [%0], {%1,%2,%3,%4}, [%5];"
                 ::"r"(dst_cluster), "r"(x), "r"(y), "r"(z), "r"(w), "r"(bar_cluster) : "memory");
}
__device__ __forceinline__ void fence_async() { asm volatile("fence.proxy.async.shared::cta;" ::: "memory"); }
__device__ __forceinline__ void named_sync(int id, int n) { asm volatile("bar.sync %0, %1;" ::"r"(id), "r"(n) : "memory"); }

__device__ __forceinline__ void ldsm4(uint32_t* r, uint32_t a) {
    asm volatile("ldmatrix.sync.aligned.m8n8.x4.shared.b16 {%0,%1,%2,%3}, [%4];"
                 : "=r"(r[0]), "=r"(r[1]), "=r"(r[2]), "=r"(r[3]) : "r"(a));
}
__device__ __forceinline__ void ldsm4t(uint32_t* r, uint32_t a) {
    asm volatile("ldmatrix.sync.aligned.m8n8.x4.trans.shared.b16 {%0,%1,%2,%3}, [%4];"
                 : "=r"(r[0]), "=r"(r[1]), "=r"(r[2]), "=r"(r[3]) : "r"(a));
}
__device__ __forceinline__ void stsm4t(uint32_t a, uint32_t x, uint32_t y, uint32_t z, uint32_t w) {
    asm volatile("stmatrix.sync.aligned.m8n8.x4.trans.shared.b16 [%0], {%1,%2,%3,%4};"
                 ::"r"(a), "r"(x), "r"(y), "r"(z), "r"(w) : "memory");
}
__device__ __forceinline__ uint32_t lds32(uint32_t a) { uint32_t v; asm volatile("ld.shared.u32 %0, [%1];" : "=r"(v) : "r"(a)); return v; }
__device__ __forceinline__ float lds32f(uint32_t a) { float v; asm volatile("ld.shared.f32 %0, [%1];" : "=f"(v) : "r"(a)); return v; }
__device__ __forceinline__ uint2 lds64(uint32_t a) { uint2 v; asm volatile("ld.shared.v2.u32 {%0,%1}, [%2];" : "=r"(v.x), "=r"(v.y) : "r"(a)); return v; }
__device__ __forceinline__ uint4 lds128(uint32_t a) {
    uint4 v; asm volatile("ld.shared.v4.u32 {%0,%1,%2,%3}, [%4];" : "=r"(v.x), "=r"(v.y), "=r"(v.z), "=r"(v.w) : "r"(a)); return v;
}
__device__ __forceinline__ uint4 lds128v(uint32_t a) {
    uint4 v; asm volatile("ld.volatile.shared.v4.u32 {%0,%1,%2,%3}, [%4];" : "=r"(v.x), "=r"(v.y), "=r"(v.z), "=r"(v.w) : "r"(a)); return v;
}
__device__ __forceinline__ uint32_t or_xor(uint32_t a, uint32_t b, uint32_t c) {
    uint32_t r; asm("lop3.b32 %0, %1, %2, %3, 0xf6;" : "=r"(r) : "r"(a), "r"(b), "r"(c)); return r;
}
__device__ __forceinline__ float4 lds128f(uint32_t a) {
    float4 v; asm volatile("ld.shared.v4.f32 {%0,%1,%2,%3}, [%4];" : "=f"(v.x), "=f"(v.y), "=f"(v.z), "=f"(v.w) : "r"(a)); return v;
}
__device__ __forceinline__ void sts32(uint32_t a, uint32_t v) { asm volatile("st.shared.u32 [%0], %1;" ::"r"(a), "r"(v) : "memory"); }
__device__ __forceinline__ void sts32f(uint32_t a, float v) { asm volatile("st.shared.f32 [%0], %1;" ::"r"(a), "f"(v) : "memory"); }
__device__ __forceinline__ void sts64(uint32_t a, uint32_t x, uint32_t y) { asm volatile("st.shared.v2.u32 [%0], {%1,%2};" ::"r"(a), "r"(x), "r"(y) : "memory"); }
__device__ __forceinline__ void sts64f(uint32_t a, float x, float y) { asm volatile("st.shared.v2.f32 [%0], {%1,%2};" ::"r"(a), "f"(x), "f"(y) : "memory"); }
__device__ __forceinline__ void sts128(uint32_t a, uint32_t x, uint32_t y, uint32_t z, uint32_t w) {
    asm volatile("st.shared.v4.u32 [%0], {%1,%2,%3,%4};" ::"r"(a), "r"(x), "r"(y), "r"(z), "r"(w) : "memory");
}
__device__ __forceinline__ void sts128f(uint32_t a, const float* v) {
    asm volatile("st.shared.v4.f32 [%0], {%1,%2,%3,%4};" ::"r"(a), "f"(v[0]), "f"(v[1]), "f"(v[2]), "f"(v[3]) : "memory");
}
__device__ __forceinline__ uint4 ldg128(const void* p) {
    uint4 v; asm volatile("ld.global.nc.L1::no_allocate.v4.u32 {%0,%1,%2,%3}, [%4];" : "=r"(v.x), "=r"(v.y), "=r"(v.z), "=r"(v.w) : "l"(p)); return v;
}
__device__ __forceinline__ uint2 ldg64(const void* p) {
    uint2 v; asm volatile("ld.global.nc.L1::no_allocate.v2.u32 {%0,%1}, [%2];" : "=r"(v.x), "=r"(v.y) : "l"(p)); return v;
}
__device__ __forceinline__ uint32_t ldg32(const void* p) {
    uint32_t v; asm volatile("ld.global.nc.u32 %0, [%1];" : "=r"(v) : "l"(p)); return v;
}
__device__ __forceinline__ uint32_t ldg16(const void* p) {
    uint32_t v; asm volatile("ld.global.nc.u16 %0, [%1];" : "=r"(v) : "l"(p)); return v;
}
__device__ __forceinline__ uint4 ld_relaxed_128(const void* p) {
    uint4 v; asm volatile("ld.relaxed.gpu.global.v4.u32 {%0,%1,%2,%3}, [%4];" : "=r"(v.x), "=r"(v.y), "=r"(v.z), "=r"(v.w) : "l"(p) : "memory"); return v;
}
__device__ __forceinline__ void ld_relaxed_128_unless(uint4& q, const void* p, bool have) {
    asm volatile("{ .reg .pred p; setp.eq.u32 p, %5, 0; @p ld.relaxed.gpu.global.v4.u32 {%0,%1,%2,%3}, [%4]; }"
                 : "+r"(q.x), "+r"(q.y), "+r"(q.z), "+r"(q.w) : "l"(p), "r"((uint32_t)have) : "memory");
}
__device__ __forceinline__ uint2 ld_relaxed_64(const void* p) {
    uint2 v; asm volatile("ld.relaxed.gpu.global.v2.u32 {%0,%1}, [%2];" : "=r"(v.x), "=r"(v.y) : "l"(p) : "memory"); return v;
}
__device__ __forceinline__ uint32_t ld_relaxed_32(const void* p) {
    uint32_t v; asm volatile("ld.relaxed.gpu.global.u32 %0, [%1];" : "=r"(v) : "l"(p) : "memory"); return v;
}
__device__ __forceinline__ void st_relaxed_128(void* p, uint32_t x, uint32_t y, uint32_t z, uint32_t w) {
    asm volatile("st.relaxed.gpu.global.v4.u32 [%0], {%1,%2,%3,%4};" ::"l"(p), "r"(x), "r"(y), "r"(z), "r"(w) : "memory");
}
__device__ __forceinline__ void st_relaxed_64(void* p, uint32_t x, uint32_t y) {
    asm volatile("st.relaxed.gpu.global.v2.u32 [%0], {%1,%2};" ::"l"(p), "r"(x), "r"(y) : "memory");
}
__device__ __forceinline__ void st_relaxed_32(void* p, uint32_t v) {
    asm volatile("st.relaxed.gpu.global.u32 [%0], %1;" ::"l"(p), "r"(v) : "memory");
}
__device__ __forceinline__ void red_add(void* p, uint32_t v) { asm volatile("red.relaxed.gpu.global.add.u32 [%0], %1;" ::"l"(p), "r"(v) : "memory"); }
__device__ __forceinline__ uint32_t now_ns() { uint32_t t; asm volatile("mov.u32 %0, %%globaltimer_lo;" : "=r"(t) :: "memory"); return t; }
__device__ __forceinline__ void spin_guard(uint32_t& it) { if (++it > SPIN_LIMIT) __trap(); }
__device__ __forceinline__ void wait_count(const uint32_t* p, uint32_t target) {
#pragma unroll 1
    for (uint32_t it = 0; __any_sync(0xffffffffu, (int)(ld_relaxed_32(p) - target) < 0); spin_guard(it)) { }
}
__device__ __forceinline__ void mma_bf16(float* c, uint32_t a0, uint32_t a1, uint32_t a2, uint32_t a3, uint32_t b0, uint32_t b1) {
    asm("mma.sync.aligned.m16n8k16.row.col.f32.bf16.bf16.f32 {%0,%1,%2,%3}, {%4,%5,%6,%7}, {%8,%9}, {%0,%1,%2,%3};"
                 : "+f"(c[0]), "+f"(c[1]), "+f"(c[2]), "+f"(c[3]) : "r"(a0), "r"(a1), "r"(a2), "r"(a3), "r"(b0), "r"(b1));
}
__device__ __forceinline__ void mma_bf16_k8(float* c, uint32_t a0, uint32_t a1, uint32_t b0) {
    asm("mma.sync.aligned.m16n8k8.row.col.f32.bf16.bf16.f32 {%0,%1,%2,%3}, {%4,%5}, {%6}, {%0,%1,%2,%3};"
                 : "+f"(c[0]), "+f"(c[1]), "+f"(c[2]), "+f"(c[3]) : "r"(a0), "r"(a1), "r"(b0));
}
__device__ __forceinline__ void mma_v(float* c, const uint32_t* a, uint32_t b0, uint32_t b1) {
    asm volatile("mma.sync.aligned.m16n8k16.row.col.f32.bf16.bf16.f32 {%0,%1,%2,%3}, {%4,%5,%6,%7}, {%8,%9}, {%0,%1,%2,%3};"
                 : "+f"(c[0]), "+f"(c[1]), "+f"(c[2]), "+f"(c[3]) : "r"(a[0]), "r"(a[1]), "r"(a[2]), "r"(a[3]), "r"(b0), "r"(b1));
}
__device__ __forceinline__ void mma_bf16_z(float* c, uint32_t a0, uint32_t a1, uint32_t a2, uint32_t a3, uint32_t b0, uint32_t b1) {
    asm volatile("mma.sync.aligned.m16n8k16.row.col.f32.bf16.bf16.f32 {%0,%1,%2,%3}, {%4,%5,%6,%7}, {%8,%9}, {%10,%10,%10,%10};"
        : "=f"(c[0]), "=f"(c[1]), "=f"(c[2]), "=f"(c[3]) : "r"(a0), "r"(a1), "r"(a2), "r"(a3), "r"(b0), "r"(b1), "f"(0.f));
}
__device__ __forceinline__ void mma_f16(float* c, uint32_t a0, uint32_t a1, uint32_t a2, uint32_t a3, uint32_t b0, uint32_t b1) {
    asm("mma.sync.aligned.m16n8k16.row.col.f32.f16.f16.f32 {%0,%1,%2,%3}, {%4,%5,%6,%7}, {%8,%9}, {%0,%1,%2,%3};"
                 : "+f"(c[0]), "+f"(c[1]), "+f"(c[2]), "+f"(c[3]) : "r"(a0), "r"(a1), "r"(a2), "r"(a3), "r"(b0), "r"(b1));
}
__device__ __forceinline__ uint32_t pack_bf16(float lo, float hi) {
    uint32_t r; asm("cvt.rn.bf16x2.f32 %0, %1, %2;" : "=r"(r) : "f"(hi), "f"(lo)); return r;
}
__device__ __forceinline__ uint32_t pack_v(float lo, float hi) {
    uint32_t r; asm volatile("cvt.rn.bf16x2.f32 %0, %1, %2;" : "=r"(r) : "f"(hi), "f"(lo)); return r;
}
__device__ __forceinline__ uint32_t pack_w(float lo, float hi) {
    uint32_t r; asm volatile("cvt.rn.satfinite.bf16x2.f32 %0, %1, %2;" : "=r"(r) : "f"(hi), "f"(lo)); return r;
}
template <int N> __device__ __forceinline__ uint32_t after_all(const uint32_t (&f)[N][4], uint32_t zero) {
    uint32_t d[3] = {0, 0, 0};
#pragma unroll
    for (int i = 0; i < N; i++) d[i % 3] |= f[i][3];
    return (d[0] | d[1] | d[2]) & zero;
}
__device__ __forceinline__ void pin(uint32_t& x) { asm volatile("" : "+r"(x)); }
template <class T> __device__ __forceinline__ void pin(T*& x) { asm volatile("" : "+l"(x)); }
__device__ __forceinline__ uint32_t pack_f16(float lo, float hi) {
    uint32_t r; asm("cvt.rn.f16x2.f32 %0, %1, %2;" : "=r"(r) : "f"(hi), "f"(lo)); return r;
}
__device__ __forceinline__ float bf_lo(uint32_t v) { return __uint_as_float(v << 16); }
__device__ __forceinline__ float bf_hi(uint32_t v) { return __uint_as_float(v & 0xffff0000u); }
__device__ __forceinline__ float bf_round(float x) { return __uint_as_float(pack_bf16(0.f, x)); }
__device__ __forceinline__ uint32_t badd2(uint32_t a, uint32_t b) { uint32_t r; asm("add.rn.bf16x2 %0, %1, %2;" : "=r"(r) : "r"(a), "r"(b)); return r; }
__device__ __forceinline__ uint32_t bsub2_lo(uint32_t a, uint32_t b) {
    uint32_t r; asm("{ .reg .b16 m, h; .reg .b32 m2; mov.b32 {m, h}, %2; mov.b32 m2, {m, m}; sub.rn.bf16x2 %0, %1, m2; }" : "=r"(r) : "r"(a), "r"(b)); return r;
}
__device__ __forceinline__ uint32_t bmax2(uint32_t a, uint32_t b) { uint32_t r; asm("max.bf16x2 %0, %1, %2;" : "=r"(r) : "r"(a), "r"(b)); return r; }
__device__ __forceinline__ uint32_t normalize2(uint32_t x, uint32_t s0, uint32_t s1) {
    uint32_t r;
    asm("{ .reg .b16 m, h, l, k; .reg .b32 m2, h2, l2, d, t;\n\t"
        "mov.b32 {m, h}, %2; mov.b32 {l, k}, %3; mov.b32 m2, {m, m}; mov.b32 h2, {h, h}; mov.b32 l2, {l, l};\n\t"
        "sub.rn.bf16x2 d, %1, m2; mul.rn.bf16x2 t, d, l2; fma.rn.bf16x2 %0, d, h2, t; }" : "=r"(r) : "r"(x), "r"(s0), "r"(s1));
    return r;
}
__device__ __forceinline__ float rcpf(float x) { float r; asm("rcp.approx.ftz.f32 %0, %1;" : "=f"(r) : "f"(x)); return r; }
__device__ __forceinline__ float sqrtaf(float x) { float r; asm("sqrt.approx.ftz.f32 %0, %1;" : "=f"(r) : "f"(x)); return r; }
__device__ __forceinline__ float ex2f(float x) { float r; asm("ex2.approx.ftz.f32 %0, %1;" : "=f"(r) : "f"(x)); return r; }

__device__ __forceinline__ int tok_off(int t) { return ((t >> 3) & 1) * VT_PLANE + (t >> 4) * 16 + (t & 7) * 2; }

__device__ __forceinline__ uint32_t order_key(uint32_t b16) { return b16 ^ ((b16 & 0x8000u) ? 0xffffu : 0x8000u); }
__device__ __forceinline__ uint32_t unorder_key(uint32_t k16) { return k16 ^ ((k16 & 0x8000u) ? 0x8000u : 0xffffu); }

struct cplx { float r, i; };
struct hc { uint32_t r, i; };
template <bool CONJ> __device__ __forceinline__ cplx csq(cplx a) {
    float im;
    asm("{ .reg .f32 t; mul.ftz.f32 t, %1, %2; mul.ftz.f32 %0, t, 0f40000000; }" : "=f"(im) : "f"(CONJ ? -a.r : a.r), "f"(a.i));
    return {fmaf(a.r, a.r, -(a.i * a.i)), im};
}
__device__ __forceinline__ cplx cexpp(float a2, float ai) {
    float m = ex2f(a2), s, c;
    __sincosf(ai, &s, &c);
    return {m * c, m * s};
}
__device__ __forceinline__ __half2 as_h2(uint32_t x) { return *reinterpret_cast<__half2*>(&x); }
__device__ __forceinline__ uint32_t as_u(__half2 x) { return *reinterpret_cast<uint32_t*>(&x); }
__device__ __forceinline__ hc hmul(hc a, hc b) {
    return {as_u(__hfma2(as_h2(a.r), as_h2(b.r), __hneg2(__hmul2(as_h2(a.i), as_h2(b.i))))),
            as_u(__hfma2(as_h2(a.r), as_h2(b.i), __hmul2(as_h2(a.i), as_h2(b.r))))};
}
__device__ __forceinline__ hc hpack(cplx a, cplx b) { return {pack_f16(a.r, b.r), pack_f16(a.i, b.i)}; }
__device__ __forceinline__ void sts16(uint32_t a, uint32_t v) { asm volatile("st.shared.u16 [%0], %1;" ::"r"(a), "r"(v) : "memory"); }

struct KgenAddr {
    uint32_t l, h, m2, m3, m4, z, w, wz;
    __device__ __forceinline__ KgenAddr(uint32_t scr, int lane) {
        const int g = lane >> 2, t = lane & 3;
        const uint32_t rec = scr + t * 480;
        l = rec + 16 * g; h = rec + 128 + 8 * g; m2 = rec + 192 + 8 * (g & 1); m3 = rec + 208 + 4 * (g & 2); m4 = rec + 224 + 2 * (g & 4);
        z = scr + 7680 + 16 * t; w = scr + 240 * lane; wz = scr + 7680 + 8 * lane;
        pin(l); pin(h); pin(m2); pin(m3); pin(m4); pin(z); pin(w); pin(wz);
    }
    __device__ __forceinline__ uint32_t any() const { return (l | h | m2) | (m3 | m4 | z) | (w | wz); }
};
template <class Hook, class Hook2>
__device__ __forceinline__ void kgen(const KgenAddr& ad, uint32_t tab, int lane, uint2 la, uint2 aim, uint2 cre, uint2 cim, float dt, float skip, int dch, Hook main_done, Hook2 half_done) {
    const int g = lane >> 2, t = lane & 3;
    const float dt2 = 2.f * dt;
    const uint32_t am = bmax2(bmax2(cre.x & 0x7fff7fffu, cre.y & 0x7fff7fffu), bmax2(cim.x & 0x7fff7fffu, cim.y & 0x7fff7fffu));
    const float mx = dt2 * fmaxf(bf_lo(am), bf_hi(am));
    const uint32_t eb = min(max(__reduce_max_sync(0xffffffffu, __float_as_uint(mx)) >> 23, 1u), 252u);
    const float cscale = dt2 * __uint_as_float((253u - eb) << 23);
    const float scale_inv = __uint_as_float((eb + 1u) << 23);
    float k0 = (bf_lo(cre.x) + bf_hi(cre.x)) + (bf_lo(cre.y) + bf_hi(cre.y));
#pragma unroll
    for (int o = 16; o; o >>= 1) k0 += __shfl_xor_sync(0xffffffffu, k0, o);
    const float ndt = -1.4426950408889634f * dt;
    STAMP(40); KSTAMP(0);

    float acc[5][4];
#pragma unroll
    for (int i = 0; i < 5; i++) { acc[i][0] = acc[i][1] = acc[i][2] = acc[i][3] = 0.f; }

#pragma unroll kBbUnroll
    for (int bb = 0; bb < 2; bb++) {
        cplx z[2][11], cz[2];
#pragma unroll
        for (int e = 0; e < 2; e++) {
            const float lg = e ? bf_hi(la.x) : bf_lo(la.x), ai = (e ? bf_hi(aim.x) : bf_lo(aim.x)) * dt;
            const float cr = (e ? bf_hi(cre.x) : bf_lo(cre.x)) * cscale, ci = (e ? bf_hi(cim.x) : bf_lo(cim.x)) * cscale;
            const float a2 = bf_round(ex2f(lg * 1.4426950408889634f)) * ndt;
            z[e][0] = cexpp(a2, ai);
            z[e][5] = cexpp(a2 * 32.f, ai * -32.f);
#pragma unroll
            for (int i = 1; i < 11; i++) if (i != 5) z[e][i] = (i == 3 || i == 7) ? csq<true>(z[e][i - 1]) : csq<false>(z[e][i - 1]);
            cz[e] = {fmaf(cr, z[e][0].r, -(ci * z[e][0].i)), fmaf(cr, z[e][0].i, ci * z[e][0].r)};
        }
        la.x = la.y; aim.x = aim.y; cre.x = cre.y; cim.x = cim.y;
        const hc z1 = hpack(z[0][0], z[1][0]), z2 = hpack(z[0][1], z[1][1]), z4 = hpack(z[0][2], z[1][2]);
        hc L[8], H[8];
        L[1] = hpack(z[0][3], z[1][3]); L[2] = hpack(z[0][4], z[1][4]); L[4] = hpack(z[0][5], z[1][5]);
        const hc y64 = hpack(z[0][6], z[1][6]), z128 = hpack(z[0][7], z[1][7]), z256 = hpack(z[0][8], z[1][8]);
        const hc z512 = hpack(z[0][9], z[1][9]), z1024 = hpack(z[0][10], z[1][10]);
        H[0] = hpack(cz[0], cz[1]);
        H[1] = hmul(H[0], z1); H[2] = hmul(H[0], z2); H[3] = hmul(H[1], z2);
        L[3] = hmul(L[1], L[2]);
#pragma unroll
        for (int i = 0; i < 4; i++) { H[4 + i] = hmul(H[i], z4); if (i) L[4 + i] = hmul(L[i], L[4]); }
        __syncwarp();
        sts128(ad.w, 0x3c003c00u, y64.r, 0u, y64.i);
#pragma unroll
        for (int i = 1; i < 8; i++) { const hc q = hmul(L[i], y64); sts128(ad.w + 16 * i, L[i].r, q.r, L[i].i, q.i); }
#pragma unroll
        for (int i = 0; i < 4; i++) sts128(ad.w + 128 + 16 * i, H[2 * i].r, H[2 * i].i, H[2 * i + 1].r, H[2 * i + 1].i);
        {
            const hc a = hmul(z256, z1), b = hmul(z256, z128), c = hmul(z256, z2), d = hmul(z512, z4);
            sts128(ad.w + 192, a.r, a.i, b.r, b.i);
            sts128(ad.w + 208, c.r, c.i, z512.r, z512.i);
            sts128(ad.w + 224, d.r, d.i, z1024.r, z1024.i);
            sts64(ad.wz, z128.r, z128.i);
        }
        __syncwarp();
        KSTAMP(1 + 2 * bb);
#pragma unroll kKgUnroll
        for (int k2 = 0; k2 < 4; k2++) {
#pragma unroll
            for (uint32_t s = 0; s < 2; s++) {
                const uint32_t o = k2 * 1920 + s * 240;
                const uint4 l = lds128(ad.l + o);
                const uint2 h0 = lds64(ad.h + o), m2 = lds64(ad.m2 + o), m3 = lds64(ad.m3 + o), m4 = lds64(ad.m4 + o), mz = lds64(ad.z + k2 * 64 + s * 8);
                const hc H0 = {h0.x, h0.y};
                const hc H1 = hmul(H0, {mz.x, mz.y}), H2 = hmul(H0, {m2.x, m2.y}), H3 = hmul(H2, {m3.x, m3.y}), H4 = hmul(H3, {m4.x, m4.y});
                mma_f16(acc[0], l.x, l.y, l.z, l.w, H0.r, H0.i);
                mma_f16(acc[1], l.x, l.y, l.z, l.w, H1.r, H1.i);
                mma_f16(acc[2], l.x, l.y, l.z, l.w, H2.r, H2.i);
                mma_f16(acc[3], l.x, l.y, l.z, l.w, H3.r, H3.i);
                mma_f16(acc[4], l.x, l.y, l.z, l.w, H4.r, H4.i);
            }
        }
        KSTAMP(2 + 2 * bb);
        if (bb == 0) half_done();
    }
    __syncwarp();
    main_done();
    KSTAMP(5);
#pragma unroll
    for (int i = 0; i < 4; i++) sts128(tab + 2048 + 512 * i + 16 * lane, 0, 0, 0, 0);
    if (lane < 15) sts32(tab + 4 * lane, 0);
    __syncwarp();
    const uint32_t d0 = tab + T_DENSE + 4 + 8 * lane, src = (lane + 31) & 31;
    const uint32_t p0 = pack_bf16(fmaf(k0, dt2, skip), 0.f);
    uint32_t prev = p0;
#pragma unroll
    for (int i = 0; i < 4; i++) {
        const uint32_t pk = pack_bf16(acc[i >> 1][2 * (i & 1) + 1] * scale_inv, acc[i >> 1][2 * (i & 1)] * scale_inv);
        sts64(d0 + 256 * i, __byte_perm(pk, __shfl_sync(0xffffffffu, lane == 31 ? prev : pk, src), 0x5432), pk);
        prev = pk;
    }
    const uint32_t w0 = pack_bf16(acc[2][0] * scale_inv, acc[2][1] * scale_inv), w1 = pack_bf16(acc[2][2] * scale_inv, acc[2][3] * scale_inv);
    const uint32_t sa = (lane & 1) ? 0x5410u : 0x5454u, sb2 = (lane & 1) ? 0x1010u : 0x5410u;
#pragma unroll
    for (int hf = 0; hf < 2; hf++) {
        const uint32_t w = hf ? w1 : w0;
        const uint32_t pv = __shfl_sync(0xffffffffu, lane != 31 ? w : hf ? w0 : __byte_perm(prev, w1, 0x5410), src);
        sts64(d0 + 1024 + 256 * hf, __byte_perm(w, pv, sa), __byte_perm(w, pv, sb2));
        sts64(d0 + 1536 + 256 * hf, __byte_perm(w, pv, sa + 0x2222u), __byte_perm(w, pv, sb2 + 0x2222u));
    }
    const uint32_t d3 = tab + T_R2 + 160 + 320 * (t & 1) + 16 * (g >> 1) + 8 * (g & 1) + 4 * (t >> 1), d3n = d3 + (g >= 6 ? 32 : 0);
    const uint32_t d4 = tab + T_R3 + 80 + 160 * t + 4 * g, d4n = d4 + (g >= 6 ? 16 : 0);
    uint32_t p3;
#pragma unroll
    for (int hf = 0; hf < 2; hf++)
#pragma unroll
        for (int e = 0; e < 2; e++) {
            const float v3 = acc[3][2 * hf + e] * scale_inv;
            const uint32_t p4 = pack_bf16(acc[4][2 * hf + e] * scale_inv, 0.f);
            p3 = pack_bf16(v3, v3);
            sts16(d3 + 64 * hf + 160 * e, p3);
            sts16((hf ? d3n : d3) + 64 * hf + 160 * e + 18, p3);
            sts16(d4 + 32 * hf + 80 * e, p4);
            sts16((hf ? d4n : d4) + 32 * hf + 80 * e + 10, p4);
        }
    if (lane == 31) {
        const uint32_t k512 = __byte_perm(w1, 0, 0x3232);
        sts32(tab + T_DENSE, p0);
        sts64(tab + T_DENSE + 4 * 513, k512, k512); sts16(tab + T_DENSE + 4 * 515 + 2, k512);
        sts16(tab + T_PATCH + 4 * 17, p3); sts32(tab + T_PATCH + 4 * 18, p3); sts16(tab + T_PATCH + 4 * 19 + 2, p3);
    }
    __syncwarp();
}

__device__ __forceinline__ void load_toep(uint32_t* a, uint32_t p, uint32_t pz) {
    a[0] = lds32(p); a[1] = lds32(p + 32); a[2] = lds32(pz - 32); a[3] = lds32(pz);
}
#define YIELDS 2
#define YIELD_AT 2
#define DENSE_BLK 4
__device__ __forceinline__ void dense_step(float (&acc)[16][4], uint32_t (&R)[8][4], const uint32_t (&A)[4][4], uint32_t (&An)[4][4],
                                           uint32_t va, uint32_t vmin, uint32_t pn, uint32_t pz, uint32_t zero, int bit, uint32_t& junk) {
#pragma unroll
    for (int i0 = 0; i0 < 8; i0 += DENSE_BLK) {
#pragma unroll 1
        do {
#pragma unroll
            for (int i = i0; i < i0 + DENSE_BLK; i++) {
                const int ip = (i - DENSE_BLK) & 7;
                ldsm4(R[ip], ip == 0 ? max(va - 16, vmin) : va + ip * 128 - (i0 ? 16 : 0));
                if ((i & 1) == 0) load_toep(An[i >> 1], pn + (i >> 1) * 512, pz + (i >> 1) * 512);
#pragma unroll
                for (int ka = 0; ka < 4; ka++) {
                    mma_v(acc[i + ka], A[ka], R[i][0], R[i][1]);
                    if (i + 8 + ka < 16) mma_v(acc[i + 8 + ka], A[ka], R[i][2], R[i][3]);
                }
                if ((YIELDS >> (i - i0)) & 1) asm volatile("xor.b32 %0, %0, %1;" : "+r"(junk) : "r"(__float_as_uint(acc[i + YIELD_AT][0])));
            }
        } while (zero & (1u << (bit + i0)));
    }
}
struct DenseTaps {
    uint32_t A[4][4], E[4], F[4], G[4];
    __device__ __forceinline__ DenseTaps(uint32_t pb, uint32_t pz) {
        constexpr int PP = T_PATCH - T_DENSE + 56;
        load_toep(E, pb + 2048, pz + 2048);
        load_toep(F, pb + PP, pz + PP);
        G[0] = lds32(pz + 2048 + 32); G[1] = lds32(pb + 2048 + 64); G[2] = lds32(pz + PP + 32); G[3] = lds32(pb + PP + 64);
    }
};
__device__ __forceinline__ uint32_t dense_phase(float (&acc)[16][4], uint32_t vmin, uint32_t va, uint32_t vo, uint32_t pb, DenseTaps& tp, uint32_t zero) {
    uint32_t R[8][4], A1[4][4], junk = 0;
    uint32_t pz = pb + zero;
    {
        uint32_t H[4][4];
#pragma unroll
        for (int i = 0; i < 4; i++) ldsm4(H[i], vo + i * 256);
#pragma unroll
        for (int i = 0; i < 8; i++) ldsm4(R[i], va + i * 128);
#pragma unroll
        for (int i = 0; i < 4; i++) load_toep(tp.A[i], pb + 512 * i, pz + 512 * i);
#pragma unroll
        for (int i = 0; i < 4; i++) mma_bf16_k8(acc[i + 4], tp.G[0], tp.G[1], H[i >> 1][2 * (i & 1) + 1]);
#pragma unroll
        for (int i = 0; i < 8; i++) mma_v(acc[i + 8], tp.G, H[i >> 1][2 * (i & 1)], H[i >> 1][2 * (i & 1) + 1]);
#pragma unroll
        for (int i = 0; i < 12; i++) mma_v(acc[i + 4], tp.E, R[i & 7][2 * (i >> 3)], R[i & 7][2 * (i >> 3) + 1]);
#pragma unroll
        for (int i = 0; i < 8; i++) mma_v(acc[i + 8], tp.F, R[i][0], R[i][1]);
    }
#pragma unroll 1
    for (int rho = 0; rho < 8; rho += 2) {
        dense_step(acc, R, tp.A, A1, va, vmin, pb + 64, pz + 64, zero, 0, junk);
        dense_step(acc, R, A1, tp.A, va - 16, vmin, pb + 128, pz + 128, zero, 8, junk);
        pb += 128; pz += 128; va -= 32;
    }
    return junk & zero;
}
__device__ __forceinline__ uint32_t ones2(int c, int lo, int hi) {
    return (((uint32_t)(c - lo) <= (uint32_t)(hi - lo)) ? 0x3f80u : 0u) | (((uint32_t)(c + 1 - lo) <= (uint32_t)(hi - lo)) ? 0x3f800000u : 0u);
}
struct Boxes {
    uint32_t q[4], ha[2];
    __device__ __forceinline__ Boxes(uint32_t vrow, int lane, int O, int L1, int H1, int L2, int H2) {
        const int g = lane >> 2, t = lane & 3, d = 2 * t - g;
        q[0] = ones2(d, L1, H1); q[1] = ones2(d, L2, H2); q[2] = ones2(d + 8, L1, H1); q[3] = ones2(d + 8, L2, H2);
#pragma unroll
        for (int i = 0; i < 2; i++) { ha[i] = vrow + 16 * g + tok_off(O + 8 * i + 2 * t); pin(ha[i]); pin(q[i]); pin(q[2 + i]); }
    }
    __device__ __forceinline__ uint32_t any() const { return (q[0] | q[1] | q[2]) | (q[3] | ha[0] | ha[1]); }
    __device__ __forceinline__ void load(int j, uint32_t* v, uint32_t zero) const {
        const uint32_t o = j * 128;
        v[0] = lds32(ha[0] + o); v[1] = lds32(ha[1] + zero + o); v[2] = lds32(ha[1] + o);
        v[3] = lds32(ha[0] + zero + o + 16); v[4] = lds32(ha[0] + o + 16); v[5] = lds32(ha[1] + o + 16);
    }
    __device__ __forceinline__ void sums(const uint32_t* v, float* Z, float* X, float* Y) const {
        mma_bf16_z(Z, q[0], q[1], q[2], q[3], v[0], v[1]);
        mma_bf16_z(X, q[0], q[1], q[2], q[3], v[2], v[3]);
        mma_bf16_z(Y, q[0], q[1], q[2], q[3], v[4], v[5]);
    }
};
template <class After>
__device__ __forceinline__ void tail_phase(float (&acc)[16][4], const Boxes& b2, const Boxes& b3, uint32_t tp2, uint32_t tp3, uint32_t zero, After after) {
    uint2 tp[10];
    uint32_t v[6], a0[4], a1[4];
    float Z[4], X[4], Y[4];
    b2.load(0, v, zero);
#pragma unroll
    for (int i = 0; i < 5; i++) { const uint4 c = lds128(tp2 + 160 * i); tp[i] = make_uint2(c.x, c.y); tp[5 + i] = make_uint2(c.z, c.w); }
#pragma unroll
    for (int j = -1; j < 20; j++) {
        if (j < 19) {
            (j < 11 ? b2 : b3).sums(v, Z, X, Y);
            if (j < 10) b2.load(j + 2, v, zero); else if (j < 18) b3.load(j - 10, v, zero);
        }
        if (j >= 0 && j < 12) {
#pragma unroll
            for (int b = 0; b < 5; b++) if (j + 4 + b < 16) mma_v(acc[j + 4 + b], a1, tp[5 + b].x, tp[5 + b].y);
        }
        if (j < 11) { a1[0] = pack_v(Z[0], Z[1]); a1[1] = pack_w(X[0], X[1]); a1[2] = pack_v(Z[2], Z[3]); a1[3] = pack_w(X[2], X[3]); }
        if (j >= 0 && j < 12) {
#pragma unroll
            for (int b = 0; b < 5; b++) if (j + 4 + b < 16) mma_v(acc[j + 4 + b], a0, tp[b].x, tp[b].y);
            if (j >= 7 && j < 11) { tp[11 - j] = lds64(tp3 + 80 * (10 - j)); tp[16 - j] = lds64(tp3 + 80 * (14 - j)); }
        } else if (j >= 12) {
#pragma unroll
            for (int b = 0; b < 8; b++) if (j - 4 + b < 16) mma_v(acc[j - 4 + b], a0, tp[b < 4 ? b + 1 : b + 2].x, tp[b < 4 ? b + 1 : b + 2].y);
        }
        if (j < 11) { a0[0] = pack_v(X[0], X[1]); a0[1] = pack_v(Y[0], Y[1]); a0[2] = pack_v(X[2], X[3]); a0[3] = pack_v(Y[2], Y[3]); }
        else if (j < 19) { a0[0] = pack_v(X[0], X[1]); a0[1] = pack_v(Y[0], Y[1]); a0[2] = pack_v(Z[2], Z[3]); a0[3] = pack_v(X[2], X[3]); }
        after(j);
    }
}
template <int G>
__device__ __forceinline__ void emit(const float (&acc)[16][4], int h, uint32_t own, uint32_t peer, uint32_t bar, uint32_t bar_peer) {
#pragma unroll
    for (int o = 0; o < 2; o++)
#pragma unroll
        for (int hf = 0; hf < 2; hf++) {
            const int n = 8 * G + 4 * o;
            asm volatile("{ .reg .pred p; setp.eq.u32 p, %7, %8;\n\t@p st.shared.v4.u32 [%0], {%1,%2,%3,%4};\n\t"
                         "@!p st.async.weak.shared::cluster.mbarrier::complete_tx::bytes.v4.b32 [%5], {%1,%2,%3,%4}, [%6]; }"
                         ::"r"(own + G * 16384 + hf * 512), "r"(pack_bf16(acc[n][2 * hf], acc[n][2 * hf + 1])), "r"(pack_bf16(acc[n + 1][2 * hf], acc[n + 1][2 * hf + 1])),
                         "r"(pack_bf16(acc[n + 2][2 * hf], acc[n + 2][2 * hf + 1])), "r"(pack_bf16(acc[n + 3][2 * hf], acc[n + 3][2 * hf + 1])),
                         "r"(peer + G * 16384 + hf * 512), "r"(bar_peer + 8 * G), "r"(h), "r"(o) : "memory");
        }
    __syncwarp();
    if (elect_one()) mbar_arrive(bar);
}
__device__ __forceinline__ uint32_t finish_src(uint32_t sb, int h, int w, int lane) {
    const int m = lane >> 3, r = lane & 7;
    return sb + OFF_XT + (h ^ 1) * 32768 + (2 * m + (r & 1)) * 1024 + (w >> 2) * 512 + (((8 * (w & 3) + (r & 4) + ((r >> 1) & 1)) ^ ((r & 1) << 1)) << 4);
}
__device__ __forceinline__ uint32_t finish_dst(uint32_t sb, int h, int w, int lane) {
    const int g = lane >> 2, t = lane & 3;
    return sb + OFF_XT + h * 32768 + w * 2048 + (g >> 1) * 512 + (t >> 1) * 144 + (2 * (t & 1) + (g & 1)) * 32;
}
__device__ __forceinline__ uint32_t tile_addr(uint32_t sb, int tok, int t) {
    return sb + OFF_XT + (tok & 512) * 64 + (tok >> 10) * 16384 + (tok & 14) * 1024 + (tok & 448) * 4 + (tok & 1) * 128 + (tok & 48) * 2 + (((t >> 1) ^ (tok & 1)) << 4) + (t & 1) * 8;
}
__device__ __forceinline__ uint2 add_update(uint2 o, uint32_t upd) {
    const float4 u = lds128f(upd);
    return make_uint2(badd2(o.x, pack_bf16(u.x, u.y)), badd2(o.y, pack_bf16(u.z, u.w)));
}
__device__ __forceinline__ void finish_half(uint32_t src, uint32_t xa, const uint4 (&x)[2]) {
    uint32_t s[2][4];
#pragma unroll
    for (int i = 0; i < 2; i++) ldsm4t(s[i], src ^ (i << 5));
#pragma unroll
    for (int i = 0; i < 2; i++) sts128(xa + i * 256, badd2(x[i].x, s[i][0]), badd2(x[i].y, s[i][1]), badd2(x[i].z, s[i][2]), badd2(x[i].w, s[i][3]));
}

__device__ __noinline__ float centred_var(uint32_t rows, float mu, int lane) {
    float var = 0.f;
#pragma unroll 1
    for (int rr = 0; rr < 16; rr++) {
        const float c0 = __shfl_sync(0xffffffffu, mu, rr);
        float c = 0.f;
#pragma unroll 1
        for (int k = 0; k < 16; k++) {
            const uint32_t q = lds32(rows + rr * ROW_PITCH + k * 128 + lane * 4);
            const float d0 = bf_lo(q) - c0, d1 = bf_hi(q) - c0;
            c = fmaf(d0, d0, fmaf(d1, d1, c));
        }
#pragma unroll 1
        for (int o = 16; o; o >>= 1) c += __shfl_xor_sync(0xffffffffu, c, o);
        if ((lane & 15) == rr) var = c * (1.f / DM);
    }
    return var;
}
__device__ __noinline__ float centred_score(uint32_t rows, uint32_t wbuf, uint32_t s0, uint32_t s1, int lane) {
    float sc = 0.f;
#pragma unroll 1
    for (int rr = 0; rr < 16; rr++) {
        const uint32_t t0 = __shfl_sync(0xffffffffu, s0, rr), t1 = __shfl_sync(0xffffffffu, s1, rr);
        float c = 0.f;
#pragma unroll 1
        for (int k = 0; k < 16; k++) {
            const uint32_t xn = normalize2(lds32(rows + rr * ROW_PITCH + k * 128 + lane * 4), t0, t1);
            const uint32_t wq = lds32(wbuf + (k >> 2) * 1024 + (k & 3) * 128 + lane * 4);
            c = fmaf(bf_lo(xn), bf_lo(wq), fmaf(bf_hi(xn), bf_hi(wq), c));
        }
#pragma unroll 1
        for (int o = 16; o; o >>= 1) c += __shfl_xor_sync(0xffffffffu, c, o);
        if ((lane & 15) == rr) sc = c;
    }
    return sc;
}

__device__ __forceinline__ void issue_rows(const __nv_bfloat16* u, uint32_t sb, int b) {
    if (elect_one()) {
        const uint32_t bar = sb + OFF_BAR + 8 * B_ROW;
#pragma unroll
        for (int j = 0; j < 4; j++) mbar_init(bar + 8 * j, 1);
        asm volatile("fence.mbarrier_init.release.cluster;" ::: "memory");
        fence_async();
#pragma unroll 1
        for (int j = 0; j < 4; j++) {
            mbar_expect_tx(bar + 8 * j, 8192);
#pragma unroll
            for (int i = 0; i < 4; i++) bulk_g2s(sb + OFF_VT + (4 * j + i) * ROW_PITCH, u + (size_t)(16 * b + 4 * j + i) * DM, 2048, bar + 8 * j);
        }
    }
    __syncwarp();
}

__global__ void __cluster_dims__(2, 1, 1) __launch_bounds__(NTHR, 1)
fused_kernel(const __grid_constant__ Ptrs p, const __grid_constant__ Maps maps) {
    extern __shared__ __align__(1024) unsigned char smem[];
    const int tid = threadIdx.x, lane = tid & 31;
    const int c_ = ((blockIdx.x >> 1) + PERM_OFF) & 63, b = 2 * ((c_ & 32) | ((c_ & 7) << 2) | ((c_ >> 3) & 3)) + (blockIdx.x & 1);
    const int dch = 8 * b + (tid >> 5) - 4;
    uint2 la, aim, cre, cim;
    uint32_t ldt16;
    if ((uint32_t)(tid - 128) < 256u) {
        la = ldg64(p.logA + dch * NMODE + 4 * lane); aim = ldg64(p.Aim + dch * NMODE + 4 * lane);
        cre = ldg64(p.Cre + dch * NMODE + 4 * lane); cim = ldg64(p.Cim + dch * NMODE + 4 * lane);
        ldt16 = ldg16(p.ldt + dch);
    }
    const uint32_t sb = s_u32(smem), bar0 = sb + OFF_BAR;
    const int warp = __shfl_sync(0xffffffffu, tid >> 5, 0);
    const int h = b & 1, cl = b >> 1;
    const int m = lane >> 3, r = lane & 7, g = lane >> 2, t = lane & 3;
    const bool has_gu = b < GU_CTAS;
    if (warp == 4) { STAMP(0); GSTAMP(24); }

    if (warp >= 12) {
        asm volatile("setmaxnreg.dec.sync.aligned.u32 24;");
        const int a = warp - 12;
        uint32_t due = now_ns() + ST_T0 + (uint32_t)(128 * a + b) * ST_PER / 128 + (has_gu ? 0 : ST_LATE * (12 * ST_PER + 4 * ST_PER2) / 16);
        const bool el = elect_one();
        if (a == 1) issue_rows(p.u, sb, b);
        if (a == 2 && el) {
#pragma unroll
            for (int i = B_XT; i < NBAR; i++) mbar_init(bar0 + 8 * i, (i == B_V || i == B_SFREE || i == B_XFREE || i == B_OWN) ? 8 : i == B_RECV ? 9 : i == B_RED ? 5 : (i == B_UPD || (i >= B_FREE && i < B_FULL)) ? 4 : 1);
            asm volatile("fence.mbarrier_init.release.cluster;" ::: "memory");
            fence_async();
            mbar_expect_tx(bar0 + 8 * B_XT, 65536);
            mbar_expect_tx(bar0 + 8 * B_RECV, 8192);
            mbar_expect_tx(bar0 + 8 * B_RECV + 8, 8192);
            mbar_expect_tx(bar0 + 8 * B_RED, 2048);
        }
        if (a == 3 && el) {
#pragma unroll
            for (int i = 0; i < 5; i++) asm volatile("prefetch.tensormap [%0];" ::"l"(&maps.u + i) : "memory");
        }
        __syncwarp();
        cluster_arrive();
        cluster_wait();
        STAMP(18);
        mbar_wait(bar0 + 8 * (B_ROW + a), 0);
        if (el) {
#pragma unroll
            for (int i = 0; i < 4; i++)
                tma_load_tile(sb + OFF_XT + h * 32768 + a * 4096 + (i & 1) * 16384 + (i >> 1) * 2048, &maps.u, 16 * cl, 4 * a + (i & 2), 16 * (i & 1) + 8 * h, bar0 + 8 * B_XT);
        }
        if (el) {
#pragma unroll 1
            for (int k = has_gu ? 0 : 4; k < 6; k++) {
                const int i = 4 * k + a, s = k < 3 ? i : i - 12;
#pragma unroll 1
                for (int left; (left = (int)(due - now_ns())) > 0;) __nanosleep(left >> 1);
                due += k == 0 ? 4 * ST_PER + ST_GAP : k < 3 ? 4 * ST_PER : 4 * ST_PER2;
                const bool again = k >= 3 && has_gu;
                if (s >= 6 || again) mbar_wait(bar0 + 8 * (s < 10 || again ? B_FREE + s : B_V), slot_priv(s) && again);
                const uint32_t dst = sb + slot_off(s), bar = bar0 + 8 * (B_FULL + s);
                if (k < 4) {
                    mbar_expect_tx(bar, 8192);
                    tma_load_2d(dst, &maps.wg, 64 * cl, 512 * h + 32 * i, bar);
                    tma_load_2d(dst + 4096, &maps.wu, 64 * cl, 512 * h + 32 * i, bar);
                } else {
                    mbar_expect_tx(bar, 7168);
                    tma_load_perm(dst, &maps.wd, 16 * cl, 56 * h + 14 * a + 7 * (k & 1), bar);
                }
            }
            STAMP(19);
        }
        __syncwarp();
        {
            const uint32_t fs = finish_src(sb, h, 2 * a, lane), fx = finish_dst(sb, h, 2 * a, lane);
            mbar_wait(bar0 + 8 * B_RECV, 0);
#pragma unroll 2
            for (int i = 0; i < 8; i++) {
                uint32_t s[4];
                ldsm4t(s, (fs ^ ((i & 1) << 5)) + (i & 2) * 4096 + (i >> 2) * 128);
                const uint32_t xa = (fx ^ ((i & 2) << 3)) + (i & 1) * 256 + (i >> 2) * 2048;
                const uint4 x = lds128(xa);
                sts128(xa, badd2(x.x, s[0]), badd2(x.y, s[1]), badd2(x.z, s[2]), badd2(x.w, s[3]));
            }
            fence_async();
            __syncwarp();
            if (el) {
                tma_store_tile(&maps.out, sb + OFF_XT + h * 32768 + a * 4096, 16 * cl, 4 * a, 8 * h);
                tma_store_tile(&maps.out, sb + OFF_XT + h * 32768 + a * 4096 + 2048, 16 * cl, 4 * a + 2, 8 * h);
            }
            STAMP(20);
            const int tok = 2047 - (int)(lds32(sb + OFF_MISC + 48 + 8 * g) & 2047);
            const bool mine = (((tok >> 7) & 12) | ((tok >> 2) & 3)) == 4 * h + a;
            if (el) asm volatile("cp.async.bulk.wait_group 0;" ::: "memory");
            if (__any_sync(0xffffffffu, mine)) {
                const uint2 o0 = lds64(tile_addr(sb, tok, t));
                mbar_wait(bar0 + 8 * B_UPD, 0);
                const uint2 o1 = add_update(o0, sb + tab_off(g) + T_RED + 16 * t);
                if (mine) *reinterpret_cast<uint2*>(p.out + (size_t)tok * DM + 16 * cl + 4 * t) = o1;
            } else STAMP(62);
        }
    } else if (warp >= 4) {
        const int w = warp - 4;
        uint32_t dsk16 = ldg16(p.dsk + dch);
        cluster_arrive();
        asm volatile("setmaxnreg.inc.sync.aligned.u32 168;");
        const uint32_t vrow = sb + OFF_VT + w * VT_PITCH + VT_PAD, tab = sb + tab_off(w);
        const uint32_t so = sb + OFF_XT + (8 * h + w) * 1024 + ((lane ^ ((w & 1) << 1)) << 4);
        uint32_t dst0 = so + (h ^ 1) * 32768;
        const uint32_t rb0 = bar0 + 8 * B_RECV, rb1 = mapa(rb0, h ^ 1);
        uint32_t fs = finish_src(sb, h, w, lane) + 16384 + h * 8192, fx = (finish_dst(sb, h, w, lane) + 16384) ^ (h << 4);
        uint32_t tpo = 80 + (g - 2 * t) * 8 - (g < 2 * t ? 16 : 0);
        uint32_t xa = sb + OFF_XT + (w & 2) * 16384 + (w >> 2) * 16384 + (w & 1) * 1024 + (g >> 1) * 2048 + (g & 1) * 128 + t * 32 + ((h ^ (g & 1)) << 4);
        uint32_t va = sb + OFF_VT + (2 * m + (r & 1)) * VT_PITCH + VT_PAD + (16 * w + (r >> 1)) * 16;
        uint32_t qa = sb + OFF_ST + 2048 * w + 128 * t + 16 * (g ^ (2 * t));
        uint32_t vmin = vrow + (m & 1) * VT_PLANE - 16, vd = vmin + 16 + (m >> 1) * 1024 + r * 16;
        uint32_t vo = vrow + VT_PLANE + 496 - (m & 1) * 512 + (m >> 1) * 128 + r * 16, vz = vrow - VT_PAD + (lane >> 1) * VT_PLANE + (lane & 1) * 16;
        pin(vmin); pin(vd); pin(vo); pin(vz);
        pin(dst0); pin(fs); pin(fx); pin(tpo); pin(xa); pin(va); pin(qa);
        const Boxes b2(vrow, lane, -18, 5, 7, 0, 4), b3(vrow, lane, -20, 1, 7, 0, 8);
        const KgenAddr ka(sb + OFF_PRIV + w * 8192, lane);
        if (__any_sync(0xffffffffu, ((dst0 | fs | vmin) | (vd | vo | vz) | (fx | tpo | xa) | (va | qa) | (b2.any() | b3.any() | ka.any())) & p.zero)) __trap();
        cluster_wait();
        pin(la.x); pin(la.y); pin(aim.x); pin(aim.y); pin(cre.x); pin(cre.y); pin(cim.x); pin(cim.y); pin(ldt16); pin(dsk16);
        uint4 x[8];
        auto load_x = [&]() {
            mbar_wait(bar0 + 8 * B_XT, 0);
#pragma unroll
            for (int i = 0; i < 8; i++) x[i] = lds128(xa + (i & 1) * 8192 + (i >> 1) * 256);
        };
        kgen(ka, tab, lane, la, aim, cre, cim, bf_round(ex2f(bf_lo(ldt16) * 1.4426950408889634f)), 1.f + bf_lo(dsk16), dch, [&]() {
            STAMP(21);
            if (elect_one()) mbar_arrive_n(bar0 + 8 * (B_FREE + 6 + ((w >> 1) ^ 2)), 2);
        }, [&]() {
            if ((LN_PAUSE >> w) & 1) mbar_wait(bar0 + 8 * B_LN, 0);
        });
        STAMP(1); KSTAMP(6);
        const uint32_t pb = tab + T_DENSE + (g - 2 * t) * 4;
        DenseTaps dt(pb, pb + p.zero);
        {
            load_x();
            STAMP(47);
            mbar_wait(bar0 + 8 * (B_ST + (w >> 1)), 0);
            uint4 q[4];
#pragma unroll
            for (int n = 0; n < 4; n++) q[n] = lds128(qa + 512 * n);
            if (lane < 4) sts128(vz, 0, 0, 0, 0);
            STAMP(2); GSTAMP(28);
#pragma unroll
            for (int i = 0; i < 8; i++) {
                const uint32_t s0 = (i & 1) ? q[i >> 1].z : q[i >> 1].x, s1 = (i & 1) ? q[i >> 1].w : q[i >> 1].y;
                stsm4t(va + (i >> 1) * 64 + (i & 1) * VT_PLANE, normalize2(x[i].x, s0, s1), normalize2(x[i].y, s0, s1),
                       normalize2(x[i].z, s0, s1), normalize2(x[i].w, s0, s1));
            }
            __syncwarp();
            if (elect_one()) mbar_arrive(bar0 + 8 * B_V);
        }
        mbar_wait(bar0 + 8 * B_V, 0);
        STAMP(3); KSTAMP(7);
        float acc[16][4];
#pragma unroll
        for (int i = 0; i < 16; i++) { acc[i][0] = acc[i][1] = acc[i][2] = acc[i][3] = 0.f; }
        tpo |= dense_phase(acc, vmin, vd, vo, pb, dt, p.zero);
        STAMP(4); KSTAMP(8);
        const uint32_t dst1 = mapa(dst0 + (h ? 32768 : -32768), h ^ 1);
        tail_phase(acc, b2, b3, tab + T_R2 + 2 * tpo, tab + T_R3 + tpo, p.zero, [&](int j) {
            if (j == 3) {
                mbar_wait(bar0 + 8 * B_SFREE, 0);
                emit<0>(acc, h, dst0, dst1, rb0, rb1);
                STAMP(5);
            }
            if (j == 12) mbar_wait(bar0 + 8 * B_XFREE, 0);
        });
        emit<1>(acc, h, dst0, dst1, bar0 + 8 * B_OWN, rb1);
        STAMP(30);
        const int tok = 2047 - (int)(lds32(sb + OFF_MISC + 48 + 8 * g) & 2047);
        const bool mine = (((tok >> 6) & 24) | ((tok >> 1) & 7)) == 16 + 8 * h + w;
        const uint32_t ta = tile_addr(sb, tok, t);
        const uint4 x0[2] = {lds128(fx), lds128(fx + 256)}, x1[2] = {lds128(fx ^ 16), lds128((fx ^ 16) + 256)};
        mbar_wait(bar0 + 8 * B_OWN, 0);
        finish_half(fs, fx, x0);
        mbar_wait(bar0 + 8 * (B_RECV + 1), 0);
        STAMP(6);
        finish_half(fs + (h ? -8192 : 8192), fx ^ 16, x1);
        __syncwarp();
        if (__any_sync(0xffffffffu, mine)) {
            const uint2 o0 = lds64(ta);
            mbar_wait(bar0 + 8 * B_UPD, 0);
            const uint2 o1 = add_update(o0, sb + tab_off(g) + T_RED + 16 * t);
            if (mine) sts64(ta, o1.x, o1.y);
        }
        fence_async();
        __syncwarp();
        if (elect_one()) {
            tma_store_tile(&maps.out, sb + OFF_XT + h * 32768 + 16384 + w * 2048, 16 * cl, 2 * w, 16 + 8 * h);
            asm volatile("cp.async.bulk.wait_group.read 0;" ::: "memory");
        }
        STAMP(7);
    } else {
        const int a = warp;
        const uint4 wq = ldg128(p.wr + 8 * tid);
        const uint32_t epoch = ld_relaxed_32(&p.sc->epoch);
        cluster_arrive();
        asm volatile("setmaxnreg.inc.sync.aligned.u32 152;");
        const uint32_t tag = __shfl_sync(0xffffffffu, epoch, 0) + 1u, misc = sb + OFF_MISC, abar = bar0 + 8 * (B_AUX + a);
        uint32_t aph = 0;
        const Exchange* in = &p.sc->x[cl & (NREP - 1)];
        uint2* pub = p.sc->x[m >> 1].stat + 16 * b + 2 * (r ^ (2 * (b & 3))) + (m & 1);
        uint32_t* cnt_s = &p.sc->x[t].n_stat[b & 96];
        pin(pub); pin(cnt_s);
        if (tid < 64) sts32(sb + OFF_XCH + 4 * tid, 0);
        const uint32_t wbuf = sb + OFF_LN + a * 1024, part = sb + OFF_LN + 4096;
        {
            sts128(wbuf + 16 * lane, wq.x, wq.y, wq.z, wq.w);
            sts128(wbuf + 512 + 16 * lane, 0x3f803f80u, 0x3f803f80u, 0x3f803f80u, 0x3f803f80u);
            float wsum = ((bf_lo(wq.x) + bf_hi(wq.x)) + (bf_lo(wq.y) + bf_hi(wq.y))) + ((bf_lo(wq.z) + bf_hi(wq.z)) + (bf_lo(wq.w) + bf_hi(wq.w)));
#pragma unroll
            for (int o = 16; o; o >>= 1) wsum += __shfl_xor_sync(0xffffffffu, wsum, o);
            sts32f(part + 1024 + 4 * a, wsum);
            uint32_t wf[4][4];
#pragma unroll
            for (int i = 0; i < 4; i++) ldsm4(wf[i], wbuf + ((uint32_t)(r - 1) < 2u ? 16 * (r - 1) : 512) + 32 * m + 128 * i);
            uint32_t ra = sb + OFF_VT + r * ROW_PITCH + 512 * a + 16 * m, pa = part + a * 256 + g * 16;
            cluster_wait();
            STAMP(22);
#pragma unroll 1
            for (int hf = 0; hf < 2; hf++) {
                mbar_wait(bar0 + 8 * B_ROW + 16 * hf, 0);
                mbar_wait(bar0 + 8 * B_ROW + 16 * hf + 8, 0);
                STAMP(23);
                uint32_t x[8][4];
                float cs[2][4], q[8][4];
#pragma unroll
                for (int i = 0; i < 40; i++) (i < 8 ? cs[i >> 2 & 1] : q[(i - 8) >> 2 & 7])[i & 3] = 0.f;
#pragma unroll
                for (int k = 0; k < 8; k++) ldsm4(x[k], ra + k * 64);
                const bool more = __any_sync(0xffffffffu, after_all(x, p.zero));
#pragma unroll 1
                do {
#pragma unroll
                    for (int k = 0; k < 8; k++) {
                        mma_v(cs[k & 1], x[k], wf[k >> 1][2 * (k & 1)], wf[k >> 1][2 * (k & 1) + 1]);
#pragma unroll
                        for (int i = 0; i < 4; i++) mma_bf16_k8(q[4 * (k & 1) + i], x[k][i & 2], x[k][i | 1], x[k][i]);
                    }
                } while (more);
                const float c2 = cs[0][2] + cs[1][2];
                if (t == 0) sts64f(pa, (cs[0][0] + cs[1][0]) + c2, cs[0][1] + cs[1][1]);
                if (t == 1) sts32f(pa + 12, c2);
                const float e0 = ((q[0][0] + q[2][0]) + (q[4][0] + q[6][0])) + ((q[1][2] + q[3][2]) + (q[5][2] + q[7][2]));
                const float e1 = ((q[0][1] + q[2][1]) + (q[4][1] + q[6][1])) + ((q[1][3] + q[3][3]) + (q[5][3] + q[7][3]));
                if (t == (g >> 1)) sts32f(pa + 8, (g & 1) ? e1 : e0);
                ra += 8 * ROW_PITCH; pa += 128;
            }
        }
        STAMP(31);
        named_sync(1, 128);
        if (a == 0) {
            const uint32_t pa = part + (lane & 15) * 16;
            const float4 p0 = lds128f(pa), p1 = lds128f(pa + 256), p2 = lds128f(pa + 512), p3 = lds128f(pa + 768), ws = lds128f(part + 1024);
            const float mu = ((p0.x + p1.x) + (p2.x + p3.x)) * (1.f / DM);
            float var = ((p0.z + p1.z) + (p2.z + p3.z)) * (1.f / DM) - mu * mu;
            const bool centred = __any_sync(0xffffffffu, !(mu * mu <= 4.f * var));
            if (centred) var = centred_var(sb + OFF_VT, mu, lane);
            const float ri = rcpf(bf_round(sqrtaf(bf_round(bf_round(var) + 1e-5f))));
            const uint32_t s0 = pack_bf16(mu, ri), s1 = (pack_bf16(ri - bf_hi(s0), 0.f) & 0xfffcu) | (tag & 3);
            float sc = ((((p0.y + p1.y) + (p2.y + p3.y)) + ((p0.w + p1.w) + (p2.w + p3.w))) - bf_lo(s0) * ((ws.x + ws.y) + (ws.z + ws.w))) * ri;
            if (centred) sc = centred_score(sb + OFF_VT, sb + OFF_LN, s0, s1, lane);
            const uint32_t sb16 = pack_bf16(0.f, sc);
            const uint32_t s2 = s1 | (sb16 ^ (((uint32_t)((int)sb16 >> 31) & 0x7fff0000u) | 0x80000000u));
            st_relaxed_64(pub, s0, s2);
            st_relaxed_64(pub + 2 * sizeof(Exchange) / 8, s0, s2);
            if (lane < NREP) red_add(cnt_s, 1);
            if (elect_one()) mbar_arrive(bar0 + 8 * B_LN);
            STAMP(9); GSTAMP(25);
        }
        const uint32_t slot0 = sb + OFF_RING + a * 8192, slot1 = sb + slot_off(4 + a), slot2 = sb + slot_off(8 + a), fbar = bar0 + 8 * (B_FULL + a);
        uint32_t mine = 0, row[2] = {0, 0};
        {
            uint32_t q[16];
            named_sync(1, 128);
            wait_count(&in->n_stat[32 * a], 32 * tag - FEW_ST);
            STAMP(41);
#pragma unroll 1
            for (uint32_t it = 0;; spin_guard(it)) {
                if (elect_one()) {
                    mbar_expect_tx(abar, 4096);
                    bulk_g2s(sb + OFF_ST + 4096 * a, in->stat + 512 * a, 4096, abar);
                }
                mbar_wait(abar, aph);
                aph ^= 1;
                uint32_t bad = 0;
#pragma unroll
                for (int n = 0; n < 8; n++) {
                    const uint4 u = lds128v(sb + OFF_ST + 4096 * a + 512 * n + 16 * lane);
                    q[2 * n] = u.y; q[2 * n + 1] = u.w;
                    bad = or_xor(bad, u.y, tag);
                }
                const bool ok = __all_sync(0xffffffffu, (bad & 3) == 0);
                asm volatile("{ .reg .pred p; setp.ne.u32 p, %1, 0; @p mbarrier.arrive.shared::cta.b64 _, [%0]; }" ::"r"(bar0 + 8 * (B_ST + a)), "r"((uint32_t)(ok && lane == 0)) : "memory");
                if (ok) break;
            }
            STAMP(8);
            const uint32_t inv = 2047 - 512 * a - 16 * m - (r ^ (2 * m));
#pragma unroll
            for (int i = 0; i < 16; i++) asm("lop3.b32 %0, %0, %1, %2, 0x9b;" : "+r"(q[i]) : "r"(inv), "r"(0xffff0000u | (64 * (i >> 1) + 8 * (i & 1))));
            auto below = [&](uint32_t x) {
                uint32_t d[4];
#pragma unroll
                for (int i = 0; i < 16; i++) d[i & 3] = i < 4 ? x + q[i] : min(d[i & 3], x + q[i]);
                d[0] = min(min(d[0], d[1]), min(d[2], d[3]));
                return d[0] < x ? x - 1 - d[0] : 0u;
            };
            const uint32_t mx0 = ~min(min(min(min(q[0], q[1]), min(q[2], q[3])), min(min(q[4], q[5]), min(q[6], q[7]))),
                                      min(min(min(q[8], q[9]), min(q[10], q[11])), min(min(q[12], q[13]), min(q[14], q[15]))));
            const uint32_t gm = min(__reduce_max_sync(0xffffffffu, lane < 16 ? mx0 : 0u), __reduce_max_sync(0xffffffffu, lane < 16 ? 0u : mx0));
            if (lane == 0) sts32(misc + 16 + 4 * a, gm);
            named_sync(1, 128);
            STAMP(42);
            if (b == 0 && tid == 0) st_relaxed_32(&p.sc->epoch, tag);
            const uint4 t0 = lds128(misc + 16);
            uint32_t tau = min(min(t0.x, t0.y), min(t0.z, t0.w));
            uint32_t mx = mx0, cnt = 0, bal;
            const uint32_t list = sb + OFF_XCH + 64 * a;
#pragma unroll 1
            while ((bal = __ballot_sync(0xffffffffu, mx >= tau)) != 0) {
                const uint32_t pos = cnt + __popc(bal & ((1u << lane) - 1u));
                cnt += __popc(bal);
                if (cnt > 16) break;
                if (mx >= tau) sts32(list + 4 * pos, mx);
                mx = below(mx);
            }
            if (cnt > 16) {
                mx = mx0;
#pragma unroll 1
                for (int j = 0; j < 8; j++) {
                    const uint32_t top = __reduce_max_sync(0xffffffffu, mx), nx = below(mx);
                    if (mx == top) { sts32(list + 4 * j, mx); sts32(list + 32 + 4 * j, 0); mx = nx; }
                }
            }
            named_sync(1, 128);
            STAMP(43);
            const uint2 k = lds64(sb + OFF_XCH + 8 * lane);
            uint32_t hi = max(k.x, k.y), lo = min(k.x, k.y);
            mbar_wait(bar0 + 8 * B_V, 0);
#pragma unroll
            for (int j = 0; j < 8; j++) {
                const uint32_t top = __reduce_max_sync(0xffffffffu, hi);
                const bool won = hi == top;
                hi = won ? lo : hi;
                lo = won ? 0u : lo;
                if (g == j) mine = top;
                if (a == (j >> 1)) row[j & 1] = top;
            }
        }
        STAMP(11);
        const int tok = 2047 - (int)(mine & 2047);
        const uint32_t xs = sb + OFF_XT + (h ^ 1) * 32768 + 16384;
        if (has_gu) {
            if (elect_one()) {
                mbar_expect_tx(abar, 2048);
#pragma unroll
                for (int j = 0; j < 2; j++) bulk_g2s(xs + (2 * a + j) * 1040, p.u + (size_t)(2047 - (row[j] & 2047)) * DM + 512 * h, 1024, abar);
            }
        }
        STAMP(44);
        const uint2 st = ld_relaxed_64(in->stat + (tok & ~15) + 2 * ((tok & 7) ^ ((tok >> 3) & 6)) + ((tok >> 3) & 1));
        if (a == 0 && t == 0) sts64(misc + 48 + 8 * g, mine, __float_as_uint(bf_hi(st.x) + bf_lo(st.y)));
        if (a == 0) STAMP(45);
        if (has_gu) {
            const uint32_t mean = __shfl_sync(0xffffffffu, st.x, 8 * a + 4 * (lane >> 4)), xr = xs + (2 * a + (lane >> 4)) * 1040 + 16 * (lane & 15);
            mbar_wait(abar, aph);
            aph ^= 1;
            STAMP(46);
            uint4 x[4];
#pragma unroll
            for (int j = 0; j < 4; j++) x[j] = lds128(xr + 256 * j);
#pragma unroll
            for (int j = 0; j < 4; j++) sts128(xr + 256 * j, bsub2_lo(x[j].x, mean), bsub2_lo(x[j].y, mean), bsub2_lo(x[j].z, mean), bsub2_lo(x[j].w, mean));
            if (elect_one()) mbar_expect_tx(abar, 512);
            named_sync(1, 128);
        }
        if (lane < (has_gu ? 2 : 4)) mbar_arrive_peer(mapa(bar0 + 8 * (lane & 2 ? B_XFREE : B_SFREE), lane & 1));
        if (has_gu) {
            STAMP(12);
            float gacc[8][4];
#pragma unroll
            for (int i = 0; i < 8; i++) { gacc[i][0] = gacc[i][1] = gacc[i][2] = gacc[i][3] = 0.f; }
            uint32_t* pubh = reinterpret_cast<uint32_t*>(&p.sc->x[0].h[b * 32 + 8 * a + (g ^ (2 * a))]) + t;
            uint32_t* cnt_h = &p.sc->x[t].n_h[32 * (b / 14)];
            uint32_t ko = sb + (m & 1) * 4096 + (r + ((m >> 1) << 3)) * 128 + ((r ^ (4 * h) ^ a) << 4), kp = ko ^ 64, xb = xs + r * 1040 + m * 16;
            uint32_t xch = sb + OFF_XCH + 16 * tid, tagm = t == 3 ? 1u : 0u;
            pin(pubh); pin(cnt_h); pin(ko); pin(kp); pin(xb); pin(xch); pin(tagm);
            const float r0 = lds32f(misc + 52 + 16 * t), r1 = lds32f(misc + 60 + 16 * t);
#pragma unroll
            for (int c = 0; c < 4; c++) {
                uint32_t af[20][4];
#pragma unroll
                for (int j = 0; j < 4; j++) ldsm4(af[16 + j], xb + 256 * c + 64 * j);
                if (c == 3) mbar_wait(bar0 + 8 * B_SFREE, 0);
#pragma unroll
                for (int j = 0; j < 4; j++) {
                    mbar_wait(bar0 + 8 * (B_FULL + 4 * (c % 3) + j), c / 3);
#pragma unroll
                    for (int i = 0; i < 4; i++) ldsm4t(af[8 * (i >> 1) + 2 * j + (i & 1)], ((i & 1) ? kp : ko) + slot_off(4 * (c % 3) + j) + (i >> 1) * 2048);
                }
                STAMP(36 + c);
                __syncwarp();
                if (c < 3 && lane < 4) mbar_arrive(bar0 + 8 * (B_FREE + 4 * c + lane));
                const bool more = __any_sync(0xffffffffu, (af[6][3] | af[7][3] | af[14][3] | af[15][3]) & p.zero);
#pragma unroll 1
                do {
#pragma unroll
                    for (int i = 0; i < 16; i++) mma_v(gacc[i & 7], af[i], af[16 + ((i >> 1) & 3)][2 * (i >> 3)], af[16 + ((i >> 1) & 3)][2 * (i >> 3) + 1]);
                } while (more);
                STAMP(52 + c);
            }
            STAMP(13);
            float own[4], oth[4];
#pragma unroll
            for (int j = 0; j < 4; j++) oth[j] = (gacc[1][j] + gacc[3][j]) + (gacc[5][j] + gacc[7][j]);
            st_async128(mapa(xch, h ^ 1), __float_as_uint(oth[0]), __float_as_uint(oth[1]), __float_as_uint(oth[2]), __float_as_uint(oth[3]), mapa(abar, h ^ 1));
            STAMP(56);
#pragma unroll
            for (int j = 0; j < 4; j++) own[j] = ((gacc[0][j] + gacc[2][j]) + (gacc[4][j] + gacc[6][j])) * ((j & 1) ? r1 : r0);
            mbar_wait(abar, aph);
            aph ^= 1;
            STAMP(57);
            const float4 o4 = lds128f(xch);
            const float g0 = bf_round(fmaf(o4.x, r0, own[0])), g1 = bf_round(fmaf(o4.y, r1, own[1]));
            const float h0 = bf_round(g0 * rcpf(1.f + ex2f(-1.4426950408889634f * g0))) * bf_round(fmaf(o4.z, r0, own[2]));
            const float h1 = bf_round(g1 * rcpf(1.f + ex2f(-1.4426950408889634f * g1))) * bf_round(fmaf(o4.w, r1, own[3]));
            uint32_t hw;
            asm volatile("movmatrix.sync.aligned.m8n8.trans.b16 %0, %1;" : "=r"(hw) : "r"(pack_bf16(h0, h1)));
            hw = (hw & ~tagm) | (tag & tagm);
#pragma unroll
            for (int j = 0; j < NREP; j++) st_relaxed_32(pubh + j * (sizeof(Exchange) / 4), hw);
            if (lane < NREP) red_add(cnt_h, 1);
            if (lane < 2) mbar_arrive_peer(mapa(bar0 + 8 * B_XFREE, lane));
            named_sync(1, 128);
            STAMP(14);
        }
        float dacc[4];
        const int tk = ((tid >> 1) & 6) | (tid & 1);
        uint32_t ro = 4 * tid, red = sb + tab_off(tk) + T_RED + 4 * ((tid >> 4) + 4 * (tid & 2));
        if (!has_gu) named_sync(1, 128);
        const float sg = bf_round(rcpf(1.f + ex2f(-1.4426950408889634f * __uint_as_float(unorder_key(lds32(misc + 48 + 8 * tk) >> 16) << 16))));
        pin(ro); pin(red);
        mbar_wait(bar0 + 8 * B_XFREE, 0);
        {
            uint32_t wo = (r + ((m >> 1) << 3)) * 32 + (((m & 1) ^ (r >> 2)) << 4), af[14][4];
            pin(wo);
            float d[7][4];
#pragma unroll
            for (int i = 0; i < 7; i++) { d[i][0] = d[i][1] = d[i][2] = d[i][3] = 0.f; }
            auto first_half = [&]() {
                mbar_wait(fbar + 32, has_gu);
#pragma unroll
                for (int j = 0; j < 14; j++) ldsm4t(af[j], slot1 + wo + j * 512);
            };
            auto fetch = [&]() {
                if (elect_one()) {
                    mbar_expect_tx(abar, 7168);
                    bulk_g2s(slot0, &in->h[(56 * h + 14 * a) * 32], 7168, abar);
                }
            };
            wait_count(&in->n_h[32 * (4 * h + a)], 56 * tag - FEW_H);
            STAMP(33);
            fetch();
            first_half();
            uint4 hq[14];
#pragma unroll 1
            for (uint32_t it = 0;; spin_guard(it)) {
                mbar_wait(abar, aph);
                aph ^= 1;
                uint32_t bad = 0;
#pragma unroll
                for (int j = 0; j < 14; j++) { hq[j] = lds128(slot0 + 512 * j + 128 * t + 16 * (g ^ (2 * t))); bad = or_xor(bad, hq[j].w, tag); }
                if (__all_sync(0xffffffffu, (bad & 1) == 0)) break;
                fetch();
            }
            STAMP(15);
#pragma unroll
            for (int s = 0; s < 2; s++) {
                if (s) {
                    mbar_wait(fbar + 64, has_gu);
#pragma unroll
                    for (int j = 0; j < 14; j++) ldsm4t(af[j], slot2 + wo + j * 512);
                }
                const bool more = __any_sync(0xffffffffu, after_all(af, p.zero));
#pragma unroll 1
                do {
#pragma unroll
                    for (int j = 0; j < 14; j++) {
                        const uint4 q = hq[7 * s + (j >> 1)];
                        mma_v(d[j % 7], af[j], (j & 1) ? q.z : q.x, (j & 1) ? q.w : q.y);
                    }
                } while (more);
            }
#pragma unroll
            for (int j = 0; j < 4; j++) dacc[j] = ((d[0][j] + d[1][j]) + (d[2][j] + d[3][j])) + ((d[4][j] + d[5][j]) + d[6][j]);
        }
        STAMP(16);
        {
            st_async128(mapa(sb + OFF_XCH + 16 * tid, h ^ 1), __float_as_uint(dacc[0]), __float_as_uint(dacc[1]), __float_as_uint(dacc[2]), __float_as_uint(dacc[3]),
                        mapa(bar0 + 8 * B_RED, h ^ 1));
            sts128f(slot0 + 7680 + lane * 16, dacc);
            __syncwarp();
            if (elect_one()) mbar_arrive(bar0 + 8 * B_RED);
            mbar_wait(bar0 + 8 * B_RED, 0);
            const uint32_t b0 = sb + OFF_RING + 7680 + ro, b1 = sb + OFF_XCH + ro;
            const float y = ((lds32f(b0) + lds32f(b0 + 8192)) + (lds32f(b0 + 16384) + lds32f(b0 + 24576))) +
                            ((lds32f(b1) + lds32f(b1 + 512)) + (lds32f(b1 + 1024) + lds32f(b1 + 1536)));
            sts32f(red, bf_round(y) * sg);
            __syncwarp();
            if (elect_one()) mbar_arrive(bar0 + 8 * B_UPD);
        }
        STAMP(17); GSTAMP(29);
    }
}

typedef CUresult (*EncodeFn)(CUtensorMap*, CUtensorMapDataType, cuuint32_t, void*, const cuuint64_t*, const cuuint64_t*,
                             const cuuint32_t*, const cuuint32_t*, CUtensorMapInterleave, CUtensorMapSwizzle,
                             CUtensorMapL2promotion, CUtensorMapFloatOOBfill);

void make_map(EncodeFn enc, CUtensorMap* m, const void* ptr, uint64_t cols, uint64_t rows, uint32_t bc, uint32_t br,
              CUtensorMapSwizzle sw, CUtensorMapL2promotion pr) {
    cuuint64_t dims[2] = {cols, rows};
    cuuint64_t str[1] = {cols * 2};
    cuuint32_t box[2] = {bc, br};
    cuuint32_t es[2] = {1, 1};
    enc(m, CU_TENSOR_MAP_DATA_TYPE_BFLOAT16, 2, const_cast<void*>(ptr), dims, str, box, es, CU_TENSOR_MAP_INTERLEAVE_NONE, sw, pr,
        CU_TENSOR_MAP_FLOAT_OOB_FILL_NONE);
}
void make_perm_map(EncodeFn enc, CUtensorMap* m, const void* ptr, CUtensorMapL2promotion pr) {
    cuuint64_t dims[5] = {DM, 2, 4, 4, FF / 32};
    cuuint64_t str[4] = {DM * 2, 8 * DM * 2, 2 * DM * 2, 32 * DM * 2};
    cuuint32_t box[5] = {16, 2, 4, 4, 7};
    cuuint32_t es[5] = {1, 1, 1, 1, 1};
    enc(m, CU_TENSOR_MAP_DATA_TYPE_BFLOAT16, 5, const_cast<void*>(ptr), dims, str, box, es, CU_TENSOR_MAP_INTERLEAVE_NONE,
        CU_TENSOR_MAP_SWIZZLE_32B, pr, CU_TENSOR_MAP_FLOAT_OOB_FILL_NONE);
}
void make_tile_map(EncodeFn enc, CUtensorMap* m, const void* ptr) {
    cuuint64_t dims[4] = {DM, 4, 16, SEQ / 64};
    cuuint64_t str[3] = {16 * DM * 2, DM * 2, 64 * DM * 2};
    cuuint32_t box[4] = {16, 4, 2, 8};
    cuuint32_t es[4] = {1, 1, 1, 1};
    enc(m, CU_TENSOR_MAP_DATA_TYPE_BFLOAT16, 4, const_cast<void*>(ptr), dims, str, box, es, CU_TENSOR_MAP_INTERLEAVE_NONE,
        CU_TENSOR_MAP_SWIZZLE_32B, CU_TENSOR_MAP_L2_PROMOTION_NONE, CU_TENSOR_MAP_FLOAT_OOB_FILL_NONE);
}

}

#define WD_PROMO CU_TENSOR_MAP_L2_PROMOTION_L2_64B
extern "C" void kernel_launch(void* const* d_in, const int* in_sizes, int n_in, void* d_out, int out_size) {
    (void)in_sizes; (void)n_in; (void)out_size;
    static EncodeFn enc = nullptr;
    static void* scratch = nullptr;
    if (!enc) {
        void* fn = nullptr;
        cudaDriverEntryPointQueryResult q;
        cudaGetDriverEntryPoint("cuTensorMapEncodeTiled", &fn, cudaEnableDefault, &q);
        enc = (EncodeFn)fn;
        cudaGetSymbolAddress(&scratch, g_scratch);
        cudaFuncSetAttribute(fused_kernel, cudaFuncAttributeMaxDynamicSharedMemorySize, SMEM_BYTES);
    }
    Maps maps;
    make_tile_map(enc, &maps.u, d_in[0]);
    make_tile_map(enc, &maps.out, d_out);
    make_map(enc, &maps.wg, d_in[9], FF, DM, 64, 32, CU_TENSOR_MAP_SWIZZLE_128B, CU_TENSOR_MAP_L2_PROMOTION_L2_128B);
    make_map(enc, &maps.wu, d_in[10], FF, DM, 64, 32, CU_TENSOR_MAP_SWIZZLE_128B, CU_TENSOR_MAP_L2_PROMOTION_L2_128B);
    make_perm_map(enc, &maps.wd, d_in[11], WD_PROMO);
    Ptrs p;
    p.sc = (Scratch*)scratch;
    p.u = (const __nv_bfloat16*)d_in[0];
    p.logA = (const __nv_bfloat16*)d_in[1];
    p.Aim = (const __nv_bfloat16*)d_in[2];
    p.Cre = (const __nv_bfloat16*)d_in[3];
    p.Cim = (const __nv_bfloat16*)d_in[4];
    p.ldt = (const __nv_bfloat16*)d_in[5];
    p.dsk = (const __nv_bfloat16*)d_in[6];
    p.wr = (const __nv_bfloat16*)d_in[8];
    p.out = (__nv_bfloat16*)d_out;
    p.zero = 0;
    fused_kernel<<<NCTA, NTHR, SMEM_BYTES, cudaStreamPerThread>>>(p, maps);
}
```

```cpp
#include <cuda_runtime.h>
#include <cuda_bf16.h>
#include <cuda_fp16.h>
#include <cuda.h>
#include <stdint.h>

namespace {

constexpr int SEQ = 2048, DM = 1024, NMODE = 128, FF = 3584;
constexpr int NCTA = 128, NTHR = 512;
constexpr int GU_CTAS = 112;
constexpr int NREP = 4;

constexpr int OFF_XT = 0;
constexpr int OFF_RING = 65536;
constexpr int OFF_PRIV = OFF_RING + 65536;
constexpr int OFF_VT = OFF_PRIV + 65536;
constexpr int VT_PAD = 32, VT_PLANE = VT_PAD + 2048, VT_PITCH = 2 * VT_PLANE, ROW_PITCH = 2064;
constexpr int OFF_BAR = OFF_VT + 8 * VT_PITCH;
constexpr int OFF_MISC = OFF_BAR + 384;
constexpr int OFF_XCH = OFF_MISC + 112;
constexpr int SMEM_BYTES = OFF_XCH + 2048;
constexpr int OFF_LN = OFF_RING + 7 * 8192;
constexpr int OFF_ST = OFF_RING + 6 * 8192;
static_assert(SMEM_BYTES <= 232448, "shared memory");

constexpr int B_ROW = 0, B_XT = 4, B_V = 5, B_LN = 6, B_SFREE = 7, B_RECV = 8, B_RED = 10, B_UPD = 11, B_ST = 12, B_XFREE = 16, B_OWN = 17, B_FREE = 20, B_FULL = 32, B_AUX = 44, NBAR = 48;

constexpr int T_DENSE = 60;
constexpr int T_PATCH = 2208;
constexpr int T_R2 = 2368;
constexpr int T_R3 = 3296;

constexpr int T_RED = 4032;
__device__ __forceinline__ bool slot_priv(int s) { return (uint32_t)(s - 6) < 4u; }
__device__ __forceinline__ uint32_t slot_off(int s) { return slot_priv(s) ? OFF_PRIV + 4096 + (s & 3) * 16384 : OFF_RING + (s < 6 ? s : s - 4) * 8192; }
__device__ __forceinline__ uint32_t tab_off(int w) { return OFF_PRIV + w * 8192 + (w & 1) * 4096; }

constexpr uint32_t SPIN_LIMIT = 1u << 20;
#define KG_UNROLL 4
constexpr int kKgUnroll = KG_UNROLL;
#define BB_UNROLL 2
constexpr int kBbUnroll = BB_UNROLL;
#define DENSE_UNROLL 1
constexpr int kDenseUnroll = DENSE_UNROLL;
#define ST_T0 2200
#define LN_PAUSE 0xf0
#define FEW_ST 8
#define FEW_H 8
#define PERM 2
#define PERM_OFF 60
#define ABL_RHO 0
#define ABL_SKIP 0
#define ABL 0
#define Q2_HELP 0
#define FFA
#define FIN_ILP 2
#define REG_S "24"
#define REG_C "176"
#define REG_A "136"
#define DCH 7
#define ST_LATE 16
#define ST_GAP 0
#define ST_PER 308
#define ST_PER2 320

struct Exchange {
    uint2 stat[SEQ];
    uint4 h[GU_CTAS * 32];
    uint32_t n_stat[4 * 32];
    uint32_t n_h[8 * 32];
};
struct Scratch {
    Exchange x[NREP];
    uint32_t epoch;
};
__device__ __align__(128) Scratch g_scratch;

struct Ptrs {
    const __nv_bfloat16 *logA, *Aim, *Cre, *Cim, *ldt, *u;
    const __nv_bfloat16 *dsk, *wr;
    Scratch* sc;
    __nv_bfloat16* out;
    uint32_t zero;
};
struct Maps {
    CUtensorMap u, out, wg, wu, wd;
};

#define STAMP(i) do { } while (0)
#define KSTAMP(i) do { } while (0)
#define GSTAMP(i) do { } while (0)

__device__ __forceinline__ uint32_t s_u32(const void* p) { return (uint32_t)__cvta_generic_to_shared(p); }
__device__ __forceinline__ void mbar_init(uint32_t b, uint32_t n) {
    asm volatile("mbarrier.init.shared::cta.b64 [%0], %1;" ::"r"(b), "r"(n) : "memory");
}
__device__ __forceinline__ void mbar_expect_tx(uint32_t b, uint32_t bytes) {
    asm volatile("mbarrier.arrive.expect_tx.shared::cta.b64 _, [%0], %1;" ::"r"(b), "r"(bytes) : "memory");
}
__device__ __forceinline__ void mbar_arrive(uint32_t b) {
    asm volatile("mbarrier.arrive.shared::cta.b64 _, [%0];" ::"r"(b) : "memory");
}
__device__ __forceinline__ void mbar_arrive_n(uint32_t b, uint32_t n) {
    asm volatile("mbarrier.arrive.shared::cta.b64 _, [%0], %1;" ::"r"(b), "r"(n) : "memory");
}
__device__ __forceinline__ void mbar_arrive_peer(uint32_t b_cluster) {
    asm volatile("mbarrier.arrive.relaxed.cluster.shared::cluster.b64 _, [%0];" ::"r"(b_cluster) : "memory");
}
__device__ __forceinline__ void mbar_wait(uint32_t b, uint32_t parity) {
    asm volatile("{\n\t.reg .pred p;\n\t.reg .u32 c;\n\tmov.u32 c, 0;\n"
                 "W:\n\tmbarrier.try_wait.parity.shared::cta.b64 p, [%0], %1;\n\t@p bra D;\n\t"
                 "add.u32 c, c, 1;\n\tsetp.lt.u32 p, c, 1048576;\n\t@p bra W;\n\ttrap;\nD:\n\t}"
                 ::"r"(b), "r"(parity) : "memory");
}
__device__ __forceinline__ bool mbar_test(uint32_t b, uint32_t parity) {
    uint32_t ok;
    asm volatile("{ .reg .pred p; mbarrier.test_wait.parity.shared::cta.b64 p, [%1], %2; selp.u32 %0, 1, 0, p; }" : "=r"(ok) : "r"(b), "r"(parity) : "memory");
    return __all_sync(0xffffffffu, ok != 0);
}
__device__ __forceinline__ bool elect_one() {
    uint32_t p;
    asm volatile("{ .reg .pred P; elect.sync _|P, 0xffffffff; selp.u32 %0, 1, 0, P; }" : "=r"(p));
    return p != 0;
}
__device__ __forceinline__ uint32_t mapa(uint32_t a, uint32_t rank) {
    uint32_t r;
    asm("mapa.shared::cluster.u32 %0, %1, %2;" : "=r"(r) : "r"(a), "r"(rank));
    return r;
}
__device__ __forceinline__ void cluster_arrive() { asm volatile("barrier.cluster.arrive.relaxed.aligned;" ::: "memory"); }
__device__ __forceinline__ void cluster_wait() { asm volatile("barrier.cluster.wait.acquire.aligned;" ::: "memory"); }
__device__ __forceinline__ void tma_load_2d(uint32_t dst, const CUtensorMap* m, int c0, int c1, uint32_t bar) {
    asm volatile("cp.async.bulk.tensor.2d.shared::cluster.global.mbarrier::complete_tx::bytes [%0], [%1, {%3, %4}], [%2];"
                 ::"r"(dst), "l"(m), "r"(bar), "r"(c0), "r"(c1) : "memory");
}
__device__ __forceinline__ void tma_load_perm(uint32_t dst, const CUtensorMap* m, int c0, int blk, uint32_t bar) {
    asm volatile("cp.async.bulk.tensor.5d.shared::cluster.global.mbarrier::complete_tx::bytes [%0], [%1, {%3, %4, %4, %4, %5}], [%2];"
                 ::"r"(dst), "l"(m), "r"(bar), "r"(c0), "r"(0), "r"(blk) : "memory");
}
__device__ __forceinline__ void tma_load_tile(uint32_t dst, const CUtensorMap* m, int c0, int c2, int c3, uint32_t bar) {
    asm volatile("cp.async.bulk.tensor.4d.shared::cluster.global.mbarrier::complete_tx::bytes.multicast::cluster [%0], [%1, {%3, %4, %5, %6}], [%2], %7;"
                 ::"r"(dst), "l"(m), "r"(bar), "r"(c0), "r"(0), "r"(c2), "r"(c3), "h"((uint16_t)3) : "memory");
}
__device__ __forceinline__ void tma_store_tile(const CUtensorMap* m, uint32_t src, int c0, int c2, int c3) {
    asm volatile("cp.async.bulk.tensor.4d.global.shared::cta.bulk_group [%0, {%2, %3, %4, %5}], [%1];"
                 ::"l"(m), "r"(src), "r"(c0), "r"(0), "r"(c2), "r"(c3) : "memory");
    asm volatile("cp.async.bulk.commit_group;" ::: "memory");
}
__device__ __forceinline__ void bulk_g2s(uint32_t dst, const void* src, uint32_t bytes, uint32_t bar) {
    asm volatile("cp.async.bulk.shared::cluster.global.mbarrier::complete_tx::bytes [%0], [%1], %2, [%3];"
                 ::"r"(dst), "l"(src), "r"(bytes), "r"(bar) : "memory");
}
__device__ __forceinline__ void cp_async16(uint32_t dst, const void* src) {
    asm volatile("cp.async.cg.shared.global [%0], [%1], 16;" ::"r"(dst), "l"(src) : "memory");
}
__device__ __forceinline__ void st_async128(uint32_t dst_cluster, uint32_t x, uint32_t y, uint32_t z, uint32_t w, uint32_t bar_cluster) {
    asm volatile("st.async.weak.shared::cluster.mbarrier::complete_tx::bytes.v4.b32 [%0], {%1,%2,%3,%4}, [%5];"
                 ::"r"(dst_cluster), "r"(x), "r"(y), "r"(z), "r"(w), "r"(bar_cluster) : "memory");
}
__device__ __forceinline__ void fence_async() { asm volatile("fence.proxy.async.shared::cta;" ::: "memory"); }
__device__ __forceinline__ void named_sync(int id, int n) { asm volatile("bar.sync %0, %1;" ::"r"(id), "r"(n) : "memory"); }

__device__ __forceinline__ void ldsm4(uint32_t* r, uint32_t a) {
    asm volatile("ldmatrix.sync.aligned.m8n8.x4.shared.b16 {%0,%1,%2,%3}, [%4];"
                 : "=r"(r[0]), "=r"(r[1]), "=r"(r[2]), "=r"(r[3]) : "r"(a));
}
__device__ __forceinline__ void ldsm4t(uint32_t* r, uint32_t a) {
    asm volatile("ldmatrix.sync.aligned.m8n8.x4.trans.shared.b16 {%0,%1,%2,%3}, [%4];"
                 : "=r"(r[0]), "=r"(r[1]), "=r"(r[2]), "=r"(r[3]) : "r"(a));
}
__device__ __forceinline__ void stsm4t(uint32_t a, uint32_t x, uint32_t y, uint32_t z, uint32_t w) {
    asm volatile("stmatrix.sync.aligned.m8n8.x4.trans.shared.b16 [%0], {%1,%2,%3,%4};"
                 ::"r"(a), "r"(x), "r"(y), "r"(z), "r"(w) : "memory");
}
__device__ __forceinline__ uint32_t lds32(uint32_t a) { uint32_t v; asm volatile("ld.shared.u32 %0, [%1];" : "=r"(v) : "r"(a)); return v; }
__device__ __forceinline__ float lds32f(uint32_t a) { float v; asm volatile("ld.shared.f32 %0, [%1];" : "=f"(v) : "r"(a)); return v; }
__device__ __forceinline__ uint2 lds64(uint32_t a) { uint2 v; asm volatile("ld.shared.v2.u32 {%0,%1}, [%2];" : "=r"(v.x), "=r"(v.y) : "r"(a)); return v; }
__device__ __forceinline__ uint4 lds128(uint32_t a) {
    uint4 v; asm volatile("ld.shared.v4.u32 {%0,%1,%2,%3}, [%4];" : "=r"(v.x), "=r"(v.y), "=r"(v.z), "=r"(v.w) : "r"(a)); return v;
}
__device__ __forceinline__ uint4 lds128v(uint32_t a) {
    uint4 v; asm volatile("ld.volatile.shared.v4.u32 {%0,%1,%2,%3}, [%4];" : "=r"(v.x), "=r"(v.y), "=r"(v.z), "=r"(v.w) : "r"(a)); return v;
}
__device__ __forceinline__ uint32_t or_xor(uint32_t a, uint32_t b, uint32_t c) {
    uint32_t r; asm("lop3.b32 %0, %1, %2, %3, 0xf6;" : "=r"(r) : "r"(a), "r"(b), "r"(c)); return r;
}
__device__ __forceinline__ float4 lds128f(uint32_t a) {
    float4 v; asm volatile("ld.shared.v4.f32 {%0,%1,%2,%3}, [%4];" : "=f"(v.x), "=f"(v.y), "=f"(v.z), "=f"(v.w) : "r"(a)); return v;
}
__device__ __forceinline__ void sts32(uint32_t a, uint32_t v) { asm volatile("st.shared.u32 [%0], %1;" ::"r"(a), "r"(v) : "memory"); }
__device__ __forceinline__ void sts32f(uint32_t a, float v) { asm volatile("st.shared.f32 [%0], %1;" ::"r"(a), "f"(v) : "memory"); }
__device__ __forceinline__ void sts64(uint32_t a, uint32_t x, uint32_t y) { asm volatile("st.shared.v2.u32 [%0], {%1,%2};" ::"r"(a), "r"(x), "r"(y) : "memory"); }
__device__ __forceinline__ void sts64f(uint32_t a, float x, float y) { asm volatile("st.shared.v2.f32 [%0], {%1,%2};" ::"r"(a), "f"(x), "f"(y) : "memory"); }
__device__ __forceinline__ void sts128(uint32_t a, uint32_t x, uint32_t y, uint32_t z, uint32_t w) {
    asm volatile("st.shared.v4.u32 [%0], {%1,%2,%3,%4};" ::"r"(a), "r"(x), "r"(y), "r"(z), "r"(w) : "memory");
}
__device__ __forceinline__ void sts128f(uint32_t a, const float* v) {
    asm volatile("st.shared.v4.f32 [%0], {%1,%2,%3,%4};" ::"r"(a), "f"(v[0]), "f"(v[1]), "f"(v[2]), "f"(v[3]) : "memory");
}
__device__ __forceinline__ uint4 ldg128(const void* p) {
    uint4 v; asm volatile("ld.global.nc.L1::no_allocate.v4.u32 {%0,%1,%2,%3}, [%4];" : "=r"(v.x), "=r"(v.y), "=r"(v.z), "=r"(v.w) : "l"(p)); return v;
}
__device__ __forceinline__ uint2 ldg64(const void* p) {
    uint2 v; asm volatile("ld.global.nc.L1::no_allocate.v2.u32 {%0,%1}, [%2];" : "=r"(v.x), "=r"(v.y) : "l"(p)); return v;
}
__device__ __forceinline__ uint32_t ldg32(const void* p) {
    uint32_t v; asm volatile("ld.global.nc.u32 %0, [%1];" : "=r"(v) : "l"(p)); return v;
}
__device__ __forceinline__ uint32_t ldg16(const void* p) {
    uint32_t v; asm volatile("ld.global.nc.u16 %0, [%1];" : "=r"(v) : "l"(p)); return v;
}
__device__ __forceinline__ uint4 ld_relaxed_128(const void* p) {
    uint4 v; asm volatile("ld.relaxed.gpu.global.v4.u32 {%0,%1,%2,%3}, [%4];" : "=r"(v.x), "=r"(v.y), "=r"(v.z), "=r"(v.w) : "l"(p) : "memory"); return v;
}
__device__ __forceinline__ void ld_relaxed_128_unless(uint4& q, const void* p, bool have) {
    asm volatile("{ .reg .pred p; setp.eq.u32 p, %5, 0; @p ld.relaxed.gpu.global.v4.u32 {%0,%1,%2,%3}, [%4]; }"
                 : "+r"(q.x), "+r"(q.y), "+r"(q.z), "+r"(q.w) : "l"(p), "r"((uint32_t)have) : "memory");
}
__device__ __forceinline__ uint2 ld_relaxed_64(const void* p) {
    uint2 v; asm volatile("ld.relaxed.gpu.global.v2.u32 {%0,%1}, [%2];" : "=r"(v.x), "=r"(v.y) : "l"(p) : "memory"); return v;
}
__device__ __forceinline__ uint32_t ld_relaxed_32(const void* p) {
    uint32_t v; asm volatile("ld.relaxed.gpu.global.u32 %0, [%1];" : "=r"(v) : "l"(p) : "memory"); return v;
}
__device__ __forceinline__ void st_relaxed_128(void* p, uint32_t x, uint32_t y, uint32_t z, uint32_t w) {
    asm volatile("st.relaxed.gpu.global.v4.u32 [%0], {%1,%2,%3,%4};" ::"l"(p), "r"(x), "r"(y), "r"(z), "r"(w) : "memory");
}
__device__ __forceinline__ void st_relaxed_64(void* p, uint32_t x, uint32_t y) {
    asm volatile("st.relaxed.gpu.global.v2.u32 [%0], {%1,%2};" ::"l"(p), "r"(x), "r"(y) : "memory");
}
__device__ __forceinline__ void st_relaxed_32(void* p, uint32_t v) {
    asm volatile("st.relaxed.gpu.global.u32 [%0], %1;" ::"l"(p), "r"(v) : "memory");
}
__device__ __forceinline__ void red_add(void* p, uint32_t v) { asm volatile("red.relaxed.gpu.global.add.u32 [%0], %1;" ::"l"(p), "r"(v) : "memory"); }
__device__ __forceinline__ uint32_t now_ns() { uint32_t t; asm volatile("mov.u32 %0, %%globaltimer_lo;" : "=r"(t) :: "memory"); return t; }
__device__ __forceinline__ void spin_guard(uint32_t& it) { if (++it > SPIN_LIMIT) __trap(); }
__device__ __forceinline__ void wait_count(const uint32_t* p, uint32_t target) {
#pragma unroll 1
    for (uint32_t it = 0; __any_sync(0xffffffffu, (int)(ld_relaxed_32(p) - target) < 0); spin_guard(it)) { }
}
__device__ __forceinline__ void mma_bf16(float* c, uint32_t a0, uint32_t a1, uint32_t a2, uint32_t a3, uint32_t b0, uint32_t b1) {
    asm("mma.sync.aligned.m16n8k16.row.col.f32.bf16.bf16.f32 {%0,%1,%2,%3}, {%4,%5,%6,%7}, {%8,%9}, {%0,%1,%2,%3};"
                 : "+f"(c[0]), "+f"(c[1]), "+f"(c[2]), "+f"(c[3]) : "r"(a0), "r"(a1), "r"(a2), "r"(a3), "r"(b0), "r"(b1));
}
__device__ __forceinline__ void mma_bf16_k8(float* c, uint32_t a0, uint32_t a1, uint32_t b0) {
    asm("mma.sync.aligned.m16n8k8.row.col.f32.bf16.bf16.f32 {%0,%1,%2,%3}, {%4,%5}, {%6}, {%0,%1,%2,%3};"
                 : "+f"(c[0]), "+f"(c[1]), "+f"(c[2]), "+f"(c[3]) : "r"(a0), "r"(a1), "r"(b0));
}
__device__ __forceinline__ void mma_v(float* c, const uint32_t* a, uint32_t b0, uint32_t b1) {
    asm volatile("mma.sync.aligned.m16n8k16.row.col.f32.bf16.bf16.f32 {%0,%1,%2,%3}, {%4,%5,%6,%7}, {%8,%9}, {%0,%1,%2,%3};"
                 : "+f"(c[0]), "+f"(c[1]), "+f"(c[2]), "+f"(c[3]) : "r"(a[0]), "r"(a[1]), "r"(a[2]), "r"(a[3]), "r"(b0), "r"(b1));
}
__device__ __forceinline__ void mma_bf16_z(float* c, uint32_t a0, uint32_t a1, uint32_t a2, uint32_t a3, uint32_t b0, uint32_t b1) {
    asm volatile("mma.sync.aligned.m16n8k16.row.col.f32.bf16.bf16.f32 {%0,%1,%2,%3}, {%4,%5,%6,%7}, {%8,%9}, {%10,%10,%10,%10};"
        : "=f"(c[0]), "=f"(c[1]), "=f"(c[2]), "=f"(c[3]) : "r"(a0), "r"(a1), "r"(a2), "r"(a3), "r"(b0), "r"(b1), "f"(0.f));
}
__device__ __forceinline__ void mma_f16(float* c, uint32_t a0, uint32_t a1, uint32_t a2, uint32_t a3, uint32_t b0, uint32_t b1) {
    asm("mma.sync.aligned.m16n8k16.row.col.f32.f16.f16.f32 {%0,%1,%2,%3}, {%4,%5,%6,%7}, {%8,%9}, {%0,%1,%2,%3};"
                 : "+f"(c[0]), "+f"(c[1]), "+f"(c[2]), "+f"(c[3]) : "r"(a0), "r"(a1), "r"(a2), "r"(a3), "r"(b0), "r"(b1));
}
__device__ __forceinline__ uint32_t pack_bf16(float lo, float hi) {
    uint32_t r; asm("cvt.rn.bf16x2.f32 %0, %1, %2;" : "=r"(r) : "f"(hi), "f"(lo)); return r;
}
__device__ __forceinline__ uint32_t pack_v(float lo, float hi) {
    uint32_t r; asm volatile("cvt.rn.bf16x2.f32 %0, %1, %2;" : "=r"(r) : "f"(hi), "f"(lo)); return r;
}
__device__ __forceinline__ uint32_t pack_w(float lo, float hi) {
    uint32_t r; asm volatile("cvt.rn.satfinite.bf16x2.f32 %0, %1, %2;" : "=r"(r) : "f"(hi), "f"(lo)); return r;
}
template <int N> __device__ __forceinline__ uint32_t after_all(const uint32_t (&f)[N][4], uint32_t zero) {
    uint32_t d[3] = {0, 0, 0};
#pragma unroll
    for (int i = 0; i < N; i++) d[i % 3] |= f[i][3];
    return (d[0] | d[1] | d[2]) & zero;
}
__device__ __forceinline__ void pin(uint32_t& x) { asm volatile("" : "+r"(x)); }
template <class T> __device__ __forceinline__ void pin(T*& x) { asm volatile("" : "+l"(x)); }
__device__ __forceinline__ uint32_t pack_f16(float lo, float hi) {
    uint32_t r; asm("cvt.rn.f16x2.f32 %0, %1, %2;" : "=r"(r) : "f"(hi), "f"(lo)); return r;
}
__device__ __forceinline__ float bf_lo(uint32_t v) { return __uint_as_float(v << 16); }
__device__ __forceinline__ float bf_hi(uint32_t v) { return __uint_as_float(v & 0xffff0000u); }
__device__ __forceinline__ float bf_round(float x) { return __uint_as_float(pack_bf16(0.f, x)); }
__device__ __forceinline__ uint32_t badd2(uint32_t a, uint32_t b) { uint32_t r; asm("add.rn.bf16x2 %0, %1, %2;" : "=r"(r) : "r"(a), "r"(b)); return r; }
__device__ __forceinline__ uint32_t bsub2_lo(uint32_t a, uint32_t b) {
    uint32_t r; asm("{ .reg .b16 m, h; .reg .b32 m2; mov.b32 {m, h}, %2; mov.b32 m2, {m, m}; sub.rn.bf16x2 %0, %1, m2; }" : "=r"(r) : "r"(a), "r"(b)); return r;
}
__device__ __forceinline__ uint32_t bmax2(uint32_t a, uint32_t b) { uint32_t r; asm("max.bf16x2 %0, %1, %2;" : "=r"(r) : "r"(a), "r"(b)); return r; }
__device__ __forceinline__ uint32_t normalize2(uint32_t x, uint32_t s0, uint32_t s1) {
    uint32_t r;
    asm("{ .reg .b16 m, h, l, k; .reg .b32 m2, h2, l2, d, t;\n\t"
        "mov.b32 {m, h}, %2; mov.b32 {l, k}, %3; mov.b32 m2, {m, m}; mov.b32 h2, {h, h}; mov.b32 l2, {l, l};\n\t"
        "sub.rn.bf16x2 d, %1, m2; mul.rn.bf16x2 t, d, l2; fma.rn.bf16x2 %0, d, h2, t; }" : "=r"(r) : "r"(x), "r"(s0), "r"(s1));
    return r;
}
__device__ __forceinline__ float rcpf(float x) { float r; asm("rcp.approx.ftz.f32 %0, %1;" : "=f"(r) : "f"(x)); return r; }
__device__ __forceinline__ float sqrtaf(float x) { float r; asm("sqrt.approx.ftz.f32 %0, %1;" : "=f"(r) : "f"(x)); return r; }
__device__ __forceinline__ float ex2f(float x) { float r; asm("ex2.approx.ftz.f32 %0, %1;" : "=f"(r) : "f"(x)); return r; }

__device__ __forceinline__ int tok_off(int t) { return ((t >> 3) & 1) * VT_PLANE + (t >> 4) * 16 + (t & 7) * 2; }

__device__ __forceinline__ uint32_t order_key(uint32_t b16) { return b16 ^ ((b16 & 0x8000u) ? 0xffffu : 0x8000u); }
__device__ __forceinline__ uint32_t unorder_key(uint32_t k16) { return k16 ^ ((k16 & 0x8000u) ? 0x8000u : 0xffffu); }

struct cplx { float r, i; };
struct hc { uint32_t r, i; };
template <bool CONJ> __device__ __forceinline__ cplx csq(cplx a) {
    float im;
    asm("{ .reg .f32 t; mul.ftz.f32 t, %1, %2; mul.ftz.f32 %0, t, 0f40000000; }" : "=f"(im) : "f"(CONJ ? -a.r : a.r), "f"(a.i));
    return {fmaf(a.r, a.r, -(a.i * a.i)), im};
}
__device__ __forceinline__ cplx cexpp(float a2, float ai) {
    float m = ex2f(a2), s, c;
    __sincosf(ai, &s, &c);
    return {m * c, m * s};
}
__device__ __forceinline__ __half2 as_h2(uint32_t x) { return *reinterpret_cast<__half2*>(&x); }
__device__ __forceinline__ uint32_t as_u(__half2 x) { return *reinterpret_cast<uint32_t*>(&x); }
__device__ __forceinline__ hc hmul(hc a, hc b) {
    return {as_u(__hfma2(as_h2(a.r), as_h2(b.r), __hneg2(__hmul2(as_h2(a.i), as_h2(b.i))))),
            as_u(__hfma2(as_h2(a.r), as_h2(b.i), __hmul2(as_h2(a.i), as_h2(b.r))))};
}
__device__ __forceinline__ hc hpack(cplx a, cplx b) { return {pack_f16(a.r, b.r), pack_f16(a.i, b.i)}; }
__device__ __forceinline__ void sts16(uint32_t a, uint32_t v) { asm volatile("st.shared.u16 [%0], %1;" ::"r"(a), "r"(v) : "memory"); }

struct KgenAddr {
    uint32_t l, h, m2, m3, m4, z, w, wz;
    __device__ __forceinline__ KgenAddr(uint32_t scr, int lane) {
        const int g = lane >> 2, t = lane & 3;
        const uint32_t rec = scr + t * 480;
        l = rec + 16 * g; h = rec + 128 + 8 * g; m2 = rec + 192 + 8 * (g & 1); m3 = rec + 208 + 4 * (g & 2); m4 = rec + 224 + 2 * (g & 4);
        z = scr + 7680 + 16 * t; w = scr + 240 * lane; wz = scr + 7680 + 8 * lane;
        pin(l); pin(h); pin(m2); pin(m3); pin(m4); pin(z); pin(w); pin(wz);
    }
    __device__ __forceinline__ uint32_t any() const { return (l | h | m2) | (m3 | m4 | z) | (w | wz); }
};
template <class Hook, class Hook2>
__device__ __forceinline__ void kgen(const KgenAddr& ad, uint32_t tab, int lane, uint2 la, uint2 aim, uint2 cre, uint2 cim, float dt, float skip, int dch, Hook main_done, Hook2 half_done) {
    const int g = lane >> 2, t = lane & 3;
    const float dt2 = 2.f * dt;
    const uint32_t am = bmax2(bmax2(cre.x & 0x7fff7fffu, cre.y & 0x7fff7fffu), bmax2(cim.x & 0x7fff7fffu, cim.y & 0x7fff7fffu));
    const float mx = dt2 * fmaxf(bf_lo(am), bf_hi(am));
    const uint32_t eb = min(max(__reduce_max_sync(0xffffffffu, __float_as_uint(mx)) >> 23, 1u), 252u);
    const float cscale = dt2 * __uint_as_float((253u - eb) << 23);
    const float scale_inv = __uint_as_float((eb + 1u) << 23);
    float k0 = (bf_lo(cre.x) + bf_hi(cre.x)) + (bf_lo(cre.y) + bf_hi(cre.y));
#pragma unroll
    for (int o = 16; o; o >>= 1) k0 += __shfl_xor_sync(0xffffffffu, k0, o);
    const float ndt = -1.4426950408889634f * dt;
    STAMP(40); KSTAMP(0);

    float acc[5][4];
#pragma unroll
    for (int i = 0; i < 5; i++) { acc[i][0] = acc[i][1] = acc[i][2] = acc[i][3] = 0.f; }

#pragma unroll kBbUnroll
    for (int bb = 0; bb < 2; bb++) {
        cplx z[2][11], cz[2];
#pragma unroll
        for (int e = 0; e < 2; e++) {
            const float lg = e ? bf_hi(la.x) : bf_lo(la.x), ai = (e ? bf_hi(aim.x) : bf_lo(aim.x)) * dt;
            const float cr = (e ? bf_hi(cre.x) : bf_lo(cre.x)) * cscale, ci = (e ? bf_hi(cim.x) : bf_lo(cim.x)) * cscale;
            const float a2 = bf_round(ex2f(lg * 1.4426950408889634f)) * ndt;
            z[e][0] = cexpp(a2, ai);
            z[e][5] = cexpp(a2 * 32.f, ai * -32.f);
#pragma unroll
            for (int i = 1; i < 11; i++) if (i != 5) z[e][i] = (i == 3 || i == 7) ? csq<true>(z[e][i - 1]) : csq<false>(z[e][i - 1]);
            cz[e] = {fmaf(cr, z[e][0].r, -(ci * z[e][0].i)), fmaf(cr, z[e][0].i, ci * z[e][0].r)};
        }
        la.x = la.y; aim.x = aim.y; cre.x = cre.y; cim.x = cim.y;
        const hc z1 = hpack(z[0][0], z[1][0]), z2 = hpack(z[0][1], z[1][1]), z4 = hpack(z[0][2], z[1][2]);
        hc L[8], H[8];
        L[1] = hpack(z[0][3], z[1][3]); L[2] = hpack(z[0][4], z[1][4]); L[4] = hpack(z[0][5], z[1][5]);
        const hc y64 = hpack(z[0][6], z[1][6]), z128 = hpack(z[0][7], z[1][7]), z256 = hpack(z[0][8], z[1][8]);
        const hc z512 = hpack(z[0][9], z[1][9]), z1024 = hpack(z[0][10], z[1][10]);
        H[0] = hpack(cz[0], cz[1]);
        H[1] = hmul(H[0], z1); H[2] = hmul(H[0], z2); H[3] = hmul(H[1], z2);
        L[3] = hmul(L[1], L[2]);
#pragma unroll
        for (int i = 0; i < 4; i++) { H[4 + i] = hmul(H[i], z4); if (i) L[4 + i] = hmul(L[i], L[4]); }
        __syncwarp();
        sts128(ad.w, 0x3c003c00u, y64.r, 0u, y64.i);
#pragma unroll
        for (int i = 1; i < 8; i++) { const hc q = hmul(L[i], y64); sts128(ad.w + 16 * i, L[i].r, q.r, L[i].i, q.i); }
#pragma unroll
        for (int i = 0; i < 4; i++) sts128(ad.w + 128 + 16 * i, H[2 * i].r, H[2 * i].i, H[2 * i + 1].r, H[2 * i + 1].i);
        {
            const hc a = hmul(z256, z1), b = hmul(z256, z128), c = hmul(z256, z2), d = hmul(z512, z4);
            sts128(ad.w + 192, a.r, a.i, b.r, b.i);
            sts128(ad.w + 208, c.r, c.i, z512.r, z512.i);
            sts128(ad.w + 224, d.r, d.i, z1024.r, z1024.i);
            sts64(ad.wz, z128.r, z128.i);
        }
        __syncwarp();
        KSTAMP(1 + 2 * bb);
#pragma unroll kKgUnroll
        for (int k2 = 0; k2 < 4; k2++) {
#pragma unroll
            for (uint32_t s = 0; s < 2; s++) {
                const uint32_t o = k2 * 1920 + s * 240;
                const uint4 l = lds128(ad.l + o);
                const uint2 h0 = lds64(ad.h + o), m2 = lds64(ad.m2 + o), m3 = lds64(ad.m3 + o), m4 = lds64(ad.m4 + o), mz = lds64(ad.z + k2 * 64 + s * 8);
                const hc H0 = {h0.x, h0.y};
                const hc H1 = hmul(H0, {mz.x, mz.y}), H2 = hmul(H0, {m2.x, m2.y}), H3 = hmul(H2, {m3.x, m3.y}), H4 = hmul(H3, {m4.x, m4.y});
                mma_f16(acc[0], l.x, l.y, l.z, l.w, H0.r, H0.i);
                mma_f16(acc[1], l.x, l.y, l.z, l.w, H1.r, H1.i);
                mma_f16(acc[2], l.x, l.y, l.z, l.w, H2.r, H2.i);
                mma_f16(acc[3], l.x, l.y, l.z, l.w, H3.r, H3.i);
                mma_f16(acc[4], l.x, l.y, l.z, l.w, H4.r, H4.i);
            }
        }
        KSTAMP(2 + 2 * bb);
        if (bb == 0) half_done();
    }
    __syncwarp();
    main_done();
    KSTAMP(5);
#pragma unroll
    for (int i = 0; i < 4; i++) sts128(tab + 2048 + 512 * i + 16 * lane, 0, 0, 0, 0);
    if (lane < 15) sts32(tab + 4 * lane, 0);
    __syncwarp();
    const uint32_t d0 = tab + T_DENSE + 4 + 8 * lane, src = (lane + 31) & 31;
    const uint32_t p0 = pack_bf16(fmaf(k0, dt2, skip), 0.f);
    uint32_t prev = p0;
#pragma unroll
    for (int i = 0; i < 4; i++) {
        const uint32_t pk = pack_bf16(acc[i >> 1][2 * (i & 1) + 1] * scale_inv, acc[i >> 1][2 * (i & 1)] * scale_inv);
        sts64(d0 + 256 * i, __byte_perm(pk, __shfl_sync(0xffffffffu, lane == 31 ? prev : pk, src), 0x5432), pk);
        prev = pk;
    }
    const uint32_t w0 = pack_bf16(acc[2][0] * scale_inv, acc[2][1] * scale_inv), w1 = pack_bf16(acc[2][2] * scale_inv, acc[2][3] * scale_inv);
    const uint32_t sa = (lane & 1) ? 0x5410u : 0x5454u, sb2 = (lane & 1) ? 0x1010u : 0x5410u;
#pragma unroll
    for (int hf = 0; hf < 2; hf++) {
        const uint32_t w = hf ? w1 : w0;
        const uint32_t pv = __shfl_sync(0xffffffffu, lane != 31 ? w : hf ? w0 : __byte_perm(prev, w1, 0x5410), src);
        sts64(d0 + 1024 + 256 * hf, __byte_perm(w, pv, sa), __byte_perm(w, pv, sb2));
        sts64(d0 + 1536 + 256 * hf, __byte_perm(w, pv, sa + 0x2222u), __byte_perm(w, pv, sb2 + 0x2222u));
    }
    const uint32_t d3 = tab + T_R2 + 160 + 320 * (t & 1) + 16 * (g >> 1) + 8 * (g & 1) + 4 * (t >> 1), d3n = d3 + (g >= 6 ? 32 : 0);
    const uint32_t d4 = tab + T_R3 + 80 + 160 * t + 4 * g, d4n = d4 + (g >= 6 ? 16 : 0);
    uint32_t p3;
#pragma unroll
    for (int hf = 0; hf < 2; hf++)
#pragma unroll
        for (int e = 0; e < 2; e++) {
            const float v3 = acc[3][2 * hf + e] * scale_inv;
            const uint32_t p4 = pack_bf16(acc[4][2 * hf + e] * scale_inv, 0.f);
            p3 = pack_bf16(v3, v3);
            sts16(d3 + 64 * hf + 160 * e, p3);
            sts16((hf ? d3n : d3) + 64 * hf + 160 * e + 18, p3);
            sts16(d4 + 32 * hf + 80 * e, p4);
            sts16((hf ? d4n : d4) + 32 * hf + 80 * e + 10, p4);
        }
    if (lane == 31) {
        const uint32_t k512 = __byte_perm(w1, 0, 0x3232);
        sts32(tab + T_DENSE, p0);
        sts64(tab + T_DENSE + 4 * 513, k512, k512); sts16(tab + T_DENSE + 4 * 515 + 2, k512);
        sts16(tab + T_PATCH + 4 * 17, p3); sts32(tab + T_PATCH + 4 * 18, p3); sts16(tab + T_PATCH + 4 * 19 + 2, p3);
    }
    __syncwarp();
}

__device__ __forceinline__ void load_toep(uint32_t* a, uint32_t p, uint32_t pz) {
    a[0] = lds32(p); a[1] = lds32(p + 32); a[2] = lds32(pz - 32); a[3] = lds32(pz);
}
#define YIELDS 2
#define YIELD_AT 2
#define DENSE_BLK 4
__device__ __forceinline__ void dense_step(float (&acc)[16][4], uint32_t (&R)[8][4], const uint32_t (&A)[4][4], uint32_t (&An)[4][4],
                                           uint32_t va, uint32_t vmin, uint32_t pn, uint32_t pz, uint32_t zero, int bit, uint32_t& junk) {
#pragma unroll
    for (int i0 = 0; i0 < 8; i0 += DENSE_BLK) {
#pragma unroll 1
        do {
#pragma unroll
            for (int i = i0; i < i0 + DENSE_BLK; i++) {
                const int ip = (i - DENSE_BLK) & 7;
                ldsm4(R[ip], ip == 0 ? max(va - 16, vmin) : va + ip * 128 - (i0 ? 16 : 0));
                if ((i & 1) == 0) load_toep(An[i >> 1], pn + (i >> 1) * 512, pz + (i >> 1) * 512);
#pragma unroll
                for (int ka = 0; ka < 4; ka++) {
                    mma_v(acc[i + ka], A[ka], R[i][0], R[i][1]);
                    if (i + 8 + ka < 16 - ABL_SKIP) mma_v(acc[i + 8 + ka], A[ka], R[i][2], R[i][3]);
                }
                if ((YIELDS >> (i - i0)) & 1) asm volatile("xor.b32 %0, %0, %1;" : "+r"(junk) : "r"(__float_as_uint(acc[i + YIELD_AT][0])));
            }
        } while (zero & (1u << (bit + i0)));
    }
}
#define FFA_BLK 0
template <int F>
__device__ __forceinline__ void ffa_step(float (&acc)[16][4], float (&W)[8][4], uint32_t (&R)[8][4], uint32_t (&A)[4][4],
                                         uint32_t va, uint32_t vmin, uint32_t pb, uint32_t pz, uint32_t zero) {
    constexpr int S = F ^ 1;
    auto load = [&](int sh) {
#pragma unroll
        for (int i = S; i < 8; i += 2) ldsm4(R[i], i == 0 ? max(va - 16 * sh, vmin) : va - 16 * sh + i * 128);
#pragma unroll
        for (int k = S; k < 4; k += 2) load_toep(A[k], pb + 64 * sh + k * 512, pz + 64 * sh + k * 512);
    };
    auto prod = [&](int par, int dst) {
#pragma unroll
        for (int k = 0; k < 2; k++)
#pragma unroll
            for (int m = k; m < 8; m++) {
                const uint32_t* x = &R[2 * ((m - k) & 3) + par][2 * ((m - k) >> 2)];
                mma_v(dst == 1 ? W[m] : acc[2 * m + (dst >> 1)], A[2 * k + par], x[0], x[1]);
            }
    };
#pragma unroll 1
    do {
#pragma unroll 1
        do { load(0); prod(F, F); } while (FFA_BLK == 2 && (zero & (1u << (4 * F))));
#pragma unroll 1
        do {
            prod(S, S);
#pragma unroll
            for (int i = 0; i < 8; i++) A[(i >> 2) * 2 + F][i & 3] = badd2(A[(i >> 2) * 2][i & 3], A[(i >> 2) * 2 + 1][i & 3]);
#pragma unroll
            for (int i = 0; i < 16; i++) R[(i >> 2) * 2 + F][i & 3] = badd2(R[(i >> 2) * 2][i & 3], R[(i >> 2) * 2 + 1][i & 3]);
        } while (FFA_BLK == 2 && (zero & (2u << (4 * F))));
#pragma unroll 1
        do { load(1); prod(F, 2); } while (FFA_BLK == 2 && (zero & (4u << (4 * F))));
    } while (FFA_BLK == 1 && (zero & (8u << (4 * F))));
}
struct DenseTaps {
    uint32_t A[4][4], E[4], F[4], G[4];
    __device__ __forceinline__ DenseTaps(uint32_t pb, uint32_t pz) {
        constexpr int PP = T_PATCH - T_DENSE + 56;
        load_toep(E, pb + 2048, pz + 2048);
        load_toep(F, pb + PP, pz + PP);
        G[0] = lds32(pz + 2048 + 32); G[1] = lds32(pb + 2048 + 64); G[2] = lds32(pz + PP + 32); G[3] = lds32(pb + PP + 64);
    }
};
__device__ __forceinline__ uint32_t dense_phase(float (&acc)[16][4], uint32_t vmin, uint32_t va, uint32_t vo, uint32_t pb, DenseTaps& tp, uint32_t zero) {
    uint32_t R[8][4], A1[4][4], junk = 0;
    uint32_t pz = pb + zero;
    {
        uint32_t H[4][4];
#pragma unroll
        for (int i = 0; i < 4; i++) ldsm4(H[i], vo + i * 256);
#pragma unroll
        for (int i = 0; i < 8; i++) ldsm4(R[i], va + i * 128);
#pragma unroll
        for (int i = 0; i < 4; i++) load_toep(tp.A[i], pb + 512 * i, pz + 512 * i);
#pragma unroll
        for (int i = 0; i < 4; i++) mma_bf16_k8(acc[i + 4], tp.G[0], tp.G[1], H[i >> 1][2 * (i & 1) + 1]);
#pragma unroll
        for (int i = 0; i < 8; i++) mma_v(acc[i + 8], tp.G, H[i >> 1][2 * (i & 1)], H[i >> 1][2 * (i & 1) + 1]);
#pragma unroll
        for (int i = 0; i < 12; i++) mma_v(acc[i + 4], tp.E, R[i & 7][2 * (i >> 3)], R[i & 7][2 * (i >> 3) + 1]);
#pragma unroll
        for (int i = 0; i < 8; i++) mma_v(acc[i + 8], tp.F, R[i][0], R[i][1]);
    }
    float W[8][4];
#pragma unroll
    for (int i = 0; i < 32; i++) { W[i >> 2][i & 3] = 0.f; if (i >= 8) acc[2 * (i >> 2) + 1][i & 3] += acc[2 * (i >> 2)][i & 3]; }
#pragma unroll 1
    for (int rho = 0; rho < 8; rho += 2) {
        ffa_step<0>(acc, W, R, tp.A, va, vmin, pb, pz, zero);
        ffa_step<1>(acc, W, R, tp.A, va - 16, vmin, pb + 64, pz + 64, zero);
        pb += 128; pz += 128; va -= 32;
    }
#pragma unroll
    for (int i = 0; i < 32; i++) {
        const int m = i >> 2, j = i & 3;
        acc[2 * m + 1][j] = (acc[2 * m + 1][j] - acc[2 * m][j]) - W[m][j];
        if (m) acc[2 * m][j] += W[m - 1][j];
    }
    return __float_as_uint(W[7][0]) & zero;
}
__device__ __forceinline__ uint32_t ones2(int c, int lo, int hi) {
    return (((uint32_t)(c - lo) <= (uint32_t)(hi - lo)) ? 1u : 0u) | (((uint32_t)(c + 1 - lo) <= (uint32_t)(hi - lo)) ? 0x10000u : 0u);
}
__device__ __forceinline__ uint32_t box_bits(int lane) {
    const int d = 2 * (lane & 3) - (lane >> 2);
    auto four = [&](int L1, int H1, int L2, int H2) { return ones2(d, L1, H1) | ones2(d, L2, H2) << 1 | ones2(d + 8, L1, H1) << 2 | ones2(d + 8, L2, H2) << 3; };
    return four(5, 7, 0, 4) | four(1, 7, 0, 8) << 4;
}
struct Boxes {
    uint32_t q[4], ha[2];
    __device__ __forceinline__ Boxes(uint32_t bits, int k0, uint32_t h0, uint32_t h1) {
#pragma unroll
        for (int i = 0; i < 4; i++) q[i] = (bits & (0x10001u << (k0 + i))) * (0x3f80u >> (k0 + i));
        ha[0] = h0; ha[1] = h1;
    }
    __device__ __forceinline__ void load(int j, uint32_t* v, uint32_t zero) const {
        const uint32_t o = j * 128;
        v[0] = lds32(ha[0] + o); v[1] = lds32(ha[1] + zero + o); v[2] = lds32(ha[1] + o);
        v[3] = lds32(ha[0] + zero + o + 16); v[4] = lds32(ha[0] + o + 16); v[5] = lds32(ha[1] + o + 16);
    }
    __device__ __forceinline__ void sums(const uint32_t* v, float* Z, float* X, float* Y) const {
        mma_bf16_z(Z, q[0], q[1], q[2], q[3], v[0], v[1]);
        mma_bf16_z(X, q[0], q[1], q[2], q[3], v[2], v[3]);
        mma_bf16_z(Y, q[0], q[1], q[2], q[3], v[4], v[5]);
    }
};
__host__ __device__ constexpr int tail_step(int n) { return n < 8 ? n : n < 12 ? n + 4 : (n & 1) ? 11 - (n - 13) / 2 : 19 - (n - 12) / 2; }
template <class After>
__device__ __forceinline__ void tail_phase(float (&acc)[16][4], const Boxes& b2, const Boxes& b3, uint32_t tp2, uint32_t tp3, uint32_t zero, After after) {
    uint4 t2[5];
    uint2 t3[8];
    uint32_t v[6], a0[4], a1[4];
    float Z[4], X[4], Y[4];
    b2.load(0, v, zero);
#pragma unroll
    for (int i = 0; i < 5; i++) t2[i] = lds128(tp2 + 160 * i);
#pragma unroll
    for (int n = -1; n < 20; n++) {
        const int j = tail_step(n), j1 = tail_step(n + 1), j2 = tail_step(n + 2);
        if (n < 19) {
            (j1 < 12 ? b2 : b3).sums(v, Z, X, Y);
            if (n < 18) { if (j2 < 12) b2.load(j2, v, zero); else b3.load(j2 - 12, v, zero); }
        }
        if (n >= 0 && j < 12) {
#pragma unroll
            for (int b = 0; b < 5; b++) if (j + 4 + b < 16) mma_v(acc[j + 4 + b], a1, t2[b].z, t2[b].w);
        }
        if (n < 19 && j1 < 12) { a1[0] = pack_v(Z[0], Z[1]); a1[1] = pack_w(X[0], X[1]); a1[2] = pack_v(Z[2], Z[3]); a1[3] = pack_w(X[2], X[3]); }
        if (n == 6) {
#pragma unroll
            for (int b = 0; b < 8; b++) t3[b] = lds64(tp3 + 80 * b);
        }
        if (n >= 0 && j < 12) {
#pragma unroll
            for (int b = 0; b < 5; b++) if (j + 4 + b < 16) mma_v(acc[j + 4 + b], a0, t2[b].x, t2[b].y);
        } else if (n >= 0) {
#pragma unroll
            for (int b = 0; b < 8; b++) if (j - 4 + b < 16) mma_v(acc[j - 4 + b], a0, t3[b].x, t3[b].y);
        }
        if (n < 19) {
            if (j1 < 12) { a0[0] = pack_v(X[0], X[1]); a0[1] = pack_v(Y[0], Y[1]); a0[2] = pack_v(X[2], X[3]); a0[3] = pack_v(Y[2], Y[3]); }
            else { a0[0] = pack_v(X[0], X[1]); a0[1] = pack_v(Y[0], Y[1]); a0[2] = pack_v(Z[2], Z[3]); a0[3] = pack_v(X[2], X[3]); }
        }
        after(n);
    }
}
template <int Q>
__device__ __forceinline__ void emit(const float (&acc)[16][4], int h, uint32_t own, uint32_t peer, uint32_t bar, uint32_t bar_peer) {
    constexpr int n = 4 * Q, G = Q >> 1;
#pragma unroll
    for (int hf = 0; hf < 2; hf++)
        asm volatile("{ .reg .pred p; setp.eq.u32 p, %7, %8;\n\t@p st.shared.v4.u32 [%0], {%1,%2,%3,%4};\n\t"
                     "@!p st.async.weak.shared::cluster.mbarrier::complete_tx::bytes.v4.b32 [%5], {%1,%2,%3,%4}, [%6]; }"
                     ::"r"(own + G * 16384 + hf * 512), "r"(pack_bf16(acc[n][2 * hf], acc[n][2 * hf + 1])), "r"(pack_bf16(acc[n + 1][2 * hf], acc[n + 1][2 * hf + 1])),
                     "r"(pack_bf16(acc[n + 2][2 * hf], acc[n + 2][2 * hf + 1])), "r"(pack_bf16(acc[n + 3][2 * hf], acc[n + 3][2 * hf + 1])),
                     "r"(peer + G * 16384 + hf * 512), "r"(bar_peer + 8 * G), "r"(h), "n"(Q & 1) : "memory");
    __syncwarp();
    if (h == (Q & 1) && elect_one()) mbar_arrive(bar);
}
__device__ __forceinline__ uint32_t finish_src(uint32_t sb, int h, int w, int lane) {
    const int m = lane >> 3, r = lane & 7;
    return sb + OFF_XT + (h ^ 1) * 32768 + (2 * m + (r & 1)) * 1024 + (w >> 2) * 512 + (((8 * (w & 3) + (r & 4) + ((r >> 1) & 1)) ^ ((r & 1) << 1)) << 4);
}
__device__ __forceinline__ uint32_t finish_dst(uint32_t sb, int h, int w, int lane) {
    const int g = lane >> 2, t = lane & 3;
    return sb + OFF_XT + h * 32768 + w * 2048 + (g >> 1) * 512 + (t >> 1) * 144 + (2 * (t & 1) + (g & 1)) * 32;
}
__device__ __forceinline__ uint32_t tile_addr(uint32_t sb, int tok, int t) {
    return sb + OFF_XT + (tok & 512) * 64 + (tok >> 10) * 16384 + (tok & 14) * 1024 + (tok & 448) * 4 + (tok & 1) * 128 + (tok & 48) * 2 + (((t >> 1) ^ (tok & 1)) << 4) + (t & 1) * 8;
}
__device__ __forceinline__ uint2 add_update(uint2 o, uint32_t upd) {
    const float4 u = lds128f(upd);
    return make_uint2(badd2(o.x, pack_bf16(u.x, u.y)), badd2(o.y, pack_bf16(u.z, u.w)));
}
__device__ __forceinline__ void finish_half(uint32_t src, uint32_t xa, const uint4 (&x)[2]) {
    uint32_t s[2][4];
#pragma unroll
    for (int i = 0; i < 2; i++) ldsm4t(s[i], src ^ (i << 5));
#pragma unroll
    for (int i = 0; i < 2; i++) sts128(xa + i * 256, badd2(x[i].x, s[i][0]), badd2(x[i].y, s[i][1]), badd2(x[i].z, s[i][2]), badd2(x[i].w, s[i][3]));
}

__device__ __noinline__ float centred_var(uint32_t rows, float mu, int lane) {
    float var = 0.f;
#pragma unroll 1
    for (int rr = 0; rr < 16; rr++) {
        const float c0 = __shfl_sync(0xffffffffu, mu, rr);
        float c = 0.f;
#pragma unroll 1
        for (int k = 0; k < 16; k++) {
            const uint32_t q = lds32(rows + rr * ROW_PITCH + k * 128 + lane * 4);
            const float d0 = bf_lo(q) - c0, d1 = bf_hi(q) - c0;
            c = fmaf(d0, d0, fmaf(d1, d1, c));
        }
#pragma unroll 1
        for (int o = 16; o; o >>= 1) c += __shfl_xor_sync(0xffffffffu, c, o);
        if ((lane & 15) == rr) var = c * (1.f / DM);
    }
    return var;
}
__device__ __noinline__ float centred_score(uint32_t rows, uint32_t wbuf, uint32_t s0, uint32_t s1, int lane) {
    float sc = 0.f;
#pragma unroll 1
    for (int rr = 0; rr < 16; rr++) {
        const uint32_t t0 = __shfl_sync(0xffffffffu, s0, rr), t1 = __shfl_sync(0xffffffffu, s1, rr);
        float c = 0.f;
#pragma unroll 1
        for (int k = 0; k < 16; k++) {
            const uint32_t xn = normalize2(lds32(rows + rr * ROW_PITCH + k * 128 + lane * 4), t0, t1);
            const uint32_t wq = lds32(wbuf + (k >> 2) * 1024 + (k & 3) * 128 + lane * 4);
            c = fmaf(bf_lo(xn), bf_lo(wq), fmaf(bf_hi(xn), bf_hi(wq), c));
        }
#pragma unroll 1
        for (int o = 16; o; o >>= 1) c += __shfl_xor_sync(0xffffffffu, c, o);
        if ((lane & 15) == rr) sc = c;
    }
    return sc;
}

__device__ __forceinline__ void issue_rows(const __nv_bfloat16* u, uint32_t sb, int b) {
    if (elect_one()) {
        const uint32_t bar = sb + OFF_BAR + 8 * B_ROW;
#pragma unroll
        for (int j = 0; j < 4; j++) mbar_init(bar + 8 * j, 1);
        asm volatile("fence.mbarrier_init.release.cluster;" ::: "memory");
        fence_async();
#pragma unroll 1
        for (int j = 0; j < 4; j++) {
            mbar_expect_tx(bar + 8 * j, 8192);
#pragma unroll
            for (int i = 0; i < 4; i++) bulk_g2s(sb + OFF_VT + (4 * j + i) * ROW_PITCH, u + (size_t)(16 * b + 4 * j + i) * DM, 2048, bar + 8 * j);
        }
    }
    __syncwarp();
}

__global__ void __cluster_dims__(2, 1, 1) __launch_bounds__(NTHR, 1)
fused_kernel(const __grid_constant__ Ptrs p, const __grid_constant__ Maps maps) {
    extern __shared__ __align__(1024) unsigned char smem[];
    const int tid = threadIdx.x, lane = tid & 31;
    const int c_ = ((blockIdx.x >> 1) + PERM_OFF) & 63, b = 2 * ((c_ & 32) | ((c_ & 7) << 2) | ((c_ >> 3) & 3)) + (blockIdx.x & 1);
    const int dch = 8 * b + (tid >> 5) - 4;
    uint2 la, aim, cre, cim;
    uint32_t ldt16;
    if ((uint32_t)(tid - 128) < 256u) {
        la = ldg64(p.logA + dch * NMODE + 4 * lane); aim = ldg64(p.Aim + dch * NMODE + 4 * lane);
        cre = ldg64(p.Cre + dch * NMODE + 4 * lane); cim = ldg64(p.Cim + dch * NMODE + 4 * lane);
        ldt16 = ldg16(p.ldt + dch);
    }
    const uint32_t sb = s_u32(smem), bar0 = sb + OFF_BAR;
    const int warp = __shfl_sync(0xffffffffu, tid >> 5, 0);
    const int h = b & 1, cl = b >> 1;
    const int m = lane >> 3, r = lane & 7, g = lane >> 2, t = lane & 3;
    const bool has_gu = b < GU_CTAS;
    if (warp == 4) { STAMP(0); GSTAMP(24); }

    if (warp >= 12) {
        asm volatile("setmaxnreg.dec.sync.aligned.u32 " REG_S ";");
        const int a = warp - 12;
        uint32_t due = now_ns() + ST_T0 + (uint32_t)(128 * a + b) * ST_PER / 128 + (has_gu ? 0 : ST_LATE * (12 * ST_PER + 4 * ST_PER2) / 16);
        const bool el = elect_one();
        if (a == 1) issue_rows(p.u, sb, b);
        if (a == 2 && el) {
#pragma unroll
            for (int i = B_XT; i < NBAR; i++) mbar_init(bar0 + 8 * i, (i == B_V || i == B_SFREE || i == B_XFREE || i == B_OWN) ? 8 : i == B_RECV ? 9 : i == B_RED ? 5 : (i == B_UPD || (i >= B_FREE && i < B_FULL)) ? 4 : 1);
            asm volatile("fence.mbarrier_init.release.cluster;" ::: "memory");
            fence_async();
            mbar_expect_tx(bar0 + 8 * B_XT, 65536);
            mbar_expect_tx(bar0 + 8 * B_RECV, 8192);
            mbar_expect_tx(bar0 + 8 * B_RECV + 8, 8192);
            mbar_expect_tx(bar0 + 8 * B_RED, 2048);
        }
        if (a == 3 && el) {
#pragma unroll
            for (int i = 0; i < 5; i++) asm volatile("prefetch.tensormap [%0];" ::"l"(&maps.u + i) : "memory");
        }
        __syncwarp();
        cluster_arrive();
        cluster_wait();
        STAMP(18);
        mbar_wait(bar0 + 8 * (B_ROW + a), 0);
        if (el) {
#pragma unroll
            for (int i = 0; i < 4; i++)
                tma_load_tile(sb + OFF_XT + h * 32768 + a * 4096 + (i & 1) * 16384 + (i >> 1) * 2048, &maps.u, 16 * cl, 4 * a + (i & 2), 16 * (i & 1) + 8 * h, bar0 + 8 * B_XT);
        }
        if (el) {
#pragma unroll 1
            for (int k = has_gu ? 0 : 4; k < 6; k++) {
                const int i = 4 * k + a, s = k < 3 ? i : i - 12;
#pragma unroll 1
                for (int left; (left = (int)(due - now_ns())) > 0;) __nanosleep(left >> 1);
                due += k == 0 ? 4 * ST_PER + ST_GAP : k < 3 ? 4 * ST_PER : 4 * ST_PER2;
                const bool again = k >= 3 && has_gu;
                if (s >= 6 || again) mbar_wait(bar0 + 8 * (s < 10 || again ? B_FREE + s : B_V), slot_priv(s) && again);
                const uint32_t dst = sb + slot_off(s), bar = bar0 + 8 * (B_FULL + s);
                if (k < 4) {
                    mbar_expect_tx(bar, 8192);
                    tma_load_2d(dst, &maps.wg, 64 * cl, 512 * h + 32 * i, bar);
                    tma_load_2d(dst + 4096, &maps.wu, 64 * cl, 512 * h + 32 * i, bar);
                } else {
                    mbar_expect_tx(bar, 7168);
                    tma_load_perm(dst, &maps.wd, 16 * cl, 56 * h + 14 * a + 7 * (k & 1), bar);
                }
            }
            STAMP(19);
        }
        __syncwarp();
        {
            uint32_t fs = finish_src(sb, h, 2 * a, lane), fx = finish_dst(sb, h, 2 * a, lane);
#pragma unroll 1
            for (int G = 0; G < (Q2_HELP ? 2 - h : 1); G++) {
                if (G) mbar_wait(bar0 + 8 * B_OWN, 0);
                mbar_wait(bar0 + 8 * (B_RECV + G), 0);
#pragma unroll 1
                for (int k = 0; k < (G && Q2_HELP == 1 ? 1 : 2); k++) {
#pragma unroll
                    for (int i0 = 0; i0 < 4; i0 += FIN_ILP) {
                        uint32_t s[FIN_ILP][4];
                        uint4 x[FIN_ILP];
#pragma unroll
                        for (int i = i0; i < i0 + FIN_ILP; i++) {
                            ldsm4t(s[i - i0], (fs ^ ((i & 1) << 5)) + (i & 2) * 4096 + k * 128);
                            x[i - i0] = lds128((fx ^ ((i & 2) << 3)) + (i & 1) * 256 + k * 2048);
                        }
#pragma unroll
                        for (int i = i0; i < i0 + FIN_ILP; i++)
                            sts128((fx ^ ((i & 2) << 3)) + (i & 1) * 256 + k * 2048, badd2(x[i - i0].x, s[i - i0][0]), badd2(x[i - i0].y, s[i - i0][1]),
                                   badd2(x[i - i0].z, s[i - i0][2]), badd2(x[i - i0].w, s[i - i0][3]));
                    }
                    fence_async();
                    __syncwarp();
                    if (!(ABL & 2) && el) tma_store_tile(&maps.out, sb + OFF_XT + h * 32768 + G * 16384 + (2 * a + k) * 2048, 16 * cl, 4 * a + 2 * k, 16 * G + 8 * h);
                }
                fs += 16384; fx += 16384;
                if (G) STAMP(60); else if (h) STAMP(59); else STAMP(20);
            }
            const int tok = 2047 - (int)(lds32(sb + OFF_MISC + 48 + 8 * g) & 2047);
            const bool mine = (((tok >> 7) & 4) | ((tok >> 2) & 3)) == 4 * h + a && (tok < 1024 || (Q2_HELP && tok < 1536 && (Q2_HELP == 2 || !(tok & 2))));
            if (el) asm volatile("cp.async.bulk.wait_group 0;" ::: "memory");
            if (!(ABL & 1) && __any_sync(0xffffffffu, mine)) {
                const uint2 o0 = lds64(tile_addr(sb, tok, t));
                mbar_wait(bar0 + 8 * B_UPD, 0);
                const uint2 o1 = add_update(o0, sb + tab_off(g) + T_RED + 16 * t);
                if (mine) *reinterpret_cast<uint2*>(p.out + (size_t)tok * DM + 16 * cl + 4 * t) = o1;
            } else STAMP(62);
        }
    } else if (warp >= 4) {
        const int w = warp - 4;
        uint32_t dsk16 = ldg16(p.dsk + dch);
        cluster_arrive();
        asm volatile("setmaxnreg.inc.sync.aligned.u32 " REG_C ";");
        const uint32_t vrow = sb + OFF_VT + w * VT_PITCH + VT_PAD, tab = sb + tab_off(w);
        const uint32_t rb0 = bar0 + 8 * B_RECV, rb1 = mapa(rb0, h ^ 1);
        uint32_t tpo = 80 + (g - 2 * t) * 8 - (g < 2 * t ? 16 : 0);
        uint32_t xa = sb + OFF_XT + (w & 2) * 16384 + (w >> 2) * 16384 + (w & 1) * 1024 + (g >> 1) * 2048 + (g & 1) * 128 + t * 32 + ((h ^ (g & 1)) << 4);
        uint32_t va = sb + OFF_VT + (2 * m + (r & 1)) * VT_PITCH + VT_PAD + (16 * w + (r >> 1)) * 16;
        uint32_t qa = sb + OFF_ST + 2048 * w + 128 * t + 16 * (g ^ (2 * t));
        uint32_t vmin = vrow + (m & 1) * VT_PLANE - 16, vd = vmin + 16 + (m >> 1) * 1024 + r * 16;
        uint32_t vo = vrow + VT_PLANE + 496 - (m & 1) * 512 + (m >> 1) * 128 + r * 16, vz = vrow - VT_PAD + (lane >> 1) * VT_PLANE + (lane & 1) * 16;
        pin(vmin); pin(vd); pin(vo); pin(vz);
        pin(tpo); pin(xa); pin(va); pin(qa);
        uint32_t bits = box_bits(lane), h0 = vrow + 16 * g + tok_off(2 * t - 18), h1 = vrow + 16 * g + tok_off(2 * t - 10);
        pin(bits); pin(h0); pin(h1);
        const KgenAddr ka(sb + OFF_PRIV + w * 8192, lane);
        if (__any_sync(0xffffffffu, (vmin | (vd | vo | vz) | (tpo | xa) | (va | qa) | (bits | h0 | h1) | ka.any()) & p.zero)) __trap();
        cluster_wait();
        pin(la.x); pin(la.y); pin(aim.x); pin(aim.y); pin(cre.x); pin(cre.y); pin(cim.x); pin(cim.y); pin(ldt16); pin(dsk16);
        uint4 x[8];
        auto load_x = [&]() {
            mbar_wait(bar0 + 8 * B_XT, 0);
#pragma unroll
            for (int i = 0; i < 8; i++) x[i] = lds128(xa + (i & 1) * 8192 + (i >> 1) * 256);
        };
        kgen(ka, tab, lane, la, aim, cre, cim, bf_round(ex2f(bf_lo(ldt16) * 1.4426950408889634f)), 1.f + bf_lo(dsk16), dch, [&]() {
            STAMP(21);
            if (elect_one()) mbar_arrive_n(bar0 + 8 * (B_FREE + 6 + ((w >> 1) ^ 2)), 2);
        }, [&]() {
            if ((LN_PAUSE >> w) & 1) mbar_wait(bar0 + 8 * B_LN, 0);
        });
        STAMP(1); KSTAMP(6);
        const uint32_t pb = tab + T_DENSE + (g - 2 * t) * 4;
        DenseTaps dt(pb, pb + p.zero);
        {
            load_x();
            STAMP(47);
            mbar_wait(bar0 + 8 * (B_ST + (w >> 1)), 0);
            uint4 q[4];
#pragma unroll
            for (int n = 0; n < 4; n++) q[n] = lds128(qa + 512 * n);
            if (lane < 4) sts128(vz, 0, 0, 0, 0);
            STAMP(2); GSTAMP(28);
#pragma unroll
            for (int i = 0; i < 8; i++) {
                const uint32_t s0 = (i & 1) ? q[i >> 1].z : q[i >> 1].x, s1 = (i & 1) ? q[i >> 1].w : q[i >> 1].y;
                stsm4t(va + (i >> 1) * 64 + (i & 1) * VT_PLANE, normalize2(x[i].x, s0, s1), normalize2(x[i].y, s0, s1),
                       normalize2(x[i].z, s0, s1), normalize2(x[i].w, s0, s1));
            }
            __syncwarp();
            if (elect_one()) mbar_arrive(bar0 + 8 * B_V);
        }
        mbar_wait(bar0 + 8 * B_V, 0);
        STAMP(3); KSTAMP(7);
        float acc[16][4];
#pragma unroll
        for (int i = 0; i < 16; i++) { acc[i][0] = acc[i][1] = acc[i][2] = acc[i][3] = 0.f; }
        bits |= dense_phase(acc, vmin, vd, vo, pb, dt, p.zero);
        const Boxes b2(bits, 0, h0, h1), b3(bits, 4, (t == 1 ? h1 : h0) - 4, t == 1 ? h0 + 12 : h1 - 4);
        STAMP(4); KSTAMP(8);
        const uint32_t so = sb + OFF_XT + (8 * h + w) * 1024 + ((lane ^ ((w & 1) << 1)) << 4);
        const uint32_t dst0 = so + (h ^ 1) * 32768, dst1 = mapa(so + h * 32768, h ^ 1);
        tail_phase(acc, b2, b3, tab + T_R2 + 2 * tpo, tab + T_R3 + tpo, p.zero, [&](int j) {
            if (j == -1) {
                mbar_wait(bar0 + 8 * B_SFREE, 0);
                emit<0>(acc, h, dst0, dst1, rb0, rb1);
            }
            if (j == 3) { emit<1>(acc, h, dst0, dst1, rb0, rb1); STAMP(5); }
            if (j == 11) {
                mbar_wait(bar0 + 8 * B_XFREE, 0);
                emit<2>(acc, h, dst0, dst1, bar0 + 8 * B_OWN, rb1);
                STAMP(58);
            }
        });
        emit<3>(acc, h, dst0, dst1, bar0 + 8 * B_OWN, rb1);
        STAMP(30);
        if (h || Q2_HELP == 0 || (Q2_HELP == 1 && (w & 1))) {
        const uint32_t fs = finish_src(sb, h, w, lane) + 16384 + h * 8192, fx = (finish_dst(sb, h, w, lane) + 16384) ^ (h << 4);
        const int tok = 2047 - (int)(lds32(sb + OFF_MISC + 48 + 8 * g) & 2047);
        const bool mine = (((tok >> 6) & 24) | ((tok >> 1) & 7)) == 16 + 8 * h + w;
        const uint32_t ta = tile_addr(sb, tok, t);
        const uint4 x0[2] = {lds128(fx), lds128(fx + 256)}, x1[2] = {lds128(fx ^ 16), lds128((fx ^ 16) + 256)};
        mbar_wait(bar0 + 8 * B_OWN, 0);
        finish_half(fs, fx, x0);
        mbar_wait(bar0 + 8 * (B_RECV + 1), 0);
        STAMP(6);
        finish_half(fs + (h ? -8192 : 8192), fx ^ 16, x1);
        __syncwarp();
        if (!(ABL & 1) && __any_sync(0xffffffffu, mine)) {
            const uint2 o0 = lds64(ta);
            mbar_wait(bar0 + 8 * B_UPD, 0);
            const uint2 o1 = add_update(o0, sb + tab_off(g) + T_RED + 16 * t);
            if (mine) sts64(ta, o1.x, o1.y);
        }
        fence_async();
        __syncwarp();
        if (!(ABL & 4) && elect_one()) {
            tma_store_tile(&maps.out, sb + OFF_XT + h * 32768 + 16384 + w * 2048, 16 * cl, 2 * w, 16 + 8 * h);
            asm volatile("cp.async.bulk.wait_group.read 0;" ::: "memory");
        }
        STAMP(7);
        }
    } else {
        const int a = warp;
        const uint4 wq = ldg128(p.wr + 8 * tid);
        const uint32_t epoch = ld_relaxed_32(&p.sc->epoch);
        cluster_arrive();
        asm volatile("setmaxnreg.inc.sync.aligned.u32 " REG_A ";");
        const uint32_t tag = __shfl_sync(0xffffffffu, epoch, 0) + 1u, misc = sb + OFF_MISC, abar = bar0 + 8 * (B_AUX + a);
        uint32_t aph = 0;
        const Exchange* in = &p.sc->x[cl & (NREP - 1)];
        uint2* pub = p.sc->x[m >> 1].stat + 16 * b + 2 * (r ^ (2 * (b & 3))) + (m & 1);
        uint32_t* cnt_s = &p.sc->x[t].n_stat[b & 96];
        pin(pub); pin(cnt_s);
        if (tid < 64) sts32(sb + OFF_XCH + 4 * tid, 0);
        const uint32_t wbuf = sb + OFF_LN + a * 1024, part = sb + OFF_LN + 4096;
        {
            sts128(wbuf + 16 * lane, wq.x, wq.y, wq.z, wq.w);
            sts128(wbuf + 512 + 16 * lane, 0x3f803f80u, 0x3f803f80u, 0x3f803f80u, 0x3f803f80u);
            float wsum = ((bf_lo(wq.x) + bf_hi(wq.x)) + (bf_lo(wq.y) + bf_hi(wq.y))) + ((bf_lo(wq.z) + bf_hi(wq.z)) + (bf_lo(wq.w) + bf_hi(wq.w)));
#pragma unroll
            for (int o = 16; o; o >>= 1) wsum += __shfl_xor_sync(0xffffffffu, wsum, o);
            sts32f(part + 1024 + 4 * a, wsum);
            uint32_t wf[4][4];
#pragma unroll
            for (int i = 0; i < 4; i++) ldsm4(wf[i], wbuf + ((uint32_t)(r - 1) < 2u ? 16 * (r - 1) : 512) + 32 * m + 128 * i);
            uint32_t ra = sb + OFF_VT + r * ROW_PITCH + 512 * a + 16 * m, pa = part + a * 256 + g * 16;
            cluster_wait();
            STAMP(22);
#pragma unroll 1
            for (int hf = 0; hf < 2; hf++) {
                mbar_wait(bar0 + 8 * B_ROW + 16 * hf, 0);
                mbar_wait(bar0 + 8 * B_ROW + 16 * hf + 8, 0);
                STAMP(23);
                uint32_t x[8][4];
                float cs[2][4], q[8][4];
#pragma unroll
                for (int i = 0; i < 40; i++) (i < 8 ? cs[i >> 2 & 1] : q[(i - 8) >> 2 & 7])[i & 3] = 0.f;
#pragma unroll
                for (int k = 0; k < 8; k++) ldsm4(x[k], ra + k * 64);
                const bool more = __any_sync(0xffffffffu, after_all(x, p.zero));
#pragma unroll 1
                do {
#pragma unroll
                    for (int k = 0; k < 8; k++) {
                        mma_v(cs[k & 1], x[k], wf[k >> 1][2 * (k & 1)], wf[k >> 1][2 * (k & 1) + 1]);
#pragma unroll
                        for (int i = 0; i < 4; i++) mma_bf16_k8(q[4 * (k & 1) + i], x[k][i & 2], x[k][i | 1], x[k][i]);
                    }
                } while (more);
                const float c2 = cs[0][2] + cs[1][2];
                if (t == 0) sts64f(pa, (cs[0][0] + cs[1][0]) + c2, cs[0][1] + cs[1][1]);
                if (t == 1) sts32f(pa + 12, c2);
                const float e0 = ((q[0][0] + q[2][0]) + (q[4][0] + q[6][0])) + ((q[1][2] + q[3][2]) + (q[5][2] + q[7][2]));
                const float e1 = ((q[0][1] + q[2][1]) + (q[4][1] + q[6][1])) + ((q[1][3] + q[3][3]) + (q[5][3] + q[7][3]));
                if (t == (g >> 1)) sts32f(pa + 8, (g & 1) ? e1 : e0);
                ra += 8 * ROW_PITCH; pa += 128;
            }
        }
        STAMP(31);
        named_sync(1, 128);
        if (a == 0) {
            const uint32_t pa = part + (lane & 15) * 16;
            const float4 p0 = lds128f(pa), p1 = lds128f(pa + 256), p2 = lds128f(pa + 512), p3 = lds128f(pa + 768), ws = lds128f(part + 1024);
            const float mu = ((p0.x + p1.x) + (p2.x + p3.x)) * (1.f / DM);
            float var = ((p0.z + p1.z) + (p2.z + p3.z)) * (1.f / DM) - mu * mu;
            const bool centred = __any_sync(0xffffffffu, !(mu * mu <= 4.f * var));
            if (centred) var = centred_var(sb + OFF_VT, mu, lane);
            const float ri = rcpf(bf_round(sqrtaf(bf_round(bf_round(var) + 1e-5f))));
            const uint32_t s0 = pack_bf16(mu, ri), s1 = (pack_bf16(ri - bf_hi(s0), 0.f) & 0xfffcu) | (tag & 3);
            float sc = ((((p0.y + p1.y) + (p2.y + p3.y)) + ((p0.w + p1.w) + (p2.w + p3.w))) - bf_lo(s0) * ((ws.x + ws.y) + (ws.z + ws.w))) * ri;
            if (centred) sc = centred_score(sb + OFF_VT, sb + OFF_LN, s0, s1, lane);
            const uint32_t sb16 = pack_bf16(0.f, sc);
            const uint32_t s2 = s1 | (sb16 ^ (((uint32_t)((int)sb16 >> 31) & 0x7fff0000u) | 0x80000000u));
            st_relaxed_64(pub, s0, s2);
            st_relaxed_64(pub + 2 * sizeof(Exchange) / 8, s0, s2);
            if (lane < NREP) red_add(cnt_s, 1);
            if (elect_one()) mbar_arrive(bar0 + 8 * B_LN);
            STAMP(9); GSTAMP(25);
        }
        const uint32_t slot0 = sb + OFF_RING + a * 8192, slot1 = sb + slot_off(4 + a), slot2 = sb + slot_off(8 + a), fbar = bar0 + 8 * (B_FULL + a);
        uint32_t mine = 0, row[2] = {0, 0};
        {
            uint32_t q[16];
            named_sync(1, 128);
            wait_count(&in->n_stat[32 * a], 32 * tag - FEW_ST);
            STAMP(41);
#pragma unroll 1
            for (uint32_t it = 0;; spin_guard(it)) {
                if (elect_one()) {
                    mbar_expect_tx(abar, 4096);
                    bulk_g2s(sb + OFF_ST + 4096 * a, in->stat + 512 * a, 4096, abar);
                }
                mbar_wait(abar, aph);
                aph ^= 1;
                uint32_t bad = 0;
#pragma unroll
                for (int n = 0; n < 8; n++) {
                    const uint4 u = lds128v(sb + OFF_ST + 4096 * a + 512 * n + 16 * lane);
                    q[2 * n] = u.y; q[2 * n + 1] = u.w;
                    bad = or_xor(bad, u.y, tag);
                }
                const bool ok = __all_sync(0xffffffffu, (bad & 3) == 0);
                asm volatile("{ .reg .pred p; setp.ne.u32 p, %1, 0; @p mbarrier.arrive.shared::cta.b64 _, [%0]; }" ::"r"(bar0 + 8 * (B_ST + a)), "r"((uint32_t)(ok && lane == 0)) : "memory");
                if (ok) break;
            }
            STAMP(8);
            const uint32_t inv = 2047 - 512 * a - 16 * m - (r ^ (2 * m));
#pragma unroll
            for (int i = 0; i < 16; i++) asm("lop3.b32 %0, %0, %1, %2, 0x9b;" : "+r"(q[i]) : "r"(inv), "r"(0xffff0000u | (64 * (i >> 1) + 8 * (i & 1))));
            auto below = [&](uint32_t x) {
                uint32_t d[4];
#pragma unroll
                for (int i = 0; i < 16; i++) d[i & 3] = i < 4 ? x + q[i] : min(d[i & 3], x + q[i]);
                d[0] = min(min(d[0], d[1]), min(d[2], d[3]));
                return d[0] < x ? x - 1 - d[0] : 0u;
            };
            const uint32_t mx0 = ~min(min(min(min(q[0], q[1]), min(q[2], q[3])), min(min(q[4], q[5]), min(q[6], q[7]))),
                                      min(min(min(q[8], q[9]), min(q[10], q[11])), min(min(q[12], q[13]), min(q[14], q[15]))));
            const uint32_t gm = min(__reduce_max_sync(0xffffffffu, lane < 16 ? mx0 : 0u), __reduce_max_sync(0xffffffffu, lane < 16 ? 0u : mx0));
            if (lane == 0) sts32(misc + 16 + 4 * a, gm);
            named_sync(1, 128);
            STAMP(42);
            if (b == 0 && tid == 0) st_relaxed_32(&p.sc->epoch, tag);
            const uint4 t0 = lds128(misc + 16);
            uint32_t tau = min(min(t0.x, t0.y), min(t0.z, t0.w));
            uint32_t mx = mx0, cnt = 0, bal;
            const uint32_t list = sb + OFF_XCH + 64 * a;
#pragma unroll 1
            while ((bal = __ballot_sync(0xffffffffu, mx >= tau)) != 0) {
                const uint32_t pos = cnt + __popc(bal & ((1u << lane) - 1u));
                cnt += __popc(bal);
                if (cnt > 16) break;
                if (mx >= tau) sts32(list + 4 * pos, mx);
                mx = below(mx);
            }
            if (cnt > 16) {
                mx = mx0;
#pragma unroll 1
                for (int j = 0; j < 8; j++) {
                    const uint32_t top = __reduce_max_sync(0xffffffffu, mx), nx = below(mx);
                    if (mx == top) { sts32(list + 4 * j, mx); sts32(list + 32 + 4 * j, 0); mx = nx; }
                }
            }
            named_sync(1, 128);
            STAMP(43);
            const uint2 k = lds64(sb + OFF_XCH + 8 * lane);
            uint32_t hi = max(k.x, k.y), lo = min(k.x, k.y);
            mbar_wait(bar0 + 8 * B_V, 0);
#pragma unroll
            for (int j = 0; j < 8; j++) {
                const uint32_t top = __reduce_max_sync(0xffffffffu, hi);
                const bool won = hi == top;
                hi = won ? lo : hi;
                lo = won ? 0u : lo;
                if (g == j) mine = top;
                if (a == (j >> 1)) row[j & 1] = top;
            }
        }
        STAMP(11);
        const int tok = 2047 - (int)(mine & 2047);
        const uint32_t xs = sb + OFF_XT + (h ^ 1) * 32768 + 16384;
        if (has_gu) {
            if (elect_one()) {
                mbar_expect_tx(abar, 2048);
#pragma unroll
                for (int j = 0; j < 2; j++) bulk_g2s(xs + (2 * a + j) * 1040, p.u + (size_t)(2047 - (row[j] & 2047)) * DM + 512 * h, 1024, abar);
            }
        }
        STAMP(44);
        const uint2 st = ld_relaxed_64(in->stat + (tok & ~15) + 2 * ((tok & 7) ^ ((tok >> 3) & 6)) + ((tok >> 3) & 1));
        if (a == 0 && t == 0) sts64(misc + 48 + 8 * g, mine, __float_as_uint(bf_hi(st.x) + bf_lo(st.y)));
        if (a == 0) STAMP(45);
        if (has_gu) {
            const uint32_t mean = __shfl_sync(0xffffffffu, st.x, 8 * a + 4 * (lane >> 4)), xr = xs + (2 * a + (lane >> 4)) * 1040 + 16 * (lane & 15);
            mbar_wait(abar, aph);
            aph ^= 1;
            STAMP(46);
            uint4 x[4];
#pragma unroll
            for (int j = 0; j < 4; j++) x[j] = lds128(xr + 256 * j);
#pragma unroll
            for (int j = 0; j < 4; j++) sts128(xr + 256 * j, bsub2_lo(x[j].x, mean), bsub2_lo(x[j].y, mean), bsub2_lo(x[j].z, mean), bsub2_lo(x[j].w, mean));
            if (elect_one()) mbar_expect_tx(abar, 512);
            named_sync(1, 128);
        }
        if (lane < (has_gu ? 2 : 4)) mbar_arrive_peer(mapa(bar0 + 8 * (lane & 2 ? B_XFREE : B_SFREE), lane & 1));
        if (has_gu) {
            STAMP(12);
            float gacc[8][4];
#pragma unroll
            for (int i = 0; i < 8; i++) { gacc[i][0] = gacc[i][1] = gacc[i][2] = gacc[i][3] = 0.f; }
            uint32_t* pubh = reinterpret_cast<uint32_t*>(&p.sc->x[0].h[b * 32 + 8 * a + (g ^ (2 * a))]) + t;
            uint32_t* cnt_h = &p.sc->x[t].n_h[32 * (b / 14)];
            uint32_t ko = sb + (m & 1) * 4096 + (r + ((m >> 1) << 3)) * 128 + ((r ^ (4 * h) ^ a) << 4), kp = ko ^ 64, xb = xs + r * 1040 + m * 16;
            uint32_t xch = sb + OFF_XCH + 16 * tid, tagm = t == 3 ? 1u : 0u;
            pin(pubh); pin(cnt_h); pin(ko); pin(kp); pin(xb); pin(xch); pin(tagm);
            const float r0 = lds32f(misc + 52 + 16 * t), r1 = lds32f(misc + 60 + 16 * t);
#pragma unroll
            for (int c = 0; c < 4; c++) {
                uint32_t af[20][4];
#pragma unroll
                for (int j = 0; j < 4; j++) ldsm4(af[16 + j], xb + 256 * c + 64 * j);
                if (c == 3) mbar_wait(bar0 + 8 * B_SFREE, 0);
#pragma unroll
                for (int j = 0; j < 4; j++) {
                    mbar_wait(bar0 + 8 * (B_FULL + 4 * (c % 3) + j), c / 3);
#pragma unroll
                    for (int i = 0; i < 4; i++) ldsm4t(af[8 * (i >> 1) + 2 * j + (i & 1)], ((i & 1) ? kp : ko) + slot_off(4 * (c % 3) + j) + (i >> 1) * 2048);
                }
                STAMP(36 + c);
                __syncwarp();
                if (c < 3 && lane < 4) mbar_arrive(bar0 + 8 * (B_FREE + 4 * c + lane));
                const bool more = __any_sync(0xffffffffu, (af[6][3] | af[7][3] | af[14][3] | af[15][3]) & p.zero);
#pragma unroll 1
                do {
#pragma unroll
                    for (int i = 0; i < 16; i++) mma_v(gacc[i & 7], af[i], af[16 + ((i >> 1) & 3)][2 * (i >> 3)], af[16 + ((i >> 1) & 3)][2 * (i >> 3) + 1]);
                } while (more);
            }
            STAMP(13);
            float own[4], oth[4];
#pragma unroll
            for (int j = 0; j < 4; j++) oth[j] = (gacc[1][j] + gacc[3][j]) + (gacc[5][j] + gacc[7][j]);
            st_async128(mapa(xch, h ^ 1), __float_as_uint(oth[0]), __float_as_uint(oth[1]), __float_as_uint(oth[2]), __float_as_uint(oth[3]), mapa(abar, h ^ 1));
            STAMP(56);
#pragma unroll
            for (int j = 0; j < 4; j++) own[j] = ((gacc[0][j] + gacc[2][j]) + (gacc[4][j] + gacc[6][j])) * ((j & 1) ? r1 : r0);
            mbar_wait(abar, aph);
            aph ^= 1;
            STAMP(57);
            const float4 o4 = lds128f(xch);
            const float g0 = bf_round(fmaf(o4.x, r0, own[0])), g1 = bf_round(fmaf(o4.y, r1, own[1]));
            const float h0 = bf_round(g0 * rcpf(1.f + ex2f(-1.4426950408889634f * g0))) * bf_round(fmaf(o4.z, r0, own[2]));
            const float h1 = bf_round(g1 * rcpf(1.f + ex2f(-1.4426950408889634f * g1))) * bf_round(fmaf(o4.w, r1, own[3]));
            uint32_t hw;
            asm volatile("movmatrix.sync.aligned.m8n8.trans.b16 %0, %1;" : "=r"(hw) : "r"(pack_bf16(h0, h1)));
            hw = (hw & ~tagm) | (tag & tagm);
#pragma unroll
            for (int j = 0; j < NREP; j++) st_relaxed_32(pubh + j * (sizeof(Exchange) / 4), hw);
            if (lane < NREP) red_add(cnt_h, 1);
            if (lane < 2) mbar_arrive_peer(mapa(bar0 + 8 * B_XFREE, lane));
            named_sync(1, 128);
            STAMP(14);
        }
        float dacc[4];
        const int tk = ((tid >> 1) & 6) | (tid & 1);
        uint32_t ro = 4 * tid, red = sb + tab_off(tk) + T_RED + 4 * ((tid >> 4) + 4 * (tid & 2));
        if (!has_gu) named_sync(1, 128);
        const float sg = bf_round(rcpf(1.f + ex2f(-1.4426950408889634f * __uint_as_float(unorder_key(lds32(misc + 48 + 8 * tk) >> 16) << 16))));
        pin(ro); pin(red);
        mbar_wait(bar0 + 8 * B_XFREE, 0);
        {
            uint32_t wo = (r + ((m >> 1) << 3)) * 32 + (((m & 1) ^ (r >> 2)) << 4), af[14][4];
            uint32_t ho = slot0 + 128 * t + 16 * (g ^ (2 * t));
            pin(wo); pin(ho);
            float d[7][4];
#pragma unroll
            for (int i = 0; i < 7; i++) { d[i][0] = d[i][1] = d[i][2] = d[i][3] = 0.f; }
            auto first_half = [&]() {
                mbar_wait(fbar + 32, has_gu);
#pragma unroll
                for (int j = 0; j < 14; j++) ldsm4t(af[j], slot1 + wo + j * 512);
            };
            auto fetch = [&]() {
                if (elect_one()) {
                    mbar_expect_tx(abar, (ABL & 8) ? 512 : 7168);
                    bulk_g2s(slot0, &in->h[(56 * h + 14 * a) * 32], (ABL & 8) ? 512 : 7168, abar);
                }
            };
            wait_count(&in->n_h[32 * (4 * h + a)], 56 * tag - FEW_H);
            STAMP(33);
            fetch();
            first_half();
            uint4 hq[7];
#pragma unroll 1
            for (uint32_t it = 0;; spin_guard(it)) {
                mbar_wait(abar, aph);
                aph ^= 1;
                uint32_t bad = 0;
#pragma unroll
                for (int j = 0; j < 7; j++) { hq[j] = lds128(ho + 512 * j); bad = or_xor(or_xor(bad, hq[j].w, tag), lds32(ho + 512 * (7 + j) + 12), tag); }
                if (__all_sync(0xffffffffu, (bad & ((ABL & 8) ? p.zero : 1)) == 0)) break;
                fetch();
            }
            STAMP(15);
#pragma unroll
            for (int s = 0; s < 2; s++) {
                if (s) {
#pragma unroll
                    for (int j = 0; j < 7; j++) hq[j] = lds128(ho + 512 * (7 + j));
                    mbar_wait(fbar + 64, has_gu);
#pragma unroll
                    for (int j = 0; j < 14; j++) ldsm4t(af[j], slot2 + wo + j * 512);
                }
                const bool more = __any_sync(0xffffffffu, after_all(af, p.zero));
#pragma unroll 1
                do {
#pragma unroll
                    for (int j = 0; j < 14; j++) {
                        const uint4 q = hq[j >> 1];
                        mma_v(d[j % 7], af[j], (j & 1) ? q.z : q.x, (j & 1) ? q.w : q.y);
                    }
                } while (more);
            }
#pragma unroll
            for (int j = 0; j < 4; j++) dacc[j] = ((d[0][j] + d[1][j]) + (d[2][j] + d[3][j])) + ((d[4][j] + d[5][j]) + d[6][j]);
        }
        STAMP(16);
        {
            st_async128(mapa(sb + OFF_XCH + 16 * tid, h ^ 1), __float_as_uint(dacc[0]), __float_as_uint(dacc[1]), __float_as_uint(dacc[2]), __float_as_uint(dacc[3]),
                        mapa(bar0 + 8 * B_RED, h ^ 1));
            sts128f(slot0 + 7680 + lane * 16, dacc);
            __syncwarp();
            if (elect_one()) mbar_arrive(bar0 + 8 * B_RED);
            mbar_wait(bar0 + 8 * B_RED, 0);
            const uint32_t b0 = sb + OFF_RING + 7680 + ro, b1 = sb + OFF_XCH + ro;
            const float y = ((lds32f(b0) + lds32f(b0 + 8192)) + (lds32f(b0 + 16384) + lds32f(b0 + 24576))) +
                            ((lds32f(b1) + lds32f(b1 + 512)) + (lds32f(b1 + 1024) + lds32f(b1 + 1536)));
            sts32f(red, bf_round(y) * sg);
            __syncwarp();
            if (elect_one()) mbar_arrive(bar0 + 8 * B_UPD);
        }
        STAMP(17); GSTAMP(29);
    }
}

typedef CUresult (*EncodeFn)(CUtensorMap*, CUtensorMapDataType, cuuint32_t, void*, const cuuint64_t*, const cuuint64_t*,
                             const cuuint32_t*, const cuuint32_t*, CUtensorMapInterleave, CUtensorMapSwizzle,
                             CUtensorMapL2promotion, CUtensorMapFloatOOBfill);

void make_map(EncodeFn enc, CUtensorMap* m, const void* ptr, uint64_t cols, uint64_t rows, uint32_t bc, uint32_t br,
              CUtensorMapSwizzle sw, CUtensorMapL2promotion pr) {
    cuuint64_t dims[2] = {cols, rows};
    cuuint64_t str[1] = {cols * 2};
    cuuint32_t box[2] = {bc, br};
    cuuint32_t es[2] = {1, 1};
    enc(m, CU_TENSOR_MAP_DATA_TYPE_BFLOAT16, 2, const_cast<void*>(ptr), dims, str, box, es, CU_TENSOR_MAP_INTERLEAVE_NONE, sw, pr,
        CU_TENSOR_MAP_FLOAT_OOB_FILL_NONE);
}
void make_perm_map(EncodeFn enc, CUtensorMap* m, const void* ptr, CUtensorMapL2promotion pr) {
    cuuint64_t dims[5] = {DM, 2, 4, 4, FF / 32};
    cuuint64_t str[4] = {DM * 2, 8 * DM * 2, 2 * DM * 2, 32 * DM * 2};
    cuuint32_t box[5] = {16, 2, 4, 4, 7};
    cuuint32_t es[5] = {1, 1, 1, 1, 1};
    enc(m, CU_TENSOR_MAP_DATA_TYPE_BFLOAT16, 5, const_cast<void*>(ptr), dims, str, box, es, CU_TENSOR_MAP_INTERLEAVE_NONE,
        CU_TENSOR_MAP_SWIZZLE_32B, pr, CU_TENSOR_MAP_FLOAT_OOB_FILL_NONE);
}
void make_tile_map(EncodeFn enc, CUtensorMap* m, const void* ptr) {
    cuuint64_t dims[4] = {DM, 4, 16, SEQ / 64};
    cuuint64_t str[3] = {16 * DM * 2, DM * 2, 64 * DM * 2};
    cuuint32_t box[4] = {16, 4, 2, 8};
    cuuint32_t es[4] = {1, 1, 1, 1};
    enc(m, CU_TENSOR_MAP_DATA_TYPE_BFLOAT16, 4, const_cast<void*>(ptr), dims, str, box, es, CU_TENSOR_MAP_INTERLEAVE_NONE,
        CU_TENSOR_MAP_SWIZZLE_32B, CU_TENSOR_MAP_L2_PROMOTION_NONE, CU_TENSOR_MAP_FLOAT_OOB_FILL_NONE);
}

}

#define WD_PROMO CU_TENSOR_MAP_L2_PROMOTION_L2_64B
extern "C" void kernel_launch(void* const* d_in, const int* in_sizes, int n_in, void* d_out, int out_size) {
    (void)in_sizes; (void)n_in; (void)out_size;
    static EncodeFn enc = nullptr;
    static void* scratch = nullptr;
    if (!enc) {
        void* fn = nullptr;
        cudaDriverEntryPointQueryResult q;
        cudaGetDriverEntryPoint("cuTensorMapEncodeTiled", &fn, cudaEnableDefault, &q);
        enc = (EncodeFn)fn;
        cudaGetSymbolAddress(&scratch, g_scratch);
        cudaFuncSetAttribute(fused_kernel, cudaFuncAttributeMaxDynamicSharedMemorySize, SMEM_BYTES);
    }
    Maps maps;
    make_tile_map(enc, &maps.u, d_in[0]);
    make_tile_map(enc, &maps.out, d_out);
    make_map(enc, &maps.wg, d_in[9], FF, DM, 64, 32, CU_TENSOR_MAP_SWIZZLE_128B, CU_TENSOR_MAP_L2_PROMOTION_L2_128B);
    make_map(enc, &maps.wu, d_in[10], FF, DM, 64, 32, CU_TENSOR_MAP_SWIZZLE_128B, CU_TENSOR_MAP_L2_PROMOTION_L2_128B);
    make_perm_map(enc, &maps.wd, d_in[11], WD_PROMO);
    Ptrs p;
    p.sc = (Scratch*)scratch;
    p.u = (const __nv_bfloat16*)d_in[0];
    p.logA = (const __nv_bfloat16*)d_in[1];
    p.Aim = (const __nv_bfloat16*)d_in[2];
    p.Cre = (const __nv_bfloat16*)d_in[3];
    p.Cim = (const __nv_bfloat16*)d_in[4];
    p.ldt = (const __nv_bfloat16*)d_in[5];
    p.dsk = (const __nv_bfloat16*)d_in[6];
    p.wr = (const __nv_bfloat16*)d_in[8];
    p.out = (__nv_bfloat16*)d_out;
    p.zero = 0;
    fused_kernel<<<NCTA, NTHR, SMEM_BYTES, cudaStreamPerThread>>>(p, maps);
}
```

```cpp
#include <cuda_runtime.h>
#include <cuda_bf16.h>
#include <cuda_fp16.h>
#include <cuda.h>
#include <stdint.h>

namespace {

constexpr int SEQ = 2048, DM = 1024, NMODE = 128, FF = 3584;
constexpr int NCTA = 128, NTHR = 512;
constexpr int GU_CTAS = 112;
constexpr int NREP = 4;

constexpr int OFF_XT = 0;
constexpr int OFF_RING = 65536;
constexpr int OFF_PRIV = OFF_RING + 65536;
constexpr int OFF_VT = OFF_PRIV + 65536;
constexpr int VT_PAD = 32, VT_PLANE = VT_PAD + 2048, VT_PITCH = 2 * VT_PLANE, ROW_PITCH = 2064;
constexpr int OFF_BAR = OFF_VT + 8 * VT_PITCH;
constexpr int OFF_MISC = OFF_BAR + 384;
constexpr int OFF_XCH = OFF_MISC + 112;
constexpr int SMEM_BYTES = OFF_XCH + 2048;
constexpr int OFF_LN = OFF_RING + 7 * 8192;
constexpr int OFF_ST = OFF_RING + 6 * 8192;
static_assert(SMEM_BYTES <= 232448, "shared memory");

constexpr int B_ROW = 0, B_XT = 4, B_V = 5, B_LN = 6, B_SFREE = 7, B_RECV = 8, B_RED = 10, B_UPD = 11, B_ST = 12, B_XFREE = 16, B_OWN = 17, B_FREE = 20, B_FULL = 32, B_AUX = 44, NBAR = 48;

constexpr int T_DENSE = 60;
constexpr int T_PATCH = 2208;
constexpr int T_R2 = 2368;
constexpr int T_R3 = 3296;

constexpr int T_RED = 4032;
__device__ __forceinline__ bool slot_priv(int s) { return (uint32_t)(s - 6) < 4u; }
__device__ __forceinline__ uint32_t slot_off(int s) { return slot_priv(s) ? OFF_PRIV + 4096 + (s & 3) * 16384 : OFF_RING + (s < 6 ? s : s - 4) * 8192; }
__device__ __forceinline__ uint32_t tab_off(int w) { return OFF_PRIV + w * 8192 + (w & 1) * 4096; }

constexpr uint32_t SPIN_LIMIT = 1u << 20;
#define KG_UNROLL 4
constexpr int kKgUnroll = KG_UNROLL;
#define BB_UNROLL 2
constexpr int kBbUnroll = BB_UNROLL;
#define DENSE_UNROLL 1
constexpr int kDenseUnroll = DENSE_UNROLL;
#define ST_T0 2200
#define LN_PAUSE 0xf0
#define FEW_ST 8
#define FEW_H 8
#define PERM 2
#define PERM_OFF 60
#define ABL_RHO 0
#define ABL_SKIP 0
#define ABL 0
#define Q2_HELP 0
#define FFA
#define FIN_ILP 2
#define REG_S "24"
#define REG_C "176"
#define REG_A "136"
#define DCH 7
#define ST_LATE 16
#define ST_GAP 0
#define ST_PER 308
#define ST_PER2 320

struct Exchange {
    uint2 stat[SEQ];
    uint4 h[GU_CTAS * 32];
    uint32_t n_stat[4 * 32];
    uint32_t n_h[8 * 32];
};
struct Scratch {
    Exchange x[NREP];
    uint32_t epoch;
};
__device__ __align__(128) Scratch g_scratch;

struct Ptrs {
    const __nv_bfloat16 *logA, *Aim, *Cre, *Cim, *ldt, *u;
    const __nv_bfloat16 *dsk, *wr;
    Scratch* sc;
    __nv_bfloat16* out;
    uint32_t zero;
};
struct Maps {
    CUtensorMap u, out, wg, wu, wd;
};

#define STAMP(i) do { } while (0)
#define KSTAMP(i) do { } while (0)
#define GSTAMP(i) do { } while (0)

__device__ __forceinline__ uint32_t s_u32(const void* p) { return (uint32_t)__cvta_generic_to_shared(p); }
__device__ __forceinline__ void mbar_init(uint32_t b, uint32_t n) {
    asm volatile("mbarrier.init.shared::cta.b64 [%0], %1;" ::"r"(b), "r"(n) : "memory");
}
__device__ __forceinline__ void mbar_expect_tx(uint32_t b, uint32_t bytes) {
    asm volatile("mbarrier.arrive.expect_tx.shared::cta.b64 _, [%0], %1;" ::"r"(b), "r"(bytes) : "memory");
}
__device__ __forceinline__ void mbar_arrive(uint32_t b) {
    asm volatile("mbarrier.arrive.shared::cta.b64 _, [%0];" ::"r"(b) : "memory");
}
__device__ __forceinline__ void mbar_arrive_n(uint32_t b, uint32_t n) {
    asm volatile("mbarrier.arrive.shared::cta.b64 _, [%0], %1;" ::"r"(b), "r"(n) : "memory");
}
__device__ __forceinline__ void mbar_arrive_peer(uint32_t b_cluster) {
    asm volatile("mbarrier.arrive.relaxed.cluster.shared::cluster.b64 _, [%0];" ::"r"(b_cluster) : "memory");
}
__device__ __forceinline__ void mbar_wait(uint32_t b, uint32_t parity) {
    asm volatile("{\n\t.reg .pred p;\n\t.reg .u32 c;\n\tmov.u32 c, 0;\n"
                 "W:\n\tmbarrier.try_wait.parity.shared::cta.b64 p, [%0], %1;\n\t@p bra D;\n\t"
                 "add.u32 c, c, 1;\n\tsetp.lt.u32 p, c, 1048576;\n\t@p bra W;\n\ttrap;\nD:\n\t}"
                 ::"r"(b), "r"(parity) : "memory");
}
__device__ __forceinline__ bool mbar_test(uint32_t b, uint32_t parity) {
    uint32_t ok;
    asm volatile("{ .reg .pred p; mbarrier.test_wait.parity.shared::cta.b64 p, [%1], %2; selp.u32 %0, 1, 0, p; }" : "=r"(ok) : "r"(b), "r"(parity) : "memory");
    return __all_sync(0xffffffffu, ok != 0);
}
__device__ __forceinline__ bool elect_one() {
    uint32_t p;
    asm volatile("{ .reg .pred P; elect.sync _|P, 0xffffffff; selp.u32 %0, 1, 0, P; }" : "=r"(p));
    return p != 0;
}
__device__ __forceinline__ uint32_t mapa(uint32_t a, uint32_t rank) {
    uint32_t r;
    asm("mapa.shared::cluster.u32 %0, %1, %2;" : "=r"(r) : "r"(a), "r"(rank));
    return r;
}
__device__ __forceinline__ void cluster_arrive() { asm volatile("barrier.cluster.arrive.relaxed.aligned;" ::: "memory"); }
__device__ __forceinline__ void cluster_wait() { asm volatile("barrier.cluster.wait.acquire.aligned;" ::: "memory"); }
__device__ __forceinline__ void tma_load_2d(uint32_t dst, const CUtensorMap* m, int c0, int c1, uint32_t bar) {
    asm volatile("cp.async.bulk.tensor.2d.shared::cluster.global.mbarrier::complete_tx::bytes [%0], [%1, {%3, %4}], [%2];"
                 ::"r"(dst), "l"(m), "r"(bar), "r"(c0), "r"(c1) : "memory");
}
__device__ __forceinline__ void tma_load_perm(uint32_t dst, const CUtensorMap* m, int c0, int blk, uint32_t bar) {
    asm volatile("cp.async.bulk.tensor.5d.shared::cluster.global.mbarrier::complete_tx::bytes [%0], [%1, {%3, %4, %4, %4, %5}], [%2];"
                 ::"r"(dst), "l"(m), "r"(bar), "r"(c0), "r"(0), "r"(blk) : "memory");
}
__device__ __forceinline__ void tma_load_tile(uint32_t dst, const CUtensorMap* m, int c0, int c2, int c3, uint32_t bar) {
    asm volatile("cp.async.bulk.tensor.4d.shared::cluster.global.mbarrier::complete_tx::bytes.multicast::cluster [%0], [%1, {%3, %4, %5, %6}], [%2], %7;"
                 ::"r"(dst), "l"(m), "r"(bar), "r"(c0), "r"(0), "r"(c2), "r"(c3), "h"((uint16_t)3) : "memory");
}
__device__ __forceinline__ void tma_store_tile(const CUtensorMap* m, uint32_t src, int c0, int c2, int c3) {
    asm volatile("cp.async.bulk.tensor.4d.global.shared::cta.bulk_group [%0, {%2, %3, %4, %5}], [%1];"
                 ::"l"(m), "r"(src), "r"(c0), "r"(0), "r"(c2), "r"(c3) : "memory");
    asm volatile("cp.async.bulk.commit_group;" ::: "memory");
}
__device__ __forceinline__ void bulk_g2s(uint32_t dst, const void* src, uint32_t bytes, uint32_t bar) {
    asm volatile("cp.async.bulk.shared::cluster.global.mbarrier::complete_tx::bytes [%0], [%1], %2, [%3];"
                 ::"r"(dst), "l"(src), "r"(bytes), "r"(bar) : "memory");
}
__device__ __forceinline__ void cp_async16(uint32_t dst, const void* src) {
    asm volatile("cp.async.cg.shared.global [%0], [%1], 16;" ::"r"(dst), "l"(src) : "memory");
}
__device__ __forceinline__ void st_async128(uint32_t dst_cluster, uint32_t x, uint32_t y, uint32_t z, uint32_t w, uint32_t bar_cluster) {
    asm volatile("st.async.weak.shared::cluster.mbarrier::complete_tx::bytes.v4.b32 [%0], {%1,%2,%3,%4}, [%5];"
                 ::"r"(dst_cluster), "r"(x), "r"(y), "r"(z), "r"(w), "r"(bar_cluster) : "memory");
}
__device__ __forceinline__ void fence_async() { asm volatile("fence.proxy.async.shared::cta;" ::: "memory"); }
__device__ __forceinline__ void named_sync(int id, int n) { asm volatile("bar.sync %0, %1;" ::"r"(id), "r"(n) : "memory"); }

__device__ __forceinline__ void ldsm4(uint32_t* r, uint32_t a) {
    asm volatile("ldmatrix.sync.aligned.m8n8.x4.shared.b16 {%0,%1,%2,%3}, [%4];"
                 : "=r"(r[0]), "=r"(r[1]), "=r"(r[2]), "=r"(r[3]) : "r"(a));
}
__device__ __forceinline__ void ldsm4t(uint32_t* r, uint32_t a) {
    asm volatile("ldmatrix.sync.aligned.m8n8.x4.trans.shared.b16 {%0,%1,%2,%3}, [%4];"
                 : "=r"(r[0]), "=r"(r[1]), "=r"(r[2]), "=r"(r[3]) : "r"(a));
}
__device__ __forceinline__ void stsm4t(uint32_t a, uint32_t x, uint32_t y, uint32_t z, uint32_t w) {
    asm volatile("stmatrix.sync.aligned.m8n8.x4.trans.shared.b16 [%0], {%1,%2,%3,%4};"
                 ::"r"(a), "r"(x), "r"(y), "r"(z), "r"(w) : "memory");
}
__device__ __forceinline__ uint32_t lds32(uint32_t a) { uint32_t v; asm volatile("ld.shared.u32 %0, [%1];" : "=r"(v) : "r"(a)); return v; }
__device__ __forceinline__ float lds32f(uint32_t a) { float v; asm volatile("ld.shared.f32 %0, [%1];" : "=f"(v) : "r"(a)); return v; }
__device__ __forceinline__ uint2 lds64(uint32_t a) { uint2 v; asm volatile("ld.shared.v2.u32 {%0,%1}, [%2];" : "=r"(v.x), "=r"(v.y) : "r"(a)); return v; }
__device__ __forceinline__ uint4 lds128(uint32_t a) {
    uint4 v; asm volatile("ld.shared.v4.u32 {%0,%1,%2,%3}, [%4];" : "=r"(v.x), "=r"(v.y), "=r"(v.z), "=r"(v.w) : "r"(a)); return v;
}
__device__ __forceinline__ uint4 lds128v(uint32_t a) {
    uint4 v; asm volatile("ld.volatile.shared.v4.u32 {%0,%1,%2,%3}, [%4];" : "=r"(v.x), "=r"(v.y), "=r"(v.z), "=r"(v.w) : "r"(a)); return v;
}
__device__ __forceinline__ uint32_t or_xor(uint32_t a, uint32_t b, uint32_t c) {
    uint32_t r; asm("lop3.b32 %0, %1, %2, %3, 0xf6;" : "=r"(r) : "r"(a), "r"(b), "r"(c)); return r;
}
__device__ __forceinline__ float4 lds128f(uint32_t a) {
    float4 v; asm volatile("ld.shared.v4.f32 {%0,%1,%2,%3}, [%4];" : "=f"(v.x), "=f"(v.y), "=f"(v.z), "=f"(v.w) : "r"(a)); return v;
}
__device__ __forceinline__ void sts32(uint32_t a, uint32_t v) { asm volatile("st.shared.u32 [%0], %1;" ::"r"(a), "r"(v) : "memory"); }
__device__ __forceinline__ void sts32f(uint32_t a, float v) { asm volatile("st.shared.f32 [%0], %1;" ::"r"(a), "f"(v) : "memory"); }
__device__ __forceinline__ void sts64(uint32_t a, uint32_t x, uint32_t y) { asm volatile("st.shared.v2.u32 [%0], {%1,%2};" ::"r"(a), "r"(x), "r"(y) : "memory"); }
__device__ __forceinline__ void sts64f(uint32_t a, float x, float y) { asm volatile("st.shared.v2.f32 [%0], {%1,%2};" ::"r"(a), "f"(x), "f"(y) : "memory"); }
__device__ __forceinline__ void sts128(uint32_t a, uint32_t x, uint32_t y, uint32_t z, uint32_t w) {
    asm volatile("st.shared.v4.u32 [%0], {%1,%2,%3,%4};" ::"r"(a), "r"(x), "r"(y), "r"(z), "r"(w) : "memory");
}
__device__ __forceinline__ void sts128f(uint32_t a, const float* v) {
    asm volatile("st.shared.v4.f32 [%0], {%1,%2,%3,%4};" ::"r"(a), "f"(v[0]), "f"(v[1]), "f"(v[2]), "f"(v[3]) : "memory");
}
__device__ __forceinline__ uint4 ldg128(const void* p) {
    uint4 v; asm volatile("ld.global.nc.L1::no_allocate.v4.u32 {%0,%1,%2,%3}, [%4];" : "=r"(v.x), "=r"(v.y), "=r"(v.z), "=r"(v.w) : "l"(p)); return v;
}
__device__ __forceinline__ uint2 ldg64(const void* p) {
    uint2 v; asm volatile("ld.global.nc.L1::no_allocate.v2.u32 {%0,%1}, [%2];" : "=r"(v.x), "=r"(v.y) : "l"(p)); return v;
}
__device__ __forceinline__ uint32_t ldg32(const void* p) {
    uint32_t v; asm volatile("ld.global.nc.u32 %0, [%1];" : "=r"(v) : "l"(p)); return v;
}
__device__ __forceinline__ uint32_t ldg16(const void* p) {
    uint32_t v; asm volatile("ld.global.nc.u16 %0, [%1];" : "=r"(v) : "l"(p)); return v;
}
__device__ __forceinline__ uint4 ld_relaxed_128(const void* p) {
    uint4 v; asm volatile("ld.relaxed.gpu.global.v4.u32 {%0,%1,%2,%3}, [%4];" : "=r"(v.x), "=r"(v.y), "=r"(v.z), "=r"(v.w) : "l"(p) : "memory"); return v;
}
__device__ __forceinline__ void ld_relaxed_128_unless(uint4& q, const void* p, bool have) {
    asm volatile("{ .reg .pred p; setp.eq.u32 p, %5, 0; @p ld.relaxed.gpu.global.v4.u32 {%0,%1,%2,%3}, [%4]; }"
                 : "+r"(q.x), "+r"(q.y), "+r"(q.z), "+r"(q.w) : "l"(p), "r"((uint32_t)have) : "memory");
}
__device__ __forceinline__ uint2 ld_relaxed_64(const void* p) {
    uint2 v; asm volatile("ld.relaxed.gpu.global.v2.u32 {%0,%1}, [%2];" : "=r"(v.x), "=r"(v.y) : "l"(p) : "memory"); return v;
}
__device__ __forceinline__ uint32_t ld_relaxed_32(const void* p) {
    uint32_t v; asm volatile("ld.relaxed.gpu.global.u32 %0, [%1];" : "=r"(v) : "l"(p) : "memory"); return v;
}
__device__ __forceinline__ void st_relaxed_128(void* p, uint32_t x, uint32_t y, uint32_t z, uint32_t w) {
    asm volatile("st.relaxed.gpu.global.v4.u32 [%0], {%1,%2,%3,%4};" ::"l"(p), "r"(x), "r"(y), "r"(z), "r"(w) : "memory");
}
__device__ __forceinline__ void st_relaxed_64(void* p, uint32_t x, uint32_t y) {
    asm volatile("st.relaxed.gpu.global.v2.u32 [%0], {%1,%2};" ::"l"(p), "r"(x), "r"(y) : "memory");
}
__device__ __forceinline__ void st_relaxed_32(void* p, uint32_t v) {
    asm volatile("st.relaxed.gpu.global.u32 [%0], %1;" ::"l"(p), "r"(v) : "memory");
}
__device__ __forceinline__ void red_add(void* p, uint32_t v) { asm volatile("red.relaxed.gpu.global.add.u32 [%0], %1;" ::"l"(p), "r"(v) : "memory"); }
__device__ __forceinline__ uint32_t now_ns() { uint32_t t; asm volatile("mov.u32 %0, %%globaltimer_lo;" : "=r"(t) :: "memory"); return t; }
__device__ __forceinline__ void spin_guard(uint32_t& it) { if (++it > SPIN_LIMIT) __trap(); }
__device__ __forceinline__ void wait_count(const uint32_t* p, uint32_t target) {
#pragma unroll 1
    for (uint32_t it = 0; __any_sync(0xffffffffu, (int)(ld_relaxed_32(p) - target) < 0); spin_guard(it)) { }
}
__device__ __forceinline__ void mma_bf16(float* c, uint32_t a0, uint32_t a1, uint32_t a2, uint32_t a3, uint32_t b0, uint32_t b1) {
    asm("mma.sync.aligned.m16n8k16.row.col.f32.bf16.bf16.f32 {%0,%1,%2,%3}, {%4,%5,%6,%7}, {%8,%9}, {%0,%1,%2,%3};"
                 : "+f"(c[0]), "+f"(c[1]), "+f"(c[2]), "+f"(c[3]) : "r"(a0), "r"(a1), "r"(a2), "r"(a3), "r"(b0), "r"(b1));
}
__device__ __forceinline__ void mma_bf16_k8(float* c, uint32_t a0, uint32_t a1, uint32_t b0) {
    asm("mma.sync.aligned.m16n8k8.row.col.f32.bf16.bf16.f32 {%0,%1,%2,%3}, {%4,%5}, {%6}, {%0,%1,%2,%3};"
                 : "+f"(c[0]), "+f"(c[1]), "+f"(c[2]), "+f"(c[3]) : "r"(a0), "r"(a1), "r"(b0));
}
__device__ __forceinline__ void mma_v(float* c, const uint32_t* a, uint32_t b0, uint32_t b1) {
    asm volatile("mma.sync.aligned.m16n8k16.row.col.f32.bf16.bf16.f32 {%0,%1,%2,%3}, {%4,%5,%6,%7}, {%8,%9}, {%0,%1,%2,%3};"
                 : "+f"(c[0]), "+f"(c[1]), "+f"(c[2]), "+f"(c[3]) : "r"(a[0]), "r"(a[1]), "r"(a[2]), "r"(a[3]), "r"(b0), "r"(b1));
}
__device__ __forceinline__ void mma_bf16_z(float* c, uint32_t a0, uint32_t a1, uint32_t a2, uint32_t a3, uint32_t b0, uint32_t b1) {
    asm volatile("mma.sync.aligned.m16n8k16.row.col.f32.bf16.bf16.f32 {%0,%1,%2,%3}, {%4,%5,%6,%7}, {%8,%9}, {%10,%10,%10,%10};"
        : "=f"(c[0]), "=f"(c[1]), "=f"(c[2]), "=f"(c[3]) : "r"(a0), "r"(a1), "r"(a2), "r"(a3), "r"(b0), "r"(b1), "f"(0.f));
}
__device__ __forceinline__ void mma_f16(float* c, uint32_t a0, uint32_t a1, uint32_t a2, uint32_t a3, uint32_t b0, uint32_t b1) {
    asm("mma.sync.aligned.m16n8k16.row.col.f32.f16.f16.f32 {%0,%1,%2,%3}, {%4,%5,%6,%7}, {%8,%9}, {%0,%1,%2,%3};"
                 : "+f"(c[0]), "+f"(c[1]), "+f"(c[2]), "+f"(c[3]) : "r"(a0), "r"(a1), "r"(a2), "r"(a3), "r"(b0), "r"(b1));
}
__device__ __forceinline__ uint32_t pack_bf16(float lo, float hi) {
    uint32_t r; asm("cvt.rn.bf16x2.f32 %0, %1, %2;" : "=r"(r) : "f"(hi), "f"(lo)); return r;
}
__device__ __forceinline__ uint32_t pack_v(float lo, float hi) {
    uint32_t r; asm volatile("cvt.rn.bf16x2.f32 %0, %1, %2;" : "=r"(r) : "f"(hi), "f"(lo)); return r;
}
__device__ __forceinline__ uint32_t pack_w(float lo, float hi) {
    uint32_t r; asm volatile("cvt.rn.satfinite.bf16x2.f32 %0, %1, %2;" : "=r"(r) : "f"(hi), "f"(lo)); return r;
}
template <int N> __device__ __forceinline__ uint32_t after_all(const uint32_t (&f)[N][4], uint32_t zero) {
    uint32_t d[3] = {0, 0, 0};
#pragma unroll
    for (int i = 0; i < N; i++) d[i % 3] |= f[i][3];
    return (d[0] | d[1] | d[2]) & zero;
}
__device__ __forceinline__ void pin(uint32_t& x) { asm volatile("" : "+r"(x)); }
template <class T> __device__ __forceinline__ void pin(T*& x) { asm volatile("" : "+l"(x)); }
__device__ __forceinline__ uint32_t pack_f16(float lo, float hi) {
    uint32_t r; asm("cvt.rn.f16x2.f32 %0, %1, %2;" : "=r"(r) : "f"(hi), "f"(lo)); return r;
}
__device__ __forceinline__ float bf_lo(uint32_t v) { return __uint_as_float(v << 16); }
__device__ __forceinline__ float bf_hi(uint32_t v) { return __uint_as_float(v & 0xffff0000u); }
__device__ __forceinline__ float bf_round(float x) { return __uint_as_float(pack_bf16(0.f, x)); }
__device__ __forceinline__ uint32_t badd2(uint32_t a, uint32_t b) { uint32_t r; asm("add.rn.bf16x2 %0, %1, %2;" : "=r"(r) : "r"(a), "r"(b)); return r; }
__device__ __forceinline__ uint32_t bsub2_lo(uint32_t a, uint32_t b) {
    uint32_t r; asm("{ .reg .b16 m, h; .reg .b32 m2; mov.b32 {m, h}, %2; mov.b32 m2, {m, m}; sub.rn.bf16x2 %0, %1, m2; }" : "=r"(r) : "r"(a), "r"(b)); return r;
}
__device__ __forceinline__ uint32_t bmax2(uint32_t a, uint32_t b) { uint32_t r; asm("max.bf16x2 %0, %1, %2;" : "=r"(r) : "r"(a), "r"(b)); return r; }
__device__ __forceinline__ uint32_t normalize2(uint32_t x, uint32_t s0, uint32_t s1) {
    uint32_t r;
    asm("{ .reg .b16 m, h, l, k; .reg .b32 m2, h2, l2, d, t;\n\t"
        "mov.b32 {m, h}, %2; mov.b32 {l, k}, %3; mov.b32 m2, {m, m}; mov.b32 h2, {h, h}; mov.b32 l2, {l, l};\n\t"
        "sub.rn.bf16x2 d, %1, m2; mul.rn.bf16x2 t, d, l2; fma.rn.bf16x2 %0, d, h2, t; }" : "=r"(r) : "r"(x), "r"(s0), "r"(s1));
    return r;
}
__device__ __forceinline__ float rcpf(float x) { float r; asm("rcp.approx.ftz.f32 %0, %1;" : "=f"(r) : "f"(x)); return r; }
__device__ __forceinline__ float sqrtaf(float x) { float r; asm("sqrt.approx.ftz.f32 %0, %1;" : "=f"(r) : "f"(x)); return r; }
__device__ __forceinline__ float ex2f(float x) { float r; asm("ex2.approx.ftz.f32 %0, %1;" : "=f"(r) : "f"(x)); return r; }

__device__ __forceinline__ int tok_off(int t) { return ((t >> 3) & 1) * VT_PLANE + (t >> 4) * 16 + (t & 7) * 2; }

__device__ __forceinline__ uint32_t order_key(uint32_t b16) { return b16 ^ ((b16 & 0x8000u) ? 0xffffu : 0x8000u); }
__device__ __forceinline__ uint32_t unorder_key(uint32_t k16) { return k16 ^ ((k16 & 0x8000u) ? 0x8000u : 0xffffu); }

struct cplx { float r, i; };
struct hc { uint32_t r, i; };
template <bool CONJ> __device__ __forceinline__ cplx csq(cplx a) {
    float im;
    asm("{ .reg .f32 t; mul.ftz.f32 t, %1, %2; mul.ftz.f32 %0, t, 0f40000000; }" : "=f"(im) : "f"(CONJ ? -a.r : a.r), "f"(a.i));
    return {fmaf(a.r, a.r, -(a.i * a.i)), im};
}
__device__ __forceinline__ cplx cexpp(float a2, float ai) {
    float m = ex2f(a2), s, c;
    __sincosf(ai, &s, &c);
    return {m * c, m * s};
}
__device__ __forceinline__ __half2 as_h2(uint32_t x) { return *reinterpret_cast<__half2*>(&x); }
__device__ __forceinline__ uint32_t as_u(__half2 x) { return *reinterpret_cast<uint32_t*>(&x); }
__device__ __forceinline__ hc hmul(hc a, hc b) {
    return {as_u(__hfma2(as_h2(a.r), as_h2(b.r), __hneg2(__hmul2(as_h2(a.i), as_h2(b.i))))),
            as_u(__hfma2(as_h2(a.r), as_h2(b.i), __hmul2(as_h2(a.i), as_h2(b.r))))};
}
__device__ __forceinline__ hc hpack(cplx a, cplx b) { return {pack_f16(a.r, b.r), pack_f16(a.i, b.i)}; }
__device__ __forceinline__ void sts16(uint32_t a, uint32_t v) { asm volatile("st.shared.u16 [%0], %1;" ::"r"(a), "r"(v) : "memory"); }

struct KgenAddr {
    uint32_t l, h, m2, m3, m4, z, w, wz;
    __device__ __forceinline__ KgenAddr(uint32_t scr, int lane) {
        const int g = lane >> 2, t = lane & 3;
        const uint32_t rec = scr + t * 480;
        l = rec + 16 * g; h = rec + 128 + 8 * g; m2 = rec + 192 + 8 * (g & 1); m3 = rec + 208 + 4 * (g & 2); m4 = rec + 224 + 2 * (g & 4);
        z = scr + 7680 + 16 * t; w = scr + 240 * lane; wz = scr + 7680 + 8 * lane;
        pin(l); pin(h); pin(m2); pin(m3); pin(m4); pin(z); pin(w); pin(wz);
    }
    __device__ __forceinline__ uint32_t any() const { return (l | h | m2) | (m3 | m4 | z) | (w | wz); }
};
template <class Hook, class Hook2>
__device__ __forceinline__ void kgen(const KgenAddr& ad, uint32_t tab, int lane, uint2 la, uint2 aim, uint2 cre, uint2 cim, float dt, float skip, int dch, Hook main_done, Hook2 half_done) {
    const int g = lane >> 2, t = lane & 3;
    const float dt2 = 2.f * dt;
    const uint32_t am = bmax2(bmax2(cre.x & 0x7fff7fffu, cre.y & 0x7fff7fffu), bmax2(cim.x & 0x7fff7fffu, cim.y & 0x7fff7fffu));
    const float mx = dt2 * fmaxf(bf_lo(am), bf_hi(am));
    const uint32_t eb = min(max(__reduce_max_sync(0xffffffffu, __float_as_uint(mx)) >> 23, 1u), 252u);
    const float cscale = dt2 * __uint_as_float((253u - eb) << 23);
    const float scale_inv = __uint_as_float((eb + 1u) << 23);
    float k0 = (bf_lo(cre.x) + bf_hi(cre.x)) + (bf_lo(cre.y) + bf_hi(cre.y));
#pragma unroll
    for (int o = 16; o; o >>= 1) k0 += __shfl_xor_sync(0xffffffffu, k0, o);
    const float ndt = -1.4426950408889634f * dt;
    STAMP(40); KSTAMP(0);

    float acc[5][4];
#pragma unroll
    for (int i = 0; i < 5; i++) { acc[i][0] = acc[i][1] = acc[i][2] = acc[i][3] = 0.f; }

#pragma unroll kBbUnroll
    for (int bb = 0; bb < 2; bb++) {
        cplx z[2][11], cz[2];
#pragma unroll
        for (int e = 0; e < 2; e++) {
            const float lg = e ? bf_hi(la.x) : bf_lo(la.x), ai = (e ? bf_hi(aim.x) : bf_lo(aim.x)) * dt;
            const float cr = (e ? bf_hi(cre.x) : bf_lo(cre.x)) * cscale, ci = (e ? bf_hi(cim.x) : bf_lo(cim.x)) * cscale;
            const float a2 = bf_round(ex2f(lg * 1.4426950408889634f)) * ndt;
            z[e][0] = cexpp(a2, ai);
            z[e][5] = cexpp(a2 * 32.f, ai * -32.f);
#pragma unroll
            for (int i = 1; i < 11; i++) if (i != 5) z[e][i] = (i == 3 || i == 7) ? csq<true>(z[e][i - 1]) : csq<false>(z[e][i - 1]);
            cz[e] = {fmaf(cr, z[e][0].r, -(ci * z[e][0].i)), fmaf(cr, z[e][0].i, ci * z[e][0].r)};
        }
        la.x = la.y; aim.x = aim.y; cre.x = cre.y; cim.x = cim.y;
        const hc z1 = hpack(z[0][0], z[1][0]), z2 = hpack(z[0][1], z[1][1]), z4 = hpack(z[0][2], z[1][2]);
        hc L[8], H[8];
        L[1] = hpack(z[0][3], z[1][3]); L[2] = hpack(z[0][4], z[1][4]); L[4] = hpack(z[0][5], z[1][5]);
        const hc y64 = hpack(z[0][6], z[1][6]), z128 = hpack(z[0][7], z[1][7]), z256 = hpack(z[0][8], z[1][8]);
        const hc z512 = hpack(z[0][9], z[1][9]), z1024 = hpack(z[0][10], z[1][10]);
        H[0] = hpack(cz[0], cz[1]);
        H[1] = hmul(H[0], z1); H[2] = hmul(H[0], z2); H[3] = hmul(H[1], z2);
        L[3] = hmul(L[1], L[2]);
#pragma unroll
        for (int i = 0; i < 4; i++) { H[4 + i] = hmul(H[i], z4); if (i) L[4 + i] = hmul(L[i], L[4]); }
        __syncwarp();
        sts128(ad.w, 0x3c003c00u, y64.r, 0u, y64.i);
#pragma unroll
        for (int i = 1; i < 8; i++) { const hc q = hmul(L[i], y64); sts128(ad.w + 16 * i, L[i].r, q.r, L[i].i, q.i); }
#pragma unroll
        for (int i = 0; i < 4; i++) sts128(ad.w + 128 + 16 * i, H[2 * i].r, H[2 * i].i, H[2 * i + 1].r, H[2 * i + 1].i);
        {
            const hc a = hmul(z256, z1), b = hmul(z256, z128), c = hmul(z256, z2), d = hmul(z512, z4);
            sts128(ad.w + 192, a.r, a.i, b.r, b.i);
            sts128(ad.w + 208, c.r, c.i, z512.r, z512.i);
            sts128(ad.w + 224, d.r, d.i, z1024.r, z1024.i);
            sts64(ad.wz, z128.r, z128.i);
        }
        __syncwarp();
        KSTAMP(1 + 2 * bb);
#pragma unroll kKgUnroll
        for (int k2 = 0; k2 < 4; k2++) {
#pragma unroll
            for (uint32_t s = 0; s < 2; s++) {
                const uint32_t o = k2 * 1920 + s * 240;
                const uint4 l = lds128(ad.l + o);
                const uint2 h0 = lds64(ad.h + o), m2 = lds64(ad.m2 + o), m3 = lds64(ad.m3 + o), m4 = lds64(ad.m4 + o), mz = lds64(ad.z + k2 * 64 + s * 8);
                const hc H0 = {h0.x, h0.y};
                const hc H1 = hmul(H0, {mz.x, mz.y}), H2 = hmul(H0, {m2.x, m2.y}), H3 = hmul(H2, {m3.x, m3.y}), H4 = hmul(H3, {m4.x, m4.y});
                mma_f16(acc[0], l.x, l.y, l.z, l.w, H0.r, H0.i);
                mma_f16(acc[1], l.x, l.y, l.z, l.w, H1.r, H1.i);
                mma_f16(acc[2], l.x, l.y, l.z, l.w, H2.r, H2.i);
                mma_f16(acc[3], l.x, l.y, l.z, l.w, H3.r, H3.i);
                mma_f16(acc[4], l.x, l.y, l.z, l.w, H4.r, H4.i);
            }
        }
        KSTAMP(2 + 2 * bb);
        if (bb == 0) half_done();
    }
    __syncwarp();
    main_done();
    KSTAMP(5);
#pragma unroll
    for (int i = 0; i < 4; i++) sts128(tab + 2048 + 512 * i + 16 * lane, 0, 0, 0, 0);
    if (lane < 15) sts32(tab + 4 * lane, 0);
    __syncwarp();
    const uint32_t d0 = tab + T_DENSE + 4 + 8 * lane, src = (lane + 31) & 31;
    const uint32_t p0 = pack_bf16(fmaf(k0, dt2, skip), 0.f);
    uint32_t prev = p0;
#pragma unroll
    for (int i = 0; i < 4; i++) {
        const uint32_t pk = pack_bf16(acc[i >> 1][2 * (i & 1) + 1] * scale_inv, acc[i >> 1][2 * (i & 1)] * scale_inv);
        sts64(d0 + 256 * i, __byte_perm(pk, __shfl_sync(0xffffffffu, lane == 31 ? prev : pk, src), 0x5432), pk);
        prev = pk;
    }
    const uint32_t w0 = pack_bf16(acc[2][0] * scale_inv, acc[2][1] * scale_inv), w1 = pack_bf16(acc[2][2] * scale_inv, acc[2][3] * scale_inv);
    const uint32_t sa = (lane & 1) ? 0x5410u : 0x5454u, sb2 = (lane & 1) ? 0x1010u : 0x5410u;
#pragma unroll
    for (int hf = 0; hf < 2; hf++) {
        const uint32_t w = hf ? w1 : w0;
        const uint32_t pv = __shfl_sync(0xffffffffu, lane != 31 ? w : hf ? w0 : __byte_perm(prev, w1, 0x5410), src);
        sts64(d0 + 1024 + 256 * hf, __byte_perm(w, pv, sa), __byte_perm(w, pv, sb2));
        sts64(d0 + 1536 + 256 * hf, __byte_perm(w, pv, sa + 0x2222u), __byte_perm(w, pv, sb2 + 0x2222u));
    }
    const uint32_t d3 = tab + T_R2 + 160 + 320 * (t & 1) + 16 * (g >> 1) + 8 * (g & 1) + 4 * (t >> 1), d3n = d3 + (g >= 6 ? 32 : 0);
    const uint32_t d4 = tab + T_R3 + 80 + 160 * t + 4 * g, d4n = d4 + (g >= 6 ? 16 : 0);
    uint32_t p3;
#pragma unroll
    for (int hf = 0; hf < 2; hf++)
#pragma unroll
        for (int e = 0; e < 2; e++) {
            const float v3 = acc[3][2 * hf + e] * scale_inv;
            const uint32_t p4 = pack_bf16(acc[4][2 * hf + e] * scale_inv, 0.f);
            p3 = pack_bf16(v3, v3);
            sts16(d3 + 64 * hf + 160 * e, p3);
            sts16((hf ? d3n : d3) + 64 * hf + 160 * e + 18, p3);
            sts16(d4 + 32 * hf + 80 * e, p4);
            sts16((hf ? d4n : d4) + 32 * hf + 80 * e + 10, p4);
        }
    if (lane == 31) {
        const uint32_t k512 = __byte_perm(w1, 0, 0x3232);
        sts32(tab + T_DENSE, p0);
        sts64(tab + T_DENSE + 4 * 513, k512, k512); sts16(tab + T_DENSE + 4 * 515 + 2, k512);
        sts16(tab + T_PATCH + 4 * 17, p3); sts32(tab + T_PATCH + 4 * 18, p3); sts16(tab + T_PATCH + 4 * 19 + 2, p3);
    }
    __syncwarp();
}

__device__ __forceinline__ void load_toep(uint32_t* a, uint32_t p, uint32_t pz) {
    a[0] = lds32(p); a[1] = lds32(p + 32); a[2] = lds32(pz - 32); a[3] = lds32(pz);
}
#define YIELDS 2
#define YIELD_AT 2
#define DENSE_BLK 4
__device__ __forceinline__ void dense_step(float (&acc)[16][4], uint32_t (&R)[8][4], const uint32_t (&A)[4][4], uint32_t (&An)[4][4],
                                           uint32_t va, uint32_t vmin, uint32_t pn, uint32_t pz, uint32_t zero, int bit, uint32_t& junk) {
#pragma unroll
    for (int i0 = 0; i0 < 8; i0 += DENSE_BLK) {
#pragma unroll 1
        do {
#pragma unroll
            for (int i = i0; i < i0 + DENSE_BLK; i++) {
                const int ip = (i - DENSE_BLK) & 7;
                ldsm4(R[ip], ip == 0 ? max(va - 16, vmin) : va + ip * 128 - (i0 ? 16 : 0));
                if ((i & 1) == 0) load_toep(An[i >> 1], pn + (i >> 1) * 512, pz + (i >> 1) * 512);
#pragma unroll
                for (int ka = 0; ka < 4; ka++) {
                    mma_v(acc[i + ka], A[ka], R[i][0], R[i][1]);
                    if (i + 8 + ka < 16 - ABL_SKIP) mma_v(acc[i + 8 + ka], A[ka], R[i][2], R[i][3]);
                }
                if ((YIELDS >> (i - i0)) & 1) asm volatile("xor.b32 %0, %0, %1;" : "+r"(junk) : "r"(__float_as_uint(acc[i + YIELD_AT][0])));
            }
        } while (zero & (1u << (bit + i0)));
    }
}
#define FFA_BLK 0
template <int F>
__device__ __forceinline__ void ffa_step(float (&acc)[16][4], float (&W)[8][4], uint32_t (&R)[8][4], uint32_t (&A)[4][4],
                                         uint32_t va, uint32_t vmin, uint32_t pb, uint32_t pz, uint32_t zero) {
    constexpr int S = F ^ 1;
    auto load = [&](int sh) {
#pragma unroll
        for (int i = S; i < 8; i += 2) ldsm4(R[i], i == 0 ? max(va - 16 * sh, vmin) : va - 16 * sh + i * 128);
#pragma unroll
        for (int k = S; k < 4; k += 2) load_toep(A[k], pb + 64 * sh + k * 512, pz + 64 * sh + k * 512);
    };
    auto prod = [&](int par, int dst) {
#pragma unroll
        for (int k = 0; k < 2; k++)
#pragma unroll
            for (int m = k; m < 8; m++) {
                const uint32_t* x = &R[2 * ((m - k) & 3) + par][2 * ((m - k) >> 2)];
                mma_v(dst == 1 ? W[m] : acc[2 * m + (dst >> 1)], A[2 * k + par], x[0], x[1]);
            }
    };
#pragma unroll 1
    do {
#pragma unroll 1
        do { load(0); prod(F, F); } while (FFA_BLK == 2 && (zero & (1u << (4 * F))));
#pragma unroll 1
        do {
            prod(S, S);
#pragma unroll
            for (int i = 0; i < 8; i++) A[(i >> 2) * 2 + F][i & 3] = badd2(A[(i >> 2) * 2][i & 3], A[(i >> 2) * 2 + 1][i & 3]);
#pragma unroll
            for (int i = 0; i < 16; i++) R[(i >> 2) * 2 + F][i & 3] = badd2(R[(i >> 2) * 2][i & 3], R[(i >> 2) * 2 + 1][i & 3]);
        } while (FFA_BLK == 2 && (zero & (2u << (4 * F))));
#pragma unroll 1
        do { load(1); prod(F, 2); } while (FFA_BLK == 2 && (zero & (4u << (4 * F))));
    } while (FFA_BLK == 1 && (zero & (8u << (4 * F))));
}
struct DenseTaps {
    uint32_t A[4][4], E[4], F[4], G[4];
    __device__ __forceinline__ DenseTaps(uint32_t pb, uint32_t pz) {
        constexpr int PP = T_PATCH - T_DENSE + 56;
        load_toep(E, pb + 2048, pz + 2048);
        load_toep(F, pb + PP, pz + PP);
        G[0] = lds32(pz + 2048 + 32); G[1] = lds32(pb + 2048 + 64); G[2] = lds32(pz + PP + 32); G[3] = lds32(pb + PP + 64);
    }
};
__device__ __forceinline__ uint32_t dense_phase(float (&acc)[16][4], uint32_t vmin, uint32_t va, uint32_t vo, uint32_t pb, DenseTaps& tp, uint32_t zero) {
    uint32_t R[8][4], A1[4][4], junk = 0;
    uint32_t pz = pb + zero;
    {
        uint32_t H[4][4];
#pragma unroll
        for (int i = 0; i < 4; i++) ldsm4(H[i], vo + i * 256);
#pragma unroll
        for (int i = 0; i < 8; i++) ldsm4(R[i], va + i * 128);
#pragma unroll
        for (int i = 0; i < 4; i++) load_toep(tp.A[i], pb + 512 * i, pz + 512 * i);
#pragma unroll
        for (int i = 0; i < 4; i++) mma_bf16_k8(acc[i + 4], tp.G[0], tp.G[1], H[i >> 1][2 * (i & 1) + 1]);
#pragma unroll
        for (int i = 0; i < 8; i++) mma_v(acc[i + 8], tp.G, H[i >> 1][2 * (i & 1)], H[i >> 1][2 * (i & 1) + 1]);
#pragma unroll
        for (int i = 0; i < 12; i++) mma_v(acc[i + 4], tp.E, R[i & 7][2 * (i >> 3)], R[i & 7][2 * (i >> 3) + 1]);
#pragma unroll
        for (int i = 0; i < 8; i++) mma_v(acc[i + 8], tp.F, R[i][0], R[i][1]);
    }
    float W[8][4];
#pragma unroll
    for (int i = 0; i < 32; i++) { W[i >> 2][i & 3] = 0.f; if (i >= 8) acc[2 * (i >> 2) + 1][i & 3] += acc[2 * (i >> 2)][i & 3]; }
#pragma unroll 1
    for (int rho = 0; rho < 8; rho += 2) {
        ffa_step<0>(acc, W, R, tp.A, va, vmin, pb, pz, zero);
        ffa_step<1>(acc, W, R, tp.A, va - 16, vmin, pb + 64, pz + 64, zero);
        pb += 128; pz += 128; va -= 32;
    }
#pragma unroll
    for (int i = 0; i < 32; i++) {
        const int m = i >> 2, j = i & 3;
        acc[2 * m + 1][j] = (acc[2 * m + 1][j] - acc[2 * m][j]) - W[m][j];
        if (m) acc[2 * m][j] += W[m - 1][j];
    }
    return __float_as_uint(W[7][0]) & zero;
}
__device__ __forceinline__ uint32_t ones2(int c, int lo, int hi) {
    return (((uint32_t)(c - lo) <= (uint32_t)(hi - lo)) ? 1u : 0u) | (((uint32_t)(c + 1 - lo) <= (uint32_t)(hi - lo)) ? 0x10000u : 0u);
}
__device__ __forceinline__ uint32_t box_bits(int lane) {
    const int d = 2 * (lane & 3) - (lane >> 2);
    auto four = [&](int L1, int H1, int L2, int H2) { return ones2(d, L1, H1) | ones2(d, L2, H2) << 1 | ones2(d + 8, L1, H1) << 2 | ones2(d + 8, L2, H2) << 3; };
    return four(5, 7, 0, 4) | four(1, 7, 0, 8) << 4;
}
struct Boxes {
    uint32_t q[4], ha[2];
    __device__ __forceinline__ Boxes(uint32_t bits, int k0, uint32_t h0, uint32_t h1) {
#pragma unroll
        for (int i = 0; i < 4; i++) q[i] = (bits & (0x10001u << (k0 + i))) * (0x3f80u >> (k0 + i));
        ha[0] = h0; ha[1] = h1;
    }
    __device__ __forceinline__ void load(int j, uint32_t* v, uint32_t zero) const {
        const uint32_t o = j * 128;
        v[0] = lds32(ha[0] + o); v[1] = lds32(ha[1] + zero + o); v[2] = lds32(ha[1] + o);
        v[3] = lds32(ha[0] + zero + o + 16); v[4] = lds32(ha[0] + o + 16); v[5] = lds32(ha[1] + o + 16);
    }
    __device__ __forceinline__ void sums(const uint32_t* v, float* Z, float* X, float* Y) const {
        mma_bf16_z(Z, q[0], q[1], q[2], q[3], v[0], v[1]);
        mma_bf16_z(X, q[0], q[1], q[2], q[3], v[2], v[3]);
        mma_bf16_z(Y, q[0], q[1], q[2], q[3], v[4], v[5]);
    }
};
__host__ __device__ constexpr int tail_step(int n) { return n < 8 ? n : n < 12 ? n + 4 : (n & 1) ? 11 - (n - 13) / 2 : 19 - (n - 12) / 2; }
template <class After>
__device__ __forceinline__ void tail_phase(float (&acc)[16][4], const Boxes& b2, const Boxes& b3, uint32_t tp2, uint32_t tp3, uint32_t zero, After after) {
    uint4 t2[5];
    uint2 t3[8];
    uint32_t v[6], a0[4], a1[4];
    float Z[4], X[4], Y[4];
    b2.load(0, v, zero);
#pragma unroll
    for (int i = 0; i < 5; i++) t2[i] = lds128(tp2 + 160 * i);
#pragma unroll
    for (int n = -1; n < 20; n++) {
        const int j = tail_step(n), j1 = tail_step(n + 1), j2 = tail_step(n + 2);
        if (n < 19) {
            (j1 < 12 ? b2 : b3).sums(v, Z, X, Y);
            if (n < 18) { if (j2 < 12) b2.load(j2, v, zero); else b3.load(j2 - 12, v, zero); }
        }
        if (n >= 0 && j < 12) {
#pragma unroll
            for (int b = 0; b < 5; b++) if (j + 4 + b < 16) mma_v(acc[j + 4 + b], a1, t2[b].z, t2[b].w);
        }
        if (n < 19 && j1 < 12) { a1[0] = pack_v(Z[0], Z[1]); a1[1] = pack_w(X[0], X[1]); a1[2] = pack_v(Z[2], Z[3]); a1[3] = pack_w(X[2], X[3]); }
        if (n == 6) {
#pragma unroll
            for (int b = 0; b < 8; b++) t3[b] = lds64(tp3 + 80 * b);
        }
        if (n >= 0 && j < 12) {
#pragma unroll
            for (int b = 0; b < 5; b++) if (j + 4 + b < 16) mma_v(acc[j + 4 + b], a0, t2[b].x, t2[b].y);
        } else if (n >= 0) {
#pragma unroll
            for (int b = 0; b < 8; b++) if (j - 4 + b < 16) mma_v(acc[j - 4 + b], a0, t3[b].x, t3[b].y);
        }
        if (n < 19) {
            if (j1 < 12) { a0[0] = pack_v(X[0], X[1]); a0[1] = pack_v(Y[0], Y[1]); a0[2] = pack_v(X[2], X[3]); a0[3] = pack_v(Y[2], Y[3]); }
            else { a0[0] = pack_v(X[0], X[1]); a0[1] = pack_v(Y[0], Y[1]); a0[2] = pack_v(Z[2], Z[3]); a0[3] = pack_v(X[2], X[3]); }
        }
        after(n);
    }
}
template <int Q>
__device__ __forceinline__ void emit(const float (&acc)[16][4], int h, uint32_t own, uint32_t peer, uint32_t bar, uint32_t bar_peer) {
    constexpr int n = 4 * Q, G = Q >> 1;
#pragma unroll
    for (int hf = 0; hf < 2; hf++)
        asm volatile("{ .reg .pred p; setp.eq.u32 p, %7, %8;\n\t@p st.shared.v4.u32 [%0], {%1,%2,%3,%4};\n\t"
                     "@!p st.async.weak.shared::cluster.mbarrier::complete_tx::bytes.v4.b32 [%5], {%1,%2,%3,%4}, [%6]; }"
                     ::"r"(own + G * 16384 + hf * 512), "r"(pack_bf16(acc[n][2 * hf], acc[n][2 * hf + 1])), "r"(pack_bf16(acc[n + 1][2 * hf], acc[n + 1][2 * hf + 1])),
                     "r"(pack_bf16(acc[n + 2][2 * hf], acc[n + 2][2 * hf + 1])), "r"(pack_bf16(acc[n + 3][2 * hf], acc[n + 3][2 * hf + 1])),
                     "r"(peer + G * 16384 + hf * 512), "r"(bar_peer + 8 * G), "r"(h), "n"(Q & 1) : "memory");
    __syncwarp();
    if (h == (Q & 1) && elect_one()) mbar_arrive(bar);
}
__device__ __forceinline__ uint32_t finish_src(uint32_t sb, int h, int w, int lane) {
    const int m = lane >> 3, r = lane & 7;
    return sb + OFF_XT + (h ^ 1) * 32768 + (2 * m + (r & 1)) * 1024 + (w >> 2) * 512 + (((8 * (w & 3) + (r & 4) + ((r >> 1) & 1)) ^ ((r & 1) << 1)) << 4);
}
__device__ __forceinline__ uint32_t finish_dst(uint32_t sb, int h, int w, int lane) {
    const int g = lane >> 2, t = lane & 3;
    return sb + OFF_XT + h * 32768 + w * 2048 + (g >> 1) * 512 + (t >> 1) * 144 + (2 * (t & 1) + (g & 1)) * 32;
}
__device__ __forceinline__ uint32_t tile_addr(uint32_t sb, int tok, int t) {
    return sb + OFF_XT + (tok & 512) * 64 + (tok >> 10) * 16384 + (tok & 14) * 1024 + (tok & 448) * 4 + (tok & 1) * 128 + (tok & 48) * 2 + (((t >> 1) ^ (tok & 1)) << 4) + (t & 1) * 8;
}
__device__ __forceinline__ uint2 add_update(uint2 o, uint32_t upd) {
    const float4 u = lds128f(upd);
    return make_uint2(badd2(o.x, pack_bf16(u.x, u.y)), badd2(o.y, pack_bf16(u.z, u.w)));
}
__device__ __forceinline__ void finish_half(uint32_t src, uint32_t xa, const uint4 (&x)[2]) {
    uint32_t s[2][4];
#pragma unroll
    for (int i = 0; i < 2; i++) ldsm4t(s[i], src ^ (i << 5));
#pragma unroll
    for (int i = 0; i < 2; i++) sts128(xa + i * 256, badd2(x[i].x, s[i][0]), badd2(x[i].y, s[i][1]), badd2(x[i].z, s[i][2]), badd2(x[i].w, s[i][3]));
}

__device__ __noinline__ float centred_var(uint32_t rows, float mu, int lane) {
    float var = 0.f;
#pragma unroll 1
    for (int rr = 0; rr < 16; rr++) {
        const float c0 = __shfl_sync(0xffffffffu, mu, rr);
        float c = 0.f;
#pragma unroll 1
        for (int k = 0; k < 16; k++) {
            const uint32_t q = lds32(rows + rr * ROW_PITCH + k * 128 + lane * 4);
            const float d0 = bf_lo(q) - c0, d1 = bf_hi(q) - c0;
            c = fmaf(d0, d0, fmaf(d1, d1, c));
        }
#pragma unroll 1
        for (int o = 16; o; o >>= 1) c += __shfl_xor_sync(0xffffffffu, c, o);
        if ((lane & 15) == rr) var = c * (1.f / DM);
    }
    return var;
}
__device__ __noinline__ float centred_score(uint32_t rows, uint32_t wbuf, uint32_t s0, uint32_t s1, int lane) {
    float sc = 0.f;
#pragma unroll 1
    for (int rr = 0; rr < 16; rr++) {
        const uint32_t t0 = __shfl_sync(0xffffffffu, s0, rr), t1 = __shfl_sync(0xffffffffu, s1, rr);
        float c = 0.f;
#pragma unroll 1
        for (int k = 0; k < 16; k++) {
            const uint32_t xn = normalize2(lds32(rows + rr * ROW_PITCH + k * 128 + lane * 4), t0, t1);
            const uint32_t wq = lds32(wbuf + (k >> 2) * 1024 + (k & 3) * 128 + lane * 4);
            c = fmaf(bf_lo(xn), bf_lo(wq), fmaf(bf_hi(xn), bf_hi(wq), c));
        }
#pragma unroll 1
        for (int o = 16; o; o >>= 1) c += __shfl_xor_sync(0xffffffffu, c, o);
        if ((lane & 15) == rr) sc = c;
    }
    return sc;
}

__device__ __forceinline__ void issue_rows(const __nv_bfloat16* u, uint32_t sb, int b) {
    if (elect_one()) {
        const uint32_t bar = sb + OFF_BAR + 8 * B_ROW;
#pragma unroll
        for (int j = 0; j < 4; j++) mbar_init(bar + 8 * j, 1);
        asm volatile("fence.mbarrier_init.release.cluster;" ::: "memory");
        fence_async();
#pragma unroll 1
        for (int j = 0; j < 4; j++) {
            mbar_expect_tx(bar + 8 * j, 8192);
#pragma unroll
            for (int i = 0; i < 4; i++) bulk_g2s(sb + OFF_VT + (4 * j + i) * ROW_PITCH, u + (size_t)(16 * b + 4 * j + i) * DM, 2048, bar + 8 * j);
        }
    }
    __syncwarp();
}

__global__ void __cluster_dims__(2, 1, 1) __launch_bounds__(NTHR, 1)
fused_kernel(const __grid_constant__ Ptrs p, const __grid_constant__ Maps maps) {
    extern __shared__ __align__(1024) unsigned char smem[];
    const int tid = threadIdx.x, lane = tid & 31;
    const int c_ = ((blockIdx.x >> 1) + PERM_OFF) & 63, b = 2 * ((c_ & 32) | ((c_ & 7) << 2) | ((c_ >> 3) & 3)) + (blockIdx.x & 1);
    const int dch = 8 * b + (tid >> 5) - 4;
    uint2 la, aim, cre, cim;
    uint32_t ldt16;
    if ((uint32_t)(tid - 128) < 256u) {
        la = ldg64(p.logA + dch * NMODE + 4 * lane); aim = ldg64(p.Aim + dch * NMODE + 4 * lane);
        cre = ldg64(p.Cre + dch * NMODE + 4 * lane); cim = ldg64(p.Cim + dch * NMODE + 4 * lane);
        ldt16 = ldg16(p.ldt + dch);
    }
    const uint32_t sb = s_u32(smem), bar0 = sb + OFF_BAR;
    const int warp = __shfl_sync(0xffffffffu, tid >> 5, 0);
    const int h = b & 1, cl = b >> 1;
    const int m = lane >> 3, r = lane & 7, g = lane >> 2, t = lane & 3;
    const bool has_gu = b < GU_CTAS;
    if (warp == 4) { STAMP(0); GSTAMP(24); }

    if (warp >= 12) {
        asm volatile("setmaxnreg.dec.sync.aligned.u32 " REG_S ";");
        const int a = warp - 12;
        uint32_t due = now_ns() + ST_T0 + (uint32_t)(128 * a + b) * ST_PER / 128 + (has_gu ? 0 : ST_LATE * (12 * ST_PER + 4 * ST_PER2) / 16);
        const bool el = elect_one();
        if (a == 1) issue_rows(p.u, sb, b);
        if (a == 2 && el) {
#pragma unroll
            for (int i = B_XT; i < NBAR; i++) mbar_init(bar0 + 8 * i, (i == B_V || i == B_SFREE || i == B_XFREE || i == B_OWN) ? 8 : i == B_RECV ? 9 : i == B_RED ? 5 : (i == B_UPD || (i >= B_FREE && i < B_FULL)) ? 4 : 1);
            asm volatile("fence.mbarrier_init.release.cluster;" ::: "memory");
            fence_async();
            mbar_expect_tx(bar0 + 8 * B_XT, 65536);
            mbar_expect_tx(bar0 + 8 * B_RECV, 8192);
            mbar_expect_tx(bar0 + 8 * B_RECV + 8, 8192);
            mbar_expect_tx(bar0 + 8 * B_RED, 2048);
        }
        if (a == 3 && el) {
#pragma unroll
            for (int i = 0; i < 5; i++) asm volatile("prefetch.tensormap [%0];" ::"l"(&maps.u + i) : "memory");
        }
        __syncwarp();
        cluster_arrive();
        cluster_wait();
        STAMP(18);
        mbar_wait(bar0 + 8 * (B_ROW + a), 0);
        if (el) {
#pragma unroll
            for (int i = 0; i < 4; i++)
                tma_load_tile(sb + OFF_XT + h * 32768 + a * 4096 + (i & 1) * 16384 + (i >> 1) * 2048, &maps.u, 16 * cl, 4 * a + (i & 2), 16 * (i & 1) + 8 * h, bar0 + 8 * B_XT);
        }
        if (el) {
#pragma unroll 1
            for (int k = has_gu ? 0 : 4; k < 6; k++) {
                const int i = 4 * k + a, s = k < 3 ? i : i - 12;
#pragma unroll 1
                for (int left; (left = (int)(due - now_ns())) > 0;) __nanosleep(left >> 1);
                due += k == 0 ? 4 * ST_PER + ST_GAP : k < 3 ? 4 * ST_PER : 4 * ST_PER2;
                const bool again = k >= 3 && has_gu;
                if (s >= 6 || again) mbar_wait(bar0 + 8 * (s < 10 || again ? B_FREE + s : B_V), slot_priv(s) && again);
                const uint32_t dst = sb + slot_off(s), bar = bar0 + 8 * (B_FULL + s);
                if (k < 4) {
                    mbar_expect_tx(bar, 8192);
                    tma_load_2d(dst, &maps.wg, 64 * cl, 512 * h + 32 * i, bar);
                    tma_load_2d(dst + 4096, &maps.wu, 64 * cl, 512 * h + 32 * i, bar);
                } else {
                    mbar_expect_tx(bar, 7168);
                    tma_load_perm(dst, &maps.wd, 16 * cl, 56 * h + 14 * a + 7 * (k & 1), bar);
                }
            }
            STAMP(19);
        }
        __syncwarp();
        {
            uint32_t fs = finish_src(sb, h, 2 * a, lane), fx = finish_dst(sb, h, 2 * a, lane);
#pragma unroll 1
            for (int G = 0; G < (Q2_HELP ? 2 - h : 1); G++) {
                if (G) mbar_wait(bar0 + 8 * B_OWN, 0);
                mbar_wait(bar0 + 8 * (B_RECV + G), 0);
#pragma unroll 1
                for (int k = 0; k < (G && Q2_HELP == 1 ? 1 : 2); k++) {
#pragma unroll
                    for (int i0 = 0; i0 < 4; i0 += FIN_ILP) {
                        uint32_t s[FIN_ILP][4];
                        uint4 x[FIN_ILP];
#pragma unroll
                        for (int i = i0; i < i0 + FIN_ILP; i++) {
                            ldsm4t(s[i - i0], (fs ^ ((i & 1) << 5)) + (i & 2) * 4096 + k * 128);
                            x[i - i0] = lds128((fx ^ ((i & 2) << 3)) + (i & 1) * 256 + k * 2048);
                        }
#pragma unroll
                        for (int i = i0; i < i0 + FIN_ILP; i++)
                            sts128((fx ^ ((i & 2) << 3)) + (i & 1) * 256 + k * 2048, badd2(x[i - i0].x, s[i - i0][0]), badd2(x[i - i0].y, s[i - i0][1]),
                                   badd2(x[i - i0].z, s[i - i0][2]), badd2(x[i - i0].w, s[i - i0][3]));
                    }
                    fence_async();
                    __syncwarp();
                    if (!(ABL & 2) && el) tma_store_tile(&maps.out, sb + OFF_XT + h * 32768 + G * 16384 + (2 * a + k) * 2048, 16 * cl, 4 * a + 2 * k, 16 * G + 8 * h);
                }
                fs += 16384; fx += 16384;
                if (G) STAMP(60); else if (h) STAMP(59); else STAMP(20);
            }
            const int tok = 2047 - (int)(lds32(sb + OFF_MISC + 48 + 8 * g) & 2047);
            const bool mine = (((tok >> 7) & 4) | ((tok >> 2) & 3)) == 4 * h + a && (tok < 1024 || (Q2_HELP && tok < 1536 && (Q2_HELP == 2 || !(tok & 2))));
            if (el) asm volatile("cp.async.bulk.wait_group 0;" ::: "memory");
            if (!(ABL & 1) && __any_sync(0xffffffffu, mine)) {
                const uint2 o0 = lds64(tile_addr(sb, tok, t));
                mbar_wait(bar0 + 8 * B_UPD, 0);
                const uint2 o1 = add_update(o0, sb + tab_off(g) + T_RED + 16 * t);
                if (mine) *reinterpret_cast<uint2*>(p.out + (size_t)tok * DM + 16 * cl + 4 * t) = o1;
            } else STAMP(62);
        }
    } else if (warp >= 4) {
        const int w = warp - 4;
        uint32_t dsk16 = ldg16(p.dsk + dch);
        cluster_arrive();
        asm volatile("setmaxnreg.inc.sync.aligned.u32 " REG_C ";");
        const uint32_t vrow = sb + OFF_VT + w * VT_PITCH + VT_PAD, tab = sb + tab_off(w);
        const uint32_t rb0 = bar0 + 8 * B_RECV, rb1 = mapa(rb0, h ^ 1);
        uint32_t tpo = 80 + (g - 2 * t) * 8 - (g < 2 * t ? 16 : 0);
        uint32_t xa = sb + OFF_XT + (w & 2) * 16384 + (w >> 2) * 16384 + (w & 1) * 1024 + (g >> 1) * 2048 + (g & 1) * 128 + t * 32 + ((h ^ (g & 1)) << 4);
        uint32_t va = sb + OFF_VT + (2 * m + (r & 1)) * VT_PITCH + VT_PAD + (16 * w + (r >> 1)) * 16;
        uint32_t qa = sb + OFF_ST + 2048 * w + 128 * t + 16 * (g ^ (2 * t));
        uint32_t vmin = vrow + (m & 1) * VT_PLANE - 16, vd = vmin + 16 + (m >> 1) * 1024 + r * 16;
        uint32_t vo = vrow + VT_PLANE + 496 - (m & 1) * 512 + (m >> 1) * 128 + r * 16, vz = vrow - VT_PAD + (lane >> 1) * VT_PLANE + (lane & 1) * 16;
        pin(vmin); pin(vd); pin(vo); pin(vz);
        pin(tpo); pin(xa); pin(va); pin(qa);
        uint32_t bits = box_bits(lane), h0 = vrow + 16 * g + tok_off(2 * t - 18), h1 = vrow + 16 * g + tok_off(2 * t - 10);
        pin(bits); pin(h0); pin(h1);
        const KgenAddr ka(sb + OFF_PRIV + w * 8192, lane);
        if (__any_sync(0xffffffffu, (vmin | (vd | vo | vz) | (tpo | xa) | (va | qa) | (bits | h0 | h1) | ka.any()) & p.zero)) __trap();
        cluster_wait();
        pin(la.x); pin(la.y); pin(aim.x); pin(aim.y); pin(cre.x); pin(cre.y); pin(cim.x); pin(cim.y); pin(ldt16); pin(dsk16);
        uint4 x[8];
        auto load_x = [&]() {
            mbar_wait(bar0 + 8 * B_XT, 0);
#pragma unroll
            for (int i = 0; i < 8; i++) x[i] = lds128(xa + (i & 1) * 8192 + (i >> 1) * 256);
        };
        kgen(ka, tab, lane, la, aim, cre, cim, bf_round(ex2f(bf_lo(ldt16) * 1.4426950408889634f)), 1.f + bf_lo(dsk16), dch, [&]() {
            STAMP(21);
            if (elect_one()) mbar_arrive_n(bar0 + 8 * (B_FREE + 6 + ((w >> 1) ^ 2)), 2);
        }, [&]() {
            if ((LN_PAUSE >> w) & 1) mbar_wait(bar0 + 8 * B_LN, 0);
        });
        STAMP(1); KSTAMP(6);
        const uint32_t pb = tab + T_DENSE + (g - 2 * t) * 4;
        DenseTaps dt(pb, pb + p.zero);
        {
            load_x();
            STAMP(47);
            mbar_wait(bar0 + 8 * (B_ST + (w >> 1)), 0);
            uint4 q[4];
#pragma unroll
            for (int n = 0; n < 4; n++) q[n] = lds128(qa + 512 * n);
            if (lane < 4) sts128(vz, 0, 0, 0, 0);
            STAMP(2); GSTAMP(28);
#pragma unroll
            for (int i = 0; i < 8; i++) {
                const uint32_t s0 = (i & 1) ? q[i >> 1].z : q[i >> 1].x, s1 = (i & 1) ? q[i >> 1].w : q[i >> 1].y;
                stsm4t(va + (i >> 1) * 64 + (i & 1) * VT_PLANE, normalize2(x[i].x, s0, s1), normalize2(x[i].y, s0, s1),
                       normalize2(x[i].z, s0, s1), normalize2(x[i].w, s0, s1));
            }
            __syncwarp();
            if (elect_one()) mbar_arrive(bar0 + 8 * B_V);
        }
        mbar_wait(bar0 + 8 * B_V, 0);
        STAMP(3); KSTAMP(7);
        float acc[16][4];
#pragma unroll
        for (int i = 0; i < 16; i++) { acc[i][0] = acc[i][1] = acc[i][2] = acc[i][3] = 0.f; }
        bits |= dense_phase(acc, vmin, vd, vo, pb, dt, p.zero);
        const Boxes b2(bits, 0, h0, h1), b3(bits, 4, (t == 1 ? h1 : h0) - 4, t == 1 ? h0 + 12 : h1 - 4);
        STAMP(4); KSTAMP(8);
        const uint32_t so = sb + OFF_XT + (8 * h + w) * 1024 + ((lane ^ ((w & 1) << 1)) << 4);
        const uint32_t dst0 = so + (h ^ 1) * 32768, dst1 = mapa(so + h * 32768, h ^ 1);
        tail_phase(acc, b2, b3, tab + T_R2 + 2 * tpo, tab + T_R3 + tpo, p.zero, [&](int j) {
            if (j == -1) {
                mbar_wait(bar0 + 8 * B_SFREE, 0);
                emit<0>(acc, h, dst0, dst1, rb0, rb1);
            }
            if (j == 3) { emit<1>(acc, h, dst0, dst1, rb0, rb1); STAMP(5); }
            if (j == 11) {
                mbar_wait(bar0 + 8 * B_XFREE, 0);
                emit<2>(acc, h, dst0, dst1, bar0 + 8 * B_OWN, rb1);
                STAMP(58);
            }
        });
        emit<3>(acc, h, dst0, dst1, bar0 + 8 * B_OWN, rb1);
        STAMP(30);
        if (h || Q2_HELP == 0 || (Q2_HELP == 1 && (w & 1))) {
        const uint32_t fs = finish_src(sb, h, w, lane) + 16384 + h * 8192, fx = (finish_dst(sb, h, w, lane) + 16384) ^ (h << 4);
        const int tok = 2047 - (int)(lds32(sb + OFF_MISC + 48 + 8 * g) & 2047);
        const bool mine = (((tok >> 6) & 24) | ((tok >> 1) & 7)) == 16 + 8 * h + w;
        const uint32_t ta = tile_addr(sb, tok, t);
        const uint4 x0[2] = {lds128(fx), lds128(fx + 256)}, x1[2] = {lds128(fx ^ 16), lds128((fx ^ 16) + 256)};
        mbar_wait(bar0 + 8 * B_OWN, 0);
        finish_half(fs, fx, x0);
        mbar_wait(bar0 + 8 * (B_RECV + 1), 0);
        STAMP(6);
        finish_half(fs + (h ? -8192 : 8192), fx ^ 16, x1);
        __syncwarp();
        if (!(ABL & 1) && __any_sync(0xffffffffu, mine)) {
            const uint2 o0 = lds64(ta);
            mbar_wait(bar0 + 8 * B_UPD, 0);
            const uint2 o1 = add_update(o0, sb + tab_off(g) + T_RED + 16 * t);
            if (mine) sts64(ta, o1.x, o1.y);
        }
        fence_async();
        __syncwarp();
        if (!(ABL & 4) && elect_one()) {
            tma_store_tile(&maps.out, sb + OFF_XT + h * 32768 + 16384 + w * 2048, 16 * cl, 2 * w, 16 + 8 * h);
            asm volatile("cp.async.bulk.wait_group.read 0;" ::: "memory");
        }
        STAMP(7);
        }
    } else {
        const int a = warp;
        const uint4 wq = ldg128(p.wr + 8 * tid);
        const uint32_t epoch = ld_relaxed_32(&p.sc->epoch);
        cluster_arrive();
        asm volatile("setmaxnreg.inc.sync.aligned.u32 " REG_A ";");
        const uint32_t tag = __shfl_sync(0xffffffffu, epoch, 0) + 1u, misc = sb + OFF_MISC, abar = bar0 + 8 * (B_AUX + a);
        uint32_t aph = 0;
        const Exchange* in = &p.sc->x[cl & (NREP - 1)];
        uint2* pub = p.sc->x[m >> 1].stat + 16 * b + 2 * (r ^ (2 * (b & 3))) + (m & 1);
        uint32_t* cnt_s = &p.sc->x[t].n_stat[b & 96];
        pin(pub); pin(cnt_s);
        if (tid < 64) sts32(sb + OFF_XCH + 4 * tid, 0);
        const uint32_t wbuf = sb + OFF_LN + a * 1024, part = sb + OFF_LN + 4096;
        {
            sts128(wbuf + 16 * lane, wq.x, wq.y, wq.z, wq.w);
            sts128(wbuf + 512 + 16 * lane, 0x3f803f80u, 0x3f803f80u, 0x3f803f80u, 0x3f803f80u);
            float wsum = ((bf_lo(wq.x) + bf_hi(wq.x)) + (bf_lo(wq.y) + bf_hi(wq.y))) + ((bf_lo(wq.z) + bf_hi(wq.z)) + (bf_lo(wq.w) + bf_hi(wq.w)));
#pragma unroll
            for (int o = 16; o; o >>= 1) wsum += __shfl_xor_sync(0xffffffffu, wsum, o);
            sts32f(part + 1024 + 4 * a, wsum);
            uint32_t wf[4][4];
#pragma unroll
            for (int i = 0; i < 4; i++) ldsm4(wf[i], wbuf + ((uint32_t)(r - 1) < 2u ? 16 * (r - 1) : 512) + 32 * m + 128 * i);
            uint32_t ra = sb + OFF_VT + r * ROW_PITCH + 512 * a + 16 * m, pa = part + a * 256 + g * 16;
            cluster_wait();
            STAMP(22);
#pragma unroll 1
            for (int hf = 0; hf < 2; hf++) {
                mbar_wait(bar0 + 8 * B_ROW + 16 * hf, 0);
                mbar_wait(bar0 + 8 * B_ROW + 16 * hf + 8, 0);
                STAMP(23);
                uint32_t x[8][4];
                float cs[2][4], q[8][4];
#pragma unroll
                for (int i = 0; i < 40; i++) (i < 8 ? cs[i >> 2 & 1] : q[(i - 8) >> 2 & 7])[i & 3] = 0.f;
#pragma unroll
                for (int k = 0; k < 8; k++) ldsm4(x[k], ra + k * 64);
                const bool more = __any_sync(0xffffffffu, after_all(x, p.zero));
#pragma unroll 1
                do {
#pragma unroll
                    for (int k = 0; k < 8; k++) {
                        mma_v(cs[k & 1], x[k], wf[k >> 1][2 * (k & 1)], wf[k >> 1][2 * (k & 1) + 1]);
#pragma unroll
                        for (int i = 0; i < 4; i++) mma_bf16_k8(q[4 * (k & 1) + i], x[k][i & 2], x[k][i | 1], x[k][i]);
                    }
                } while (more);
                const float c2 = cs[0][2] + cs[1][2];
                if (t == 0) sts64f(pa, (cs[0][0] + cs[1][0]) + c2, cs[0][1] + cs[1][1]);
                if (t == 1) sts32f(pa + 12, c2);
                const float e0 = ((q[0][0] + q[2][0]) + (q[4][0] + q[6][0])) + ((q[1][2] + q[3][2]) + (q[5][2] + q[7][2]));
                const float e1 = ((q[0][1] + q[2][1]) + (q[4][1] + q[6][1])) + ((q[1][3] + q[3][3]) + (q[5][3] + q[7][3]));
                if (t == (g >> 1)) sts32f(pa + 8, (g & 1) ? e1 : e0);
                ra += 8 * ROW_PITCH; pa += 128;
            }
        }
        STAMP(31);
        named_sync(1, 128);
        if (a == 0) {
            const uint32_t pa = part + (lane & 15) * 16;
            const float4 p0 = lds128f(pa), p1 = lds128f(pa + 256), p2 = lds128f(pa + 512), p3 = lds128f(pa + 768), ws = lds128f(part + 1024);
            const float mu = ((p0.x + p1.x) + (p2.x + p3.x)) * (1.f / DM);
            float var = ((p0.z + p1.z) + (p2.z + p3.z)) * (1.f / DM) - mu * mu;
            const bool centred = __any_sync(0xffffffffu, !(mu * mu <= 4.f * var));
            if (centred) var = centred_var(sb + OFF_VT, mu, lane);
            const float ri = rcpf(bf_round(sqrtaf(bf_round(bf_round(var) + 1e-5f))));
            const uint32_t s0 = pack_bf16(mu, ri), s1 = (pack_bf16(ri - bf_hi(s0), 0.f) & 0xfffcu) | (tag & 3);
            float sc = ((((p0.y + p1.y) + (p2.y + p3.y)) + ((p0.w + p1.w) + (p2.w + p3.w))) - bf_lo(s0) * ((ws.x + ws.y) + (ws.z + ws.w))) * ri;
            if (centred) sc = centred_score(sb + OFF_VT, sb + OFF_LN, s0, s1, lane);
            const uint32_t sb16 = pack_bf16(0.f, sc);
            const uint32_t s2 = s1 | (sb16 ^ (((uint32_t)((int)sb16 >> 31) & 0x7fff0000u) | 0x80000000u));
            st_relaxed_64(pub, s0, s2);
            st_relaxed_64(pub + 2 * sizeof(Exchange) / 8, s0, s2);
            if (lane < NREP) red_add(cnt_s, 1);
            if (elect_one()) mbar_arrive(bar0 + 8 * B_LN);
            STAMP(9); GSTAMP(25);
        }
        const uint32_t slot0 = sb + OFF_RING + a * 8192, slot1 = sb + slot_off(4 + a), slot2 = sb + slot_off(8 + a), fbar = bar0 + 8 * (B_FULL + a);
        uint32_t mine = 0, row[2] = {0, 0};
        {
            uint32_t q[16];
            named_sync(1, 128);
            wait_count(&in->n_stat[32 * a], 32 * tag - FEW_ST);
            STAMP(41);
#pragma unroll 1
            for (uint32_t it = 0;; spin_guard(it)) {
                if (elect_one()) {
                    mbar_expect_tx(abar, 4096);
                    bulk_g2s(sb + OFF_ST + 4096 * a, in->stat + 512 * a, 4096, abar);
                }
                mbar_wait(abar, aph);
                aph ^= 1;
                uint32_t bad = 0;
#pragma unroll
                for (int n = 0; n < 8; n++) {
                    const uint4 u = lds128v(sb + OFF_ST + 4096 * a + 512 * n + 16 * lane);
                    q[2 * n] = u.y; q[2 * n + 1] = u.w;
                    bad = or_xor(bad, u.y, tag);
                }
                const bool ok = __all_sync(0xffffffffu, (bad & 3) == 0);
                asm volatile("{ .reg .pred p; setp.ne.u32 p, %1, 0; @p mbarrier.arrive.shared::cta.b64 _, [%0]; }" ::"r"(bar0 + 8 * (B_ST + a)), "r"((uint32_t)(ok && lane == 0)) : "memory");
                if (ok) break;
            }
            STAMP(8);
            const uint32_t inv = 2047 - 512 * a - 16 * m - (r ^ (2 * m));
#pragma unroll
            for (int i = 0; i < 16; i++) asm("lop3.b32 %0, %0, %1, %2, 0x9b;" : "+r"(q[i]) : "r"(inv), "r"(0xffff0000u | (64 * (i >> 1) + 8 * (i & 1))));
            auto below = [&](uint32_t x) {
                uint32_t d[4];
#pragma unroll
                for (int i = 0; i < 16; i++) d[i & 3] = i < 4 ? x + q[i] : min(d[i & 3], x + q[i]);
                d[0] = min(min(d[0], d[1]), min(d[2], d[3]));
                return d[0] < x ? x - 1 - d[0] : 0u;
            };
            const uint32_t mx0 = ~min(min(min(min(q[0], q[1]), min(q[2], q[3])), min(min(q[4], q[5]), min(q[6], q[7]))),
                                      min(min(min(q[8], q[9]), min(q[10], q[11])), min(min(q[12], q[13]), min(q[14], q[15]))));
            const uint32_t gm = min(__reduce_max_sync(0xffffffffu, lane < 16 ? mx0 : 0u), __reduce_max_sync(0xffffffffu, lane < 16 ? 0u : mx0));
            if (lane == 0) sts32(misc + 16 + 4 * a, gm);
            named_sync(1, 128);
            STAMP(42);
            if (b == 0 && tid == 0) st_relaxed_32(&p.sc->epoch, tag);
            const uint4 t0 = lds128(misc + 16);
            uint32_t tau = min(min(t0.x, t0.y), min(t0.z, t0.w));
            uint32_t mx = mx0, cnt = 0, bal;
            const uint32_t list = sb + OFF_XCH + 64 * a;
#pragma unroll 1
            while ((bal = __ballot_sync(0xffffffffu, mx >= tau)) != 0) {
                const uint32_t pos = cnt + __popc(bal & ((1u << lane) - 1u));
                cnt += __popc(bal);
                if (cnt > 16) break;
                if (mx >= tau) sts32(list + 4 * pos, mx);
                mx = below(mx);
            }
            if (cnt > 16) {
                mx = mx0;
#pragma unroll 1
                for (int j = 0; j < 8; j++) {
                    const uint32_t top = __reduce_max_sync(0xffffffffu, mx), nx = below(mx);
                    if (mx == top) { sts32(list + 4 * j, mx); sts32(list + 32 + 4 * j, 0); mx = nx; }
                }
            }
            named_sync(1, 128);
            STAMP(43);
            const uint2 k = lds64(sb + OFF_XCH + 8 * lane);
            uint32_t hi = max(k.x, k.y), lo = min(k.x, k.y);
            mbar_wait(bar0 + 8 * B_V, 0);
#pragma unroll
            for (int j = 0; j < 8; j++) {
                const uint32_t top = __reduce_max_sync(0xffffffffu, hi);
                const bool won = hi == top;
                hi = won ? lo : hi;
                lo = won ? 0u : lo;
                if (g == j) mine = top;
                if (a == (j >> 1)) row[j & 1] = top;
            }
        }
        STAMP(11);
        const int tok = 2047 - (int)(mine & 2047);
        const uint32_t xs = sb + OFF_XT + (h ^ 1) * 32768 + 16384;
        if (has_gu) {
            if (elect_one()) {
                mbar_expect_tx(abar, 2048);
#pragma unroll
                for (int j = 0; j < 2; j++) bulk_g2s(xs + (2 * a + j) * 1040, p.u + (size_t)(2047 - (row[j] & 2047)) * DM + 512 * h, 1024, abar);
            }
        }
        STAMP(44);
        const uint2 st = ld_relaxed_64(in->stat + (tok & ~15) + 2 * ((tok & 7) ^ ((tok >> 3) & 6)) + ((tok >> 3) & 1));
        if (a == 0 && t == 0) sts64(misc + 48 + 8 * g, mine, __float_as_uint(bf_hi(st.x) + bf_lo(st.y)));
        if (a == 0) STAMP(45);
        if (has_gu) {
            const uint32_t mean = __shfl_sync(0xffffffffu, st.x, 8 * a + 4 * (lane >> 4)), xr = xs + (2 * a + (lane >> 4)) * 1040 + 16 * (lane & 15);
            mbar_wait(abar, aph);
            aph ^= 1;
            STAMP(46);
            uint4 x[4];
#pragma unroll
            for (int j = 0; j < 4; j++) x[j] = lds128(xr + 256 * j);
#pragma unroll
            for (int j = 0; j < 4; j++) sts128(xr + 256 * j, bsub2_lo(x[j].x, mean), bsub2_lo(x[j].y, mean), bsub2_lo(x[j].z, mean), bsub2_lo(x[j].w, mean));
            if (elect_one()) mbar_expect_tx(abar, 512);
            named_sync(1, 128);
        }
        if (lane < (has_gu ? 2 : 4)) mbar_arrive_peer(mapa(bar0 + 8 * (lane & 2 ? B_XFREE : B_SFREE), lane & 1));
        if (has_gu) {
            STAMP(12);
            float gacc[8][4];
#pragma unroll
            for (int i = 0; i < 8; i++) { gacc[i][0] = gacc[i][1] = gacc[i][2] = gacc[i][3] = 0.f; }
            uint32_t* pubh = reinterpret_cast<uint32_t*>(&p.sc->x[0].h[b * 32 + 8 * a + (g ^ (2 * a))]) + t;
            uint32_t* cnt_h = &p.sc->x[t].n_h[32 * (b / 14)];
            uint32_t ko = sb + (m & 1) * 4096 + (r + ((m >> 1) << 3)) * 128 + ((r ^ (4 * h) ^ a) << 4), kp = ko ^ 64, xb = xs + r * 1040 + m * 16;
            uint32_t xch = sb + OFF_XCH + 16 * tid, tagm = t == 3 ? 1u : 0u;
            pin(pubh); pin(cnt_h); pin(ko); pin(kp); pin(xb); pin(xch); pin(tagm);
            const float r0 = lds32f(misc + 52 + 16 * t), r1 = lds32f(misc + 60 + 16 * t);
#pragma unroll
            for (int c = 0; c < 4; c++) {
                uint32_t af[20][4];
#pragma unroll
                for (int j = 0; j < 4; j++) ldsm4(af[16 + j], xb + 256 * c + 64 * j);
                if (c == 3) mbar_wait(bar0 + 8 * B_SFREE, 0);
#pragma unroll
                for (int j = 0; j < 4; j++) {
                    mbar_wait(bar0 + 8 * (B_FULL + 4 * (c % 3) + j), c / 3);
#pragma unroll
                    for (int i = 0; i < 4; i++) ldsm4t(af[8 * (i >> 1) + 2 * j + (i & 1)], ((i & 1) ? kp : ko) + slot_off(4 * (c % 3) + j) + (i >> 1) * 2048);
                }
                STAMP(36 + c);
                __syncwarp();
                if (c < 3 && lane < 4) mbar_arrive(bar0 + 8 * (B_FREE + 4 * c + lane));
                const bool more = __any_sync(0xffffffffu, (af[6][3] | af[7][3] | af[14][3] | af[15][3]) & p.zero);
#pragma unroll 1
                do {
#pragma unroll
                    for (int i = 0; i < 16; i++) mma_v(gacc[i & 7], af[i], af[16 + ((i >> 1) & 3)][2 * (i >> 3)], af[16 + ((i >> 1) & 3)][2 * (i >> 3) + 1]);
                } while (more);
            }
            STAMP(13);
            float own[4], oth[4];
#pragma unroll
            for (int j = 0; j < 4; j++) oth[j] = (gacc[1][j] + gacc[3][j]) + (gacc[5][j] + gacc[7][j]);
            st_async128(mapa(xch, h ^ 1), __float_as_uint(oth[0]), __float_as_uint(oth[1]), __float_as_uint(oth[2]), __float_as_uint(oth[3]), mapa(abar, h ^ 1));
            STAMP(56);
#pragma unroll
            for (int j = 0; j < 4; j++) own[j] = ((gacc[0][j] + gacc[2][j]) + (gacc[4][j] + gacc[6][j])) * ((j & 1) ? r1 : r0);
            mbar_wait(abar, aph);
            aph ^= 1;
            STAMP(57);
            const float4 o4 = lds128f(xch);
            const float g0 = bf_round(fmaf(o4.x, r0, own[0])), g1 = bf_round(fmaf(o4.y, r1, own[1]));
            const float h0 = bf_round(g0 * rcpf(1.f + ex2f(-1.4426950408889634f * g0))) * bf_round(fmaf(o4.z, r0, own[2]));
            const float h1 = bf_round(g1 * rcpf(1.f + ex2f(-1.4426950408889634f * g1))) * bf_round(fmaf(o4.w, r1, own[3]));
            uint32_t hw;
            asm volatile("movmatrix.sync.aligned.m8n8.trans.b16 %0, %1;" : "=r"(hw) : "r"(pack_bf16(h0, h1)));
            hw = (hw & ~tagm) | (tag & tagm);
#pragma unroll
            for (int j = 0; j < NREP; j++) st_relaxed_32(pubh + j * (sizeof(Exchange) / 4), hw);
            if (lane < NREP) red_add(cnt_h, 1);
            if (lane < 2) mbar_arrive_peer(mapa(bar0 + 8 * B_XFREE, lane));
            named_sync(1, 128);
            STAMP(14);
        }
        float dacc[4];
        const int tk = ((tid >> 1) & 6) | (tid & 1);
        uint32_t ro = 4 * tid, red = sb + tab_off(tk) + T_RED + 4 * ((tid >> 4) + 4 * (tid & 2));
        if (!has_gu) named_sync(1, 128);
        const float sg = bf_round(rcpf(1.f + ex2f(-1.4426950408889634f * __uint_as_float(unorder_key(lds32(misc + 48 + 8 * tk) >> 16) << 16))));
        pin(ro); pin(red);
        mbar_wait(bar0 + 8 * B_XFREE, 0);
        {
            uint32_t wo = (r + ((m >> 1) << 3)) * 32 + (((m & 1) ^ (r >> 2)) << 4), af[14][4];
            uint32_t ho = slot0 + 128 * t + 16 * (g ^ (2 * t));
            pin(wo); pin(ho);
            float d[7][4];
#pragma unroll
            for (int i = 0; i < 7; i++) { d[i][0] = d[i][1] = d[i][2] = d[i][3] = 0.f; }
            auto first_half = [&]() {
                mbar_wait(fbar + 32, has_gu);
#pragma unroll
                for (int j = 0; j < 14; j++) ldsm4t(af[j], slot1 + wo + j * 512);
            };
            auto fetch = [&]() {
                if (elect_one()) {
                    mbar_expect_tx(abar, 7168);
                    bulk_g2s(slot0, &in->h[(56 * h + 14 * a) * 32], 7168, abar);
                }
            };
            wait_count(&in->n_h[32 * (4 * h + a)], 56 * tag - FEW_H);
            STAMP(33);
            fetch();
            first_half();
            mbar_wait(abar, aph);
#pragma unroll
            for (int s = 0; s < 2; s++) {
                if (s) {
                    mbar_wait(fbar + 64, has_gu);
#pragma unroll
                    for (int j = 0; j < 14; j++) ldsm4t(af[j], slot2 + wo + j * 512);
                }
                uint4 hq[7];
#pragma unroll 1
                for (uint32_t it = 0;; spin_guard(it)) {
                    uint32_t bad = 0;
#pragma unroll
                    for (int j = 0; j < 7; j++) { hq[j] = lds128(ho + 512 * (7 * s + j)); bad = or_xor(bad, hq[j].w, tag); }
                    if (__all_sync(0xffffffffu, (bad & 1) == 0)) break;
                    fetch();
                    aph ^= 1;
                    mbar_wait(abar, aph);
                }
                if (s == 0) STAMP(15);
#pragma unroll
                for (int j = 0; j < 14; j++) {
                    const uint4 q = hq[j >> 1];
                    mma_v(d[j % 7], af[j], (j & 1) ? q.z : q.x, (j & 1) ? q.w : q.y);
                }
            }
#pragma unroll
            for (int j = 0; j < 4; j++) dacc[j] = ((d[0][j] + d[1][j]) + (d[2][j] + d[3][j])) + ((d[4][j] + d[5][j]) + d[6][j]);
        }
        STAMP(16);
        {
            st_async128(mapa(sb + OFF_XCH + 16 * tid, h ^ 1), __float_as_uint(dacc[0]), __float_as_uint(dacc[1]), __float_as_uint(dacc[2]), __float_as_uint(dacc[3]),
                        mapa(bar0 + 8 * B_RED, h ^ 1));
            sts128f(slot0 + 7680 + lane * 16, dacc);
            __syncwarp();
            if (elect_one()) mbar_arrive(bar0 + 8 * B_RED);
            mbar_wait(bar0 + 8 * B_RED, 0);
            const uint32_t b0 = sb + OFF_RING + 7680 + ro, b1 = sb + OFF_XCH + ro;
            const float y = ((lds32f(b0) + lds32f(b0 + 8192)) + (lds32f(b0 + 16384) + lds32f(b0 + 24576))) +
                            ((lds32f(b1) + lds32f(b1 + 512)) + (lds32f(b1 + 1024) + lds32f(b1 + 1536)));
            sts32f(red, bf_round(y) * sg);
            __syncwarp();
            if (elect_one()) mbar_arrive(bar0 + 8 * B_UPD);
        }
        STAMP(17); GSTAMP(29);
    }
}

typedef CUresult (*EncodeFn)(CUtensorMap*, CUtensorMapDataType, cuuint32_t, void*, const cuuint64_t*, const cuuint64_t*,
                             const cuuint32_t*, const cuuint32_t*, CUtensorMapInterleave, CUtensorMapSwizzle,
                             CUtensorMapL2promotion, CUtensorMapFloatOOBfill);

void make_map(EncodeFn enc, CUtensorMap* m, const void* ptr, uint64_t cols, uint64_t rows, uint32_t bc, uint32_t br,
              CUtensorMapSwizzle sw, CUtensorMapL2promotion pr) {
    cuuint64_t dims[2] = {cols, rows};
    cuuint64_t str[1] = {cols * 2};
    cuuint32_t box[2] = {bc, br};
    cuuint32_t es[2] = {1, 1};
    enc(m, CU_TENSOR_MAP_DATA_TYPE_BFLOAT16, 2, const_cast<void*>(ptr), dims, str, box, es, CU_TENSOR_MAP_INTERLEAVE_NONE, sw, pr,
        CU_TENSOR_MAP_FLOAT_OOB_FILL_NONE);
}
void make_perm_map(EncodeFn enc, CUtensorMap* m, const void* ptr, CUtensorMapL2promotion pr) {
    cuuint64_t dims[5] = {DM, 2, 4, 4, FF / 32};
    cuuint64_t str[4] = {DM * 2, 8 * DM * 2, 2 * DM * 2, 32 * DM * 2};
    cuuint32_t box[5] = {16, 2, 4, 4, 7};
    cuuint32_t es[5] = {1, 1, 1, 1, 1};
    enc(m, CU_TENSOR_MAP_DATA_TYPE_BFLOAT16, 5, const_cast<void*>(ptr), dims, str, box, es, CU_TENSOR_MAP_INTERLEAVE_NONE,
        CU_TENSOR_MAP_SWIZZLE_32B, pr, CU_TENSOR_MAP_FLOAT_OOB_FILL_NONE);
}
void make_tile_map(EncodeFn enc, CUtensorMap* m, const void* ptr) {
    cuuint64_t dims[4] = {DM, 4, 16, SEQ / 64};
    cuuint64_t str[3] = {16 * DM * 2, DM * 2, 64 * DM * 2};
    cuuint32_t box[4] = {16, 4, 2, 8};
    cuuint32_t es[4] = {1, 1, 1, 1};
    enc(m, CU_TENSOR_MAP_DATA_TYPE_BFLOAT16, 4, const_cast<void*>(ptr), dims, str, box, es, CU_TENSOR_MAP_INTERLEAVE_NONE,
        CU_TENSOR_MAP_SWIZZLE_32B, CU_TENSOR_MAP_L2_PROMOTION_NONE, CU_TENSOR_MAP_FLOAT_OOB_FILL_NONE);
}

}

#define WD_PROMO CU_TENSOR_MAP_L2_PROMOTION_L2_64B
extern "C" void kernel_launch(void* const* d_in, const int* in_sizes, int n_in, void* d_out, int out_size) {
    (void)in_sizes; (void)n_in; (void)out_size;
    static EncodeFn enc = nullptr;
    static void* scratch = nullptr;
    if (!enc) {
        void* fn = nullptr;
        cudaDriverEntryPointQueryResult q;
        cudaGetDriverEntryPoint("cuTensorMapEncodeTiled", &fn, cudaEnableDefault, &q);
        enc = (EncodeFn)fn;
        cudaGetSymbolAddress(&scratch, g_scratch);
        cudaFuncSetAttribute(fused_kernel, cudaFuncAttributeMaxDynamicSharedMemorySize, SMEM_BYTES);
    }
    Maps maps;
    make_tile_map(enc, &maps.u, d_in[0]);
    make_tile_map(enc, &maps.out, d_out);
    make_map(enc, &maps.wg, d_in[9], FF, DM, 64, 32, CU_TENSOR_MAP_SWIZZLE_128B, CU_TENSOR_MAP_L2_PROMOTION_L2_128B);
    make_map(enc, &maps.wu, d_in[10], FF, DM, 64, 32, CU_TENSOR_MAP_SWIZZLE_128B, CU_TENSOR_MAP_L2_PROMOTION_L2_128B);
    make_perm_map(enc, &maps.wd, d_in[11], WD_PROMO);
    Ptrs p;
    p.sc = (Scratch*)scratch;
    p.u = (const __nv_bfloat16*)d_in[0];
    p.logA = (const __nv_bfloat16*)d_in[1];
    p.Aim = (const __nv_bfloat16*)d_in[2];
    p.Cre = (const __nv_bfloat16*)d_in[3];
    p.Cim = (const __nv_bfloat16*)d_in[4];
    p.ldt = (const __nv_bfloat16*)d_in[5];
    p.dsk = (const __nv_bfloat16*)d_in[6];
    p.wr = (const __nv_bfloat16*)d_in[8];
    p.out = (__nv_bfloat16*)d_out;
    p.zero = 0;
    fused_kernel<<<NCTA, NTHR, SMEM_BYTES, cudaStreamPerThread>>>(p, maps);
}
```

```cpp
#include <cuda_runtime.h>
#include <cuda_bf16.h>
#include <cuda_fp16.h>
#include <cuda.h>
#include <stdint.h>

namespace {

constexpr int SEQ = 2048, DM = 1024, NMODE = 128, FF = 3584;
constexpr int NCTA = 128, NTHR = 512;
constexpr int GU_CTAS = 112;
constexpr int NREP = 4;

constexpr int OFF_XT = 0;
constexpr int OFF_RING = 65536;
constexpr int OFF_PRIV = OFF_RING + 65536;
constexpr int OFF_VT = OFF_PRIV + 65536;
constexpr int VT_PAD = 32, VT_PLANE = VT_PAD + 2048, VT_PITCH = 2 * VT_PLANE, ROW_PITCH = 2064;
constexpr int OFF_BAR = OFF_VT + 8 * VT_PITCH;
constexpr int OFF_MISC = OFF_BAR + 384;
constexpr int OFF_XCH = OFF_MISC + 112;
constexpr int SMEM_BYTES = OFF_XCH + 2048;
constexpr int OFF_LN = OFF_RING + 7 * 8192;
constexpr int OFF_ST = OFF_RING + 6 * 8192;
static_assert(SMEM_BYTES <= 232448, "shared memory");

constexpr int B_ROW = 0, B_XT = 4, B_V = 5, B_LN = 6, B_SFREE = 7, B_RECV = 8, B_RED = 10, B_UPD = 11, B_ST = 12, B_XFREE = 16, B_OWN = 17, B_FREE = 20, B_FULL = 32, B_AUX = 44, NBAR = 48;

constexpr int T_DENSE = 60;
constexpr int T_PATCH = 2208;
constexpr int T_R2 = 2368;
constexpr int T_R3 = 3296;

constexpr int T_RED = 4032;
__device__ __forceinline__ bool slot_priv(int s) { return (uint32_t)(s - 6) < 4u; }
__device__ __forceinline__ uint32_t slot_off(int s) { return slot_priv(s) ? OFF_PRIV + 4096 + (s & 3) * 16384 : OFF_RING + (s < 6 ? s : s - 4) * 8192; }
__device__ __forceinline__ uint32_t tab_off(int w) { return OFF_PRIV + w * 8192 + (w & 1) * 4096; }

constexpr uint32_t SPIN_LIMIT = 1u << 20;
#define ST_T0 2280
#define ST_PER 308
#define ST_PER2 320
#define LN_PAUSE 0xf0
#define FEW_ST 8
#define FEW_H 8

struct Exchange {
    uint2 stat[SEQ];
    uint4 h[GU_CTAS * 32];
    uint32_t n_stat[4 * 32];
    uint32_t n_h[8 * 32];
};
struct Scratch {
    Exchange x[NREP];
    uint32_t epoch;
};
__device__ __align__(128) Scratch g_scratch;

struct Ptrs {
    const __nv_bfloat16 *logA, *Aim, *Cre, *Cim, *ldt, *u;
    const __nv_bfloat16 *dsk, *wr;
    Scratch* sc;
    __nv_bfloat16* out;
    uint32_t zero;
};
struct Maps {
    CUtensorMap u, out, wg, wu, wd;
};

#define STAMP(i) do { } while (0)
#define GSTAMP(i) do { } while (0)

__device__ __forceinline__ uint32_t s_u32(const void* p) { return (uint32_t)__cvta_generic_to_shared(p); }
__device__ __forceinline__ void mbar_init(uint32_t b, uint32_t n) {
    asm volatile("mbarrier.init.shared::cta.b64 [%0], %1;" ::"r"(b), "r"(n) : "memory");
}
__device__ __forceinline__ void mbar_expect_tx(uint32_t b, uint32_t bytes) {
    asm volatile("mbarrier.arrive.expect_tx.shared::cta.b64 _, [%0], %1;" ::"r"(b), "r"(bytes) : "memory");
}
__device__ __forceinline__ void mbar_arrive(uint32_t b) {
    asm volatile("mbarrier.arrive.shared::cta.b64 _, [%0];" ::"r"(b) : "memory");
}
__device__ __forceinline__ void mbar_arrive_n(uint32_t b, uint32_t n) {
    asm volatile("mbarrier.arrive.shared::cta.b64 _, [%0], %1;" ::"r"(b), "r"(n) : "memory");
}
__device__ __forceinline__ void mbar_arrive_peer(uint32_t b_cluster) {
    asm volatile("mbarrier.arrive.relaxed.cluster.shared::cluster.b64 _, [%0];" ::"r"(b_cluster) : "memory");
}
__device__ __forceinline__ void mbar_wait(uint32_t b, uint32_t parity) {
    asm volatile("{\n\t.reg .pred p;\n\t.reg .u32 c;\n\tmov.u32 c, 0;\n"
                 "W:\n\tmbarrier.try_wait.parity.shared::cta.b64 p, [%0], %1;\n\t@p bra D;\n\t"
                 "add.u32 c, c, 1;\n\tsetp.lt.u32 p, c, 1048576;\n\t@p bra W;\n\ttrap;\nD:\n\t}"
                 ::"r"(b), "r"(parity) : "memory");
}
__device__ __forceinline__ bool elect_one() {
    uint32_t p;
    asm volatile("{ .reg .pred P; elect.sync _|P, 0xffffffff; selp.u32 %0, 1, 0, P; }" : "=r"(p));
    return p != 0;
}
__device__ __forceinline__ uint32_t mapa(uint32_t a, uint32_t rank) {
    uint32_t r;
    asm("mapa.shared::cluster.u32 %0, %1, %2;" : "=r"(r) : "r"(a), "r"(rank));
    return r;
}
__device__ __forceinline__ void cluster_arrive() { asm volatile("barrier.cluster.arrive.relaxed.aligned;" ::: "memory"); }
__device__ __forceinline__ void cluster_wait() { asm volatile("barrier.cluster.wait.acquire.aligned;" ::: "memory"); }
__device__ __forceinline__ void tma_load_2d(uint32_t dst, const CUtensorMap* m, int c0, int c1, uint32_t bar) {
    asm volatile("cp.async.bulk.tensor.2d.shared::cluster.global.mbarrier::complete_tx::bytes [%0], [%1, {%3, %4}], [%2];"
                 ::"r"(dst), "l"(m), "r"(bar), "r"(c0), "r"(c1) : "memory");
}
__device__ __forceinline__ void tma_load_perm(uint32_t dst, const CUtensorMap* m, int c0, int blk, uint32_t bar) {
    asm volatile("cp.async.bulk.tensor.5d.shared::cluster.global.mbarrier::complete_tx::bytes [%0], [%1, {%3, %4, %4, %4, %5}], [%2];"
                 ::"r"(dst), "l"(m), "r"(bar), "r"(c0), "r"(0), "r"(blk) : "memory");
}
__device__ __forceinline__ void tma_load_tile(uint32_t dst, const CUtensorMap* m, int c0, int c2, int c3, uint32_t bar) {
    asm volatile("cp.async.bulk.tensor.4d.shared::cluster.global.mbarrier::complete_tx::bytes.multicast::cluster [%0], [%1, {%3, %4, %5, %6}], [%2], %7;"
                 ::"r"(dst), "l"(m), "r"(bar), "r"(c0), "r"(0), "r"(c2), "r"(c3), "h"((uint16_t)3) : "memory");
}
__device__ __forceinline__ void tma_store_tile(const CUtensorMap* m, uint32_t src, int c0, int c2, int c3) {
    asm volatile("cp.async.bulk.tensor.4d.global.shared::cta.bulk_group [%0, {%2, %3, %4, %5}], [%1];"
                 ::"l"(m), "r"(src), "r"(c0), "r"(0), "r"(c2), "r"(c3) : "memory");
    asm volatile("cp.async.bulk.commit_group;" ::: "memory");
}
__device__ __forceinline__ void bulk_g2s(uint32_t dst, const void* src, uint32_t bytes, uint32_t bar) {
    asm volatile("cp.async.bulk.shared::cluster.global.mbarrier::complete_tx::bytes [%0], [%1], %2, [%3];"
                 ::"r"(dst), "l"(src), "r"(bytes), "r"(bar) : "memory");
}
__device__ __forceinline__ void st_async128(uint32_t dst_cluster, uint32_t x, uint32_t y, uint32_t z, uint32_t w, uint32_t bar_cluster) {
    asm volatile("st.async.weak.shared::cluster.mbarrier::complete_tx::bytes.v4.b32 [%0], {%1,%2,%3,%4}, [%5];"
                 ::"r"(dst_cluster), "r"(x), "r"(y), "r"(z), "r"(w), "r"(bar_cluster) : "memory");
}
__device__ __forceinline__ void fence_async() { asm volatile("fence.proxy.async.shared::cta;" ::: "memory"); }
__device__ __forceinline__ void named_sync(int id, int n) { asm volatile("bar.sync %0, %1;" ::"r"(id), "r"(n) : "memory"); }

__device__ __forceinline__ void ldsm4(uint32_t* r, uint32_t a) {
    asm volatile("ldmatrix.sync.aligned.m8n8.x4.shared.b16 {%0,%1,%2,%3}, [%4];"
                 : "=r"(r[0]), "=r"(r[1]), "=r"(r[2]), "=r"(r[3]) : "r"(a));
}
__device__ __forceinline__ void ldsm4t(uint32_t* r, uint32_t a) {
    asm volatile("ldmatrix.sync.aligned.m8n8.x4.trans.shared.b16 {%0,%1,%2,%3}, [%4];"
                 : "=r"(r[0]), "=r"(r[1]), "=r"(r[2]), "=r"(r[3]) : "r"(a));
}
__device__ __forceinline__ void stsm4t(uint32_t a, uint32_t x, uint32_t y, uint32_t z, uint32_t w) {
    asm volatile("stmatrix.sync.aligned.m8n8.x4.trans.shared.b16 [%0], {%1,%2,%3,%4};"
                 ::"r"(a), "r"(x), "r"(y), "r"(z), "r"(w) : "memory");
}
__device__ __forceinline__ uint32_t lds32(uint32_t a) { uint32_t v; asm volatile("ld.shared.u32 %0, [%1];" : "=r"(v) : "r"(a)); return v; }
__device__ __forceinline__ float lds32f(uint32_t a) { float v; asm volatile("ld.shared.f32 %0, [%1];" : "=f"(v) : "r"(a)); return v; }
__device__ __forceinline__ uint2 lds64(uint32_t a) { uint2 v; asm volatile("ld.shared.v2.u32 {%0,%1}, [%2];" : "=r"(v.x), "=r"(v.y) : "r"(a)); return v; }
__device__ __forceinline__ uint4 lds128(uint32_t a) {
    uint4 v; asm volatile("ld.shared.v4.u32 {%0,%1,%2,%3}, [%4];" : "=r"(v.x), "=r"(v.y), "=r"(v.z), "=r"(v.w) : "r"(a)); return v;
}
__device__ __forceinline__ uint4 lds128v(uint32_t a) {
    uint4 v; asm volatile("ld.volatile.shared.v4.u32 {%0,%1,%2,%3}, [%4];" : "=r"(v.x), "=r"(v.y), "=r"(v.z), "=r"(v.w) : "r"(a)); return v;
}
__device__ __forceinline__ uint32_t or_xor(uint32_t a, uint32_t b, uint32_t c) {
    uint32_t r; asm("lop3.b32 %0, %1, %2, %3, 0xf6;" : "=r"(r) : "r"(a), "r"(b), "r"(c)); return r;
}
__device__ __forceinline__ float4 lds128f(uint32_t a) {
    float4 v; asm volatile("ld.shared.v4.f32 {%0,%1,%2,%3}, [%4];" : "=f"(v.x), "=f"(v.y), "=f"(v.z), "=f"(v.w) : "r"(a)); return v;
}
__device__ __forceinline__ void sts32(uint32_t a, uint32_t v) { asm volatile("st.shared.u32 [%0], %1;" ::"r"(a), "r"(v) : "memory"); }
__device__ __forceinline__ void sts32f(uint32_t a, float v) { asm volatile("st.shared.f32 [%0], %1;" ::"r"(a), "f"(v) : "memory"); }
__device__ __forceinline__ void sts64(uint32_t a, uint32_t x, uint32_t y) { asm volatile("st.shared.v2.u32 [%0], {%1,%2};" ::"r"(a), "r"(x), "r"(y) : "memory"); }
__device__ __forceinline__ void sts64f(uint32_t a, float x, float y) { asm volatile("st.shared.v2.f32 [%0], {%1,%2};" ::"r"(a), "f"(x), "f"(y) : "memory"); }
__device__ __forceinline__ void sts128(uint32_t a, uint32_t x, uint32_t y, uint32_t z, uint32_t w) {
    asm volatile("st.shared.v4.u32 [%0], {%1,%2,%3,%4};" ::"r"(a), "r"(x), "r"(y), "r"(z), "r"(w) : "memory");
}
__device__ __forceinline__ void sts128f(uint32_t a, const float* v) {
    asm volatile("st.shared.v4.f32 [%0], {%1,%2,%3,%4};" ::"r"(a), "f"(v[0]), "f"(v[1]), "f"(v[2]), "f"(v[3]) : "memory");
}
__device__ __forceinline__ uint4 ldg128(const void* p) {
    uint4 v; asm volatile("ld.global.nc.L1::no_allocate.v4.u32 {%0,%1,%2,%3}, [%4];" : "=r"(v.x), "=r"(v.y), "=r"(v.z), "=r"(v.w) : "l"(p)); return v;
}
__device__ __forceinline__ uint2 ldg64(const void* p) {
    uint2 v; asm volatile("ld.global.nc.L1::no_allocate.v2.u32 {%0,%1}, [%2];" : "=r"(v.x), "=r"(v.y) : "l"(p)); return v;
}
__device__ __forceinline__ uint32_t ldg16(const void* p) {
    uint32_t v; asm volatile("ld.global.nc.u16 %0, [%1];" : "=r"(v) : "l"(p)); return v;
}
__device__ __forceinline__ uint2 ld_relaxed_64(const void* p) {
    uint2 v; asm volatile("ld.relaxed.gpu.global.v2.u32 {%0,%1}, [%2];" : "=r"(v.x), "=r"(v.y) : "l"(p) : "memory"); return v;
}
__device__ __forceinline__ uint32_t ld_relaxed_32(const void* p) {
    uint32_t v; asm volatile("ld.relaxed.gpu.global.u32 %0, [%1];" : "=r"(v) : "l"(p) : "memory"); return v;
}
__device__ __forceinline__ void st_relaxed_64(void* p, uint32_t x, uint32_t y) {
    asm volatile("st.relaxed.gpu.global.v2.u32 [%0], {%1,%2};" ::"l"(p), "r"(x), "r"(y) : "memory");
}
__device__ __forceinline__ void st_relaxed_32(void* p, uint32_t v) {
    asm volatile("st.relaxed.gpu.global.u32 [%0], %1;" ::"l"(p), "r"(v) : "memory");
}
__device__ __forceinline__ void red_add(void* p, uint32_t v) { asm volatile("red.relaxed.gpu.global.add.u32 [%0], %1;" ::"l"(p), "r"(v) : "memory"); }
__device__ __forceinline__ uint32_t now_ns() { uint32_t t; asm volatile("mov.u32 %0, %%globaltimer_lo;" : "=r"(t) :: "memory"); return t; }
__device__ __forceinline__ void spin_guard(uint32_t& it) { if (++it > SPIN_LIMIT) __trap(); }
__device__ __forceinline__ void wait_count(const uint32_t* p, uint32_t target) {
#pragma unroll 1
    for (uint32_t it = 0; __any_sync(0xffffffffu, (int)(ld_relaxed_32(p) - target) < 0); spin_guard(it)) { }
}
__device__ __forceinline__ void mma_bf16_k8(float* c, uint32_t a0, uint32_t a1, uint32_t b0) {
    asm("mma.sync.aligned.m16n8k8.row.col.f32.bf16.bf16.f32 {%0,%1,%2,%3}, {%4,%5}, {%6}, {%0,%1,%2,%3};"
                 : "+f"(c[0]), "+f"(c[1]), "+f"(c[2]), "+f"(c[3]) : "r"(a0), "r"(a1), "r"(b0));
}
__device__ __forceinline__ void mma_v(float* c, const uint32_t* a, uint32_t b0, uint32_t b1) {
    asm volatile("mma.sync.aligned.m16n8k16.row.col.f32.bf16.bf16.f32 {%0,%1,%2,%3}, {%4,%5,%6,%7}, {%8,%9}, {%0,%1,%2,%3};"
                 : "+f"(c[0]), "+f"(c[1]), "+f"(c[2]), "+f"(c[3]) : "r"(a[0]), "r"(a[1]), "r"(a[2]), "r"(a[3]), "r"(b0), "r"(b1));
}
__device__ __forceinline__ void mma_bf16_z(float* c, uint32_t a0, uint32_t a1, uint32_t a2, uint32_t a3, uint32_t b0, uint32_t b1) {
    asm volatile("mma.sync.aligned.m16n8k16.row.col.f32.bf16.bf16.f32 {%0,%1,%2,%3}, {%4,%5,%6,%7}, {%8,%9}, {%10,%10,%10,%10};"
        : "=f"(c[0]), "=f"(c[1]), "=f"(c[2]), "=f"(c[3]) : "r"(a0), "r"(a1), "r"(a2), "r"(a3), "r"(b0), "r"(b1), "f"(0.f));
}
__device__ __forceinline__ void mma_f16(float* c, uint32_t a0, uint32_t a1, uint32_t a2, uint32_t a3, uint32_t b0, uint32_t b1) {
    asm("mma.sync.aligned.m16n8k16.row.col.f32.f16.f16.f32 {%0,%1,%2,%3}, {%4,%5,%6,%7}, {%8,%9}, {%0,%1,%2,%3};"
                 : "+f"(c[0]), "+f"(c[1]), "+f"(c[2]), "+f"(c[3]) : "r"(a0), "r"(a1), "r"(a2), "r"(a3), "r"(b0), "r"(b1));
}
__device__ __forceinline__ uint32_t pack_bf16(float lo, float hi) {
    uint32_t r; asm("cvt.rn.bf16x2.f32 %0, %1, %2;" : "=r"(r) : "f"(hi), "f"(lo)); return r;
}
__device__ __forceinline__ uint32_t pack_v(float lo, float hi) {
    uint32_t r; asm volatile("cvt.rn.bf16x2.f32 %0, %1, %2;" : "=r"(r) : "f"(hi), "f"(lo)); return r;
}
__device__ __forceinline__ uint32_t pack_w(float lo, float hi) {
    uint32_t r; asm volatile("cvt.rn.satfinite.bf16x2.f32 %0, %1, %2;" : "=r"(r) : "f"(hi), "f"(lo)); return r;
}
template <int N> __device__ __forceinline__ uint32_t after_all(const uint32_t (&f)[N][4], uint32_t zero) {
    uint32_t d[3] = {0, 0, 0};
#pragma unroll
    for (int i = 0; i < N; i++) d[i % 3] |= f[i][3];
    return (d[0] | d[1] | d[2]) & zero;
}
__device__ __forceinline__ void pin(uint32_t& x) { asm volatile("" : "+r"(x)); }
template <class T> __device__ __forceinline__ void pin(T*& x) { asm volatile("" : "+l"(x)); }
__device__ __forceinline__ uint32_t pack_f16(float lo, float hi) {
    uint32_t r; asm("cvt.rn.f16x2.f32 %0, %1, %2;" : "=r"(r) : "f"(hi), "f"(lo)); return r;
}
__device__ __forceinline__ float bf_lo(uint32_t v) { return __uint_as_float(v << 16); }
__device__ __forceinline__ float bf_hi(uint32_t v) { return __uint_as_float(v & 0xffff0000u); }
__device__ __forceinline__ float bf_round(float x) { return __uint_as_float(pack_bf16(0.f, x)); }
__device__ __forceinline__ uint32_t badd2(uint32_t a, uint32_t b) { uint32_t r; asm("add.rn.bf16x2 %0, %1, %2;" : "=r"(r) : "r"(a), "r"(b)); return r; }
__device__ __forceinline__ uint32_t bsub2_lo(uint32_t a, uint32_t b) {
    uint32_t r; asm("{ .reg .b16 m, h; .reg .b32 m2; mov.b32 {m, h}, %2; mov.b32 m2, {m, m}; sub.rn.bf16x2 %0, %1, m2; }" : "=r"(r) : "r"(a), "r"(b)); return r;
}
__device__ __forceinline__ uint32_t bmax2(uint32_t a, uint32_t b) { uint32_t r; asm("max.bf16x2 %0, %1, %2;" : "=r"(r) : "r"(a), "r"(b)); return r; }
__device__ __forceinline__ uint32_t normalize2(uint32_t x, uint32_t s0, uint32_t s1) {
    uint32_t r;
    asm("{ .reg .b16 m, h, l, k; .reg .b32 m2, h2, l2, d, t;\n\t"
        "mov.b32 {m, h}, %2; mov.b32 {l, k}, %3; mov.b32 m2, {m, m}; mov.b32 h2, {h, h}; mov.b32 l2, {l, l};\n\t"
        "sub.rn.bf16x2 d, %1, m2; mul.rn.bf16x2 t, d, l2; fma.rn.bf16x2 %0, d, h2, t; }" : "=r"(r) : "r"(x), "r"(s0), "r"(s1));
    return r;
}
__device__ __forceinline__ float rcpf(float x) { float r; asm("rcp.approx.ftz.f32 %0, %1;" : "=f"(r) : "f"(x)); return r; }
__device__ __forceinline__ float sqrtaf(float x) { float r; asm("sqrt.approx.ftz.f32 %0, %1;" : "=f"(r) : "f"(x)); return r; }
__device__ __forceinline__ float ex2f(float x) { float r; asm("ex2.approx.ftz.f32 %0, %1;" : "=f"(r) : "f"(x)); return r; }

__device__ __forceinline__ int tok_off(int t) { return ((t >> 3) & 1) * VT_PLANE + (t >> 4) * 16 + (t & 7) * 2; }

__device__ __forceinline__ uint32_t unorder_key(uint32_t k16) { return k16 ^ ((k16 & 0x8000u) ? 0x8000u : 0xffffu); }

struct cplx { float r, i; };
struct hc { uint32_t r, i; };
template <bool CONJ> __device__ __forceinline__ cplx csq(cplx a) {
    float im;
    asm("{ .reg .f32 t; mul.ftz.f32 t, %1, %2; mul.ftz.f32 %0, t, 0f40000000; }" : "=f"(im) : "f"(CONJ ? -a.r : a.r), "f"(a.i));
    return {fmaf(a.r, a.r, -(a.i * a.i)), im};
}
__device__ __forceinline__ cplx cexpp(float a2, float ai) {
    float m = ex2f(a2), s, c;
    __sincosf(ai, &s, &c);
    return {m * c, m * s};
}
__device__ __forceinline__ __half2 as_h2(uint32_t x) { return *reinterpret_cast<__half2*>(&x); }
__device__ __forceinline__ uint32_t as_u(__half2 x) { return *reinterpret_cast<uint32_t*>(&x); }
__device__ __forceinline__ hc hmul(hc a, hc b) {
    return {as_u(__hfma2(as_h2(a.r), as_h2(b.r), __hneg2(__hmul2(as_h2(a.i), as_h2(b.i))))),
            as_u(__hfma2(as_h2(a.r), as_h2(b.i), __hmul2(as_h2(a.i), as_h2(b.r))))};
}
__device__ __forceinline__ hc hpack(cplx a, cplx b) { return {pack_f16(a.r, b.r), pack_f16(a.i, b.i)}; }
__device__ __forceinline__ void sts16(uint32_t a, uint32_t v) { asm volatile("st.shared.u16 [%0], %1;" ::"r"(a), "r"(v) : "memory"); }

struct KgenAddr {
    uint32_t l, h, m2, m3, m4, z, w, wz;
    __device__ __forceinline__ KgenAddr(uint32_t scr, int lane) {
        const int g = lane >> 2, t = lane & 3;
        const uint32_t rec = scr + t * 480;
        l = rec + 16 * g; h = rec + 128 + 8 * g; m2 = rec + 192 + 8 * (g & 1); m3 = rec + 208 + 4 * (g & 2); m4 = rec + 224 + 2 * (g & 4);
        z = scr + 7680 + 16 * t; w = scr + 240 * lane; wz = scr + 7680 + 8 * lane;
        pin(l); pin(h); pin(m2); pin(m3); pin(m4); pin(z); pin(w); pin(wz);
    }
    __device__ __forceinline__ uint32_t any() const { return (l | h | m2) | (m3 | m4 | z) | (w | wz); }
};
template <class Hook, class Hook2>
__device__ __forceinline__ void kgen(const KgenAddr& ad, uint32_t tab, int lane, uint2 la, uint2 aim, uint2 cre, uint2 cim, float dt, float skip, int dch, Hook main_done, Hook2 half_done) {
    const int g = lane >> 2, t = lane & 3;
    const float dt2 = 2.f * dt;
    const uint32_t am = bmax2(bmax2(cre.x & 0x7fff7fffu, cre.y & 0x7fff7fffu), bmax2(cim.x & 0x7fff7fffu, cim.y & 0x7fff7fffu));
    const float mx = dt2 * fmaxf(bf_lo(am), bf_hi(am));
    const uint32_t eb = min(max(__reduce_max_sync(0xffffffffu, __float_as_uint(mx)) >> 23, 1u), 252u);
    const float cscale = dt2 * __uint_as_float((253u - eb) << 23);
    const float scale_inv = __uint_as_float((eb + 1u) << 23);
    float k0 = (bf_lo(cre.x) + bf_hi(cre.x)) + (bf_lo(cre.y) + bf_hi(cre.y));
#pragma unroll
    for (int o = 16; o; o >>= 1) k0 += __shfl_xor_sync(0xffffffffu, k0, o);
    const float ndt = -1.4426950408889634f * dt;
    STAMP(40);

    float acc[5][4];
#pragma unroll
    for (int i = 0; i < 5; i++) { acc[i][0] = acc[i][1] = acc[i][2] = acc[i][3] = 0.f; }

#pragma unroll 1
    for (int bb = 0; bb < 2; bb++) {
        cplx z[2][11], cz[2];
#pragma unroll
        for (int e = 0; e < 2; e++) {
            const float lg = e ? bf_hi(la.x) : bf_lo(la.x), ai = (e ? bf_hi(aim.x) : bf_lo(aim.x)) * dt;
            const float cr = (e ? bf_hi(cre.x) : bf_lo(cre.x)) * cscale, ci = (e ? bf_hi(cim.x) : bf_lo(cim.x)) * cscale;
            const float a2 = bf_round(ex2f(lg * 1.4426950408889634f)) * ndt;
            z[e][0] = cexpp(a2, ai);
            z[e][5] = cexpp(a2 * 32.f, ai * -32.f);
#pragma unroll
            for (int i = 1; i < 11; i++) if (i != 5) z[e][i] = (i == 3 || i == 7) ? csq<true>(z[e][i - 1]) : csq<false>(z[e][i - 1]);
            cz[e] = {fmaf(cr, z[e][0].r, -(ci * z[e][0].i)), fmaf(cr, z[e][0].i, ci * z[e][0].r)};
        }
        la.x = la.y; aim.x = aim.y; cre.x = cre.y; cim.x = cim.y;
        const hc z1 = hpack(z[0][0], z[1][0]), z2 = hpack(z[0][1], z[1][1]), z4 = hpack(z[0][2], z[1][2]);
        hc L[8], H[8];
        L[1] = hpack(z[0][3], z[1][3]); L[2] = hpack(z[0][4], z[1][4]); L[4] = hpack(z[0][5], z[1][5]);
        const hc y64 = hpack(z[0][6], z[1][6]), z128 = hpack(z[0][7], z[1][7]), z256 = hpack(z[0][8], z[1][8]);
        const hc z512 = hpack(z[0][9], z[1][9]), z1024 = hpack(z[0][10], z[1][10]);
        H[0] = hpack(cz[0], cz[1]);
        H[1] = hmul(H[0], z1); H[2] = hmul(H[0], z2); H[3] = hmul(H[1], z2);
        L[3] = hmul(L[1], L[2]);
#pragma unroll
        for (int i = 0; i < 4; i++) { H[4 + i] = hmul(H[i], z4); if (i) L[4 + i] = hmul(L[i], L[4]); }
        __syncwarp();
        sts128(ad.w, 0x3c003c00u, y64.r, 0u, y64.i);
#pragma unroll
        for (int i = 1; i < 8; i++) { const hc q = hmul(L[i], y64); sts128(ad.w + 16 * i, L[i].r, q.r, L[i].i, q.i); }
#pragma unroll
        for (int i = 0; i < 4; i++) sts128(ad.w + 128 + 16 * i, H[2 * i].r, H[2 * i].i, H[2 * i + 1].r, H[2 * i + 1].i);
        {
            const hc a = hmul(z256, z1), b = hmul(z256, z128), c = hmul(z256, z2), d = hmul(z512, z4);
            sts128(ad.w + 192, a.r, a.i, b.r, b.i);
            sts128(ad.w + 208, c.r, c.i, z512.r, z512.i);
            sts128(ad.w + 224, d.r, d.i, z1024.r, z1024.i);
            sts64(ad.wz, z128.r, z128.i);
        }
        __syncwarp();

#pragma unroll
        for (int k2 = 0; k2 < 4; k2++) {
#pragma unroll
            for (uint32_t s = 0; s < 2; s++) {
                const uint32_t o = k2 * 1920 + s * 240;
                const uint4 l = lds128(ad.l + o);
                const uint2 h0 = lds64(ad.h + o), m2 = lds64(ad.m2 + o), m3 = lds64(ad.m3 + o), m4 = lds64(ad.m4 + o), mz = lds64(ad.z + k2 * 64 + s * 8);
                const hc H0 = {h0.x, h0.y};
                const hc H1 = hmul(H0, {mz.x, mz.y}), H2 = hmul(H0, {m2.x, m2.y}), H3 = hmul(H2, {m3.x, m3.y}), H4 = hmul(H3, {m4.x, m4.y});
                mma_f16(acc[0], l.x, l.y, l.z, l.w, H0.r, H0.i);
                mma_f16(acc[1], l.x, l.y, l.z, l.w, H1.r, H1.i);
                mma_f16(acc[2], l.x, l.y, l.z, l.w, H2.r, H2.i);
                mma_f16(acc[3], l.x, l.y, l.z, l.w, H3.r, H3.i);
                mma_f16(acc[4], l.x, l.y, l.z, l.w, H4.r, H4.i);
            }
        }

        if (bb == 0) half_done();
    }
    __syncwarp();
    main_done();

#pragma unroll
    for (int i = 0; i < 4; i++) sts128(tab + 2048 + 512 * i + 16 * lane, 0, 0, 0, 0);
    if (lane < 15) sts32(tab + 4 * lane, 0);
    __syncwarp();
    const uint32_t d0 = tab + T_DENSE + 4 + 8 * lane, src = (lane + 31) & 31;
    const uint32_t p0 = pack_bf16(fmaf(k0, dt2, skip), 0.f);
    uint32_t prev = p0;
#pragma unroll
    for (int i = 0; i < 4; i++) {
        const uint32_t pk = pack_bf16(acc[i >> 1][2 * (i & 1) + 1] * scale_inv, acc[i >> 1][2 * (i & 1)] * scale_inv);
        sts64(d0 + 256 * i, __byte_perm(pk, __shfl_sync(0xffffffffu, lane == 31 ? prev : pk, src), 0x5432), pk);
        prev = pk;
    }
    const uint32_t w0 = pack_bf16(acc[2][0] * scale_inv, acc[2][1] * scale_inv), w1 = pack_bf16(acc[2][2] * scale_inv, acc[2][3] * scale_inv);
    const uint32_t sa = (lane & 1) ? 0x5410u : 0x5454u, sb2 = (lane & 1) ? 0x1010u : 0x5410u;
#pragma unroll
    for (int hf = 0; hf < 2; hf++) {
        const uint32_t w = hf ? w1 : w0;
        const uint32_t pv = __shfl_sync(0xffffffffu, lane != 31 ? w : hf ? w0 : __byte_perm(prev, w1, 0x5410), src);
        sts64(d0 + 1024 + 256 * hf, __byte_perm(w, pv, sa), __byte_perm(w, pv, sb2));
        sts64(d0 + 1536 + 256 * hf, __byte_perm(w, pv, sa + 0x2222u), __byte_perm(w, pv, sb2 + 0x2222u));
    }
    const uint32_t d3 = tab + T_R2 + 160 + 320 * (t & 1) + 16 * (g >> 1) + 8 * (g & 1) + 4 * (t >> 1), d3n = d3 + (g >= 6 ? 32 : 0);
    const uint32_t d4 = tab + T_R3 + 80 + 160 * t + 4 * g, d4n = d4 + (g >= 6 ? 16 : 0);
    uint32_t p3;
#pragma unroll
    for (int hf = 0; hf < 2; hf++)
#pragma unroll
        for (int e = 0; e < 2; e++) {
            const float v3 = acc[3][2 * hf + e] * scale_inv;
            const uint32_t p4 = pack_bf16(acc[4][2 * hf + e] * scale_inv, 0.f);
            p3 = pack_bf16(v3, v3);
            sts16(d3 + 64 * hf + 160 * e, p3);
            sts16((hf ? d3n : d3) + 64 * hf + 160 * e + 18, p3);
            sts16(d4 + 32 * hf + 80 * e, p4);
            sts16((hf ? d4n : d4) + 32 * hf + 80 * e + 10, p4);
        }
    if (lane == 31) {
        const uint32_t k512 = __byte_perm(w1, 0, 0x3232);
        sts32(tab + T_DENSE, p0);
        sts64(tab + T_DENSE + 4 * 513, k512, k512); sts16(tab + T_DENSE + 4 * 515 + 2, k512);
        sts16(tab + T_PATCH + 4 * 17, p3); sts32(tab + T_PATCH + 4 * 18, p3); sts16(tab + T_PATCH + 4 * 19 + 2, p3);
    }
    __syncwarp();
}

__device__ __forceinline__ void load_toep(uint32_t* a, uint32_t p, uint32_t pz) {
    a[0] = lds32(p); a[1] = lds32(p + 32); a[2] = lds32(pz - 32); a[3] = lds32(pz);
}
template <int F>
__device__ __forceinline__ void ffa_step(float (&acc)[16][4], float (&W)[8][4], uint32_t (&R)[8][4], uint32_t (&A)[4][4],
                                         uint32_t va, uint32_t vmin, uint32_t pb, uint32_t pz) {
    constexpr int S = F ^ 1;
    auto load = [&](int sh) {
#pragma unroll
        for (int i = S; i < 8; i += 2) ldsm4(R[i], i == 0 ? max(va - 16 * sh, vmin) : va - 16 * sh + i * 128);
#pragma unroll
        for (int k = S; k < 4; k += 2) load_toep(A[k], pb + 64 * sh + k * 512, pz + 64 * sh + k * 512);
    };
    auto prod = [&](int par, int dst) {
#pragma unroll
        for (int k = 0; k < 2; k++)
#pragma unroll
            for (int m = k; m < 8; m++) {
                const uint32_t* x = &R[2 * ((m - k) & 3) + par][2 * ((m - k) >> 2)];
                mma_v(dst == 1 ? W[m] : acc[2 * m + (dst >> 1)], A[2 * k + par], x[0], x[1]);
            }
    };
    load(0);
    prod(F, F);
    prod(S, S);
#pragma unroll
    for (int i = 0; i < 8; i++) A[(i >> 2) * 2 + F][i & 3] = badd2(A[(i >> 2) * 2][i & 3], A[(i >> 2) * 2 + 1][i & 3]);
#pragma unroll
    for (int i = 0; i < 16; i++) R[(i >> 2) * 2 + F][i & 3] = badd2(R[(i >> 2) * 2][i & 3], R[(i >> 2) * 2 + 1][i & 3]);
    load(1);
    prod(F, 2);
}
struct DenseTaps {
    uint32_t A[4][4], E[4], F[4], G[4];
    __device__ __forceinline__ DenseTaps(uint32_t pb, uint32_t pz) {
        constexpr int PP = T_PATCH - T_DENSE + 56;
        load_toep(E, pb + 2048, pz + 2048);
        load_toep(F, pb + PP, pz + PP);
        G[0] = lds32(pz + 2048 + 32); G[1] = lds32(pb + 2048 + 64); G[2] = lds32(pz + PP + 32); G[3] = lds32(pb + PP + 64);
    }
};
__device__ __forceinline__ uint32_t dense_phase(float (&acc)[16][4], uint32_t vmin, uint32_t va, uint32_t vo, uint32_t pb, DenseTaps& tp, uint32_t zero) {
    uint32_t R[8][4];
    uint32_t pz = pb + zero;
    {
        uint32_t H[4][4];
#pragma unroll
        for (int i = 0; i < 4; i++) ldsm4(H[i], vo + i * 256);
#pragma unroll
        for (int i = 0; i < 8; i++) ldsm4(R[i], va + i * 128);
#pragma unroll
        for (int i = 0; i < 4; i += 2) load_toep(tp.A[i], pb + 512 * i, pz + 512 * i);
#pragma unroll
        for (int i = 0; i < 4; i++) mma_bf16_k8(acc[i + 4], tp.G[0], tp.G[1], H[i >> 1][2 * (i & 1) + 1]);
#pragma unroll
        for (int i = 0; i < 8; i++) mma_v(acc[i + 8], tp.G, H[i >> 1][2 * (i & 1)], H[i >> 1][2 * (i & 1) + 1]);
#pragma unroll
        for (int i = 0; i < 12; i++) mma_v(acc[i + 4], tp.E, R[i & 7][2 * (i >> 3)], R[i & 7][2 * (i >> 3) + 1]);
#pragma unroll
        for (int i = 0; i < 8; i++) mma_v(acc[i + 8], tp.F, R[i][0], R[i][1]);
    }
    float W[8][4];
#pragma unroll
    for (int i = 0; i < 32; i++) { W[i >> 2][i & 3] = 0.f; if (i >= 8) acc[2 * (i >> 2) + 1][i & 3] += acc[2 * (i >> 2)][i & 3]; }
#pragma unroll 1
    for (int rho = 0; rho < 8; rho += 2) {
        ffa_step<0>(acc, W, R, tp.A, va, vmin, pb, pz);
        ffa_step<1>(acc, W, R, tp.A, va - 16, vmin, pb + 64, pz + 64);
        pb += 128; pz += 128; va -= 32;
    }
#pragma unroll
    for (int i = 0; i < 32; i++) {
        const int m = i >> 2, j = i & 3;
        acc[2 * m + 1][j] = (acc[2 * m + 1][j] - acc[2 * m][j]) - W[m][j];
        if (m) acc[2 * m][j] += W[m - 1][j];
    }
    return __float_as_uint(W[7][0]) & zero;
}
__device__ __forceinline__ uint32_t ones2(int c, int lo, int hi) {
    return (((uint32_t)(c - lo) <= (uint32_t)(hi - lo)) ? 1u : 0u) | (((uint32_t)(c + 1 - lo) <= (uint32_t)(hi - lo)) ? 0x10000u : 0u);
}
__device__ __forceinline__ uint32_t box_bits(int lane) {
    const int d = 2 * (lane & 3) - (lane >> 2);
    auto four = [&](int L1, int H1, int L2, int H2) { return ones2(d, L1, H1) | ones2(d, L2, H2) << 1 | ones2(d + 8, L1, H1) << 2 | ones2(d + 8, L2, H2) << 3; };
    return four(5, 7, 0, 4) | four(1, 7, 0, 8) << 4;
}
struct Boxes {
    uint32_t q[4], ha[2];
    __device__ __forceinline__ Boxes(uint32_t bits, int k0, uint32_t h0, uint32_t h1) {
#pragma unroll
        for (int i = 0; i < 4; i++) q[i] = (bits & (0x10001u << (k0 + i))) * (0x3f80u >> (k0 + i));
        ha[0] = h0; ha[1] = h1;
    }
    __device__ __forceinline__ void load(int j, uint32_t* v, uint32_t zero) const {
        const uint32_t o = j * 128;
        v[0] = lds32(ha[0] + o); v[1] = lds32(ha[1] + zero + o); v[2] = lds32(ha[1] + o);
        v[3] = lds32(ha[0] + zero + o + 16); v[4] = lds32(ha[0] + o + 16); v[5] = lds32(ha[1] + o + 16);
    }
    __device__ __forceinline__ void sums(const uint32_t* v, float* Z, float* X, float* Y) const {
        mma_bf16_z(Z, q[0], q[1], q[2], q[3], v[0], v[1]);
        mma_bf16_z(X, q[0], q[1], q[2], q[3], v[2], v[3]);
        mma_bf16_z(Y, q[0], q[1], q[2], q[3], v[4], v[5]);
    }
};
__host__ __device__ constexpr int tail_step(int n) { return n < 8 ? n : n < 12 ? n + 4 : (n & 1) ? 11 - (n - 13) / 2 : 19 - (n - 12) / 2; }
template <class After>
__device__ __forceinline__ void tail_phase(float (&acc)[16][4], const Boxes& b2, const Boxes& b3, uint32_t tp2, uint32_t tp3, uint32_t zero, After after) {
    uint4 t2[5];
    uint2 t3[8];
    uint32_t v[6], a0[4], a1[4];
    float Z[4], X[4], Y[4];
    b2.load(0, v, zero);
#pragma unroll
    for (int i = 0; i < 5; i++) t2[i] = lds128(tp2 + 160 * i);
#pragma unroll
    for (int n = -1; n < 20; n++) {
        const int j = tail_step(n), j1 = tail_step(n + 1), j2 = tail_step(n + 2);
        if (n < 19) {
            (j1 < 12 ? b2 : b3).sums(v, Z, X, Y);
            if (n < 18) { if (j2 < 12) b2.load(j2, v, zero); else b3.load(j2 - 12, v, zero); }
        }
        if (n >= 0 && j < 12) {
#pragma unroll
            for (int b = 0; b < 5; b++) if (j + 4 + b < 16) mma_v(acc[j + 4 + b], a1, t2[b].z, t2[b].w);
        }
        if (n < 19 && j1 < 12) { a1[0] = pack_v(Z[0], Z[1]); a1[1] = pack_w(X[0], X[1]); a1[2] = pack_v(Z[2], Z[3]); a1[3] = pack_w(X[2], X[3]); }
        if (n == 6) {
#pragma unroll
            for (int b = 0; b < 8; b++) t3[b] = lds64(tp3 + 80 * b);
        }
        if (n >= 0 && j < 12) {
#pragma unroll
            for (int b = 0; b < 5; b++) if (j + 4 + b < 16) mma_v(acc[j + 4 + b], a0, t2[b].x, t2[b].y);
        } else if (n >= 0) {
#pragma unroll
            for (int b = 0; b < 8; b++) if (j - 4 + b < 16) mma_v(acc[j - 4 + b], a0, t3[b].x, t3[b].y);
        }
        if (n < 19) {
            if (j1 < 12) { a0[0] = pack_v(X[0], X[1]); a0[1] = pack_v(Y[0], Y[1]); a0[2] = pack_v(X[2], X[3]); a0[3] = pack_v(Y[2], Y[3]); }
            else { a0[0] = pack_v(X[0], X[1]); a0[1] = pack_v(Y[0], Y[1]); a0[2] = pack_v(Z[2], Z[3]); a0[3] = pack_v(X[2], X[3]); }
        }
        after(n);
    }
}
template <int Q>
__device__ __forceinline__ void emit(const float (&acc)[16][4], int h, uint32_t own, uint32_t peer, uint32_t bar, uint32_t bar_peer) {
    constexpr int n = 4 * Q, G = Q >> 1;
#pragma unroll
    for (int hf = 0; hf < 2; hf++)
        asm volatile("{ .reg .pred p; setp.eq.u32 p, %7, %8;\n\t@p st.shared.v4.u32 [%0], {%1,%2,%3,%4};\n\t"
                     "@!p st.async.weak.shared::cluster.mbarrier::complete_tx::bytes.v4.b32 [%5], {%1,%2,%3,%4}, [%6]; }"
                     ::"r"(own + G * 16384 + hf * 512), "r"(pack_bf16(acc[n][2 * hf], acc[n][2 * hf + 1])), "r"(pack_bf16(acc[n + 1][2 * hf], acc[n + 1][2 * hf + 1])),
                     "r"(pack_bf16(acc[n + 2][2 * hf], acc[n + 2][2 * hf + 1])), "r"(pack_bf16(acc[n + 3][2 * hf], acc[n + 3][2 * hf + 1])),
                     "r"(peer + G * 16384 + hf * 512), "r"(bar_peer + 8 * G), "r"(h), "n"(Q & 1) : "memory");
    __syncwarp();
    if (h == (Q & 1) && elect_one()) mbar_arrive(bar);
}
__device__ __forceinline__ uint32_t finish_src(uint32_t sb, int h, int w, int lane) {
    const int m = lane >> 3, r = lane & 7;
    return sb + OFF_XT + (h ^ 1) * 32768 + (2 * m + (r & 1)) * 1024 + (w >> 2) * 512 + (((8 * (w & 3) + (r & 4) + ((r >> 1) & 1)) ^ ((r & 1) << 1)) << 4);
}
__device__ __forceinline__ uint32_t finish_dst(uint32_t sb, int h, int w, int lane) {
    const int g = lane >> 2, t = lane & 3;
    return sb + OFF_XT + h * 32768 + w * 2048 + (g >> 1) * 512 + (t >> 1) * 144 + (2 * (t & 1) + (g & 1)) * 32;
}
__device__ __forceinline__ uint32_t tile_addr(uint32_t sb, int tok, int t) {
    return sb + OFF_XT + (tok & 512) * 64 + (tok >> 10) * 16384 + (tok & 14) * 1024 + (tok & 448) * 4 + (tok & 1) * 128 + (tok & 48) * 2 + (((t >> 1) ^ (tok & 1)) << 4) + (t & 1) * 8;
}
__device__ __forceinline__ uint2 add_update(uint2 o, uint32_t upd) {
    const float4 u = lds128f(upd);
    return make_uint2(badd2(o.x, pack_bf16(u.x, u.y)), badd2(o.y, pack_bf16(u.z, u.w)));
}
__device__ __forceinline__ void finish_half(uint32_t src, uint32_t xa, const uint4 (&x)[2]) {
    uint32_t s[2][4];
#pragma unroll
    for (int i = 0; i < 2; i++) ldsm4t(s[i], src ^ (i << 5));
#pragma unroll
    for (int i = 0; i < 2; i++) sts128(xa + i * 256, badd2(x[i].x, s[i][0]), badd2(x[i].y, s[i][1]), badd2(x[i].z, s[i][2]), badd2(x[i].w, s[i][3]));
}

__device__ __noinline__ float centred_var(uint32_t rows, float mu, int lane) {
    float var = 0.f;
#pragma unroll 1
    for (int rr = 0; rr < 16; rr++) {
        const float c0 = __shfl_sync(0xffffffffu, mu, rr);
        float c = 0.f;
#pragma unroll 1
        for (int k = 0; k < 16; k++) {
            const uint32_t q = lds32(rows + rr * ROW_PITCH + k * 128 + lane * 4);
            const float d0 = bf_lo(q) - c0, d1 = bf_hi(q) - c0;
            c = fmaf(d0, d0, fmaf(d1, d1, c));
        }
#pragma unroll 1
        for (int o = 16; o; o >>= 1) c += __shfl_xor_sync(0xffffffffu, c, o);
        if ((lane & 15) == rr) var = c * (1.f / DM);
    }
    return var;
}
__device__ __noinline__ float centred_score(uint32_t rows, uint32_t wbuf, uint32_t s0, uint32_t s1, int lane) {
    float sc = 0.f;
#pragma unroll 1
    for (int rr = 0; rr < 16; rr++) {
        const uint32_t t0 = __shfl_sync(0xffffffffu, s0, rr), t1 = __shfl_sync(0xffffffffu, s1, rr);
        float c = 0.f;
#pragma unroll 1
        for (int k = 0; k < 16; k++) {
            const uint32_t xn = normalize2(lds32(rows + rr * ROW_PITCH + k * 128 + lane * 4), t0, t1);
            const uint32_t wq = lds32(wbuf + (k >> 2) * 1024 + (k & 3) * 128 + lane * 4);
            c = fmaf(bf_lo(xn), bf_lo(wq), fmaf(bf_hi(xn), bf_hi(wq), c));
        }
#pragma unroll 1
        for (int o = 16; o; o >>= 1) c += __shfl_xor_sync(0xffffffffu, c, o);
        if ((lane & 15) == rr) sc = c;
    }
    return sc;
}

__device__ __forceinline__ void issue_rows(const __nv_bfloat16* u, uint32_t sb, int b) {
    if (elect_one()) {
        const uint32_t bar = sb + OFF_BAR + 8 * B_ROW;
#pragma unroll
        for (int j = 0; j < 4; j++) mbar_init(bar + 8 * j, 1);
        asm volatile("fence.mbarrier_init.release.cluster;" ::: "memory");
        fence_async();
#pragma unroll 1
        for (int j = 0; j < 4; j++) {
            mbar_expect_tx(bar + 8 * j, 8192);
#pragma unroll
            for (int i = 0; i < 4; i++) bulk_g2s(sb + OFF_VT + (4 * j + i) * ROW_PITCH, u + (size_t)(16 * b + 4 * j + i) * DM, 2048, bar + 8 * j);
        }
    }
    __syncwarp();
}

__global__ void __cluster_dims__(2, 1, 1) __launch_bounds__(NTHR, 1)
fused_kernel(const __grid_constant__ Ptrs p, const __grid_constant__ Maps maps) {
    extern __shared__ __align__(1024) unsigned char smem[];
    const int tid = threadIdx.x, lane = tid & 31;
    const int c_ = ((blockIdx.x >> 1) + 60) & 63, b = 2 * ((c_ & 32) | ((c_ & 7) << 2) | ((c_ >> 3) & 3)) + (blockIdx.x & 1);
    const int dch = 8 * b + (tid >> 5) - 4;
    uint2 la, aim, cre, cim;
    uint32_t ldt16;
    if ((uint32_t)(tid - 128) < 256u) {
        la = ldg64(p.logA + dch * NMODE + 4 * lane); aim = ldg64(p.Aim + dch * NMODE + 4 * lane);
        cre = ldg64(p.Cre + dch * NMODE + 4 * lane); cim = ldg64(p.Cim + dch * NMODE + 4 * lane);
        ldt16 = ldg16(p.ldt + dch);
    }
    const uint32_t sb = s_u32(smem), bar0 = sb + OFF_BAR;
    const int warp = __shfl_sync(0xffffffffu, tid >> 5, 0);
    const int h = b & 1, cl = b >> 1;
    const int m = lane >> 3, r = lane & 7, g = lane >> 2, t = lane & 3;
    const bool has_gu = b < GU_CTAS;
    if (warp == 4) { STAMP(0); GSTAMP(24); }

    if (warp >= 12) {
        asm volatile("setmaxnreg.dec.sync.aligned.u32 24;");
        const int a = warp - 12;
        uint32_t due = now_ns() + ST_T0 + (uint32_t)(2 * a + h) * (ST_PER / 2) + (has_gu ? 0 : 12 * ST_PER + 4 * ST_PER2);
        const bool el = elect_one();
        if (a == 1) issue_rows(p.u, sb, b);
        if (a == 2 && el) {
#pragma unroll
            for (int i = B_XT; i < NBAR; i++) mbar_init(bar0 + 8 * i, (i == B_V || i == B_SFREE || i == B_XFREE || i == B_OWN) ? 8 : i == B_RECV ? 9 : i == B_RED ? 5 : (i == B_UPD || (i >= B_FREE && i < B_FULL)) ? 4 : 1);
            asm volatile("fence.mbarrier_init.release.cluster;" ::: "memory");
            fence_async();
            mbar_expect_tx(bar0 + 8 * B_XT, 65536);
            mbar_expect_tx(bar0 + 8 * B_RECV, 8192);
            mbar_expect_tx(bar0 + 8 * B_RECV + 8, 8192);
            mbar_expect_tx(bar0 + 8 * B_RED, 2048);
        }
        if (a == 3 && el) {
#pragma unroll
            for (int i = 0; i < 5; i++) asm volatile("prefetch.tensormap [%0];" ::"l"(&maps.u + i) : "memory");
        }
        __syncwarp();
        cluster_arrive();
        cluster_wait();
        STAMP(18);
        mbar_wait(bar0 + 8 * (B_ROW + a), 0);
        if (el) {
#pragma unroll
            for (int i = 0; i < 4; i++)
                tma_load_tile(sb + OFF_XT + h * 32768 + a * 4096 + (i & 1) * 16384 + (i >> 1) * 2048, &maps.u, 16 * cl, 4 * a + (i & 2), 16 * (i & 1) + 8 * h, bar0 + 8 * B_XT);
        }
        if (el) {
#pragma unroll 1
            for (int k = has_gu ? 0 : 4; k < 6; k++) {
                const int i = 4 * k + a, s = k < 3 ? i : i - 12;
#pragma unroll 1
                for (int left; (left = (int)(due - now_ns())) > 0;) __nanosleep(left >> 1);
                due += k < 3 ? 4 * ST_PER : 4 * ST_PER2;
                const bool again = k >= 3 && has_gu;
                if (s >= 6 || again) mbar_wait(bar0 + 8 * (s < 10 || again ? B_FREE + s : B_V), slot_priv(s) && again);
                const uint32_t dst = sb + slot_off(s), bar = bar0 + 8 * (B_FULL + s);
                if (k < 4) {
                    mbar_expect_tx(bar, 8192);
                    tma_load_2d(dst, &maps.wg, 64 * cl, 512 * h + 32 * i, bar);
                    tma_load_2d(dst + 4096, &maps.wu, 64 * cl, 512 * h + 32 * i, bar);
                } else {
                    mbar_expect_tx(bar, 7168);
                    tma_load_perm(dst, &maps.wd, 16 * cl, 56 * h + 14 * a + 7 * (k & 1), bar);
                }
            }
            STAMP(19);
        }
        __syncwarp();
        {
            const uint32_t fs = finish_src(sb, h, 2 * a, lane), fx = finish_dst(sb, h, 2 * a, lane);
            mbar_wait(bar0 + 8 * B_RECV, 0);
#pragma unroll 1
            for (int k = 0; k < 2; k++) {
#pragma unroll
                for (int q = 0; q < 2; q++) {
                    const uint32_t xa = (fx ^ (q << 4)) + k * 2048;
                    const uint4 x[2] = {lds128(xa), lds128(xa + 256)};
                    finish_half(fs + q * 8192 + k * 128, xa, x);
                }
                fence_async();
                __syncwarp();
                if (el) tma_store_tile(&maps.out, sb + OFF_XT + h * 32768 + (2 * a + k) * 2048, 16 * cl, 4 * a + 2 * k, 8 * h);
            }
            if (h) STAMP(59); else STAMP(20);
            const int tok = 2047 - (int)(lds32(sb + OFF_MISC + 48 + 8 * g) & 2047);
            const bool mine = (((tok >> 7) & 12) | ((tok >> 2) & 3)) == 4 * h + a;
            if (el) asm volatile("cp.async.bulk.wait_group 0;" ::: "memory");
            if (__any_sync(0xffffffffu, mine)) {
                const uint2 o0 = lds64(tile_addr(sb, tok, t));
                mbar_wait(bar0 + 8 * B_UPD, 0);
                const uint2 o1 = add_update(o0, sb + tab_off(g) + T_RED + 16 * t);
                if (mine) *reinterpret_cast<uint2*>(p.out + (size_t)tok * DM + 16 * cl + 4 * t) = o1;
            } else STAMP(62);
        }
    } else if (warp >= 4) {
        const int w = warp - 4;
        uint32_t dsk16 = ldg16(p.dsk + dch);
        cluster_arrive();
        asm volatile("setmaxnreg.inc.sync.aligned.u32 176;");
        const uint32_t vrow = sb + OFF_VT + w * VT_PITCH + VT_PAD, tab = sb + tab_off(w);
        const uint32_t rb0 = bar0 + 8 * B_RECV, rb1 = mapa(rb0, h ^ 1);
        uint32_t tpo = 80 + (g - 2 * t) * 8 - (g < 2 * t ? 16 : 0);
        uint32_t xa = sb + OFF_XT + (w & 2) * 16384 + (w >> 2) * 16384 + (w & 1) * 1024 + (g >> 1) * 2048 + (g & 1) * 128 + t * 32 + ((h ^ (g & 1)) << 4);
        uint32_t va = sb + OFF_VT + (2 * m + (r & 1)) * VT_PITCH + VT_PAD + (16 * w + (r >> 1)) * 16;
        uint32_t qa = sb + OFF_ST + 2048 * w + 128 * t + 16 * (g ^ (2 * t));
        uint32_t vmin = vrow + (m & 1) * VT_PLANE - 16, vd = vmin + 16 + (m >> 1) * 1024 + r * 16;
        uint32_t vo = vrow + VT_PLANE + 496 - (m & 1) * 512 + (m >> 1) * 128 + r * 16, vz = vrow - VT_PAD + (lane >> 1) * VT_PLANE + (lane & 1) * 16;
        pin(vmin); pin(vd); pin(vo); pin(vz);
        pin(tpo); pin(xa); pin(va); pin(qa);
        uint32_t bits = box_bits(lane), h0 = vrow + 16 * g + tok_off(2 * t - 18), h1 = vrow + 16 * g + tok_off(2 * t - 10);
        pin(bits); pin(h0); pin(h1);
        const KgenAddr ka(sb + OFF_PRIV + w * 8192, lane);
        if (__any_sync(0xffffffffu, (vmin | (vd | vo | vz) | (tpo | xa) | (va | qa) | (bits | h0 | h1) | ka.any()) & p.zero)) __trap();
        cluster_wait();
        pin(la.x); pin(la.y); pin(aim.x); pin(aim.y); pin(cre.x); pin(cre.y); pin(cim.x); pin(cim.y); pin(ldt16); pin(dsk16);
        uint4 x[8];
        auto load_x = [&]() {
            mbar_wait(bar0 + 8 * B_XT, 0);
#pragma unroll
            for (int i = 0; i < 8; i++) x[i] = lds128(xa + (i & 1) * 8192 + (i >> 1) * 256);
        };
        kgen(ka, tab, lane, la, aim, cre, cim, bf_round(ex2f(bf_lo(ldt16) * 1.4426950408889634f)), 1.f + bf_lo(dsk16), dch, [&]() {
            STAMP(21);
            if (elect_one()) mbar_arrive_n(bar0 + 8 * (B_FREE + 6 + ((w >> 1) ^ 2)), 2);
        }, [&]() {
            if ((LN_PAUSE >> w) & 1) mbar_wait(bar0 + 8 * B_LN, 0);
        });
        STAMP(1);
        const uint32_t pb = tab + T_DENSE + (g - 2 * t) * 4;
        DenseTaps dt(pb, pb + p.zero);
        {
            load_x();
            STAMP(47);
            mbar_wait(bar0 + 8 * (B_ST + (w >> 1)), 0);
            uint4 q[4];
#pragma unroll
            for (int n = 0; n < 4; n++) q[n] = lds128(qa + 512 * n);
            if (lane < 4) sts128(vz, 0, 0, 0, 0);
            STAMP(2); GSTAMP(28);
#pragma unroll
            for (int i = 0; i < 8; i++) {
                const uint32_t s0 = (i & 1) ? q[i >> 1].z : q[i >> 1].x, s1 = (i & 1) ? q[i >> 1].w : q[i >> 1].y;
                stsm4t(va + (i >> 1) * 64 + (i & 1) * VT_PLANE, normalize2(x[i].x, s0, s1), normalize2(x[i].y, s0, s1),
                       normalize2(x[i].z, s0, s1), normalize2(x[i].w, s0, s1));
            }
            __syncwarp();
            if (elect_one()) mbar_arrive(bar0 + 8 * B_V);
        }
        mbar_wait(bar0 + 8 * B_V, 0);
        STAMP(3);
        float acc[16][4];
#pragma unroll
        for (int i = 0; i < 16; i++) { acc[i][0] = acc[i][1] = acc[i][2] = acc[i][3] = 0.f; }
        bits |= dense_phase(acc, vmin, vd, vo, pb, dt, p.zero);
        const Boxes b2(bits, 0, h0, h1), b3(bits, 4, (t == 1 ? h1 : h0) - 4, t == 1 ? h0 + 12 : h1 - 4);
        STAMP(4);
        const uint32_t so = sb + OFF_XT + (8 * h + w) * 1024 + ((lane ^ ((w & 1) << 1)) << 4);
        const uint32_t dst0 = so + (h ^ 1) * 32768, dst1 = mapa(so + h * 32768, h ^ 1);
        tail_phase(acc, b2, b3, tab + T_R2 + 2 * tpo, tab + T_R3 + tpo, p.zero, [&](int j) {
            if (j == -1) {
                mbar_wait(bar0 + 8 * B_SFREE, 0);
                emit<0>(acc, h, dst0, dst1, rb0, rb1);
            }
            if (j == 3) { emit<1>(acc, h, dst0, dst1, rb0, rb1); STAMP(5); }
            if (j == 11) {
                mbar_wait(bar0 + 8 * B_XFREE, 0);
                emit<2>(acc, h, dst0, dst1, bar0 + 8 * B_OWN, rb1);
                STAMP(58);
            }
        });
        emit<3>(acc, h, dst0, dst1, bar0 + 8 * B_OWN, rb1);
        STAMP(30);
        const uint32_t fs = finish_src(sb, h, w, lane) + 16384 + h * 8192, fx = (finish_dst(sb, h, w, lane) + 16384) ^ (h << 4);
        const int tok = 2047 - (int)(lds32(sb + OFF_MISC + 48 + 8 * g) & 2047);
        const bool mine = (((tok >> 6) & 24) | ((tok >> 1) & 7)) == 16 + 8 * h + w;
        const uint32_t ta = tile_addr(sb, tok, t);
        const uint4 x0[2] = {lds128(fx), lds128(fx + 256)}, x1[2] = {lds128(fx ^ 16), lds128((fx ^ 16) + 256)};
        mbar_wait(bar0 + 8 * B_OWN, 0);
        finish_half(fs, fx, x0);
        mbar_wait(bar0 + 8 * (B_RECV + 1), 0);
        STAMP(6);
        finish_half(fs + (h ? -8192 : 8192), fx ^ 16, x1);
        __syncwarp();
        if (__any_sync(0xffffffffu, mine)) {
            const uint2 o0 = lds64(ta);
            mbar_wait(bar0 + 8 * B_UPD, 0);
            const uint2 o1 = add_update(o0, sb + tab_off(g) + T_RED + 16 * t);
            if (mine) sts64(ta, o1.x, o1.y);
        }
        fence_async();
        __syncwarp();
        if (elect_one()) {
            tma_store_tile(&maps.out, sb + OFF_XT + h * 32768 + 16384 + w * 2048, 16 * cl, 2 * w, 16 + 8 * h);
            asm volatile("cp.async.bulk.wait_group.read 0;" ::: "memory");
        }
        STAMP(7);
    } else {
        const int a = warp;
        const uint4 wq = ldg128(p.wr + 8 * tid);
        const uint32_t epoch = ld_relaxed_32(&p.sc->epoch);
        cluster_arrive();
        asm volatile("setmaxnreg.inc.sync.aligned.u32 136;");
        const uint32_t tag = __shfl_sync(0xffffffffu, epoch, 0) + 1u, misc = sb + OFF_MISC, abar = bar0 + 8 * (B_AUX + a);
        uint32_t aph = 0;
        const Exchange* in = &p.sc->x[cl & (NREP - 1)];
        uint2* pub = p.sc->x[m >> 1].stat + 16 * b + 2 * (r ^ (2 * (b & 3))) + (m & 1);
        uint32_t* cnt_s = &p.sc->x[t].n_stat[b & 96];
        pin(pub); pin(cnt_s);
        if (tid < 64) sts32(sb + OFF_XCH + 4 * tid, 0);
        const uint32_t wbuf = sb + OFF_LN + a * 1024, part = sb + OFF_LN + 4096;
        {
            sts128(wbuf + 16 * lane, wq.x, wq.y, wq.z, wq.w);
            sts128(wbuf + 512 + 16 * lane, 0x3f803f80u, 0x3f803f80u, 0x3f803f80u, 0x3f803f80u);
            float wsum = ((bf_lo(wq.x) + bf_hi(wq.x)) + (bf_lo(wq.y) + bf_hi(wq.y))) + ((bf_lo(wq.z) + bf_hi(wq.z)) + (bf_lo(wq.w) + bf_hi(wq.w)));
#pragma unroll
            for (int o = 16; o; o >>= 1) wsum += __shfl_xor_sync(0xffffffffu, wsum, o);
            sts32f(part + 1024 + 4 * a, wsum);
            uint32_t wf[4][4];
#pragma unroll
            for (int i = 0; i < 4; i++) ldsm4(wf[i], wbuf + ((uint32_t)(r - 1) < 2u ? 16 * (r - 1) : 512) + 32 * m + 128 * i);
            uint32_t ra = sb + OFF_VT + r * ROW_PITCH + 512 * a + 16 * m, pa = part + a * 256 + g * 16;
            cluster_wait();
            STAMP(22);
#pragma unroll 1
            for (int hf = 0; hf < 2; hf++) {
                mbar_wait(bar0 + 8 * B_ROW + 16 * hf, 0);
                mbar_wait(bar0 + 8 * B_ROW + 16 * hf + 8, 0);
                STAMP(23);
                uint32_t x[8][4];
                float cs[2][4], q[8][4];
#pragma unroll
                for (int i = 0; i < 40; i++) (i < 8 ? cs[i >> 2 & 1] : q[(i - 8) >> 2 & 7])[i & 3] = 0.f;
#pragma unroll
                for (int k = 0; k < 8; k++) ldsm4(x[k], ra + k * 64);
                const bool more = __any_sync(0xffffffffu, after_all(x, p.zero));
#pragma unroll 1
                do {
#pragma unroll
                    for (int k = 0; k < 8; k++) {
                        mma_v(cs[k & 1], x[k], wf[k >> 1][2 * (k & 1)], wf[k >> 1][2 * (k & 1) + 1]);
#pragma unroll
                        for (int i = 0; i < 4; i++) mma_bf16_k8(q[4 * (k & 1) + i], x[k][i & 2], x[k][i | 1], x[k][i]);
                    }
                } while (more);
                const float c2 = cs[0][2] + cs[1][2];
                if (t == 0) sts64f(pa, (cs[0][0] + cs[1][0]) + c2, cs[0][1] + cs[1][1]);
                if (t == 1) sts32f(pa + 12, c2);
                const float e0 = ((q[0][0] + q[2][0]) + (q[4][0] + q[6][0])) + ((q[1][2] + q[3][2]) + (q[5][2] + q[7][2]));
                const float e1 = ((q[0][1] + q[2][1]) + (q[4][1] + q[6][1])) + ((q[1][3] + q[3][3]) + (q[5][3] + q[7][3]));
                if (t == (g >> 1)) sts32f(pa + 8, (g & 1) ? e1 : e0);
                ra += 8 * ROW_PITCH; pa += 128;
            }
        }
        STAMP(31);
        named_sync(1, 128);
        if (a == 0) {
            const uint32_t pa = part + (lane & 15) * 16;
            const float4 p0 = lds128f(pa), p1 = lds128f(pa + 256), p2 = lds128f(pa + 512), p3 = lds128f(pa + 768), ws = lds128f(part + 1024);
            const float mu = ((p0.x + p1.x) + (p2.x + p3.x)) * (1.f / DM);
            float var = ((p0.z + p1.z) + (p2.z + p3.z)) * (1.f / DM) - mu * mu;
            const bool centred = __any_sync(0xffffffffu, !(mu * mu <= 4.f * var));
            if (centred) var = centred_var(sb + OFF_VT, mu, lane);
            const float ri = rcpf(bf_round(sqrtaf(bf_round(bf_round(var) + 1e-5f))));
            const uint32_t s0 = pack_bf16(mu, ri), s1 = (pack_bf16(ri - bf_hi(s0), 0.f) & 0xfffcu) | (tag & 3);
            float sc = ((((p0.y + p1.y) + (p2.y + p3.y)) + ((p0.w + p1.w) + (p2.w + p3.w))) - bf_lo(s0) * ((ws.x + ws.y) + (ws.z + ws.w))) * ri;
            if (centred) sc = centred_score(sb + OFF_VT, sb + OFF_LN, s0, s1, lane);
            const uint32_t sb16 = pack_bf16(0.f, sc);
            const uint32_t s2 = s1 | (sb16 ^ (((uint32_t)((int)sb16 >> 31) & 0x7fff0000u) | 0x80000000u));
            st_relaxed_64(pub, s0, s2);
            st_relaxed_64(pub + 2 * sizeof(Exchange) / 8, s0, s2);
            if (lane < NREP) red_add(cnt_s, 1);
            if (elect_one()) mbar_arrive(bar0 + 8 * B_LN);
            STAMP(9); GSTAMP(25);
        }
        const uint32_t slot0 = sb + OFF_RING + a * 8192, slot1 = sb + slot_off(4 + a), slot2 = sb + slot_off(8 + a), fbar = bar0 + 8 * (B_FULL + a);
        uint32_t mine = 0, row[2] = {0, 0};
        {
            uint32_t q[16];
            named_sync(1, 128);
            wait_count(&in->n_stat[32 * a], 32 * tag - FEW_ST);
            STAMP(41);
#pragma unroll 1
            for (uint32_t it = 0;; spin_guard(it)) {
                if (elect_one()) {
                    mbar_expect_tx(abar, 4096);
                    bulk_g2s(sb + OFF_ST + 4096 * a, in->stat + 512 * a, 4096, abar);
                }
                mbar_wait(abar, aph);
                aph ^= 1;
                uint32_t bad = 0;
#pragma unroll
                for (int n = 0; n < 8; n++) {
                    const uint4 u = lds128v(sb + OFF_ST + 4096 * a + 512 * n + 16 * lane);
                    q[2 * n] = u.y; q[2 * n + 1] = u.w;
                    bad = or_xor(bad, u.y, tag);
                }
                const bool ok = __all_sync(0xffffffffu, (bad & 3) == 0);
                asm volatile("{ .reg .pred p; setp.ne.u32 p, %1, 0; @p mbarrier.arrive.shared::cta.b64 _, [%0]; }" ::"r"(bar0 + 8 * (B_ST + a)), "r"((uint32_t)(ok && lane == 0)) : "memory");
                if (ok) break;
            }
            STAMP(8);
            const uint32_t inv = 2047 - 512 * a - 16 * m - (r ^ (2 * m));
#pragma unroll
            for (int i = 0; i < 16; i++) asm("lop3.b32 %0, %0, %1, %2, 0x9b;" : "+r"(q[i]) : "r"(inv), "r"(0xffff0000u | (64 * (i >> 1) + 8 * (i & 1))));
            auto below = [&](uint32_t x) {
                uint32_t d[4];
#pragma unroll
                for (int i = 0; i < 16; i++) d[i & 3] = i < 4 ? x + q[i] : min(d[i & 3], x + q[i]);
                d[0] = min(min(d[0], d[1]), min(d[2], d[3]));
                return d[0] < x ? x - 1 - d[0] : 0u;
            };
            const uint32_t mx0 = ~min(min(min(min(q[0], q[1]), min(q[2], q[3])), min(min(q[4], q[5]), min(q[6], q[7]))),
                                      min(min(min(q[8], q[9]), min(q[10], q[11])), min(min(q[12], q[13]), min(q[14], q[15]))));
            const uint32_t gm = min(__reduce_max_sync(0xffffffffu, lane < 16 ? mx0 : 0u), __reduce_max_sync(0xffffffffu, lane < 16 ? 0u : mx0));
            if (lane == 0) sts32(misc + 16 + 4 * a, gm);
            named_sync(1, 128);
            STAMP(42);
            if (b == 0 && tid == 0) st_relaxed_32(&p.sc->epoch, tag);
            const uint4 t0 = lds128(misc + 16);
            uint32_t tau = min(min(t0.x, t0.y), min(t0.z, t0.w));
            uint32_t mx = mx0, cnt = 0, bal;
            const uint32_t list = sb + OFF_XCH + 64 * a;
#pragma unroll 1
            while ((bal = __ballot_sync(0xffffffffu, mx >= tau)) != 0) {
                const uint32_t pos = cnt + __popc(bal & ((1u << lane) - 1u));
                cnt += __popc(bal);
                if (cnt > 16) break;
                if (mx >= tau) sts32(list + 4 * pos, mx);
                mx = below(mx);
            }
            if (cnt > 16) {
                mx = mx0;
#pragma unroll 1
                for (int j = 0; j < 8; j++) {
                    const uint32_t top = __reduce_max_sync(0xffffffffu, mx), nx = below(mx);
                    if (mx == top) { sts32(list + 4 * j, mx); sts32(list + 32 + 4 * j, 0); mx = nx; }
                }
            }
            named_sync(1, 128);
            STAMP(43);
            const uint2 k = lds64(sb + OFF_XCH + 8 * lane);
            uint32_t hi = max(k.x, k.y), lo = min(k.x, k.y);
            mbar_wait(bar0 + 8 * B_V, 0);
#pragma unroll
            for (int j = 0; j < 8; j++) {
                const uint32_t top = __reduce_max_sync(0xffffffffu, hi);
                const bool won = hi == top;
                hi = won ? lo : hi;
                lo = won ? 0u : lo;
                if (g == j) mine = top;
                if (a == (j >> 1)) row[j & 1] = top;
            }
        }
        STAMP(11);
        const int tok = 2047 - (int)(mine & 2047);
        const uint32_t xs = sb + OFF_XT + (h ^ 1) * 32768 + 16384;
        if (has_gu) {
            if (elect_one()) {
                mbar_expect_tx(abar, 2048);
#pragma unroll
                for (int j = 0; j < 2; j++) bulk_g2s(xs + (2 * a + j) * 1040, p.u + (size_t)(2047 - (row[j] & 2047)) * DM + 512 * h, 1024, abar);
            }
        }
        STAMP(44);
        const uint2 st = ld_relaxed_64(in->stat + (tok & ~15) + 2 * ((tok & 7) ^ ((tok >> 3) & 6)) + ((tok >> 3) & 1));
        if (a == 0 && t == 0) sts64(misc + 48 + 8 * g, mine, __float_as_uint(bf_hi(st.x) + bf_lo(st.y)));
        if (a == 0) STAMP(45);
        if (has_gu) {
            const uint32_t mean = __shfl_sync(0xffffffffu, st.x, 8 * a + 4 * (lane >> 4)), xr = xs + (2 * a + (lane >> 4)) * 1040 + 16 * (lane & 15);
            mbar_wait(abar, aph);
            aph ^= 1;
            STAMP(46);
            uint4 x[4];
#pragma unroll
            for (int j = 0; j < 4; j++) x[j] = lds128(xr + 256 * j);
#pragma unroll
            for (int j = 0; j < 4; j++) sts128(xr + 256 * j, bsub2_lo(x[j].x, mean), bsub2_lo(x[j].y, mean), bsub2_lo(x[j].z, mean), bsub2_lo(x[j].w, mean));
            if (elect_one()) mbar_expect_tx(abar, 512);
            named_sync(1, 128);
        }
        if (lane < (has_gu ? 2 : 4)) mbar_arrive_peer(mapa(bar0 + 8 * (lane & 2 ? B_XFREE : B_SFREE), lane & 1));
        if (has_gu) {
            STAMP(12);
            float gacc[8][4];
#pragma unroll
            for (int i = 0; i < 8; i++) { gacc[i][0] = gacc[i][1] = gacc[i][2] = gacc[i][3] = 0.f; }
            uint32_t* pubh = reinterpret_cast<uint32_t*>(&p.sc->x[0].h[b * 32 + 8 * a + (g ^ (2 * a))]) + t;
            uint32_t* cnt_h = &p.sc->x[t].n_h[32 * (b / 14)];
            uint32_t ko = sb + (m & 1) * 4096 + (r + ((m >> 1) << 3)) * 128 + ((r ^ (4 * h) ^ a) << 4), kp = ko ^ 64, xb = xs + r * 1040 + m * 16;
            uint32_t xch = sb + OFF_XCH + 16 * tid, tagm = t == 3 ? 1u : 0u;
            pin(pubh); pin(cnt_h); pin(ko); pin(kp); pin(xb); pin(xch); pin(tagm);
            const float r0 = lds32f(misc + 52 + 16 * t), r1 = lds32f(misc + 60 + 16 * t);
#pragma unroll
            for (int c = 0; c < 4; c++) {
                uint32_t af[20][4];
#pragma unroll
                for (int j = 0; j < 4; j++) ldsm4(af[16 + j], xb + 256 * c + 64 * j);
                if (c == 3) mbar_wait(bar0 + 8 * B_SFREE, 0);
#pragma unroll
                for (int j = 0; j < 4; j++) {
                    mbar_wait(bar0 + 8 * (B_FULL + 4 * (c % 3) + j), c / 3);
#pragma unroll
                    for (int i = 0; i < 4; i++) ldsm4t(af[8 * (i >> 1) + 2 * j + (i & 1)], ((i & 1) ? kp : ko) + slot_off(4 * (c % 3) + j) + (i >> 1) * 2048);
                }
                STAMP(36 + c);
                __syncwarp();
                if (c < 3 && lane < 4) mbar_arrive(bar0 + 8 * (B_FREE + 4 * c + lane));
                const bool more = __any_sync(0xffffffffu, (af[6][3] | af[7][3] | af[14][3] | af[15][3]) & p.zero);
#pragma unroll 1
                do {
#pragma unroll
                    for (int i = 0; i < 16; i++) mma_v(gacc[i & 7], af[i], af[16 + ((i >> 1) & 3)][2 * (i >> 3)], af[16 + ((i >> 1) & 3)][2 * (i >> 3) + 1]);
                } while (more);
            }
            STAMP(13);
            float own[4], oth[4];
#pragma unroll
            for (int j = 0; j < 4; j++) oth[j] = (gacc[1][j] + gacc[3][j]) + (gacc[5][j] + gacc[7][j]);
            st_async128(mapa(xch, h ^ 1), __float_as_uint(oth[0]), __float_as_uint(oth[1]), __float_as_uint(oth[2]), __float_as_uint(oth[3]), mapa(abar, h ^ 1));
            STAMP(56);
#pragma unroll
            for (int j = 0; j < 4; j++) own[j] = ((gacc[0][j] + gacc[2][j]) + (gacc[4][j] + gacc[6][j])) * ((j & 1) ? r1 : r0);
            mbar_wait(abar, aph);
            aph ^= 1;
            STAMP(57);
            const float4 o4 = lds128f(xch);
            const float g0 = bf_round(fmaf(o4.x, r0, own[0])), g1 = bf_round(fmaf(o4.y, r1, own[1]));
            const float h0 = bf_round(g0 * rcpf(1.f + ex2f(-1.4426950408889634f * g0))) * bf_round(fmaf(o4.z, r0, own[2]));
            const float h1 = bf_round(g1 * rcpf(1.f + ex2f(-1.4426950408889634f * g1))) * bf_round(fmaf(o4.w, r1, own[3]));
            uint32_t hw;
            asm volatile("movmatrix.sync.aligned.m8n8.trans.b16 %0, %1;" : "=r"(hw) : "r"(pack_bf16(h0, h1)));
            hw = (hw & ~tagm) | (tag & tagm);
#pragma unroll
            for (int j = 0; j < NREP; j++) st_relaxed_32(pubh + j * (sizeof(Exchange) / 4), hw);
            if (lane < NREP) red_add(cnt_h, 1);
            if (lane < 2) mbar_arrive_peer(mapa(bar0 + 8 * B_XFREE, lane));
            named_sync(1, 128);
            STAMP(14);
        }
        float dacc[4];
        const int tk = ((tid >> 1) & 6) | (tid & 1);
        uint32_t ro = 4 * tid, red = sb + tab_off(tk) + T_RED + 4 * ((tid >> 4) + 4 * (tid & 2));
        if (!has_gu) named_sync(1, 128);
        const float sg = bf_round(rcpf(1.f + ex2f(-1.4426950408889634f * __uint_as_float(unorder_key(lds32(misc + 48 + 8 * tk) >> 16) << 16))));
        pin(ro); pin(red);
        mbar_wait(bar0 + 8 * B_XFREE, 0);
        {
            uint32_t wo = (r + ((m >> 1) << 3)) * 32 + (((m & 1) ^ (r >> 2)) << 4), af[14][4];
            uint32_t ho = slot0 + 128 * t + 16 * (g ^ (2 * t));
            pin(wo); pin(ho);
            float d[7][4];
#pragma unroll
            for (int i = 0; i < 7; i++) { d[i][0] = d[i][1] = d[i][2] = d[i][3] = 0.f; }
            auto first_half = [&]() {
                mbar_wait(fbar + 32, has_gu);
#pragma unroll
                for (int j = 0; j < 14; j++) ldsm4t(af[j], slot1 + wo + j * 512);
            };
            auto fetch = [&]() {
                if (elect_one()) {
                    mbar_expect_tx(abar, 7168);
                    bulk_g2s(slot0, &in->h[(56 * h + 14 * a) * 32], 7168, abar);
                }
            };
            wait_count(&in->n_h[32 * (4 * h + a)], 56 * tag - FEW_H);
            STAMP(33);
            fetch();
            first_half();
            mbar_wait(abar, aph);
#pragma unroll
            for (int s = 0; s < 2; s++) {
                if (s) {
                    mbar_wait(fbar + 64, has_gu);
#pragma unroll
                    for (int j = 0; j < 14; j++) ldsm4t(af[j], slot2 + wo + j * 512);
                }
                uint4 hq[7];
#pragma unroll 1
                for (uint32_t it = 0;; spin_guard(it)) {
                    uint32_t bad = 0;
#pragma unroll
                    for (int j = 0; j < 7; j++) { hq[j] = lds128(ho + 512 * (7 * s + j)); bad = or_xor(bad, hq[j].w, tag); }
                    if (__all_sync(0xffffffffu, (bad & 1) == 0)) break;
                    fetch();
                    aph ^= 1;
                    mbar_wait(abar, aph);
                }
                if (s == 0) STAMP(15);
#pragma unroll
                for (int j = 0; j < 14; j++) {
                    const uint4 q = hq[j >> 1];
                    mma_v(d[j % 7], af[j], (j & 1) ? q.z : q.x, (j & 1) ? q.w : q.y);
                }
            }
#pragma unroll
            for (int j = 0; j < 4; j++) dacc[j] = ((d[0][j] + d[1][j]) + (d[2][j] + d[3][j])) + ((d[4][j] + d[5][j]) + d[6][j]);
        }
        STAMP(16);
        {
            st_async128(mapa(sb + OFF_XCH + 16 * tid, h ^ 1), __float_as_uint(dacc[0]), __float_as_uint(dacc[1]), __float_as_uint(dacc[2]), __float_as_uint(dacc[3]),
                        mapa(bar0 + 8 * B_RED, h ^ 1));
            sts128f(slot0 + 7680 + lane * 16, dacc);
            __syncwarp();
            if (elect_one()) mbar_arrive(bar0 + 8 * B_RED);
            mbar_wait(bar0 + 8 * B_RED, 0);
            const uint32_t b0 = sb + OFF_RING + 7680 + ro, b1 = sb + OFF_XCH + ro;
            const float y = ((lds32f(b0) + lds32f(b0 + 8192)) + (lds32f(b0 + 16384) + lds32f(b0 + 24576))) +
                            ((lds32f(b1) + lds32f(b1 + 512)) + (lds32f(b1 + 1024) + lds32f(b1 + 1536)));
            sts32f(red, bf_round(y) * sg);
            __syncwarp();
            if (elect_one()) mbar_arrive(bar0 + 8 * B_UPD);
        }
        STAMP(17); GSTAMP(29);
    }
}

typedef CUresult (*EncodeFn)(CUtensorMap*, CUtensorMapDataType, cuuint32_t, void*, const cuuint64_t*, const cuuint64_t*,
                             const cuuint32_t*, const cuuint32_t*, CUtensorMapInterleave, CUtensorMapSwizzle,
                             CUtensorMapL2promotion, CUtensorMapFloatOOBfill);

void make_map(EncodeFn enc, CUtensorMap* m, const void* ptr, uint64_t cols, uint64_t rows, uint32_t bc, uint32_t br,
              CUtensorMapSwizzle sw, CUtensorMapL2promotion pr) {
    cuuint64_t dims[2] = {cols, rows};
    cuuint64_t str[1] = {cols * 2};
    cuuint32_t box[2] = {bc, br};
    cuuint32_t es[2] = {1, 1};
    enc(m, CU_TENSOR_MAP_DATA_TYPE_BFLOAT16, 2, const_cast<void*>(ptr), dims, str, box, es, CU_TENSOR_MAP_INTERLEAVE_NONE, sw, pr,
        CU_TENSOR_MAP_FLOAT_OOB_FILL_NONE);
}
void make_perm_map(EncodeFn enc, CUtensorMap* m, const void* ptr, CUtensorMapL2promotion pr) {
    cuuint64_t dims[5] = {DM, 2, 4, 4, FF / 32};
    cuuint64_t str[4] = {DM * 2, 8 * DM * 2, 2 * DM * 2, 32 * DM * 2};
    cuuint32_t box[5] = {16, 2, 4, 4, 7};
    cuuint32_t es[5] = {1, 1, 1, 1, 1};
    enc(m, CU_TENSOR_MAP_DATA_TYPE_BFLOAT16, 5, const_cast<void*>(ptr), dims, str, box, es, CU_TENSOR_MAP_INTERLEAVE_NONE,
        CU_TENSOR_MAP_SWIZZLE_32B, pr, CU_TENSOR_MAP_FLOAT_OOB_FILL_NONE);
}
void make_tile_map(EncodeFn enc, CUtensorMap* m, const void* ptr) {
    cuuint64_t dims[4] = {DM, 4, 16, SEQ / 64};
    cuuint64_t str[3] = {16 * DM * 2, DM * 2, 64 * DM * 2};
    cuuint32_t box[4] = {16, 4, 2, 8};
    cuuint32_t es[4] = {1, 1, 1, 1};
    enc(m, CU_TENSOR_MAP_DATA_TYPE_BFLOAT16, 4, const_cast<void*>(ptr), dims, str, box, es, CU_TENSOR_MAP_INTERLEAVE_NONE,
        CU_TENSOR_MAP_SWIZZLE_32B, CU_TENSOR_MAP_L2_PROMOTION_NONE, CU_TENSOR_MAP_FLOAT_OOB_FILL_NONE);
}

}

extern "C" void kernel_launch(void* const* d_in, const int* in_sizes, int n_in, void* d_out, int out_size) {
    (void)in_sizes; (void)n_in; (void)out_size;
    static EncodeFn enc = nullptr;
    static void* scratch = nullptr;
    if (!enc) {
        void* fn = nullptr;
        cudaDriverEntryPointQueryResult q;
        cudaGetDriverEntryPoint("cuTensorMapEncodeTiled", &fn, cudaEnableDefault, &q);
        enc = (EncodeFn)fn;
        cudaGetSymbolAddress(&scratch, g_scratch);
        cudaFuncSetAttribute(fused_kernel, cudaFuncAttributeMaxDynamicSharedMemorySize, SMEM_BYTES);
    }
    Maps maps;
    make_tile_map(enc, &maps.u, d_in[0]);
    make_tile_map(enc, &maps.out, d_out);
    make_map(enc, &maps.wg, d_in[9], FF, DM, 64, 32, CU_TENSOR_MAP_SWIZZLE_128B, CU_TENSOR_MAP_L2_PROMOTION_L2_128B);
    make_map(enc, &maps.wu, d_in[10], FF, DM, 64, 32, CU_TENSOR_MAP_SWIZZLE_128B, CU_TENSOR_MAP_L2_PROMOTION_L2_128B);
    make_perm_map(enc, &maps.wd, d_in[11], CU_TENSOR_MAP_L2_PROMOTION_L2_64B);
    Ptrs p;
    p.sc = (Scratch*)scratch;
    p.u = (const __nv_bfloat16*)d_in[0];
    p.logA = (const __nv_bfloat16*)d_in[1];
    p.Aim = (const __nv_bfloat16*)d_in[2];
    p.Cre = (const __nv_bfloat16*)d_in[3];
    p.Cim = (const __nv_bfloat16*)d_in[4];
    p.ldt = (const __nv_bfloat16*)d_in[5];
    p.dsk = (const __nv_bfloat16*)d_in[6];
    p.wr = (const __nv_bfloat16*)d_in[8];
    p.out = (__nv_bfloat16*)d_out;
    p.zero = 0;
    fused_kernel<<<NCTA, NTHR, SMEM_BYTES, cudaStreamPerThread>>>(p, maps);
}
```

```cpp
#include <cuda_runtime.h>
#include <cuda_bf16.h>
#include <cuda_fp16.h>
#include <cuda.h>
#include <stdint.h>

namespace {

constexpr int SEQ = 2048, DM = 1024, NMODE = 128, FF = 3584;
constexpr int NCTA = 128, NTHR = 512;
constexpr int GU_CTAS = 112;
constexpr int NREP = 4;

constexpr int OFF_XT = 0;
constexpr int OFF_RING = 65536;
constexpr int OFF_PRIV = OFF_RING + 65536;
constexpr int OFF_VT = OFF_PRIV + 65536;
constexpr int VT_PAD = 32, VT_PLANE = VT_PAD + 2048, VT_PITCH = 2 * VT_PLANE, ROW_PITCH = 2064;
constexpr int OFF_BAR = OFF_VT + 8 * VT_PITCH;
constexpr int OFF_MISC = OFF_BAR + 384;
constexpr int OFF_XCH = OFF_MISC + 112;
constexpr int SMEM_BYTES = OFF_XCH + 2048;
constexpr int OFF_LN = OFF_RING + 7 * 8192;
constexpr int OFF_ST = OFF_RING + 6 * 8192;
static_assert(SMEM_BYTES <= 232448, "shared memory");

constexpr int B_ROW = 0, B_XT = 4, B_V = 5, B_LN = 6, B_SFREE = 7, B_RECV = 8, B_RED = 10, B_UPD = 11, B_ST = 12, B_XFREE = 16, B_OWN = 17, B_FREE = 20, B_FULL = 32, B_AUX = 44, NBAR = 48;

constexpr int T_DENSE = 60;
constexpr int T_PATCH = 2208;
constexpr int T_R2 = 2368;
constexpr int T_R3 = 3296;

constexpr int T_RED = 4032;
__device__ __forceinline__ bool slot_priv(int s) { return (uint32_t)(s - 6) < 4u; }
__device__ __forceinline__ uint32_t slot_off(int s) { return slot_priv(s) ? OFF_PRIV + 4096 + (s & 3) * 16384 : OFF_RING + (s < 6 ? s : s - 4) * 8192; }
__device__ __forceinline__ uint32_t tab_off(int w) { return OFF_PRIV + w * 8192 + (w & 1) * 4096; }

constexpr uint32_t SPIN_LIMIT = 1u << 20;
#define BB_UNROLL 2
constexpr int kBbUnroll = BB_UNROLL;
#define ST_T0 2280
#define ST_PER 308
#define ST_PER2 320
#define LN_PAUSE 0xf0
#define FEW_ST 8
#define FEW_H 8

struct Exchange {
    uint2 stat[SEQ];
    uint4 h[GU_CTAS * 32];
    uint32_t cnt[4 * 32];
};
__device__ __align__(128) Exchange g_scratch[NREP];

struct Ptrs {
    const __nv_bfloat16 *logA, *Aim, *Cre, *Cim, *ldt, *u;
    const __nv_bfloat16 *dsk, *wr;
    Exchange* sc;
    __nv_bfloat16* out;
    uint32_t zero;
};
struct Maps {
    CUtensorMap u, out, wg, wu, wd;
};

#define STAMP(i) do { } while (0)
#define GSTAMP(i) do { } while (0)

__device__ __forceinline__ uint32_t s_u32(const void* p) { return (uint32_t)__cvta_generic_to_shared(p); }
__device__ __forceinline__ void mbar_init(uint32_t b, uint32_t n) {
    asm volatile("mbarrier.init.shared::cta.b64 [%0], %1;" ::"r"(b), "r"(n) : "memory");
}
__device__ __forceinline__ void mbar_expect_tx(uint32_t b, uint32_t bytes) {
    asm volatile("mbarrier.arrive.expect_tx.shared::cta.b64 _, [%0], %1;" ::"r"(b), "r"(bytes) : "memory");
}
__device__ __forceinline__ void mbar_arrive(uint32_t b) {
    asm volatile("mbarrier.arrive.shared::cta.b64 _, [%0];" ::"r"(b) : "memory");
}
__device__ __forceinline__ void mbar_arrive_n(uint32_t b, uint32_t n) {
    asm volatile("mbarrier.arrive.shared::cta.b64 _, [%0], %1;" ::"r"(b), "r"(n) : "memory");
}
__device__ __forceinline__ void mbar_arrive_peer(uint32_t b_cluster) {
    asm volatile("mbarrier.arrive.relaxed.cluster.shared::cluster.b64 _, [%0];" ::"r"(b_cluster) : "memory");
}
__device__ __forceinline__ void mbar_wait(uint32_t b, uint32_t parity) {
    asm volatile("{\n\t.reg .pred p;\n\t.reg .u32 c;\n\tmov.u32 c, 0;\n"
                 "W:\n\tmbarrier.try_wait.parity.shared::cta.b64 p, [%0], %1;\n\t@p bra D;\n\t"
                 "add.u32 c, c, 1;\n\tsetp.lt.u32 p, c, 1048576;\n\t@p bra W;\n\ttrap;\nD:\n\t}"
                 ::"r"(b), "r"(parity) : "memory");
}
__device__ __forceinline__ bool elect_one() {
    uint32_t p;
    asm volatile("{ .reg .pred P; elect.sync _|P, 0xffffffff; selp.u32 %0, 1, 0, P; }" : "=r"(p));
    return p != 0;
}
__device__ __forceinline__ uint32_t mapa(uint32_t a, uint32_t rank) {
    uint32_t r;
    asm("mapa.shared::cluster.u32 %0, %1, %2;" : "=r"(r) : "r"(a), "r"(rank));
    return r;
}
__device__ __forceinline__ void cluster_arrive() { asm volatile("barrier.cluster.arrive.relaxed.aligned;" ::: "memory"); }
__device__ __forceinline__ void cluster_wait() { asm volatile("barrier.cluster.wait.acquire.aligned;" ::: "memory"); }
__device__ __forceinline__ void tma_load_2d(uint32_t dst, const CUtensorMap* m, int c0, int c1, uint32_t bar) {
    asm volatile("cp.async.bulk.tensor.2d.shared::cluster.global.mbarrier::complete_tx::bytes [%0], [%1, {%3, %4}], [%2];"
                 ::"r"(dst), "l"(m), "r"(bar), "r"(c0), "r"(c1) : "memory");
}
__device__ __forceinline__ void tma_load_perm(uint32_t dst, const CUtensorMap* m, int c0, int blk, uint32_t bar) {
    asm volatile("cp.async.bulk.tensor.5d.shared::cluster.global.mbarrier::complete_tx::bytes [%0], [%1, {%3, %4, %4, %4, %5}], [%2];"
                 ::"r"(dst), "l"(m), "r"(bar), "r"(c0), "r"(0), "r"(blk) : "memory");
}
__device__ __forceinline__ void tma_load_tile(uint32_t dst, const CUtensorMap* m, int c0, int c2, int c3, uint32_t bar) {
    asm volatile("cp.async.bulk.tensor.4d.shared::cluster.global.mbarrier::complete_tx::bytes.multicast::cluster [%0], [%1, {%3, %4, %5, %6}], [%2], %7;"
                 ::"r"(dst), "l"(m), "r"(bar), "r"(c0), "r"(0), "r"(c2), "r"(c3), "h"((uint16_t)3) : "memory");
}
__device__ __forceinline__ void tma_store_tile(const CUtensorMap* m, uint32_t src, int c0, int c2, int c3) {
    asm volatile("cp.async.bulk.tensor.4d.global.shared::cta.bulk_group [%0, {%2, %3, %4, %5}], [%1];"
                 ::"l"(m), "r"(src), "r"(c0), "r"(0), "r"(c2), "r"(c3) : "memory");
    asm volatile("cp.async.bulk.commit_group;" ::: "memory");
}
__device__ __forceinline__ void bulk_g2s(uint32_t dst, const void* src, uint32_t bytes, uint32_t bar) {
    asm volatile("cp.async.bulk.shared::cluster.global.mbarrier::complete_tx::bytes [%0], [%1], %2, [%3];"
                 ::"r"(dst), "l"(src), "r"(bytes), "r"(bar) : "memory");
}
__device__ __forceinline__ void st_async128(uint32_t dst_cluster, uint32_t x, uint32_t y, uint32_t z, uint32_t w, uint32_t bar_cluster) {
    asm volatile("st.async.weak.shared::cluster.mbarrier::complete_tx::bytes.v4.b32 [%0], {%1,%2,%3,%4}, [%5];"
                 ::"r"(dst_cluster), "r"(x), "r"(y), "r"(z), "r"(w), "r"(bar_cluster) : "memory");
}
__device__ __forceinline__ void fence_async() { asm volatile("fence.proxy.async.shared::cta;" ::: "memory"); }
__device__ __forceinline__ void named_sync(int id, int n) { asm volatile("bar.sync %0, %1;" ::"r"(id), "r"(n) : "memory"); }

__device__ __forceinline__ void ldsm4(uint32_t* r, uint32_t a) {
    asm volatile("ldmatrix.sync.aligned.m8n8.x4.shared.b16 {%0,%1,%2,%3}, [%4];"
                 : "=r"(r[0]), "=r"(r[1]), "=r"(r[2]), "=r"(r[3]) : "r"(a));
}
__device__ __forceinline__ void ldsm4t(uint32_t* r, uint32_t a) {
    asm volatile("ldmatrix.sync.aligned.m8n8.x4.trans.shared.b16 {%0,%1,%2,%3}, [%4];"
                 : "=r"(r[0]), "=r"(r[1]), "=r"(r[2]), "=r"(r[3]) : "r"(a));
}
__device__ __forceinline__ void stsm4t(uint32_t a, uint32_t x, uint32_t y, uint32_t z, uint32_t w) {
    asm volatile("stmatrix.sync.aligned.m8n8.x4.trans.shared.b16 [%0], {%1,%2,%3,%4};"
                 ::"r"(a), "r"(x), "r"(y), "r"(z), "r"(w) : "memory");
}
__device__ __forceinline__ uint32_t lds32(uint32_t a) { uint32_t v; asm volatile("ld.shared.u32 %0, [%1];" : "=r"(v) : "r"(a)); return v; }
__device__ __forceinline__ float lds32f(uint32_t a) { float v; asm volatile("ld.shared.f32 %0, [%1];" : "=f"(v) : "r"(a)); return v; }
__device__ __forceinline__ uint2 lds64(uint32_t a) { uint2 v; asm volatile("ld.shared.v2.u32 {%0,%1}, [%2];" : "=r"(v.x), "=r"(v.y) : "r"(a)); return v; }
__device__ __forceinline__ uint4 lds128(uint32_t a) {
    uint4 v; asm volatile("ld.shared.v4.u32 {%0,%1,%2,%3}, [%4];" : "=r"(v.x), "=r"(v.y), "=r"(v.z), "=r"(v.w) : "r"(a)); return v;
}
__device__ __forceinline__ uint4 lds128v(uint32_t a) {
    uint4 v; asm volatile("ld.volatile.shared.v4.u32 {%0,%1,%2,%3}, [%4];" : "=r"(v.x), "=r"(v.y), "=r"(v.z), "=r"(v.w) : "r"(a)); return v;
}
__device__ __forceinline__ uint32_t or_xor(uint32_t a, uint32_t b, uint32_t c) {
    uint32_t r; asm("lop3.b32 %0, %1, %2, %3, 0xf6;" : "=r"(r) : "r"(a), "r"(b), "r"(c)); return r;
}
__device__ __forceinline__ float4 lds128f(uint32_t a) {
    float4 v; asm volatile("ld.shared.v4.f32 {%0,%1,%2,%3}, [%4];" : "=f"(v.x), "=f"(v.y), "=f"(v.z), "=f"(v.w) : "r"(a)); return v;
}
__device__ __forceinline__ void sts32(uint32_t a, uint32_t v) { asm volatile("st.shared.u32 [%0], %1;" ::"r"(a), "r"(v) : "memory"); }
__device__ __forceinline__ void sts32f(uint32_t a, float v) { asm volatile("st.shared.f32 [%0], %1;" ::"r"(a), "f"(v) : "memory"); }
__device__ __forceinline__ void sts64(uint32_t a, uint32_t x, uint32_t y) { asm volatile("st.shared.v2.u32 [%0], {%1,%2};" ::"r"(a), "r"(x), "r"(y) : "memory"); }
__device__ __forceinline__ void sts64f(uint32_t a, float x, float y) { asm volatile("st.shared.v2.f32 [%0], {%1,%2};" ::"r"(a), "f"(x), "f"(y) : "memory"); }
__device__ __forceinline__ void sts128(uint32_t a, uint32_t x, uint32_t y, uint32_t z, uint32_t w) {
    asm volatile("st.shared.v4.u32 [%0], {%1,%2,%3,%4};" ::"r"(a), "r"(x), "r"(y), "r"(z), "r"(w) : "memory");
}
__device__ __forceinline__ void sts128f(uint32_t a, const float* v) {
    asm volatile("st.shared.v4.f32 [%0], {%1,%2,%3,%4};" ::"r"(a), "f"(v[0]), "f"(v[1]), "f"(v[2]), "f"(v[3]) : "memory");
}
__device__ __forceinline__ uint4 ldg128(const void* p) {
    uint4 v; asm volatile("ld.global.nc.L1::no_allocate.v4.u32 {%0,%1,%2,%3}, [%4];" : "=r"(v.x), "=r"(v.y), "=r"(v.z), "=r"(v.w) : "l"(p)); return v;
}
__device__ __forceinline__ uint2 ldg64(const void* p) {
    uint2 v; asm volatile("ld.global.nc.L1::no_allocate.v2.u32 {%0,%1}, [%2];" : "=r"(v.x), "=r"(v.y) : "l"(p)); return v;
}
__device__ __forceinline__ uint32_t ldg16(const void* p) {
    uint32_t v; asm volatile("ld.global.nc.u16 %0, [%1];" : "=r"(v) : "l"(p)); return v;
}
__device__ __forceinline__ uint2 ld_relaxed_64(const void* p) {
    uint2 v; asm volatile("ld.relaxed.gpu.global.v2.u32 {%0,%1}, [%2];" : "=r"(v.x), "=r"(v.y) : "l"(p) : "memory"); return v;
}
__device__ __forceinline__ uint32_t ld_relaxed_32(const void* p) {
    uint32_t v; asm volatile("ld.relaxed.gpu.global.u32 %0, [%1];" : "=r"(v) : "l"(p) : "memory"); return v;
}
__device__ __forceinline__ void st_relaxed_64(void* p, uint32_t x, uint32_t y) {
    asm volatile("st.relaxed.gpu.global.v2.u32 [%0], {%1,%2};" ::"l"(p), "r"(x), "r"(y) : "memory");
}
__device__ __forceinline__ void st_relaxed_32(void* p, uint32_t v) {
    asm volatile("st.relaxed.gpu.global.u32 [%0], %1;" ::"l"(p), "r"(v) : "memory");
}
__device__ __forceinline__ void red_add(void* p, uint32_t v) { asm volatile("red.relaxed.gpu.global.add.u32 [%0], %1;" ::"l"(p), "r"(v) : "memory"); }
__device__ __forceinline__ uint32_t now_ns() { uint32_t t; asm volatile("mov.u32 %0, %%globaltimer_lo;" : "=r"(t) :: "memory"); return t; }
__device__ __forceinline__ void sleep_until(uint32_t t) {
#pragma unroll 1
    for (int left; (left = (int)(t - now_ns())) > 0;) __nanosleep(left >> 1);
}
__device__ __forceinline__ void spin_guard(uint32_t& it) { if (++it > SPIN_LIMIT) __trap(); }
__device__ __forceinline__ void wait_count(const uint32_t* p, uint32_t target) {
#pragma unroll 1
    for (uint32_t it = 0; __any_sync(0xffffffffu, (int)(ld_relaxed_32(p) - target) < 0); spin_guard(it)) { }
}
__device__ __forceinline__ void mma_bf16_k8(float* c, uint32_t a0, uint32_t a1, uint32_t b0) {
    asm("mma.sync.aligned.m16n8k8.row.col.f32.bf16.bf16.f32 {%0,%1,%2,%3}, {%4,%5}, {%6}, {%0,%1,%2,%3};"
                 : "+f"(c[0]), "+f"(c[1]), "+f"(c[2]), "+f"(c[3]) : "r"(a0), "r"(a1), "r"(b0));
}
__device__ __forceinline__ void mma_v(float* c, const uint32_t* a, uint32_t b0, uint32_t b1) {
    asm volatile("mma.sync.aligned.m16n8k16.row.col.f32.bf16.bf16.f32 {%0,%1,%2,%3}, {%4,%5,%6,%7}, {%8,%9}, {%0,%1,%2,%3};"
                 : "+f"(c[0]), "+f"(c[1]), "+f"(c[2]), "+f"(c[3]) : "r"(a[0]), "r"(a[1]), "r"(a[2]), "r"(a[3]), "r"(b0), "r"(b1));
}
__device__ __forceinline__ void mma_bf16_z(float* c, uint32_t a0, uint32_t a1, uint32_t a2, uint32_t a3, uint32_t b0, uint32_t b1) {
    asm volatile("mma.sync.aligned.m16n8k16.row.col.f32.bf16.bf16.f32 {%0,%1,%2,%3}, {%4,%5,%6,%7}, {%8,%9}, {%10,%10,%10,%10};"
        : "=f"(c[0]), "=f"(c[1]), "=f"(c[2]), "=f"(c[3]) : "r"(a0), "r"(a1), "r"(a2), "r"(a3), "r"(b0), "r"(b1), "f"(0.f));
}
__device__ __forceinline__ void mma_f16(float* c, uint32_t a0, uint32_t a1, uint32_t a2, uint32_t a3, uint32_t b0, uint32_t b1) {
    asm("mma.sync.aligned.m16n8k16.row.col.f32.f16.f16.f32 {%0,%1,%2,%3}, {%4,%5,%6,%7}, {%8,%9}, {%0,%1,%2,%3};"
                 : "+f"(c[0]), "+f"(c[1]), "+f"(c[2]), "+f"(c[3]) : "r"(a0), "r"(a1), "r"(a2), "r"(a3), "r"(b0), "r"(b1));
}
__device__ __forceinline__ uint32_t pack_bf16(float lo, float hi) {
    uint32_t r; asm("cvt.rn.bf16x2.f32 %0, %1, %2;" : "=r"(r) : "f"(hi), "f"(lo)); return r;
}
__device__ __forceinline__ uint32_t pack_v(float lo, float hi) {
    uint32_t r; asm volatile("cvt.rn.bf16x2.f32 %0, %1, %2;" : "=r"(r) : "f"(hi), "f"(lo)); return r;
}
__device__ __forceinline__ uint32_t pack_w(float lo, float hi) {
    uint32_t r; asm volatile("cvt.rn.satfinite.bf16x2.f32 %0, %1, %2;" : "=r"(r) : "f"(hi), "f"(lo)); return r;
}
template <int N> __device__ __forceinline__ uint32_t after_all(const uint32_t (&f)[N][4], uint32_t zero) {
    uint32_t d[3] = {0, 0, 0};
#pragma unroll
    for (int i = 0; i < N; i++) d[i % 3] |= f[i][3];
    return (d[0] | d[1] | d[2]) & zero;
}
__device__ __forceinline__ void pin(uint32_t& x) { asm volatile("" : "+r"(x)); }
template <class T> __device__ __forceinline__ void pin(T*& x) { asm volatile("" : "+l"(x)); }
__device__ __forceinline__ uint32_t pack_f16(float lo, float hi) {
    uint32_t r; asm("cvt.rn.f16x2.f32 %0, %1, %2;" : "=r"(r) : "f"(hi), "f"(lo)); return r;
}
__device__ __forceinline__ float bf_lo(uint32_t v) { return __uint_as_float(v << 16); }
__device__ __forceinline__ float bf_hi(uint32_t v) { return __uint_as_float(v & 0xffff0000u); }
__device__ __forceinline__ float bf_round(float x) { return __uint_as_float(pack_bf16(0.f, x)); }
__device__ __forceinline__ uint32_t badd2(uint32_t a, uint32_t b) { uint32_t r; asm("add.rn.bf16x2 %0, %1, %2;" : "=r"(r) : "r"(a), "r"(b)); return r; }
__device__ __forceinline__ uint32_t bsub2_lo(uint32_t a, uint32_t b) {
    uint32_t r; asm("{ .reg .b16 m, h; .reg .b32 m2; mov.b32 {m, h}, %2; mov.b32 m2, {m, m}; sub.rn.bf16x2 %0, %1, m2; }" : "=r"(r) : "r"(a), "r"(b)); return r;
}
__device__ __forceinline__ uint32_t bmax2(uint32_t a, uint32_t b) { uint32_t r; asm("max.bf16x2 %0, %1, %2;" : "=r"(r) : "r"(a), "r"(b)); return r; }
__device__ __forceinline__ uint32_t normalize2(uint32_t x, uint32_t s0, uint32_t s1) {
    uint32_t r;
    asm("{ .reg .b16 m, h, l, k; .reg .b32 m2, h2, l2, d, t;\n\t"
        "mov.b32 {m, h}, %2; mov.b32 {l, k}, %3; mov.b32 m2, {m, m}; mov.b32 h2, {h, h}; mov.b32 l2, {l, l};\n\t"
        "sub.rn.bf16x2 d, %1, m2; mul.rn.bf16x2 t, d, l2; fma.rn.bf16x2 %0, d, h2, t; }" : "=r"(r) : "r"(x), "r"(s0), "r"(s1));
    return r;
}
__device__ __forceinline__ float rcpf(float x) { float r; asm("rcp.approx.ftz.f32 %0, %1;" : "=f"(r) : "f"(x)); return r; }
__device__ __forceinline__ float sqrtaf(float x) { float r; asm("sqrt.approx.ftz.f32 %0, %1;" : "=f"(r) : "f"(x)); return r; }
__device__ __forceinline__ float ex2f(float x) { float r; asm("ex2.approx.ftz.f32 %0, %1;" : "=f"(r) : "f"(x)); return r; }

__device__ __forceinline__ int tok_off(int t) { return ((t >> 3) & 1) * VT_PLANE + (t >> 4) * 16 + (t & 7) * 2; }

__device__ __forceinline__ uint32_t unorder_key(uint32_t k16) { return k16 ^ ((k16 & 0x8000u) ? 0x8000u : 0xffffu); }

struct cplx { float r, i; };
struct hc { uint32_t r, i; };
template <bool CONJ> __device__ __forceinline__ cplx csq(cplx a) {
    float im;
    asm("{ .reg .f32 t; mul.ftz.f32 t, %1, %2; mul.ftz.f32 %0, t, 0f40000000; }" : "=f"(im) : "f"(CONJ ? -a.r : a.r), "f"(a.i));
    return {fmaf(a.r, a.r, -(a.i * a.i)), im};
}
__device__ __forceinline__ cplx cexpp(float a2, float ai) {
    float m = ex2f(a2), s, c;
    __sincosf(ai, &s, &c);
    return {m * c, m * s};
}
__device__ __forceinline__ __half2 as_h2(uint32_t x) { return *reinterpret_cast<__half2*>(&x); }
__device__ __forceinline__ uint32_t as_u(__half2 x) { return *reinterpret_cast<uint32_t*>(&x); }
__device__ __forceinline__ hc hmul(hc a, hc b) {
    return {as_u(__hfma2(as_h2(a.r), as_h2(b.r), __hneg2(__hmul2(as_h2(a.i), as_h2(b.i))))),
            as_u(__hfma2(as_h2(a.r), as_h2(b.i), __hmul2(as_h2(a.i), as_h2(b.r))))};
}
__device__ __forceinline__ hc hpack(cplx a, cplx b) { return {pack_f16(a.r, b.r), pack_f16(a.i, b.i)}; }
__device__ __forceinline__ void sts16(uint32_t a, uint32_t v) { asm volatile("st.shared.u16 [%0], %1;" ::"r"(a), "r"(v) : "memory"); }

struct KgenAddr {
    uint32_t l, h, m2, m3, m4, z, w, wz;
    __device__ __forceinline__ KgenAddr(uint32_t scr, int lane) {
        const int g = lane >> 2, t = lane & 3;
        const uint32_t rec = scr + t * 480;
        l = rec + 16 * g; h = rec + 128 + 8 * g; m2 = rec + 192 + 8 * (g & 1); m3 = rec + 208 + 4 * (g & 2); m4 = rec + 224 + 2 * (g & 4);
        z = scr + 7680 + 16 * t; w = scr + 240 * lane; wz = scr + 7680 + 8 * lane;
        pin(l); pin(h); pin(m2); pin(m3); pin(m4); pin(z); pin(w); pin(wz);
    }
    __device__ __forceinline__ uint32_t any() const { return (l | h | m2) | (m3 | m4 | z) | (w | wz); }
};
template <class Hook, class Hook2>
__device__ __forceinline__ void kgen(const KgenAddr& ad, uint32_t tab, int lane, uint2 la, uint2 aim, uint2 cre, uint2 cim, float dt, float skip, int dch, Hook main_done, Hook2 half_done) {
    const int g = lane >> 2, t = lane & 3;
    const float dt2 = 2.f * dt;
    const uint32_t am = bmax2(bmax2(cre.x & 0x7fff7fffu, cre.y & 0x7fff7fffu), bmax2(cim.x & 0x7fff7fffu, cim.y & 0x7fff7fffu));
    const float mx = dt2 * fmaxf(bf_lo(am), bf_hi(am));
    const uint32_t eb = min(max(__reduce_max_sync(0xffffffffu, __float_as_uint(mx)) >> 23, 1u), 252u);
    const float cscale = dt2 * __uint_as_float((253u - eb) << 23);
    const float scale_inv = __uint_as_float((eb + 1u) << 23);
    float k0 = (bf_lo(cre.x) + bf_hi(cre.x)) + (bf_lo(cre.y) + bf_hi(cre.y));
#pragma unroll
    for (int o = 16; o; o >>= 1) k0 += __shfl_xor_sync(0xffffffffu, k0, o);
    const float ndt = -1.4426950408889634f * dt;
    STAMP(40);

    float acc[5][4];
#pragma unroll
    for (int i = 0; i < 5; i++) { acc[i][0] = acc[i][1] = acc[i][2] = acc[i][3] = 0.f; }

#pragma unroll kBbUnroll
    for (int bb = 0; bb < 2; bb++) {
        cplx z[2][11], cz[2];
#pragma unroll
        for (int e = 0; e < 2; e++) {
            const float lg = e ? bf_hi(la.x) : bf_lo(la.x), ai = (e ? bf_hi(aim.x) : bf_lo(aim.x)) * dt;
            const float cr = (e ? bf_hi(cre.x) : bf_lo(cre.x)) * cscale, ci = (e ? bf_hi(cim.x) : bf_lo(cim.x)) * cscale;
            const float a2 = bf_round(ex2f(lg * 1.4426950408889634f)) * ndt;
            z[e][0] = cexpp(a2, ai);
            z[e][5] = cexpp(a2 * 32.f, ai * -32.f);
#pragma unroll
            for (int i = 1; i < 11; i++) if (i != 5) z[e][i] = (i == 3 || i == 7) ? csq<true>(z[e][i - 1]) : csq<false>(z[e][i - 1]);
            cz[e] = {fmaf(cr, z[e][0].r, -(ci * z[e][0].i)), fmaf(cr, z[e][0].i, ci * z[e][0].r)};
        }
        la.x = la.y; aim.x = aim.y; cre.x = cre.y; cim.x = cim.y;
        const hc z1 = hpack(z[0][0], z[1][0]), z2 = hpack(z[0][1], z[1][1]), z4 = hpack(z[0][2], z[1][2]);
        hc L[8], H[8];
        L[1] = hpack(z[0][3], z[1][3]); L[2] = hpack(z[0][4], z[1][4]); L[4] = hpack(z[0][5], z[1][5]);
        const hc y64 = hpack(z[0][6], z[1][6]), z128 = hpack(z[0][7], z[1][7]), z256 = hpack(z[0][8], z[1][8]);
        const hc z512 = hpack(z[0][9], z[1][9]), z1024 = hpack(z[0][10], z[1][10]);
        H[0] = hpack(cz[0], cz[1]);
        H[1] = hmul(H[0], z1); H[2] = hmul(H[0], z2); H[3] = hmul(H[1], z2);
        L[3] = hmul(L[1], L[2]);
#pragma unroll
        for (int i = 0; i < 4; i++) { H[4 + i] = hmul(H[i], z4); if (i) L[4 + i] = hmul(L[i], L[4]); }
        __syncwarp();
        sts128(ad.w, 0x3c003c00u, y64.r, 0u, y64.i);
#pragma unroll
        for (int i = 1; i < 8; i++) { const hc q = hmul(L[i], y64); sts128(ad.w + 16 * i, L[i].r, q.r, L[i].i, q.i); }
#pragma unroll
        for (int i = 0; i < 4; i++) sts128(ad.w + 128 + 16 * i, H[2 * i].r, H[2 * i].i, H[2 * i + 1].r, H[2 * i + 1].i);
        {
            const hc a = hmul(z256, z1), b = hmul(z256, z128), c = hmul(z256, z2), d = hmul(z512, z4);
            sts128(ad.w + 192, a.r, a.i, b.r, b.i);
            sts128(ad.w + 208, c.r, c.i, z512.r, z512.i);
            sts128(ad.w + 224, d.r, d.i, z1024.r, z1024.i);
            sts64(ad.wz, z128.r, z128.i);
        }
        __syncwarp();

#pragma unroll
        for (int k2 = 0; k2 < 4; k2++) {
#pragma unroll
            for (uint32_t s = 0; s < 2; s++) {
                const uint32_t o = k2 * 1920 + s * 240;
                const uint4 l = lds128(ad.l + o);
                const uint2 h0 = lds64(ad.h + o), m2 = lds64(ad.m2 + o), m3 = lds64(ad.m3 + o), m4 = lds64(ad.m4 + o), mz = lds64(ad.z + k2 * 64 + s * 8);
                const hc H0 = {h0.x, h0.y};
                const hc H1 = hmul(H0, {mz.x, mz.y}), H2 = hmul(H0, {m2.x, m2.y}), H3 = hmul(H2, {m3.x, m3.y}), H4 = hmul(H3, {m4.x, m4.y});
                mma_f16(acc[0], l.x, l.y, l.z, l.w, H0.r, H0.i);
                mma_f16(acc[1], l.x, l.y, l.z, l.w, H1.r, H1.i);
                mma_f16(acc[2], l.x, l.y, l.z, l.w, H2.r, H2.i);
                mma_f16(acc[3], l.x, l.y, l.z, l.w, H3.r, H3.i);
                mma_f16(acc[4], l.x, l.y, l.z, l.w, H4.r, H4.i);
            }
        }

        if (bb == 0) half_done();
    }
    __syncwarp();
    main_done();

#pragma unroll
    for (int i = 0; i < 4; i++) sts128(tab + 2048 + 512 * i + 16 * lane, 0, 0, 0, 0);
    if (lane < 15) sts32(tab + 4 * lane, 0);
    __syncwarp();
    const uint32_t d0 = tab + T_DENSE + 4 + 8 * lane, src = (lane + 31) & 31;
    const uint32_t p0 = pack_bf16(fmaf(k0, dt2, skip), 0.f);
    uint32_t prev = p0;
#pragma unroll
    for (int i = 0; i < 4; i++) {
        const uint32_t pk = pack_bf16(acc[i >> 1][2 * (i & 1) + 1] * scale_inv, acc[i >> 1][2 * (i & 1)] * scale_inv);
        sts64(d0 + 256 * i, __byte_perm(pk, __shfl_sync(0xffffffffu, lane == 31 ? prev : pk, src), 0x5432), pk);
        prev = pk;
    }
    const uint32_t w0 = pack_bf16(acc[2][0] * scale_inv, acc[2][1] * scale_inv), w1 = pack_bf16(acc[2][2] * scale_inv, acc[2][3] * scale_inv);
    const uint32_t sa = (lane & 1) ? 0x5410u : 0x5454u, sb2 = (lane & 1) ? 0x1010u : 0x5410u;
#pragma unroll
    for (int hf = 0; hf < 2; hf++) {
        const uint32_t w = hf ? w1 : w0;
        const uint32_t pv = __shfl_sync(0xffffffffu, lane != 31 ? w : hf ? w0 : __byte_perm(prev, w1, 0x5410), src);
        sts64(d0 + 1024 + 256 * hf, __byte_perm(w, pv, sa), __byte_perm(w, pv, sb2));
        sts64(d0 + 1536 + 256 * hf, __byte_perm(w, pv, sa + 0x2222u), __byte_perm(w, pv, sb2 + 0x2222u));
    }
    const uint32_t d3 = tab + T_R2 + 160 + 320 * (t & 1) + 16 * (g >> 1) + 8 * (g & 1) + 4 * (t >> 1), d3n = d3 + (g >= 6 ? 32 : 0);
    const uint32_t d4 = tab + T_R3 + 80 + 160 * t + 4 * g, d4n = d4 + (g >= 6 ? 16 : 0);
    uint32_t p3;
#pragma unroll
    for (int hf = 0; hf < 2; hf++)
#pragma unroll
        for (int e = 0; e < 2; e++) {
            const float v3 = acc[3][2 * hf + e] * scale_inv;
            const uint32_t p4 = pack_bf16(acc[4][2 * hf + e] * scale_inv, 0.f);
            p3 = pack_bf16(v3, v3);
            sts16(d3 + 64 * hf + 160 * e, p3);
            sts16((hf ? d3n : d3) + 64 * hf + 160 * e + 18, p3);
            sts16(d4 + 32 * hf + 80 * e, p4);
            sts16((hf ? d4n : d4) + 32 * hf + 80 * e + 10, p4);
        }
    if (lane == 31) {
        const uint32_t k512 = __byte_perm(w1, 0, 0x3232);
        sts32(tab + T_DENSE, p0);
        sts64(tab + T_DENSE + 4 * 513, k512, k512); sts16(tab + T_DENSE + 4 * 515 + 2, k512);
        sts16(tab + T_PATCH + 4 * 17, p3); sts32(tab + T_PATCH + 4 * 18, p3); sts16(tab + T_PATCH + 4 * 19 + 2, p3);
    }
    __syncwarp();
}

__device__ __forceinline__ void load_toep(uint32_t* a, uint32_t p, uint32_t pz) {
    a[0] = lds32(p); a[1] = lds32(p + 32); a[2] = lds32(pz - 32); a[3] = lds32(pz);
}
template <int F>
__device__ __forceinline__ void ffa_step(float (&acc)[16][4], float (&W)[8][4], uint32_t (&R)[8][4], uint32_t (&A)[4][4],
                                         uint32_t va, uint32_t vmin, uint32_t pb, uint32_t pz) {
    constexpr int S = F ^ 1;
    auto load = [&](int sh) {
#pragma unroll
        for (int i = S; i < 8; i += 2) ldsm4(R[i], i == 0 ? max(va - 16 * sh, vmin) : va - 16 * sh + i * 128);
#pragma unroll
        for (int k = S; k < 4; k += 2) load_toep(A[k], pb + 64 * sh + k * 512, pz + 64 * sh + k * 512);
    };
    auto prod = [&](int par, int dst) {
#pragma unroll
        for (int k = 0; k < 2; k++)
#pragma unroll
            for (int m = k; m < 8; m++) {
                const uint32_t* x = &R[2 * ((m - k) & 3) + par][2 * ((m - k) >> 2)];
                mma_v(dst == 1 ? W[m] : acc[2 * m + (dst >> 1)], A[2 * k + par], x[0], x[1]);
            }
    };
    load(0);
    prod(F, F);
    prod(S, S);
#pragma unroll
    for (int i = 0; i < 8; i++) A[(i >> 2) * 2 + F][i & 3] = badd2(A[(i >> 2) * 2][i & 3], A[(i >> 2) * 2 + 1][i & 3]);
#pragma unroll
    for (int i = 0; i < 16; i++) R[(i >> 2) * 2 + F][i & 3] = badd2(R[(i >> 2) * 2][i & 3], R[(i >> 2) * 2 + 1][i & 3]);
    load(1);
    prod(F, 2);
}
struct DenseTaps {
    uint32_t A[4][4], E[4], F[4], G[4];
    __device__ __forceinline__ DenseTaps(uint32_t pb, uint32_t pz) {
        constexpr int PP = T_PATCH - T_DENSE + 56;
        load_toep(E, pb + 2048, pz + 2048);
        load_toep(F, pb + PP, pz + PP);
        G[0] = lds32(pz + 2048 + 32); G[1] = lds32(pb + 2048 + 64); G[2] = lds32(pz + PP + 32); G[3] = lds32(pb + PP + 64);
    }
};
__device__ __forceinline__ uint32_t dense_phase(float (&acc)[16][4], uint32_t vmin, uint32_t va, uint32_t vo, uint32_t pb, DenseTaps& tp, uint32_t zero) {
    uint32_t R[8][4];
    uint32_t pz = pb + zero;
    {
        uint32_t H[4][4];
#pragma unroll
        for (int i = 0; i < 4; i++) ldsm4(H[i], vo + i * 256);
#pragma unroll
        for (int i = 0; i < 8; i++) ldsm4(R[i], va + i * 128);
#pragma unroll
        for (int i = 0; i < 4; i += 2) load_toep(tp.A[i], pb + 512 * i, pz + 512 * i);
#pragma unroll
        for (int i = 0; i < 4; i++) mma_bf16_k8(acc[i + 4], tp.G[0], tp.G[1], H[i >> 1][2 * (i & 1) + 1]);
#pragma unroll
        for (int i = 0; i < 8; i++) mma_v(acc[i + 8], tp.G, H[i >> 1][2 * (i & 1)], H[i >> 1][2 * (i & 1) + 1]);
#pragma unroll
        for (int i = 0; i < 12; i++) mma_v(acc[i + 4], tp.E, R[i & 7][2 * (i >> 3)], R[i & 7][2 * (i >> 3) + 1]);
#pragma unroll
        for (int i = 0; i < 8; i++) mma_v(acc[i + 8], tp.F, R[i][0], R[i][1]);
    }
    float W[8][4];
#pragma unroll
    for (int i = 0; i < 32; i++) { W[i >> 2][i & 3] = 0.f; if (i >= 8) acc[2 * (i >> 2) + 1][i & 3] += acc[2 * (i >> 2)][i & 3]; }
#pragma unroll 1
    for (int rho = 0; rho < 8; rho += 2) {
        ffa_step<0>(acc, W, R, tp.A, va, vmin, pb, pz);
        ffa_step<1>(acc, W, R, tp.A, va - 16, vmin, pb + 64, pz + 64);
        pb += 128; pz += 128; va -= 32;
    }
#pragma unroll
    for (int i = 0; i < 32; i++) {
        const int m = i >> 2, j = i & 3;
        acc[2 * m + 1][j] = (acc[2 * m + 1][j] - acc[2 * m][j]) - W[m][j];
        if (m) acc[2 * m][j] += W[m - 1][j];
    }
    return __float_as_uint(W[7][0]) & zero;
}
__device__ __forceinline__ uint32_t ones2(int c, int lo, int hi) {
    return (((uint32_t)(c - lo) <= (uint32_t)(hi - lo)) ? 1u : 0u) | (((uint32_t)(c + 1 - lo) <= (uint32_t)(hi - lo)) ? 0x10000u : 0u);
}
__device__ __forceinline__ uint32_t box_bits(int lane) {
    const int d = 2 * (lane & 3) - (lane >> 2);
    auto four = [&](int L1, int H1, int L2, int H2) { return ones2(d, L1, H1) | ones2(d, L2, H2) << 1 | ones2(d + 8, L1, H1) << 2 | ones2(d + 8, L2, H2) << 3; };
    return four(5, 7, 0, 4) | four(1, 7, 0, 8) << 4;
}
struct Boxes {
    uint32_t q[4], ha[2];
    __device__ __forceinline__ Boxes(uint32_t bits, int k0, uint32_t h0, uint32_t h1) {
#pragma unroll
        for (int i = 0; i < 4; i++) q[i] = (bits & (0x10001u << (k0 + i))) * (0x3f80u >> (k0 + i));
        ha[0] = h0; ha[1] = h1;
    }
    __device__ __forceinline__ void load(int j, uint32_t* v, uint32_t zero) const {
        const uint32_t o = j * 128;
        v[0] = lds32(ha[0] + o); v[1] = lds32(ha[1] + zero + o); v[2] = lds32(ha[1] + o);
        v[3] = lds32(ha[0] + zero + o + 16); v[4] = lds32(ha[0] + o + 16); v[5] = lds32(ha[1] + o + 16);
    }
    __device__ __forceinline__ void sums(const uint32_t* v, float* Z, float* X, float* Y) const {
        mma_bf16_z(Z, q[0], q[1], q[2], q[3], v[0], v[1]);
        mma_bf16_z(X, q[0], q[1], q[2], q[3], v[2], v[3]);
        mma_bf16_z(Y, q[0], q[1], q[2], q[3], v[4], v[5]);
    }
};
__host__ __device__ constexpr int tail_step(int n) { return n < 8 ? n : n < 12 ? n + 4 : (n & 1) ? 11 - (n - 13) / 2 : 19 - (n - 12) / 2; }
template <class After>
__device__ __forceinline__ void tail_phase(float (&acc)[16][4], const Boxes& b2, const Boxes& b3, uint32_t tp2, uint32_t tp3, uint32_t zero, After after) {
    uint4 t2[5];
    uint2 t3[8];
    uint32_t v[6], a0[4], a1[4];
    float Z[4], X[4], Y[4];
    b2.load(0, v, zero);
#pragma unroll
    for (int i = 0; i < 5; i++) t2[i] = lds128(tp2 + 160 * i);
#pragma unroll
    for (int n = -1; n < 20; n++) {
        const int j = tail_step(n), j1 = tail_step(n + 1), j2 = tail_step(n + 2);
        if (n < 19) {
            (j1 < 12 ? b2 : b3).sums(v, Z, X, Y);
            if (n < 18) { if (j2 < 12) b2.load(j2, v, zero); else b3.load(j2 - 12, v, zero); }
        }
        if (n >= 0 && j < 12) {
#pragma unroll
            for (int b = 0; b < 5; b++) if (j + 4 + b < 16) mma_v(acc[j + 4 + b], a1, t2[b].z, t2[b].w);
        }
        if (n < 19 && j1 < 12) { a1[0] = pack_v(Z[0], Z[1]); a1[1] = pack_w(X[0], X[1]); a1[2] = pack_v(Z[2], Z[3]); a1[3] = pack_w(X[2], X[3]); }
        if (n == 6) {
#pragma unroll
            for (int b = 0; b < 8; b++) t3[b] = lds64(tp3 + 80 * b);
        }
        if (n >= 0 && j < 12) {
#pragma unroll
            for (int b = 0; b < 5; b++) if (j + 4 + b < 16) mma_v(acc[j + 4 + b], a0, t2[b].x, t2[b].y);
        } else if (n >= 0) {
#pragma unroll
            for (int b = 0; b < 8; b++) if (j - 4 + b < 16) mma_v(acc[j - 4 + b], a0, t3[b].x, t3[b].y);
        }
        if (n < 19) {
            if (j1 < 12) { a0[0] = pack_v(X[0], X[1]); a0[1] = pack_v(Y[0], Y[1]); a0[2] = pack_v(X[2], X[3]); a0[3] = pack_v(Y[2], Y[3]); }
            else { a0[0] = pack_v(X[0], X[1]); a0[1] = pack_v(Y[0], Y[1]); a0[2] = pack_v(Z[2], Z[3]); a0[3] = pack_v(X[2], X[3]); }
        }
        after(n);
    }
}
template <int Q>
__device__ __forceinline__ void emit(const float (&acc)[16][4], int h, uint32_t own, uint32_t peer, uint32_t bar, uint32_t bar_peer) {
    constexpr int n = 4 * Q, G = Q >> 1;
#pragma unroll
    for (int hf = 0; hf < 2; hf++)
        asm volatile("{ .reg .pred p; setp.eq.u32 p, %7, %8;\n\t@p st.shared.v4.u32 [%0], {%1,%2,%3,%4};\n\t"
                     "@!p st.async.weak.shared::cluster.mbarrier::complete_tx::bytes.v4.b32 [%5], {%1,%2,%3,%4}, [%6]; }"
                     ::"r"(own + G * 16384 + hf * 512), "r"(pack_bf16(acc[n][2 * hf], acc[n][2 * hf + 1])), "r"(pack_bf16(acc[n + 1][2 * hf], acc[n + 1][2 * hf + 1])),
                     "r"(pack_bf16(acc[n + 2][2 * hf], acc[n + 2][2 * hf + 1])), "r"(pack_bf16(acc[n + 3][2 * hf], acc[n + 3][2 * hf + 1])),
                     "r"(peer + G * 16384 + hf * 512), "r"(bar_peer + 8 * G), "r"(h), "n"(Q & 1) : "memory");
    __syncwarp();
    if (h == (Q & 1) && elect_one()) mbar_arrive(bar);
}
__device__ __forceinline__ uint32_t finish_src(uint32_t sb, int h, int w, int lane) {
    const int m = lane >> 3, r = lane & 7;
    return sb + OFF_XT + (h ^ 1) * 32768 + (2 * m + (r & 1)) * 1024 + (w >> 2) * 512 + (((8 * (w & 3) + (r & 4) + ((r >> 1) & 1)) ^ ((r & 1) << 1)) << 4);
}
__device__ __forceinline__ uint32_t finish_dst(uint32_t sb, int h, int w, int lane) {
    const int g = lane >> 2, t = lane & 3;
    return sb + OFF_XT + h * 32768 + w * 2048 + (g >> 1) * 512 + (t >> 1) * 144 + (2 * (t & 1) + (g & 1)) * 32;
}
__device__ __forceinline__ uint32_t tile_addr(uint32_t sb, int tok, int t) {
    return sb + OFF_XT + (tok & 512) * 64 + (tok >> 10) * 16384 + (tok & 14) * 1024 + (tok & 448) * 4 + (tok & 1) * 128 + (tok & 48) * 2 + (((t >> 1) ^ (tok & 1)) << 4) + (t & 1) * 8;
}
__device__ __forceinline__ uint2 add_update(uint2 o, uint32_t upd) {
    const float4 u = lds128f(upd);
    return make_uint2(badd2(o.x, pack_bf16(u.x, u.y)), badd2(o.y, pack_bf16(u.z, u.w)));
}
__device__ __forceinline__ void finish_half(uint32_t src, uint32_t xa, const uint4 (&x)[2]) {
    uint32_t s[2][4];
#pragma unroll
    for (int i = 0; i < 2; i++) ldsm4t(s[i], src ^ (i << 5));
#pragma unroll
    for (int i = 0; i < 2; i++) sts128(xa + i * 256, badd2(x[i].x, s[i][0]), badd2(x[i].y, s[i][1]), badd2(x[i].z, s[i][2]), badd2(x[i].w, s[i][3]));
}

__device__ __noinline__ float centred_var(uint32_t rows, float mu, int lane) {
    float var = 0.f;
#pragma unroll 1
    for (int rr = 0; rr < 16; rr++) {
        const float c0 = __shfl_sync(0xffffffffu, mu, rr);
        float c = 0.f;
#pragma unroll 1
        for (int k = 0; k < 16; k++) {
            const uint32_t q = lds32(rows + rr * ROW_PITCH + k * 128 + lane * 4);
            const float d0 = bf_lo(q) - c0, d1 = bf_hi(q) - c0;
            c = fmaf(d0, d0, fmaf(d1, d1, c));
        }
#pragma unroll 1
        for (int o = 16; o; o >>= 1) c += __shfl_xor_sync(0xffffffffu, c, o);
        if ((lane & 15) == rr) var = c * (1.f / DM);
    }
    return var;
}
__device__ __noinline__ float centred_score(uint32_t rows, uint32_t wbuf, uint32_t s0, uint32_t s1, int lane) {
    float sc = 0.f;
#pragma unroll 1
    for (int rr = 0; rr < 16; rr++) {
        const uint32_t t0 = __shfl_sync(0xffffffffu, s0, rr), t1 = __shfl_sync(0xffffffffu, s1, rr);
        float c = 0.f;
#pragma unroll 1
        for (int k = 0; k < 16; k++) {
            const uint32_t xn = normalize2(lds32(rows + rr * ROW_PITCH + k * 128 + lane * 4), t0, t1);
            const uint32_t wq = lds32(wbuf + (k >> 2) * 1024 + (k & 3) * 128 + lane * 4);
            c = fmaf(bf_lo(xn), bf_lo(wq), fmaf(bf_hi(xn), bf_hi(wq), c));
        }
#pragma unroll 1
        for (int o = 16; o; o >>= 1) c += __shfl_xor_sync(0xffffffffu, c, o);
        if ((lane & 15) == rr) sc = c;
    }
    return sc;
}

__device__ __forceinline__ void issue_rows(const __nv_bfloat16* u, uint32_t sb, int b) {
    if (elect_one()) {
        const uint32_t bar = sb + OFF_BAR + 8 * B_ROW;
#pragma unroll
        for (int j = 0; j < 4; j++) mbar_init(bar + 8 * j, 1);
        asm volatile("fence.mbarrier_init.release.cluster;" ::: "memory");
        fence_async();
#pragma unroll 1
        for (int j = 0; j < 4; j++) {
            mbar_expect_tx(bar + 8 * j, 8192);
#pragma unroll
            for (int i = 0; i < 4; i++) bulk_g2s(sb + OFF_VT + (4 * j + i) * ROW_PITCH, u + (size_t)(16 * b + 4 * j + i) * DM, 2048, bar + 8 * j);
        }
    }
    __syncwarp();
}

__global__ void __cluster_dims__(2, 1, 1) __launch_bounds__(NTHR, 1)
fused_kernel(const __grid_constant__ Ptrs p, const __grid_constant__ Maps maps) {
    extern __shared__ __align__(1024) unsigned char smem[];
    const int tid = threadIdx.x, lane = tid & 31;
    const int c_ = ((blockIdx.x >> 1) + 60) & 63, b = 2 * ((c_ & 32) | ((c_ & 7) << 2) | ((c_ >> 3) & 3)) + (blockIdx.x & 1);
    const int dch = 8 * b + (tid >> 5) - 4;
    uint2 la, aim, cre, cim;
    uint32_t ldt16;
    if ((uint32_t)(tid - 128) < 256u) {
        la = ldg64(p.logA + dch * NMODE + 4 * lane); aim = ldg64(p.Aim + dch * NMODE + 4 * lane);
        cre = ldg64(p.Cre + dch * NMODE + 4 * lane); cim = ldg64(p.Cim + dch * NMODE + 4 * lane);
        ldt16 = ldg16(p.ldt + dch);
    }
    const uint32_t sb = s_u32(smem), bar0 = sb + OFF_BAR;
    const int warp = __shfl_sync(0xffffffffu, tid >> 5, 0);
    const int h = b & 1, cl = b >> 1;
    const int m = lane >> 3, r = lane & 7, g = lane >> 2, t = lane & 3;
    const bool has_gu = b < GU_CTAS;
    if (warp == 4) { STAMP(0); GSTAMP(24); }

    if (warp >= 12) {
        asm volatile("setmaxnreg.dec.sync.aligned.u32 24;");
        const int a = warp - 12;
        uint32_t due = now_ns() + ST_T0 + (uint32_t)(2 * a + h) * (ST_PER / 2) + (has_gu ? 0 : 12 * ST_PER + 4 * ST_PER2);
        const bool el = elect_one();
        if (a == 1) issue_rows(p.u, sb, b);
        if (a == 2 && el) {
#pragma unroll
            for (int i = B_XT; i < NBAR; i++) mbar_init(bar0 + 8 * i, (i == B_V || i == B_SFREE || i == B_XFREE || i == B_OWN) ? 8 : i == B_RECV ? 9 : i == B_RED ? 5 : (i == B_UPD || (i >= B_FREE && i < B_FULL)) ? 4 : 1);
            asm volatile("fence.mbarrier_init.release.cluster;" ::: "memory");
            fence_async();
            mbar_expect_tx(bar0 + 8 * B_XT, 65536);
            mbar_expect_tx(bar0 + 8 * B_RECV, 8192);
            mbar_expect_tx(bar0 + 8 * B_RECV + 8, 8192);
            mbar_expect_tx(bar0 + 8 * B_RED, 2048);
        }
        if (a == 3 && el) {
#pragma unroll
            for (int i = 0; i < 5; i++) asm volatile("prefetch.tensormap [%0];" ::"l"(&maps.u + i) : "memory");
        }
        __syncwarp();
        cluster_arrive();
        cluster_wait();
        STAMP(18);
        mbar_wait(bar0 + 8 * (B_ROW + a), 0);
        if (el) {
#pragma unroll
            for (int i = 0; i < 4; i++)
                tma_load_tile(sb + OFF_XT + h * 32768 + a * 4096 + (i & 1) * 16384 + (i >> 1) * 2048, &maps.u, 16 * cl, 4 * a + (i & 2), 16 * (i & 1) + 8 * h, bar0 + 8 * B_XT);
        }
        if (el) {
#pragma unroll 1
            for (int k = has_gu ? 0 : 4; k < 6; k++) {
                const int i = 4 * k + a, s = k < 3 ? i : i - 12;
                sleep_until(due);
                due += k < 3 ? 4 * ST_PER : 4 * ST_PER2;
                const bool again = k >= 3 && has_gu;
                if (s >= 6 || again) mbar_wait(bar0 + 8 * (s < 10 || again ? B_FREE + s : B_V), slot_priv(s) && again);
                const uint32_t dst = sb + slot_off(s), bar = bar0 + 8 * (B_FULL + s);
                if (k < 4) {
                    mbar_expect_tx(bar, 8192);
                    tma_load_2d(dst, &maps.wg, 64 * cl, 512 * h + 32 * i, bar);
                    tma_load_2d(dst + 4096, &maps.wu, 64 * cl, 512 * h + 32 * i, bar);
                } else {
                    mbar_expect_tx(bar, 7168);
                    tma_load_perm(dst, &maps.wd, 16 * cl, 56 * h + 14 * a + 7 * (k & 1), bar);
                }
            }
            STAMP(19);
        }
        __syncwarp();
        {
            const uint32_t fs = finish_src(sb, h, 2 * a, lane), fx = finish_dst(sb, h, 2 * a, lane);
            mbar_wait(bar0 + 8 * B_RECV, 0);
#pragma unroll 1
            for (int k = 0; k < 2; k++) {
#pragma unroll
                for (int q = 0; q < 2; q++) {
                    const uint32_t xa = (fx ^ (q << 4)) + k * 2048;
                    const uint4 x[2] = {lds128(xa), lds128(xa + 256)};
                    finish_half(fs + q * 8192 + k * 128, xa, x);
                }
                fence_async();
                __syncwarp();
                if (el) tma_store_tile(&maps.out, sb + OFF_XT + h * 32768 + (2 * a + k) * 2048, 16 * cl, 4 * a + 2 * k, 8 * h);
            }
            if (h) STAMP(59); else STAMP(20);
            const int tok = 2047 - (int)(lds32(sb + OFF_MISC + 48 + 8 * g) & 2047);
            const bool mine = (((tok >> 7) & 12) | ((tok >> 2) & 3)) == 4 * h + a;
            if (el) asm volatile("cp.async.bulk.wait_group 0;" ::: "memory");
            if (__any_sync(0xffffffffu, mine)) {
                const uint2 o0 = lds64(tile_addr(sb, tok, t));
                mbar_wait(bar0 + 8 * B_UPD, 0);
                const uint2 o1 = add_update(o0, sb + tab_off(g) + T_RED + 16 * t);
                if (mine) *reinterpret_cast<uint2*>(p.out + (size_t)tok * DM + 16 * cl + 4 * t) = o1;
            } else STAMP(62);
        }
    } else if (warp >= 4) {
        const int w = warp - 4;
        uint32_t dsk16 = ldg16(p.dsk + dch);
        cluster_arrive();
        asm volatile("setmaxnreg.inc.sync.aligned.u32 176;");
        const uint32_t vrow = sb + OFF_VT + w * VT_PITCH + VT_PAD, tab = sb + tab_off(w);
        const uint32_t rb0 = bar0 + 8 * B_RECV, rb1 = mapa(rb0, h ^ 1);
        uint32_t tpo = 80 + (g - 2 * t) * 8 - (g < 2 * t ? 16 : 0);
        uint32_t xa = sb + OFF_XT + (w & 2) * 16384 + (w >> 2) * 16384 + (w & 1) * 1024 + (g >> 1) * 2048 + (g & 1) * 128 + t * 32 + ((h ^ (g & 1)) << 4);
        uint32_t va = sb + OFF_VT + (2 * m + (r & 1)) * VT_PITCH + VT_PAD + (16 * w + (r >> 1)) * 16;
        uint32_t qa = sb + OFF_ST + 2048 * w + 128 * t + 16 * (g ^ (2 * t));
        uint32_t vmin = vrow + (m & 1) * VT_PLANE - 16, vd = vmin + 16 + (m >> 1) * 1024 + r * 16;
        uint32_t vo = vrow + VT_PLANE + 496 - (m & 1) * 512 + (m >> 1) * 128 + r * 16, vz = vrow - VT_PAD + (lane >> 1) * VT_PLANE + (lane & 1) * 16;
        pin(vmin); pin(vd); pin(vo); pin(vz);
        pin(tpo); pin(xa); pin(va); pin(qa);
        uint32_t bits = box_bits(lane), h0 = vrow + 16 * g + tok_off(2 * t - 18), h1 = vrow + 16 * g + tok_off(2 * t - 10);
        pin(bits); pin(h0); pin(h1);
        const KgenAddr ka(sb + OFF_PRIV + w * 8192, lane);
        if (__any_sync(0xffffffffu, (vmin | (vd | vo | vz) | (tpo | xa) | (va | qa) | (bits | h0 | h1) | ka.any()) & p.zero)) __trap();
        cluster_wait();
        pin(la.x); pin(la.y); pin(aim.x); pin(aim.y); pin(cre.x); pin(cre.y); pin(cim.x); pin(cim.y); pin(ldt16); pin(dsk16);
        uint4 x[8];
        auto load_x = [&]() {
            mbar_wait(bar0 + 8 * B_XT, 0);
#pragma unroll
            for (int i = 0; i < 8; i++) x[i] = lds128(xa + (i & 1) * 8192 + (i >> 1) * 256);
        };
        kgen(ka, tab, lane, la, aim, cre, cim, bf_round(ex2f(bf_lo(ldt16) * 1.4426950408889634f)), 1.f + bf_lo(dsk16), dch, [&]() {
            STAMP(21);
            if (elect_one()) mbar_arrive_n(bar0 + 8 * (B_FREE + 6 + ((w >> 1) ^ 2)), 2);
        }, [&]() {
            if ((LN_PAUSE >> w) & 1) mbar_wait(bar0 + 8 * B_LN, 0);
        });
        STAMP(1);
        const uint32_t pb = tab + T_DENSE + (g - 2 * t) * 4;
        DenseTaps dt(pb, pb + p.zero);
        {
            load_x();
            STAMP(47);
            mbar_wait(bar0 + 8 * (B_ST + (w >> 1)), 0);
            uint4 q[4];
#pragma unroll
            for (int n = 0; n < 4; n++) q[n] = lds128(qa + 512 * n);
            if (lane < 4) sts128(vz, 0, 0, 0, 0);
            STAMP(2); GSTAMP(28);
#pragma unroll
            for (int i = 0; i < 8; i++) {
                const uint32_t s0 = (i & 1) ? q[i >> 1].z : q[i >> 1].x, s1 = (i & 1) ? q[i >> 1].w : q[i >> 1].y;
                stsm4t(va + (i >> 1) * 64 + (i & 1) * VT_PLANE, normalize2(x[i].x, s0, s1), normalize2(x[i].y, s0, s1),
                       normalize2(x[i].z, s0, s1), normalize2(x[i].w, s0, s1));
            }
            __syncwarp();
            if (elect_one()) mbar_arrive(bar0 + 8 * B_V);
        }
        mbar_wait(bar0 + 8 * B_V, 0);
        STAMP(3);
        float acc[16][4];
#pragma unroll
        for (int i = 0; i < 16; i++) { acc[i][0] = acc[i][1] = acc[i][2] = acc[i][3] = 0.f; }
        bits |= dense_phase(acc, vmin, vd, vo, pb, dt, p.zero);
        const Boxes b2(bits, 0, h0, h1), b3(bits, 4, (t == 1 ? h1 : h0) - 4, t == 1 ? h0 + 12 : h1 - 4);
        STAMP(4);
        const uint32_t so = sb + OFF_XT + (8 * h + w) * 1024 + ((lane ^ ((w & 1) << 1)) << 4);
        const uint32_t dst0 = so + (h ^ 1) * 32768, dst1 = mapa(so + h * 32768, h ^ 1);
        tail_phase(acc, b2, b3, tab + T_R2 + 2 * tpo, tab + T_R3 + tpo, p.zero, [&](int j) {
            if (j == -1) {
                mbar_wait(bar0 + 8 * B_SFREE, 0);
                emit<0>(acc, h, dst0, dst1, rb0, rb1);
            }
            if (j == 3) { emit<1>(acc, h, dst0, dst1, rb0, rb1); STAMP(5); }
            if (j == 11) {
                mbar_wait(bar0 + 8 * B_XFREE, 0);
                emit<2>(acc, h, dst0, dst1, bar0 + 8 * B_OWN, rb1);
                STAMP(58);
            }
        });
        emit<3>(acc, h, dst0, dst1, bar0 + 8 * B_OWN, rb1);
        STAMP(30);
        const uint32_t fs = finish_src(sb, h, w, lane) + 16384 + h * 8192, fx = (finish_dst(sb, h, w, lane) + 16384) ^ (h << 4);
        const int tok = 2047 - (int)(lds32(sb + OFF_MISC + 48 + 8 * g) & 2047);
        const bool mine = (((tok >> 6) & 24) | ((tok >> 1) & 7)) == 16 + 8 * h + w;
        const uint32_t ta = tile_addr(sb, tok, t);
        const uint4 x0[2] = {lds128(fx), lds128(fx + 256)}, x1[2] = {lds128(fx ^ 16), lds128((fx ^ 16) + 256)};
        mbar_wait(bar0 + 8 * B_OWN, 0);
        finish_half(fs, fx, x0);
        mbar_wait(bar0 + 8 * (B_RECV + 1), 0);
        STAMP(6);
        finish_half(fs + (h ? -8192 : 8192), fx ^ 16, x1);
        __syncwarp();
        if (__any_sync(0xffffffffu, mine)) {
            const uint2 o0 = lds64(ta);
            mbar_wait(bar0 + 8 * B_UPD, 0);
            const uint2 o1 = add_update(o0, sb + tab_off(g) + T_RED + 16 * t);
            if (mine) sts64(ta, o1.x, o1.y);
        }
        fence_async();
        __syncwarp();
        if (elect_one()) {
            tma_store_tile(&maps.out, sb + OFF_XT + h * 32768 + 16384 + w * 2048, 16 * cl, 2 * w, 16 + 8 * h);
            asm volatile("cp.async.bulk.wait_group.read 0;" ::: "memory");
        }
        STAMP(7);
    } else {
        const int a = warp;
        const uint4 wq = ldg128(p.wr + 8 * tid);
        const uint32_t epoch = ld_relaxed_32(&p.sc[a].cnt[b & 96]) >> 5;
        cluster_arrive();
        asm volatile("setmaxnreg.inc.sync.aligned.u32 136;");
        const uint32_t tag = __shfl_sync(0xffffffffu, epoch, 0) + 1u, misc = sb + OFF_MISC, abar = bar0 + 8 * (B_AUX + a);
        uint32_t aph = 0;
        const Exchange* in = &p.sc[cl & (NREP - 1)];
        uint2* pub = p.sc[m >> 1].stat + 16 * b + 2 * (r ^ (2 * (b & 3))) + (m & 1);
        uint32_t* cnt_s = &p.sc[t].cnt[b & 96];
        pin(pub); pin(cnt_s);
        if (tid < 64) sts32(sb + OFF_XCH + 4 * tid, 0);
        const uint32_t wbuf = sb + OFF_LN + a * 1024, part = sb + OFF_LN + 4096;
        {
            sts128(wbuf + 16 * lane, wq.x, wq.y, wq.z, wq.w);
            sts128(wbuf + 512 + 16 * lane, 0x3f803f80u, 0x3f803f80u, 0x3f803f80u, 0x3f803f80u);
            float wsum = ((bf_lo(wq.x) + bf_hi(wq.x)) + (bf_lo(wq.y) + bf_hi(wq.y))) + ((bf_lo(wq.z) + bf_hi(wq.z)) + (bf_lo(wq.w) + bf_hi(wq.w)));
#pragma unroll
            for (int o = 16; o; o >>= 1) wsum += __shfl_xor_sync(0xffffffffu, wsum, o);
            sts32f(part + 1024 + 4 * a, wsum);
            uint32_t wf[4][4];
#pragma unroll
            for (int i = 0; i < 4; i++) ldsm4(wf[i], wbuf + ((uint32_t)(r - 1) < 2u ? 16 * (r - 1) : 512) + 32 * m + 128 * i);
            uint32_t ra = sb + OFF_VT + r * ROW_PITCH + 512 * a + 16 * m, pa = part + a * 256 + g * 16;
            cluster_wait();
            STAMP(22);
#pragma unroll 1
            for (int hf = 0; hf < 2; hf++) {
                mbar_wait(bar0 + 8 * B_ROW + 16 * hf, 0);
                mbar_wait(bar0 + 8 * B_ROW + 16 * hf + 8, 0);
                STAMP(23);
                uint32_t x[8][4];
                float cs[2][4], q[8][4];
#pragma unroll
                for (int i = 0; i < 40; i++) (i < 8 ? cs[i >> 2 & 1] : q[(i - 8) >> 2 & 7])[i & 3] = 0.f;
#pragma unroll
                for (int k = 0; k < 8; k++) ldsm4(x[k], ra + k * 64);
                const bool more = __any_sync(0xffffffffu, after_all(x, p.zero));
#pragma unroll 1
                do {
#pragma unroll
                    for (int k = 0; k < 8; k++) {
                        mma_v(cs[k & 1], x[k], wf[k >> 1][2 * (k & 1)], wf[k >> 1][2 * (k & 1) + 1]);
#pragma unroll
                        for (int i = 0; i < 4; i++) mma_bf16_k8(q[4 * (k & 1) + i], x[k][i & 2], x[k][i | 1], x[k][i]);
                    }
                } while (more);
                const float c2 = cs[0][2] + cs[1][2];
                if (t == 0) sts64f(pa, (cs[0][0] + cs[1][0]) + c2, cs[0][1] + cs[1][1]);
                if (t == 1) sts32f(pa + 12, c2);
                const float e0 = ((q[0][0] + q[2][0]) + (q[4][0] + q[6][0])) + ((q[1][2] + q[3][2]) + (q[5][2] + q[7][2]));
                const float e1 = ((q[0][1] + q[2][1]) + (q[4][1] + q[6][1])) + ((q[1][3] + q[3][3]) + (q[5][3] + q[7][3]));
                if (t == (g >> 1)) sts32f(pa + 8, (g & 1) ? e1 : e0);
                ra += 8 * ROW_PITCH; pa += 128;
            }
        }
        STAMP(31);
        named_sync(1, 128);
        if (a == 0) {
            const uint32_t pa = part + (lane & 15) * 16;
            const float4 p0 = lds128f(pa), p1 = lds128f(pa + 256), p2 = lds128f(pa + 512), p3 = lds128f(pa + 768), ws = lds128f(part + 1024);
            const float mu = ((p0.x + p1.x) + (p2.x + p3.x)) * (1.f / DM);
            float var = ((p0.z + p1.z) + (p2.z + p3.z)) * (1.f / DM) - mu * mu;
            const bool centred = __any_sync(0xffffffffu, !(mu * mu <= 4.f * var));
            if (centred) var = centred_var(sb + OFF_VT, mu, lane);
            const float ri = rcpf(bf_round(sqrtaf(bf_round(bf_round(var) + 1e-5f))));
            const uint32_t s0 = pack_bf16(mu, ri), s1 = (pack_bf16(ri - bf_hi(s0), 0.f) & 0xfffcu) | (tag & 3);
            float sc = ((((p0.y + p1.y) + (p2.y + p3.y)) + ((p0.w + p1.w) + (p2.w + p3.w))) - bf_lo(s0) * ((ws.x + ws.y) + (ws.z + ws.w))) * ri;
            if (centred) sc = centred_score(sb + OFF_VT, sb + OFF_LN, s0, s1, lane);
            const uint32_t sb16 = pack_bf16(0.f, sc);
            const uint32_t s2 = s1 | (sb16 ^ (((uint32_t)((int)sb16 >> 31) & 0x7fff0000u) | 0x80000000u));
            st_relaxed_64(pub, s0, s2);
            st_relaxed_64(pub + 2 * sizeof(Exchange) / 8, s0, s2);
            if (lane < NREP) red_add(cnt_s, 1);
            if (elect_one()) mbar_arrive(bar0 + 8 * B_LN);
            STAMP(9); GSTAMP(25);
        }
        const uint32_t slot0 = sb + OFF_RING + a * 8192, slot1 = sb + slot_off(4 + a), slot2 = sb + slot_off(8 + a), fbar = bar0 + 8 * (B_FULL + a);
        uint32_t mine = 0, row[2] = {0, 0};
        {
            uint32_t q[16];
            named_sync(1, 128);
            wait_count(&in->cnt[32 * a], 32 * tag - FEW_ST);
            STAMP(41);
#pragma unroll 1
            for (uint32_t it = 0;; spin_guard(it)) {
                if (elect_one()) {
                    mbar_expect_tx(abar, 4096);
                    bulk_g2s(sb + OFF_ST + 4096 * a, in->stat + 512 * a, 4096, abar);
                }
                mbar_wait(abar, aph);
                aph ^= 1;
                uint32_t bad = 0;
#pragma unroll
                for (int n = 0; n < 8; n++) {
                    const uint4 u = lds128v(sb + OFF_ST + 4096 * a + 512 * n + 16 * lane);
                    q[2 * n] = u.y; q[2 * n + 1] = u.w;
                    bad = or_xor(bad, u.y, tag);
                }
                const bool ok = __all_sync(0xffffffffu, (bad & 3) == 0);
                asm volatile("{ .reg .pred p; setp.ne.u32 p, %1, 0; @p mbarrier.arrive.shared::cta.b64 _, [%0]; }" ::"r"(bar0 + 8 * (B_ST + a)), "r"((uint32_t)(ok && lane == 0)) : "memory");
                if (ok) break;
            }
            STAMP(8);
            const uint32_t inv = 2047 - 512 * a - 16 * m - (r ^ (2 * m));
#pragma unroll
            for (int i = 0; i < 16; i++) asm("lop3.b32 %0, %0, %1, %2, 0x9b;" : "+r"(q[i]) : "r"(inv), "r"(0xffff0000u | (64 * (i >> 1) + 8 * (i & 1))));
            auto below = [&](uint32_t x) {
                uint32_t d[4];
#pragma unroll
                for (int i = 0; i < 16; i++) d[i & 3] = i < 4 ? x + q[i] : min(d[i & 3], x + q[i]);
                d[0] = min(min(d[0], d[1]), min(d[2], d[3]));
                return d[0] < x ? x - 1 - d[0] : 0u;
            };
            const uint32_t mx0 = ~min(min(min(min(q[0], q[1]), min(q[2], q[3])), min(min(q[4], q[5]), min(q[6], q[7]))),
                                      min(min(min(q[8], q[9]), min(q[10], q[11])), min(min(q[12], q[13]), min(q[14], q[15]))));
            const uint32_t gm = min(__reduce_max_sync(0xffffffffu, lane < 16 ? mx0 : 0u), __reduce_max_sync(0xffffffffu, lane < 16 ? 0u : mx0));
            if (lane == 0) sts32(misc + 16 + 4 * a, gm);
            named_sync(1, 128);
            STAMP(42);
            const uint4 t0 = lds128(misc + 16);
            uint32_t tau = min(min(t0.x, t0.y), min(t0.z, t0.w));
            uint32_t mx = mx0, cnt = 0, bal;
            const uint32_t list = sb + OFF_XCH + 64 * a;
#pragma unroll 1
            while ((bal = __ballot_sync(0xffffffffu, mx >= tau)) != 0) {
                const uint32_t pos = cnt + __popc(bal & ((1u << lane) - 1u));
                cnt += __popc(bal);
                if (cnt > 16) break;
                if (mx >= tau) sts32(list + 4 * pos, mx);
                mx = below(mx);
            }
            if (cnt > 16) {
                mx = mx0;
#pragma unroll 1
                for (int j = 0; j < 8; j++) {
                    const uint32_t top = __reduce_max_sync(0xffffffffu, mx), nx = below(mx);
                    if (mx == top) { sts32(list + 4 * j, mx); sts32(list + 32 + 4 * j, 0); mx = nx; }
                }
            }
            named_sync(1, 128);
            STAMP(43);
            const uint2 k = lds64(sb + OFF_XCH + 8 * lane);
            uint32_t hi = max(k.x, k.y), lo = min(k.x, k.y);
            mbar_wait(bar0 + 8 * B_V, 0);
#pragma unroll
            for (int j = 0; j < 8; j++) {
                const uint32_t top = __reduce_max_sync(0xffffffffu, hi);
                const bool won = hi == top;
                hi = won ? lo : hi;
                lo = won ? 0u : lo;
                if (g == j) mine = top;
                if (a == (j >> 1)) row[j & 1] = top;
            }
        }
        STAMP(11);
        const int tok = 2047 - (int)(mine & 2047);
        const uint32_t xs = sb + OFF_XT + (h ^ 1) * 32768 + 16384;
        if (has_gu) {
            if (elect_one()) {
                mbar_expect_tx(abar, 2048);
#pragma unroll
                for (int j = 0; j < 2; j++) bulk_g2s(xs + (2 * a + j) * 1040, p.u + (size_t)(2047 - (row[j] & 2047)) * DM + 512 * h, 1024, abar);
            }
        }
        STAMP(44);
        const uint2 st = ld_relaxed_64(in->stat + (tok & ~15) + 2 * ((tok & 7) ^ ((tok >> 3) & 6)) + ((tok >> 3) & 1));
        if (a == 0 && t == 0) sts64(misc + 48 + 8 * g, mine, __float_as_uint(bf_hi(st.x) + bf_lo(st.y)));
        if (a == 0) STAMP(45);
        if (has_gu) {
            const uint32_t mean = __shfl_sync(0xffffffffu, st.x, 8 * a + 4 * (lane >> 4)), xr = xs + (2 * a + (lane >> 4)) * 1040 + 16 * (lane & 15);
            mbar_wait(abar, aph);
            aph ^= 1;
            STAMP(46);
            uint4 x[4];
#pragma unroll
            for (int j = 0; j < 4; j++) x[j] = lds128(xr + 256 * j);
#pragma unroll
            for (int j = 0; j < 4; j++) sts128(xr + 256 * j, bsub2_lo(x[j].x, mean), bsub2_lo(x[j].y, mean), bsub2_lo(x[j].z, mean), bsub2_lo(x[j].w, mean));
            if (elect_one()) mbar_expect_tx(abar, 512);
            named_sync(1, 128);
        }
        if (lane < (has_gu ? 2 : 4)) mbar_arrive_peer(mapa(bar0 + 8 * (lane & 2 ? B_XFREE : B_SFREE), lane & 1));
        if (has_gu) {
            STAMP(12);
            float gacc[8][4];
#pragma unroll
            for (int i = 0; i < 8; i++) { gacc[i][0] = gacc[i][1] = gacc[i][2] = gacc[i][3] = 0.f; }
            uint32_t* pubh = reinterpret_cast<uint32_t*>(&p.sc[0].h[b * 32 + 8 * a + (g ^ (2 * a))]) + t;
            uint32_t* cnt_h = &p.sc[t].cnt[32 * (b / 28) + 1 + ((b / 14) & 1)];
            uint32_t ko = sb + (m & 1) * 4096 + (r + ((m >> 1) << 3)) * 128 + ((r ^ (4 * h) ^ a) << 4), kp = ko ^ 64, xb = xs + r * 1040 + m * 16;
            uint32_t xch = sb + OFF_XCH + 16 * tid, tagm = t == 3 ? 1u : 0u;
            pin(pubh); pin(cnt_h); pin(ko); pin(kp); pin(xb); pin(xch); pin(tagm);
            const float r0 = lds32f(misc + 52 + 16 * t), r1 = lds32f(misc + 60 + 16 * t);
#pragma unroll
            for (int c = 0; c < 4; c++) {
                uint32_t af[20][4];
#pragma unroll
                for (int j = 0; j < 4; j++) ldsm4(af[16 + j], xb + 256 * c + 64 * j);
                if (c == 3) mbar_wait(bar0 + 8 * B_SFREE, 0);
#pragma unroll
                for (int j = 0; j < 4; j++) {
                    mbar_wait(bar0 + 8 * (B_FULL + 4 * (c % 3) + j), c / 3);
#pragma unroll
                    for (int i = 0; i < 4; i++) ldsm4t(af[8 * (i >> 1) + 2 * j + (i & 1)], ((i & 1) ? kp : ko) + slot_off(4 * (c % 3) + j) + (i >> 1) * 2048);
                }
                STAMP(36 + c);
                __syncwarp();
                if (c < 3 && lane < 4) mbar_arrive(bar0 + 8 * (B_FREE + 4 * c + lane));
                const bool more = __any_sync(0xffffffffu, (af[6][3] | af[7][3] | af[14][3] | af[15][3]) & p.zero);
#pragma unroll 1
                do {
#pragma unroll
                    for (int i = 0; i < 16; i++) mma_v(gacc[i & 7], af[i], af[16 + ((i >> 1) & 3)][2 * (i >> 3)], af[16 + ((i >> 1) & 3)][2 * (i >> 3) + 1]);
                } while (more);
            }
            STAMP(13);
            float own[4], oth[4];
#pragma unroll
            for (int j = 0; j < 4; j++) oth[j] = (gacc[1][j] + gacc[3][j]) + (gacc[5][j] + gacc[7][j]);
            st_async128(mapa(xch, h ^ 1), __float_as_uint(oth[0]), __float_as_uint(oth[1]), __float_as_uint(oth[2]), __float_as_uint(oth[3]), mapa(abar, h ^ 1));
            STAMP(56);
#pragma unroll
            for (int j = 0; j < 4; j++) own[j] = ((gacc[0][j] + gacc[2][j]) + (gacc[4][j] + gacc[6][j])) * ((j & 1) ? r1 : r0);
            mbar_wait(abar, aph);
            aph ^= 1;
            STAMP(57);
            const float4 o4 = lds128f(xch);
            const float g0 = bf_round(fmaf(o4.x, r0, own[0])), g1 = bf_round(fmaf(o4.y, r1, own[1]));
            const float h0 = bf_round(g0 * rcpf(1.f + ex2f(-1.4426950408889634f * g0))) * bf_round(fmaf(o4.z, r0, own[2]));
            const float h1 = bf_round(g1 * rcpf(1.f + ex2f(-1.4426950408889634f * g1))) * bf_round(fmaf(o4.w, r1, own[3]));
            uint32_t hw;
            asm volatile("movmatrix.sync.aligned.m8n8.trans.b16 %0, %1;" : "=r"(hw) : "r"(pack_bf16(h0, h1)));
            hw = (hw & ~tagm) | (tag & tagm);
#pragma unroll
            for (int j = 0; j < NREP; j++) st_relaxed_32(pubh + j * (sizeof(Exchange) / 4), hw);
            if (lane < NREP) red_add(cnt_h, b % 14 < 2 ? 2 : 1);
            if (lane < 2) mbar_arrive_peer(mapa(bar0 + 8 * B_XFREE, lane));
            named_sync(1, 128);
            STAMP(14);
        }
        float dacc[4];
        const int tk = ((tid >> 1) & 6) | (tid & 1);
        uint32_t ro = 4 * tid, red = sb + tab_off(tk) + T_RED + 4 * ((tid >> 4) + 4 * (tid & 2));
        if (!has_gu) named_sync(1, 128);
        const float sg = bf_round(rcpf(1.f + ex2f(-1.4426950408889634f * __uint_as_float(unorder_key(lds32(misc + 48 + 8 * tk) >> 16) << 16))));
        pin(ro); pin(red);
        mbar_wait(bar0 + 8 * B_XFREE, 0);
        {
            uint32_t wo = (r + ((m >> 1) << 3)) * 32 + (((m & 1) ^ (r >> 2)) << 4), af[14][4];
            uint32_t ho = slot0 + 128 * t + 16 * (g ^ (2 * t));
            pin(wo); pin(ho);
            float d[7][4];
#pragma unroll
            for (int i = 0; i < 7; i++) { d[i][0] = d[i][1] = d[i][2] = d[i][3] = 0.f; }
            auto first_half = [&]() {
                mbar_wait(fbar + 32, has_gu);
#pragma unroll
                for (int j = 0; j < 14; j++) ldsm4t(af[j], slot1 + wo + j * 512);
            };
            auto fetch = [&]() {
                if (elect_one()) {
                    mbar_expect_tx(abar, 7168);
                    bulk_g2s(slot0, &in->h[(56 * h + 14 * a) * 32], 7168, abar);
                }
            };
            wait_count(&in->cnt[64 * h + 32 * (a >> 1) + 1 + (a & 1)], 64 * tag - FEW_H);
            STAMP(33);
            fetch();
            first_half();
            mbar_wait(abar, aph);
#pragma unroll
            for (int s = 0; s < 2; s++) {
                if (s) {
                    mbar_wait(fbar + 64, has_gu);
#pragma unroll
                    for (int j = 0; j < 14; j++) ldsm4t(af[j], slot2 + wo + j * 512);
                }
                uint4 hq[7];
#pragma unroll 1
                for (uint32_t it = 0;; spin_guard(it)) {
                    uint32_t bad = 0;
#pragma unroll
                    for (int j = 0; j < 7; j++) { hq[j] = lds128(ho + 512 * (7 * s + j)); bad = or_xor(bad, hq[j].w, tag); }
                    if (__all_sync(0xffffffffu, (bad & 1) == 0)) break;
                    fetch();
                    aph ^= 1;
                    mbar_wait(abar, aph);
                }
                if (s == 0) STAMP(15);
#pragma unroll
                for (int j = 0; j < 14; j++) {
                    const uint4 q = hq[j >> 1];
                    mma_v(d[j % 7], af[j], (j & 1) ? q.z : q.x, (j & 1) ? q.w : q.y);
                }
            }
#pragma unroll
            for (int j = 0; j < 4; j++) dacc[j] = ((d[0][j] + d[1][j]) + (d[2][j] + d[3][j])) + ((d[4][j] + d[5][j]) + d[6][j]);
        }
        STAMP(16);
        {
            st_async128(mapa(sb + OFF_XCH + 16 * tid, h ^ 1), __float_as_uint(dacc[0]), __float_as_uint(dacc[1]), __float_as_uint(dacc[2]), __float_as_uint(dacc[3]),
                        mapa(bar0 + 8 * B_RED, h ^ 1));
            sts128f(slot0 + 7680 + lane * 16, dacc);
            __syncwarp();
            if (elect_one()) mbar_arrive(bar0 + 8 * B_RED);
            mbar_wait(bar0 + 8 * B_RED, 0);
            const uint32_t b0 = sb + OFF_RING + 7680 + ro, b1 = sb + OFF_XCH + ro;
            const float y = ((lds32f(b0) + lds32f(b0 + 8192)) + (lds32f(b0 + 16384) + lds32f(b0 + 24576))) +
                            ((lds32f(b1) + lds32f(b1 + 512)) + (lds32f(b1 + 1024) + lds32f(b1 + 1536)));
            sts32f(red, bf_round(y) * sg);
            __syncwarp();
            if (elect_one()) mbar_arrive(bar0 + 8 * B_UPD);
        }
        STAMP(17); GSTAMP(29);
    }
}

typedef CUresult (*EncodeFn)(CUtensorMap*, CUtensorMapDataType, cuuint32_t, void*, const cuuint64_t*, const cuuint64_t*,
                             const cuuint32_t*, const cuuint32_t*, CUtensorMapInterleave, CUtensorMapSwizzle,
                             CUtensorMapL2promotion, CUtensorMapFloatOOBfill);

void make_map(EncodeFn enc, CUtensorMap* m, const void* ptr, uint64_t cols, uint64_t rows, uint32_t bc, uint32_t br,
              CUtensorMapSwizzle sw, CUtensorMapL2promotion pr) {
    cuuint64_t dims[2] = {cols, rows};
    cuuint64_t str[1] = {cols * 2};
    cuuint32_t box[2] = {bc, br};
    cuuint32_t es[2] = {1, 1};
    enc(m, CU_TENSOR_MAP_DATA_TYPE_BFLOAT16, 2, const_cast<void*>(ptr), dims, str, box, es, CU_TENSOR_MAP_INTERLEAVE_NONE, sw, pr,
        CU_TENSOR_MAP_FLOAT_OOB_FILL_NONE);
}
void make_perm_map(EncodeFn enc, CUtensorMap* m, const void* ptr, CUtensorMapL2promotion pr) {
    cuuint64_t dims[5] = {DM, 2, 4, 4, FF / 32};
    cuuint64_t str[4] = {DM * 2, 8 * DM * 2, 2 * DM * 2, 32 * DM * 2};
    cuuint32_t box[5] = {16, 2, 4, 4, 7};
    cuuint32_t es[5] = {1, 1, 1, 1, 1};
    enc(m, CU_TENSOR_MAP_DATA_TYPE_BFLOAT16, 5, const_cast<void*>(ptr), dims, str, box, es, CU_TENSOR_MAP_INTERLEAVE_NONE,
        CU_TENSOR_MAP_SWIZZLE_32B, pr, CU_TENSOR_MAP_FLOAT_OOB_FILL_NONE);
}
void make_tile_map(EncodeFn enc, CUtensorMap* m, const void* ptr) {
    cuuint64_t dims[4] = {DM, 4, 16, SEQ / 64};
    cuuint64_t str[3] = {16 * DM * 2, DM * 2, 64 * DM * 2};
    cuuint32_t box[4] = {16, 4, 2, 8};
    cuuint32_t es[4] = {1, 1, 1, 1};
    enc(m, CU_TENSOR_MAP_DATA_TYPE_BFLOAT16, 4, const_cast<void*>(ptr), dims, str, box, es, CU_TENSOR_MAP_INTERLEAVE_NONE,
        CU_TENSOR_MAP_SWIZZLE_32B, CU_TENSOR_MAP_L2_PROMOTION_NONE, CU_TENSOR_MAP_FLOAT_OOB_FILL_NONE);
}

}

extern "C" void kernel_launch(void* const* d_in, const int* in_sizes, int n_in, void* d_out, int out_size) {
    (void)in_sizes; (void)n_in; (void)out_size;
    static EncodeFn enc = nullptr;
    static void* scratch = nullptr;
    if (!enc) {
        void* fn = nullptr;
        cudaDriverEntryPointQueryResult q;
        cudaGetDriverEntryPoint("cuTensorMapEncodeTiled", &fn, cudaEnableDefault, &q);
        enc = (EncodeFn)fn;
        cudaGetSymbolAddress(&scratch, g_scratch);
        cudaFuncSetAttribute(fused_kernel, cudaFuncAttributeMaxDynamicSharedMemorySize, SMEM_BYTES);
    }
    Maps maps;
    make_tile_map(enc, &maps.u, d_in[0]);
    make_tile_map(enc, &maps.out, d_out);
    make_map(enc, &maps.wg, d_in[9], FF, DM, 64, 32, CU_TENSOR_MAP_SWIZZLE_128B, CU_TENSOR_MAP_L2_PROMOTION_L2_128B);
    make_map(enc, &maps.wu, d_in[10], FF, DM, 64, 32, CU_TENSOR_MAP_SWIZZLE_128B, CU_TENSOR_MAP_L2_PROMOTION_L2_128B);
    make_perm_map(enc, &maps.wd, d_in[11], CU_TENSOR_MAP_L2_PROMOTION_L2_64B);
    Ptrs p;
    p.sc = (Exchange*)scratch;
    p.u = (const __nv_bfloat16*)d_in[0];
    p.logA = (const __nv_bfloat16*)d_in[1];
    p.Aim = (const __nv_bfloat16*)d_in[2];
    p.Cre = (const __nv_bfloat16*)d_in[3];
    p.Cim = (const __nv_bfloat16*)d_in[4];
    p.ldt = (const __nv_bfloat16*)d_in[5];
    p.dsk = (const __nv_bfloat16*)d_in[6];
    p.wr = (const __nv_bfloat16*)d_in[8];
    p.out = (__nv_bfloat16*)d_out;
    p.zero = 0;
    fused_kernel<<<NCTA, NTHR, SMEM_BYTES, cudaStreamPerThread>>>(p, maps);
}
```

```cpp
#include <cuda_runtime.h>
#include <cuda_bf16.h>
#include <cuda_fp16.h>
#include <cuda.h>
#include <stdint.h>

namespace {

constexpr int SEQ = 2048, DM = 1024, NMODE = 128, FF = 3584;
constexpr int NCTA = 128, NTHR = 512;
constexpr int GU_CTAS = 112;
constexpr int NREP = 4;

constexpr int OFF_XT = 0;
constexpr int OFF_RING = 65536;
constexpr int OFF_PRIV = OFF_RING + 65536;
constexpr int OFF_VT = OFF_PRIV + 65536;
constexpr int VT_PAD = 32, VT_PLANE = VT_PAD + 2048, VT_PITCH = 2 * VT_PLANE, ROW_PITCH = 2064;
constexpr int OFF_BAR = OFF_VT + 8 * VT_PITCH;
constexpr int OFF_MISC = OFF_BAR + 384;
constexpr int OFF_XCH = OFF_MISC + 112;
constexpr int SMEM_BYTES = OFF_XCH + 2048;
constexpr int OFF_LN = OFF_RING + 7 * 8192;
constexpr int OFF_ST = OFF_RING + 6 * 8192;
static_assert(SMEM_BYTES <= 232448, "shared memory");

constexpr int B_ROW = 0, B_XT = 4, B_V = 5, B_LN = 6, B_SFREE = 7, B_RECV = 8, B_RED = 10, B_UPD = 11, B_ST = 12, B_XFREE = 16, B_OWN = 17, B_FREE = 20, B_FULL = 32, B_AUX = 44, NBAR = 48;

constexpr int T_DENSE = 60;
constexpr int T_PATCH = 2208;
constexpr int T_R2 = 2368;
constexpr int T_R3 = 3296;

constexpr int T_RED = 4032;
__device__ __forceinline__ bool slot_priv(int s) { return (uint32_t)(s - 6) < 4u; }
__device__ __forceinline__ uint32_t slot_off(int s) { return slot_priv(s) ? OFF_PRIV + 4096 + (s & 3) * 16384 : OFF_RING + (s < 6 ? s : s - 4) * 8192; }
__device__ __forceinline__ uint32_t tab_off(int w) { return OFF_PRIV + w * 8192 + (w & 1) * 4096; }

constexpr uint32_t SPIN_LIMIT = 1u << 20;
#define BB_UNROLL 2
constexpr int kBbUnroll = BB_UNROLL;
#define ST_T0 2250
#define ST_PER 294
#define ST_PER2 320
#define LN_PAUSE 0xf0
#define FEW_ST 10
#define FEW_H 24

struct Exchange {
    uint2 stat[SEQ];
    uint4 h[GU_CTAS * 32];
    uint32_t cnt[4 * 32];
};
__device__ __align__(128) Exchange g_scratch[NREP];

struct Ptrs {
    const __nv_bfloat16 *logA, *Aim, *Cre, *Cim, *ldt, *u;
    const __nv_bfloat16 *dsk, *wr;
    Exchange* sc;
    __nv_bfloat16* out;
    uint32_t zero;
};
struct Maps {
    CUtensorMap u, out, wg, wu, wd;
};

#define STAMP(i) do { } while (0)
#define GSTAMP(i) do { } while (0)

__device__ __forceinline__ uint32_t s_u32(const void* p) { return (uint32_t)__cvta_generic_to_shared(p); }
__device__ __forceinline__ void mbar_init(uint32_t b, uint32_t n) {
    asm volatile("mbarrier.init.shared::cta.b64 [%0], %1;" ::"r"(b), "r"(n) : "memory");
}
__device__ __forceinline__ void mbar_expect_tx(uint32_t b, uint32_t bytes) {
    asm volatile("mbarrier.arrive.expect_tx.shared::cta.b64 _, [%0], %1;" ::"r"(b), "r"(bytes) : "memory");
}
__device__ __forceinline__ void mbar_arrive(uint32_t b) {
    asm volatile("mbarrier.arrive.shared::cta.b64 _, [%0];" ::"r"(b) : "memory");
}
__device__ __forceinline__ void mbar_arrive_n(uint32_t b, uint32_t n) {
    asm volatile("mbarrier.arrive.shared::cta.b64 _, [%0], %1;" ::"r"(b), "r"(n) : "memory");
}
__device__ __forceinline__ void mbar_arrive_peer(uint32_t b_cluster) {
    asm volatile("mbarrier.arrive.relaxed.cluster.shared::cluster.b64 _, [%0];" ::"r"(b_cluster) : "memory");
}
__device__ __forceinline__ void mbar_wait(uint32_t b, uint32_t parity) {
    asm volatile("{\n\t.reg .pred p;\n\t.reg .u32 c;\n\tmov.u32 c, 0;\n"
                 "W:\n\tmbarrier.try_wait.parity.shared::cta.b64 p, [%0], %1;\n\t@p bra D;\n\t"
                 "add.u32 c, c, 1;\n\tsetp.lt.u32 p, c, 1048576;\n\t@p bra W;\n\ttrap;\nD:\n\t}"
                 ::"r"(b), "r"(parity) : "memory");
}
__device__ __forceinline__ bool elect_one() {
    uint32_t p;
    asm volatile("{ .reg .pred P; elect.sync _|P, 0xffffffff; selp.u32 %0, 1, 0, P; }" : "=r"(p));
    return p != 0;
}
__device__ __forceinline__ uint32_t mapa(uint32_t a, uint32_t rank) {
    uint32_t r;
    asm("mapa.shared::cluster.u32 %0, %1, %2;" : "=r"(r) : "r"(a), "r"(rank));
    return r;
}
__device__ __forceinline__ void cluster_arrive() { asm volatile("barrier.cluster.arrive.relaxed.aligned;" ::: "memory"); }
__device__ __forceinline__ void cluster_wait() { asm volatile("barrier.cluster.wait.acquire.aligned;" ::: "memory"); }
__device__ __forceinline__ void tma_load_2d(uint32_t dst, const CUtensorMap* m, int c0, int c1, uint32_t bar) {
    asm volatile("cp.async.bulk.tensor.2d.shared::cluster.global.mbarrier::complete_tx::bytes [%0], [%1, {%3, %4}], [%2];"
                 ::"r"(dst), "l"(m), "r"(bar), "r"(c0), "r"(c1) : "memory");
}
__device__ __forceinline__ void tma_load_perm(uint32_t dst, const CUtensorMap* m, int c0, int blk, uint32_t bar) {
    asm volatile("cp.async.bulk.tensor.5d.shared::cluster.global.mbarrier::complete_tx::bytes [%0], [%1, {%3, %4, %4, %4, %5}], [%2];"
                 ::"r"(dst), "l"(m), "r"(bar), "r"(c0), "r"(0), "r"(blk) : "memory");
}
__device__ __forceinline__ void tma_load_tile(uint32_t dst, const CUtensorMap* m, int c0, int c2, int c3, uint32_t bar) {
    asm volatile("cp.async.bulk.tensor.4d.shared::cluster.global.mbarrier::complete_tx::bytes.multicast::cluster [%0], [%1, {%3, %4, %5, %6}], [%2], %7;"
                 ::"r"(dst), "l"(m), "r"(bar), "r"(c0), "r"(0), "r"(c2), "r"(c3), "h"((uint16_t)3) : "memory");
}
__device__ __forceinline__ void tma_store_tile(const CUtensorMap* m, uint32_t src, int c0, int c2, int c3) {
    asm volatile("cp.async.bulk.tensor.4d.global.shared::cta.bulk_group [%0, {%2, %3, %4, %5}], [%1];"
                 ::"l"(m), "r"(src), "r"(c0), "r"(0), "r"(c2), "r"(c3) : "memory");
    asm volatile("cp.async.bulk.commit_group;" ::: "memory");
}
__device__ __forceinline__ void bulk_g2s(uint32_t dst, const void* src, uint32_t bytes, uint32_t bar) {
    asm volatile("cp.async.bulk.shared::cluster.global.mbarrier::complete_tx::bytes [%0], [%1], %2, [%3];"
                 ::"r"(dst), "l"(src), "r"(bytes), "r"(bar) : "memory");
}
__device__ __forceinline__ void st_async128(uint32_t dst_cluster, uint32_t x, uint32_t y, uint32_t z, uint32_t w, uint32_t bar_cluster) {
    asm volatile("st.async.weak.shared::cluster.mbarrier::complete_tx::bytes.v4.b32 [%0], {%1,%2,%3,%4}, [%5];"
                 ::"r"(dst_cluster), "r"(x), "r"(y), "r"(z), "r"(w), "r"(bar_cluster) : "memory");
}
__device__ __forceinline__ void fence_async() { asm volatile("fence.proxy.async.shared::cta;" ::: "memory"); }
__device__ __forceinline__ void named_sync(int id, int n) { asm volatile("bar.sync %0, %1;" ::"r"(id), "r"(n) : "memory"); }

__device__ __forceinline__ void ldsm4(uint32_t* r, uint32_t a) {
    asm volatile("ldmatrix.sync.aligned.m8n8.x4.shared.b16 {%0,%1,%2,%3}, [%4];"
                 : "=r"(r[0]), "=r"(r[1]), "=r"(r[2]), "=r"(r[3]) : "r"(a));
}
__device__ __forceinline__ void ldsm4t(uint32_t* r, uint32_t a) {
    asm volatile("ldmatrix.sync.aligned.m8n8.x4.trans.shared.b16 {%0,%1,%2,%3}, [%4];"
                 : "=r"(r[0]), "=r"(r[1]), "=r"(r[2]), "=r"(r[3]) : "r"(a));
}
__device__ __forceinline__ void stsm4t(uint32_t a, uint32_t x, uint32_t y, uint32_t z, uint32_t w) {
    asm volatile("stmatrix.sync.aligned.m8n8.x4.trans.shared.b16 [%0], {%1,%2,%3,%4};"
                 ::"r"(a), "r"(x), "r"(y), "r"(z), "r"(w) : "memory");
}
__device__ __forceinline__ uint32_t lds32(uint32_t a) { uint32_t v; asm volatile("ld.shared.u32 %0, [%1];" : "=r"(v) : "r"(a)); return v; }
__device__ __forceinline__ float lds32f(uint32_t a) { float v; asm volatile("ld.shared.f32 %0, [%1];" : "=f"(v) : "r"(a)); return v; }
__device__ __forceinline__ uint2 lds64(uint32_t a) { uint2 v; asm volatile("ld.shared.v2.u32 {%0,%1}, [%2];" : "=r"(v.x), "=r"(v.y) : "r"(a)); return v; }
__device__ __forceinline__ uint4 lds128(uint32_t a) {
    uint4 v; asm volatile("ld.shared.v4.u32 {%0,%1,%2,%3}, [%4];" : "=r"(v.x), "=r"(v.y), "=r"(v.z), "=r"(v.w) : "r"(a)); return v;
}
__device__ __forceinline__ uint4 lds128v(uint32_t a) {
    uint4 v; asm volatile("ld.volatile.shared.v4.u32 {%0,%1,%2,%3}, [%4];" : "=r"(v.x), "=r"(v.y), "=r"(v.z), "=r"(v.w) : "r"(a)); return v;
}
__device__ __forceinline__ uint32_t or_xor(uint32_t a, uint32_t b, uint32_t c) {
    uint32_t r; asm("lop3.b32 %0, %1, %2, %3, 0xf6;" : "=r"(r) : "r"(a), "r"(b), "r"(c)); return r;
}
__device__ __forceinline__ float4 lds128f(uint32_t a) {
    float4 v; asm volatile("ld.shared.v4.f32 {%0,%1,%2,%3}, [%4];" : "=f"(v.x), "=f"(v.y), "=f"(v.z), "=f"(v.w) : "r"(a)); return v;
}
__device__ __forceinline__ void sts32(uint32_t a, uint32_t v) { asm volatile("st.shared.u32 [%0], %1;" ::"r"(a), "r"(v) : "memory"); }
__device__ __forceinline__ void sts32f(uint32_t a, float v) { asm volatile("st.shared.f32 [%0], %1;" ::"r"(a), "f"(v) : "memory"); }
__device__ __forceinline__ void sts64(uint32_t a, uint32_t x, uint32_t y) { asm volatile("st.shared.v2.u32 [%0], {%1,%2};" ::"r"(a), "r"(x), "r"(y) : "memory"); }
__device__ __forceinline__ void sts64f(uint32_t a, float x, float y) { asm volatile("st.shared.v2.f32 [%0], {%1,%2};" ::"r"(a), "f"(x), "f"(y) : "memory"); }
__device__ __forceinline__ void sts128(uint32_t a, uint32_t x, uint32_t y, uint32_t z, uint32_t w) {
    asm volatile("st.shared.v4.u32 [%0], {%1,%2,%3,%4};" ::"r"(a), "r"(x), "r"(y), "r"(z), "r"(w) : "memory");
}
__device__ __forceinline__ void sts128f(uint32_t a, const float* v) {
    asm volatile("st.shared.v4.f32 [%0], {%1,%2,%3,%4};" ::"r"(a), "f"(v[0]), "f"(v[1]), "f"(v[2]), "f"(v[3]) : "memory");
}
__device__ __forceinline__ uint4 ldg128(const void* p) {
    uint4 v; asm volatile("ld.global.nc.L1::no_allocate.v4.u32 {%0,%1,%2,%3}, [%4];" : "=r"(v.x), "=r"(v.y), "=r"(v.z), "=r"(v.w) : "l"(p)); return v;
}
__device__ __forceinline__ uint2 ldg64(const void* p) {
    uint2 v; asm volatile("ld.global.nc.L1::no_allocate.v2.u32 {%0,%1}, [%2];" : "=r"(v.x), "=r"(v.y) : "l"(p)); return v;
}
__device__ __forceinline__ uint32_t ldg16(const void* p) {
    uint32_t v; asm volatile("ld.global.nc.u16 %0, [%1];" : "=r"(v) : "l"(p)); return v;
}
__device__ __forceinline__ uint2 ld_relaxed_64(const void* p) {
    uint2 v; asm volatile("ld.relaxed.gpu.global.v2.u32 {%0,%1}, [%2];" : "=r"(v.x), "=r"(v.y) : "l"(p) : "memory"); return v;
}
__device__ __forceinline__ uint32_t ld_relaxed_32(const void* p) {
    uint32_t v; asm volatile("ld.relaxed.gpu.global.u32 %0, [%1];" : "=r"(v) : "l"(p) : "memory"); return v;
}
__device__ __forceinline__ void st_relaxed_64(void* p, uint32_t x, uint32_t y) {
    asm volatile("st.relaxed.gpu.global.v2.u32 [%0], {%1,%2};" ::"l"(p), "r"(x), "r"(y) : "memory");
}
__device__ __forceinline__ void st_relaxed_32(void* p, uint32_t v) {
    asm volatile("st.relaxed.gpu.global.u32 [%0], %1;" ::"l"(p), "r"(v) : "memory");
}
__device__ __forceinline__ void red_add(void* p, uint32_t v) { asm volatile("red.relaxed.gpu.global.add.u32 [%0], %1;" ::"l"(p), "r"(v) : "memory"); }
__device__ __forceinline__ uint32_t now_ns() { uint32_t t; asm volatile("mov.u32 %0, %%globaltimer_lo;" : "=r"(t) :: "memory"); return t; }
__device__ __forceinline__ void sleep_until(uint32_t t) {
#pragma unroll 1
    for (int left; (left = (int)(t - now_ns())) > 0;) __nanosleep(left >> 1);
}
__device__ __forceinline__ void spin_guard(uint32_t& it) { if (++it > SPIN_LIMIT) __trap(); }
__device__ __forceinline__ void wait_count(const uint32_t* p, uint32_t target) {
#pragma unroll 1
    for (uint32_t it = 0; __any_sync(0xffffffffu, (int)(ld_relaxed_32(p) - target) < 0); spin_guard(it)) { }
}
__device__ __forceinline__ void mma_bf16_k8(float* c, uint32_t a0, uint32_t a1, uint32_t b0) {
    asm("mma.sync.aligned.m16n8k8.row.col.f32.bf16.bf16.f32 {%0,%1,%2,%3}, {%4,%5}, {%6}, {%0,%1,%2,%3};"
                 : "+f"(c[0]), "+f"(c[1]), "+f"(c[2]), "+f"(c[3]) : "r"(a0), "r"(a1), "r"(b0));
}
__device__ __forceinline__ void mma_v(float* c, const uint32_t* a, uint32_t b0, uint32_t b1) {
    asm volatile("mma.sync.aligned.m16n8k16.row.col.f32.bf16.bf16.f32 {%0,%1,%2,%3}, {%4,%5,%6,%7}, {%8,%9}, {%0,%1,%2,%3};"
                 : "+f"(c[0]), "+f"(c[1]), "+f"(c[2]), "+f"(c[3]) : "r"(a[0]), "r"(a[1]), "r"(a[2]), "r"(a[3]), "r"(b0), "r"(b1));
}
__device__ __forceinline__ void mma_bf16_z(float* c, uint32_t a0, uint32_t a1, uint32_t a2, uint32_t a3, uint32_t b0, uint32_t b1) {
    asm volatile("mma.sync.aligned.m16n8k16.row.col.f32.bf16.bf16.f32 {%0,%1,%2,%3}, {%4,%5,%6,%7}, {%8,%9}, {%10,%10,%10,%10};"
        : "=f"(c[0]), "=f"(c[1]), "=f"(c[2]), "=f"(c[3]) : "r"(a0), "r"(a1), "r"(a2), "r"(a3), "r"(b0), "r"(b1), "f"(0.f));
}
__device__ __forceinline__ void mma_f16(float* c, uint32_t a0, uint32_t a1, uint32_t a2, uint32_t a3, uint32_t b0, uint32_t b1) {
    asm("mma.sync.aligned.m16n8k16.row.col.f32.f16.f16.f32 {%0,%1,%2,%3}, {%4,%5,%6,%7}, {%8,%9}, {%0,%1,%2,%3};"
                 : "+f"(c[0]), "+f"(c[1]), "+f"(c[2]), "+f"(c[3]) : "r"(a0), "r"(a1), "r"(a2), "r"(a3), "r"(b0), "r"(b1));
}
__device__ __forceinline__ uint32_t pack_bf16(float lo, float hi) {
    uint32_t r; asm("cvt.rn.bf16x2.f32 %0, %1, %2;" : "=r"(r) : "f"(hi), "f"(lo)); return r;
}
__device__ __forceinline__ uint32_t pack_v(float lo, float hi) {
    uint32_t r; asm volatile("cvt.rn.bf16x2.f32 %0, %1, %2;" : "=r"(r) : "f"(hi), "f"(lo)); return r;
}
__device__ __forceinline__ uint32_t pack_w(float lo, float hi) {
    uint32_t r; asm volatile("cvt.rn.satfinite.bf16x2.f32 %0, %1, %2;" : "=r"(r) : "f"(hi), "f"(lo)); return r;
}
template <int N> __device__ __forceinline__ uint32_t after_all(const uint32_t (&f)[N][4], uint32_t zero) {
    uint32_t d[3] = {0, 0, 0};
#pragma unroll
    for (int i = 0; i < N; i++) d[i % 3] |= f[i][3];
    return (d[0] | d[1] | d[2]) & zero;
}
__device__ __forceinline__ void pin(uint32_t& x) { asm volatile("" : "+r"(x)); }
template <class T> __device__ __forceinline__ void pin(T*& x) { asm volatile("" : "+l"(x)); }
__device__ __forceinline__ uint32_t pack_f16(float lo, float hi) {
    uint32_t r; asm("cvt.rn.f16x2.f32 %0, %1, %2;" : "=r"(r) : "f"(hi), "f"(lo)); return r;
}
__device__ __forceinline__ float bf_lo(uint32_t v) { return __uint_as_float(v << 16); }
__device__ __forceinline__ float bf_hi(uint32_t v) { return __uint_as_float(v & 0xffff0000u); }
__device__ __forceinline__ float bf_round(float x) { return __uint_as_float(pack_bf16(0.f, x)); }
__device__ __forceinline__ uint32_t badd2(uint32_t a, uint32_t b) { uint32_t r; asm("add.rn.bf16x2 %0, %1, %2;" : "=r"(r) : "r"(a), "r"(b)); return r; }
__device__ __forceinline__ uint32_t bsub2_lo(uint32_t a, uint32_t b) {
    uint32_t r; asm("{ .reg .b16 m, h; .reg .b32 m2; mov.b32 {m, h}, %2; mov.b32 m2, {m, m}; sub.rn.bf16x2 %0, %1, m2; }" : "=r"(r) : "r"(a), "r"(b)); return r;
}
__device__ __forceinline__ uint32_t bmax2(uint32_t a, uint32_t b) { uint32_t r; asm("max.bf16x2 %0, %1, %2;" : "=r"(r) : "r"(a), "r"(b)); return r; }
__device__ __forceinline__ uint32_t normalize2(uint32_t x, uint32_t s0, uint32_t s1) {
    uint32_t r;
    asm("{ .reg .b16 m, h, l, k; .reg .b32 m2, h2, l2, d, t;\n\t"
        "mov.b32 {m, h}, %2; mov.b32 {l, k}, %3; mov.b32 m2, {m, m}; mov.b32 h2, {h, h}; mov.b32 l2, {l, l};\n\t"
        "sub.rn.bf16x2 d, %1, m2; mul.rn.bf16x2 t, d, l2; fma.rn.bf16x2 %0, d, h2, t; }" : "=r"(r) : "r"(x), "r"(s0), "r"(s1));
    return r;
}
__device__ __forceinline__ float rcpf(float x) { float r; asm("rcp.approx.ftz.f32 %0, %1;" : "=f"(r) : "f"(x)); return r; }
__device__ __forceinline__ float sqrtaf(float x) { float r; asm("sqrt.approx.ftz.f32 %0, %1;" : "=f"(r) : "f"(x)); return r; }
__device__ __forceinline__ float ex2f(float x) { float r; asm("ex2.approx.ftz.f32 %0, %1;" : "=f"(r) : "f"(x)); return r; }

__device__ __forceinline__ int tok_off(int t) { return ((t >> 3) & 1) * VT_PLANE + (t >> 4) * 16 + (t & 7) * 2; }

__device__ __forceinline__ uint32_t unorder_key(uint32_t k16) { return k16 ^ ((k16 & 0x8000u) ? 0x8000u : 0xffffu); }

struct cplx { float r, i; };
struct hc { uint32_t r, i; };
template <bool CONJ> __device__ __forceinline__ cplx csq(cplx a) {
    float im;
    asm("{ .reg .f32 t; mul.ftz.f32 t, %1, %2; mul.ftz.f32 %0, t, 0f40000000; }" : "=f"(im) : "f"(CONJ ? -a.r : a.r), "f"(a.i));
    return {fmaf(a.r, a.r, -(a.i * a.i)), im};
}
__device__ __forceinline__ cplx cexpp(float a2, float ai) {
    float m = ex2f(a2), s, c;
    __sincosf(ai, &s, &c);
    return {m * c, m * s};
}
__device__ __forceinline__ __half2 as_h2(uint32_t x) { return *reinterpret_cast<__half2*>(&x); }
__device__ __forceinline__ uint32_t as_u(__half2 x) { return *reinterpret_cast<uint32_t*>(&x); }
__device__ __forceinline__ hc hmul(hc a, hc b) {
    return {as_u(__hfma2(as_h2(a.r), as_h2(b.r), __hneg2(__hmul2(as_h2(a.i), as_h2(b.i))))),
            as_u(__hfma2(as_h2(a.r), as_h2(b.i), __hmul2(as_h2(a.i), as_h2(b.r))))};
}
__device__ __forceinline__ hc hpack(cplx a, cplx b) { return {pack_f16(a.r, b.r), pack_f16(a.i, b.i)}; }
__device__ __forceinline__ void sts16(uint32_t a, uint32_t v) { asm volatile("st.shared.u16 [%0], %1;" ::"r"(a), "r"(v) : "memory"); }

struct KgenAddr {
    uint32_t l, h, m2, m3, m4, z, w, wz;
    __device__ __forceinline__ KgenAddr(uint32_t scr, int lane) {
        const int g = lane >> 2, t = lane & 3;
        const uint32_t rec = scr + t * 480;
        l = rec + 16 * g; h = rec + 128 + 8 * g; m2 = rec + 192 + 8 * (g & 1); m3 = rec + 208 + 4 * (g & 2); m4 = rec + 224 + 2 * (g & 4);
        z = scr + 7680 + 16 * t; w = scr + 240 * lane; wz = scr + 7680 + 8 * lane;
        pin(l); pin(h); pin(m2); pin(m3); pin(m4); pin(z); pin(w); pin(wz);
    }
    __device__ __forceinline__ uint32_t any() const { return (l | h | m2) | (m3 | m4 | z) | (w | wz); }
};
template <class Hook, class Hook2>
__device__ __forceinline__ void kgen(const KgenAddr& ad, uint32_t tab, int lane, uint2 la, uint2 aim, uint2 cre, uint2 cim, float dt, float skip, int dch, Hook main_done, Hook2 half_done) {
    const int g = lane >> 2, t = lane & 3;
    const float dt2 = 2.f * dt;
    const uint32_t am = bmax2(bmax2(cre.x & 0x7fff7fffu, cre.y & 0x7fff7fffu), bmax2(cim.x & 0x7fff7fffu, cim.y & 0x7fff7fffu));
    const float mx = dt2 * fmaxf(bf_lo(am), bf_hi(am));
    const uint32_t eb = min(max(__reduce_max_sync(0xffffffffu, __float_as_uint(mx)) >> 23, 1u), 252u);
    const float cscale = dt2 * __uint_as_float((253u - eb) << 23);
    const float scale_inv = __uint_as_float((eb + 1u) << 23);
    float k0 = (bf_lo(cre.x) + bf_hi(cre.x)) + (bf_lo(cre.y) + bf_hi(cre.y));
#pragma unroll
    for (int o = 16; o; o >>= 1) k0 += __shfl_xor_sync(0xffffffffu, k0, o);
    const float ndt = -1.4426950408889634f * dt;
    STAMP(40);

    float acc[5][4];
#pragma unroll
    for (int i = 0; i < 5; i++) { acc[i][0] = acc[i][1] = acc[i][2] = acc[i][3] = 0.f; }

#pragma unroll kBbUnroll
    for (int bb = 0; bb < 2; bb++) {
        cplx z[2][11], cz[2];
#pragma unroll
        for (int e = 0; e < 2; e++) {
            const float lg = e ? bf_hi(la.x) : bf_lo(la.x), ai = (e ? bf_hi(aim.x) : bf_lo(aim.x)) * dt;
            const float cr = (e ? bf_hi(cre.x) : bf_lo(cre.x)) * cscale, ci = (e ? bf_hi(cim.x) : bf_lo(cim.x)) * cscale;
            const float a2 = bf_round(ex2f(lg * 1.4426950408889634f)) * ndt;
            z[e][0] = cexpp(a2, ai);
            z[e][5] = cexpp(a2 * 32.f, ai * -32.f);
#pragma unroll
            for (int i = 1; i < 11; i++) if (i != 5) z[e][i] = (i == 3 || i == 7) ? csq<true>(z[e][i - 1]) : csq<false>(z[e][i - 1]);
            cz[e] = {fmaf(cr, z[e][0].r, -(ci * z[e][0].i)), fmaf(cr, z[e][0].i, ci * z[e][0].r)};
        }
        la.x = la.y; aim.x = aim.y; cre.x = cre.y; cim.x = cim.y;
        const hc z1 = hpack(z[0][0], z[1][0]), z2 = hpack(z[0][1], z[1][1]), z4 = hpack(z[0][2], z[1][2]);
        hc L[8], H[8];
        L[1] = hpack(z[0][3], z[1][3]); L[2] = hpack(z[0][4], z[1][4]); L[4] = hpack(z[0][5], z[1][5]);
        const hc y64 = hpack(z[0][6], z[1][6]), z128 = hpack(z[0][7], z[1][7]), z256 = hpack(z[0][8], z[1][8]);
        const hc z512 = hpack(z[0][9], z[1][9]), z1024 = hpack(z[0][10], z[1][10]);
        H[0] = hpack(cz[0], cz[1]);
        H[1] = hmul(H[0], z1); H[2] = hmul(H[0], z2); H[3] = hmul(H[1], z2);
        L[3] = hmul(L[1], L[2]);
#pragma unroll
        for (int i = 0; i < 4; i++) { H[4 + i] = hmul(H[i], z4); if (i) L[4 + i] = hmul(L[i], L[4]); }
        __syncwarp();
        sts128(ad.w, 0x3c003c00u, y64.r, 0u, y64.i);
#pragma unroll
        for (int i = 1; i < 8; i++) { const hc q = hmul(L[i], y64); sts128(ad.w + 16 * i, L[i].r, q.r, L[i].i, q.i); }
#pragma unroll
        for (int i = 0; i < 4; i++) sts128(ad.w + 128 + 16 * i, H[2 * i].r, H[2 * i].i, H[2 * i + 1].r, H[2 * i + 1].i);
        {
            const hc a = hmul(z256, z1), b = hmul(z256, z128), c = hmul(z256, z2), d = hmul(z512, z4);
            sts128(ad.w + 192, a.r, a.i, b.r, b.i);
            sts128(ad.w + 208, c.r, c.i, z512.r, z512.i);
            sts128(ad.w + 224, d.r, d.i, z1024.r, z1024.i);
            sts64(ad.wz, z128.r, z128.i);
        }
        __syncwarp();

#pragma unroll
        for (int k2 = 0; k2 < 4; k2++) {
#pragma unroll
            for (uint32_t s = 0; s < 2; s++) {
                const uint32_t o = k2 * 1920 + s * 240;
                const uint4 l = lds128(ad.l + o);
                const uint2 h0 = lds64(ad.h + o), m2 = lds64(ad.m2 + o), m3 = lds64(ad.m3 + o), m4 = lds64(ad.m4 + o), mz = lds64(ad.z + k2 * 64 + s * 8);
                const hc H0 = {h0.x, h0.y};
                const hc H1 = hmul(H0, {mz.x, mz.y}), H2 = hmul(H0, {m2.x, m2.y}), H3 = hmul(H2, {m3.x, m3.y}), H4 = hmul(H3, {m4.x, m4.y});
                mma_f16(acc[0], l.x, l.y, l.z, l.w, H0.r, H0.i);
                mma_f16(acc[1], l.x, l.y, l.z, l.w, H1.r, H1.i);
                mma_f16(acc[2], l.x, l.y, l.z, l.w, H2.r, H2.i);
                mma_f16(acc[3], l.x, l.y, l.z, l.w, H3.r, H3.i);
                mma_f16(acc[4], l.x, l.y, l.z, l.w, H4.r, H4.i);
            }
        }

        if (bb == 0) half_done();
    }
    __syncwarp();
    main_done();

#pragma unroll
    for (int i = 0; i < 4; i++) sts128(tab + 2048 + 512 * i + 16 * lane, 0, 0, 0, 0);
    if (lane < 15) sts32(tab + 4 * lane, 0);
    __syncwarp();
    const uint32_t d0 = tab + T_DENSE + 4 + 8 * lane, src = (lane + 31) & 31;
    const uint32_t p0 = pack_bf16(fmaf(k0, dt2, skip), 0.f);
    uint32_t prev = p0;
#pragma unroll
    for (int i = 0; i < 4; i++) {
        const uint32_t pk = pack_bf16(acc[i >> 1][2 * (i & 1) + 1] * scale_inv, acc[i >> 1][2 * (i & 1)] * scale_inv);
        sts64(d0 + 256 * i, __byte_perm(pk, __shfl_sync(0xffffffffu, lane == 31 ? prev : pk, src), 0x5432), pk);
        prev = pk;
    }
    const uint32_t w0 = pack_bf16(acc[2][0] * scale_inv, acc[2][1] * scale_inv), w1 = pack_bf16(acc[2][2] * scale_inv, acc[2][3] * scale_inv);
    const uint32_t sa = (lane & 1) ? 0x5410u : 0x5454u, sb2 = (lane & 1) ? 0x1010u : 0x5410u;
#pragma unroll
    for (int hf = 0; hf < 2; hf++) {
        const uint32_t w = hf ? w1 : w0;
        const uint32_t pv = __shfl_sync(0xffffffffu, lane != 31 ? w : hf ? w0 : __byte_perm(prev, w1, 0x5410), src);
        sts64(d0 + 1024 + 256 * hf, __byte_perm(w, pv, sa), __byte_perm(w, pv, sb2));
        sts64(d0 + 1536 + 256 * hf, __byte_perm(w, pv, sa + 0x2222u), __byte_perm(w, pv, sb2 + 0x2222u));
    }
    const uint32_t d3 = tab + T_R2 + 160 + 320 * (t & 1) + 16 * (g >> 1) + 8 * (g & 1) + 4 * (t >> 1), d3n = d3 + (g >= 6 ? 32 : 0);
    const uint32_t d4 = tab + T_R3 + 80 + 160 * t + 4 * g, d4n = d4 + (g >= 6 ? 16 : 0);
    uint32_t p3;
#pragma unroll
    for (int hf = 0; hf < 2; hf++)
#pragma unroll
        for (int e = 0; e < 2; e++) {
            const float v3 = acc[3][2 * hf + e] * scale_inv;
            const uint32_t p4 = pack_bf16(acc[4][2 * hf + e] * scale_inv, 0.f);
            p3 = pack_bf16(v3, v3);
            sts16(d3 + 64 * hf + 160 * e, p3);
            sts16((hf ? d3n : d3) + 64 * hf + 160 * e + 18, p3);
            sts16(d4 + 32 * hf + 80 * e, p4);
            sts16((hf ? d4n : d4) + 32 * hf + 80 * e + 10, p4);
        }
    if (lane == 31) {
        const uint32_t k512 = __byte_perm(w1, 0, 0x3232);
        sts32(tab + T_DENSE, p0);
        sts64(tab + T_DENSE + 4 * 513, k512, k512); sts16(tab + T_DENSE + 4 * 515 + 2, k512);
        sts16(tab + T_PATCH + 4 * 17, p3); sts32(tab + T_PATCH + 4 * 18, p3); sts16(tab + T_PATCH + 4 * 19 + 2, p3);
    }
    __syncwarp();
}

__device__ __forceinline__ void load_toep(uint32_t* a, uint32_t p, uint32_t pz) {
    a[0] = lds32(p); a[1] = lds32(p + 32); a[2] = lds32(pz - 32); a[3] = lds32(pz);
}
template <int F>
__device__ __forceinline__ void ffa_step(float (&acc)[16][4], float (&W)[8][4], uint32_t (&R)[8][4], uint32_t (&A)[4][4],
                                         uint32_t va, uint32_t vmin, uint32_t pb, uint32_t pz) {
    constexpr int S = F ^ 1;
    auto load = [&](int sh) {
#pragma unroll
        for (int i = S; i < 8; i += 2) ldsm4(R[i], i == 0 ? max(va - 16 * sh, vmin) : va - 16 * sh + i * 128);
#pragma unroll
        for (int k = S; k < 4; k += 2) load_toep(A[k], pb + 64 * sh + k * 512, pz + 64 * sh + k * 512);
    };
    auto prod = [&](int par, int dst) {
#pragma unroll
        for (int k = 0; k < 2; k++)
#pragma unroll
            for (int m = k; m < 8; m++) {
                const uint32_t* x = &R[2 * ((m - k) & 3) + par][2 * ((m - k) >> 2)];
                mma_v(dst == 1 ? W[m] : acc[2 * m + (dst >> 1)], A[2 * k + par], x[0], x[1]);
            }
    };
    load(0);
    prod(F, F);
    prod(S, S);
#pragma unroll
    for (int i = 0; i < 8; i++) A[(i >> 2) * 2 + F][i & 3] = badd2(A[(i >> 2) * 2][i & 3], A[(i >> 2) * 2 + 1][i & 3]);
#pragma unroll
    for (int i = 0; i < 16; i++) R[(i >> 2) * 2 + F][i & 3] = badd2(R[(i >> 2) * 2][i & 3], R[(i >> 2) * 2 + 1][i & 3]);
    load(1);
    prod(F, 2);
}
struct DenseTaps {
    uint32_t A[4][4], E[4], F[4], G[4];
    __device__ __forceinline__ DenseTaps(uint32_t pb, uint32_t pz) {
        constexpr int PP = T_PATCH - T_DENSE + 56;
        load_toep(E, pb + 2048, pz + 2048);
        load_toep(F, pb + PP, pz + PP);
        G[0] = lds32(pz + 2048 + 32); G[1] = lds32(pb + 2048 + 64); G[2] = lds32(pz + PP + 32); G[3] = lds32(pb + PP + 64);
    }
};
__device__ __forceinline__ uint32_t dense_phase(float (&acc)[16][4], uint32_t vmin, uint32_t va, uint32_t vo, uint32_t pb, DenseTaps& tp, uint32_t zero) {
    uint32_t R[8][4];
    uint32_t pz = pb + zero;
    {
        uint32_t H[4][4];
#pragma unroll
        for (int i = 0; i < 4; i++) ldsm4(H[i], vo + i * 256);
#pragma unroll
        for (int i = 0; i < 8; i++) ldsm4(R[i], va + i * 128);
#pragma unroll
        for (int i = 0; i < 4; i += 2) load_toep(tp.A[i], pb + 512 * i, pz + 512 * i);
#pragma unroll
        for (int i = 0; i < 4; i++) mma_bf16_k8(acc[i + 4], tp.G[0], tp.G[1], H[i >> 1][2 * (i & 1) + 1]);
#pragma unroll
        for (int i = 0; i < 8; i++) mma_v(acc[i + 8], tp.G, H[i >> 1][2 * (i & 1)], H[i >> 1][2 * (i & 1) + 1]);
#pragma unroll
        for (int i = 0; i < 12; i++) mma_v(acc[i + 4], tp.E, R[i & 7][2 * (i >> 3)], R[i & 7][2 * (i >> 3) + 1]);
#pragma unroll
        for (int i = 0; i < 8; i++) mma_v(acc[i + 8], tp.F, R[i][0], R[i][1]);
    }
    float W[8][4];
#pragma unroll
    for (int i = 0; i < 32; i++) { W[i >> 2][i & 3] = 0.f; if (i >= 8) acc[2 * (i >> 2) + 1][i & 3] += acc[2 * (i >> 2)][i & 3]; }
#pragma unroll 1
    for (int rho = 0; rho < 8; rho += 2) {
        ffa_step<0>(acc, W, R, tp.A, va, vmin, pb, pz);
        ffa_step<1>(acc, W, R, tp.A, va - 16, vmin, pb + 64, pz + 64);
        pb += 128; pz += 128; va -= 32;
    }
#pragma unroll
    for (int i = 0; i < 32; i++) {
        const int m = i >> 2, j = i & 3;
        acc[2 * m + 1][j] = (acc[2 * m + 1][j] - acc[2 * m][j]) - W[m][j];
        if (m) acc[2 * m][j] += W[m - 1][j];
    }
    return __float_as_uint(W[7][0]) & zero;
}
__device__ __forceinline__ uint32_t ones2(int c, int lo, int hi) {
    return (((uint32_t)(c - lo) <= (uint32_t)(hi - lo)) ? 1u : 0u) | (((uint32_t)(c + 1 - lo) <= (uint32_t)(hi - lo)) ? 0x10000u : 0u);
}
__device__ __forceinline__ uint32_t box_bits(int lane) {
    const int d = 2 * (lane & 3) - (lane >> 2);
    auto four = [&](int L1, int H1, int L2, int H2) { return ones2(d, L1, H1) | ones2(d, L2, H2) << 1 | ones2(d + 8, L1, H1) << 2 | ones2(d + 8, L2, H2) << 3; };
    return four(5, 7, 0, 4) | four(1, 7, 0, 8) << 4;
}
struct Boxes {
    uint32_t q[4], ha[2];
    __device__ __forceinline__ Boxes(uint32_t bits, int k0, uint32_t h0, uint32_t h1) {
#pragma unroll
        for (int i = 0; i < 4; i++) q[i] = (bits & (0x10001u << (k0 + i))) * (0x3f80u >> (k0 + i));
        ha[0] = h0; ha[1] = h1;
    }
    __device__ __forceinline__ void load(int j, uint32_t* v, uint32_t zero) const {
        const uint32_t o = j * 128;
        v[0] = lds32(ha[0] + o); v[1] = lds32(ha[1] + zero + o); v[2] = lds32(ha[1] + o);
        v[3] = lds32(ha[0] + zero + o + 16); v[4] = lds32(ha[0] + o + 16); v[5] = lds32(ha[1] + o + 16);
    }
    __device__ __forceinline__ void sums(const uint32_t* v, float* Z, float* X, float* Y) const {
        mma_bf16_z(Z, q[0], q[1], q[2], q[3], v[0], v[1]);
        mma_bf16_z(X, q[0], q[1], q[2], q[3], v[2], v[3]);
        mma_bf16_z(Y, q[0], q[1], q[2], q[3], v[4], v[5]);
    }
};
__host__ __device__ constexpr int tail_step(int n) { return n < 8 ? n : n < 12 ? n + 4 : (n & 1) ? 11 - (n - 13) / 2 : 19 - (n - 12) / 2; }
template <class After>
__device__ __forceinline__ void tail_phase(float (&acc)[16][4], const Boxes& b2, const Boxes& b3, uint32_t tp2, uint32_t tp3, uint32_t zero, After after) {
    uint4 t2[5];
    uint2 t3[8];
    uint32_t v[6], a0[4], a1[4];
    float Z[4], X[4], Y[4];
    b2.load(0, v, zero);
#pragma unroll
    for (int i = 0; i < 5; i++) t2[i] = lds128(tp2 + 160 * i);
#pragma unroll
    for (int n = -1; n < 20; n++) {
        const int j = tail_step(n), j1 = tail_step(n + 1), j2 = tail_step(n + 2);
        if (n < 19) {
            (j1 < 12 ? b2 : b3).sums(v, Z, X, Y);
            if (n < 18) { if (j2 < 12) b2.load(j2, v, zero); else b3.load(j2 - 12, v, zero); }
        }
        if (n >= 0 && j < 12) {
#pragma unroll
            for (int b = 0; b < 5; b++) if (j + 4 + b < 16) mma_v(acc[j + 4 + b], a1, t2[b].z, t2[b].w);
        }
        if (n < 19 && j1 < 12) { a1[0] = pack_v(Z[0], Z[1]); a1[1] = pack_w(X[0], X[1]); a1[2] = pack_v(Z[2], Z[3]); a1[3] = pack_w(X[2], X[3]); }
        if (n == 6) {
#pragma unroll
            for (int b = 0; b < 8; b++) t3[b] = lds64(tp3 + 80 * b);
        }
        if (n >= 0 && j < 12) {
#pragma unroll
            for (int b = 0; b < 5; b++) if (j + 4 + b < 16) mma_v(acc[j + 4 + b], a0, t2[b].x, t2[b].y);
        } else if (n >= 0) {
#pragma unroll
            for (int b = 0; b < 8; b++) if (j - 4 + b < 16) mma_v(acc[j - 4 + b], a0, t3[b].x, t3[b].y);
        }
        if (n < 19) {
            if (j1 < 12) { a0[0] = pack_v(X[0], X[1]); a0[1] = pack_v(Y[0], Y[1]); a0[2] = pack_v(X[2], X[3]); a0[3] = pack_v(Y[2], Y[3]); }
            else { a0[0] = pack_v(X[0], X[1]); a0[1] = pack_v(Y[0], Y[1]); a0[2] = pack_v(Z[2], Z[3]); a0[3] = pack_v(X[2], X[3]); }
        }
        after(n);
    }
}
template <int Q>
__device__ __forceinline__ void emit(const float (&acc)[16][4], int h, uint32_t own, uint32_t peer, uint32_t bar, uint32_t bar_peer) {
    constexpr int n = 4 * Q, G = Q >> 1;
#pragma unroll
    for (int hf = 0; hf < 2; hf++)
        asm volatile("{ .reg .pred p; setp.eq.u32 p, %7, %8;\n\t@p st.shared.v4.u32 [%0], {%1,%2,%3,%4};\n\t"
                     "@!p st.async.weak.shared::cluster.mbarrier::complete_tx::bytes.v4.b32 [%5], {%1,%2,%3,%4}, [%6]; }"
                     ::"r"(own + G * 16384 + hf * 512), "r"(pack_bf16(acc[n][2 * hf], acc[n][2 * hf + 1])), "r"(pack_bf16(acc[n + 1][2 * hf], acc[n + 1][2 * hf + 1])),
                     "r"(pack_bf16(acc[n + 2][2 * hf], acc[n + 2][2 * hf + 1])), "r"(pack_bf16(acc[n + 3][2 * hf], acc[n + 3][2 * hf + 1])),
                     "r"(peer + G * 16384 + hf * 512), "r"(bar_peer + 8 * G), "r"(h), "n"(Q & 1) : "memory");
    __syncwarp();
    if (h == (Q & 1) && elect_one()) mbar_arrive(bar);
}
__device__ __forceinline__ uint32_t finish_src(uint32_t sb, int h, int w, int lane) {
    const int m = lane >> 3, r = lane & 7;
    return sb + OFF_XT + (h ^ 1) * 32768 + (2 * m + (r & 1)) * 1024 + (w >> 2) * 512 + (((8 * (w & 3) + (r & 4) + ((r >> 1) & 1)) ^ ((r & 1) << 1)) << 4);
}
__device__ __forceinline__ uint32_t finish_dst(uint32_t sb, int h, int w, int lane) {
    const int g = lane >> 2, t = lane & 3;
    return sb + OFF_XT + h * 32768 + w * 2048 + (g >> 1) * 512 + (t >> 1) * 144 + (2 * (t & 1) + (g & 1)) * 32;
}
__device__ __forceinline__ uint32_t tile_addr(uint32_t sb, int tok, int t) {
    return sb + OFF_XT + (tok & 512) * 64 + (tok >> 10) * 16384 + (tok & 14) * 1024 + (tok & 448) * 4 + (tok & 1) * 128 + (tok & 48) * 2 + (((t >> 1) ^ (tok & 1)) << 4) + (t & 1) * 8;
}
__device__ __forceinline__ uint2 add_update(uint2 o, uint32_t upd) {
    const float4 u = lds128f(upd);
    return make_uint2(badd2(o.x, pack_bf16(u.x, u.y)), badd2(o.y, pack_bf16(u.z, u.w)));
}
__device__ __forceinline__ void finish_half(uint32_t src, uint32_t xa, const uint4 (&x)[2]) {
    uint32_t s[2][4];
#pragma unroll
    for (int i = 0; i < 2; i++) ldsm4t(s[i], src ^ (i << 5));
#pragma unroll
    for (int i = 0; i < 2; i++) sts128(xa + i * 256, badd2(x[i].x, s[i][0]), badd2(x[i].y, s[i][1]), badd2(x[i].z, s[i][2]), badd2(x[i].w, s[i][3]));
}

__device__ __noinline__ float centred_var(uint32_t rows, float mu, int lane) {
    float var = 0.f;
#pragma unroll 1
    for (int rr = 0; rr < 16; rr++) {
        const float c0 = __shfl_sync(0xffffffffu, mu, rr);
        float c = 0.f;
#pragma unroll 1
        for (int k = 0; k < 16; k++) {
            const uint32_t q = lds32(rows + rr * ROW_PITCH + k * 128 + lane * 4);
            const float d0 = bf_lo(q) - c0, d1 = bf_hi(q) - c0;
            c = fmaf(d0, d0, fmaf(d1, d1, c));
        }
#pragma unroll 1
        for (int o = 16; o; o >>= 1) c += __shfl_xor_sync(0xffffffffu, c, o);
        if ((lane & 15) == rr) var = c * (1.f / DM);
    }
    return var;
}
__device__ __noinline__ float centred_score(uint32_t rows, uint32_t wbuf, uint32_t s0, uint32_t s1, int lane) {
    float sc = 0.f;
#pragma unroll 1
    for (int rr = 0; rr < 16; rr++) {
        const uint32_t t0 = __shfl_sync(0xffffffffu, s0, rr), t1 = __shfl_sync(0xffffffffu, s1, rr);
        float c = 0.f;
#pragma unroll 1
        for (int k = 0; k < 16; k++) {
            const uint32_t xn = normalize2(lds32(rows + rr * ROW_PITCH + k * 128 + lane * 4), t0, t1);
            const uint32_t wq = lds32(wbuf + (k >> 2) * 1024 + (k & 3) * 128 + lane * 4);
            c = fmaf(bf_lo(xn), bf_lo(wq), fmaf(bf_hi(xn), bf_hi(wq), c));
        }
#pragma unroll 1
        for (int o = 16; o; o >>= 1) c += __shfl_xor_sync(0xffffffffu, c, o);
        if ((lane & 15) == rr) sc = c;
    }
    return sc;
}

__device__ __forceinline__ void issue_rows(const __nv_bfloat16* u, uint32_t sb, int b) {
    if (elect_one()) {
        const uint32_t bar = sb + OFF_BAR + 8 * B_ROW;
#pragma unroll
        for (int j = 0; j < 4; j++) mbar_init(bar + 8 * j, 1);
        asm volatile("fence.mbarrier_init.release.cluster;" ::: "memory");
        fence_async();
#pragma unroll 1
        for (int j = 0; j < 4; j++) {
            mbar_expect_tx(bar + 8 * j, 8192);
#pragma unroll
            for (int i = 0; i < 4; i++) bulk_g2s(sb + OFF_VT + (4 * j + i) * ROW_PITCH, u + (size_t)(16 * b + 4 * j + i) * DM, 2048, bar + 8 * j);
        }
    }
    __syncwarp();
}

__global__ void __cluster_dims__(2, 1, 1) __launch_bounds__(NTHR, 1)
fused_kernel(const __grid_constant__ Ptrs p, const __grid_constant__ Maps maps) {
    extern __shared__ __align__(1024) unsigned char smem[];
    const int tid = threadIdx.x, lane = tid & 31;
    const int c_ = ((blockIdx.x >> 1) + 60) & 63, b = 2 * ((c_ & 32) | ((c_ & 7) << 2) | ((c_ >> 3) & 3)) + (blockIdx.x & 1);
    const int dch = 8 * b + (tid >> 5) - 4;
    uint2 la, aim, cre, cim;
    uint32_t ldt16;
    if ((uint32_t)(tid - 128) < 256u) {
        la = ldg64(p.logA + dch * NMODE + 4 * lane); aim = ldg64(p.Aim + dch * NMODE + 4 * lane);
        cre = ldg64(p.Cre + dch * NMODE + 4 * lane); cim = ldg64(p.Cim + dch * NMODE + 4 * lane);
        ldt16 = ldg16(p.ldt + dch);
    }
    const uint32_t sb = s_u32(smem), bar0 = sb + OFF_BAR;
    const int warp = __shfl_sync(0xffffffffu, tid >> 5, 0);
    const int h = b & 1, cl = b >> 1;
    const int m = lane >> 3, r = lane & 7, g = lane >> 2, t = lane & 3;
    const bool has_gu = b < GU_CTAS;
    if (warp == 4) { STAMP(0); GSTAMP(24); }

    if (warp >= 12) {
        asm volatile("setmaxnreg.dec.sync.aligned.u32 24;");
        const int a = warp - 12;
        uint32_t due = now_ns() + ST_T0 + (uint32_t)(2 * a + h) * (ST_PER / 2) + (has_gu ? 0 : 12 * ST_PER + 4 * ST_PER2);
        const bool el = elect_one();
        if (a == 1) issue_rows(p.u, sb, b);
        if (a == 2 && el) {
#pragma unroll
            for (int i = B_XT; i < NBAR; i++) mbar_init(bar0 + 8 * i, (i == B_V || i == B_SFREE || i == B_XFREE || i == B_OWN) ? 8 : i == B_RECV ? 9 : i == B_RED ? 5 : (i == B_UPD || (i >= B_FREE && i < B_FULL)) ? 4 : 1);
            asm volatile("fence.mbarrier_init.release.cluster;" ::: "memory");
            fence_async();
            mbar_expect_tx(bar0 + 8 * B_XT, 65536);
            mbar_expect_tx(bar0 + 8 * B_RECV, 8192);
            mbar_expect_tx(bar0 + 8 * B_RECV + 8, 8192);
            mbar_expect_tx(bar0 + 8 * B_RED, 2048);
        }
        if (a == 3 && el) {
#pragma unroll
            for (int i = 0; i < 5; i++) asm volatile("prefetch.tensormap [%0];" ::"l"(&maps.u + i) : "memory");
        }
        __syncwarp();
        cluster_arrive();
        cluster_wait();
        STAMP(18);
        mbar_wait(bar0 + 8 * (B_ROW + a), 0);
        if (el) {
#pragma unroll
            for (int i = 0; i < 4; i++)
                tma_load_tile(sb + OFF_XT + h * 32768 + a * 4096 + (i & 1) * 16384 + (i >> 1) * 2048, &maps.u, 16 * cl, 4 * a + (i & 2), 16 * (i & 1) + 8 * h, bar0 + 8 * B_XT);
        }
        if (el) {
#pragma unroll 1
            for (int k = has_gu ? 0 : 4; k < 6; k++) {
                const int i = 4 * k + a, s = k < 3 ? i : i - 12;
                sleep_until(due);
                due += k < 3 ? 4 * ST_PER : 4 * ST_PER2;
                const bool again = k >= 3 && has_gu;
                if (s >= 6 || again) mbar_wait(bar0 + 8 * (s < 10 || again ? B_FREE + s : B_V), slot_priv(s) && again);
                const uint32_t dst = sb + slot_off(s), bar = bar0 + 8 * (B_FULL + s);
                if (k < 4) {
                    mbar_expect_tx(bar, 8192);
                    tma_load_2d(dst, &maps.wg, 64 * cl, 512 * h + 32 * i, bar);
                    tma_load_2d(dst + 4096, &maps.wu, 64 * cl, 512 * h + 32 * i, bar);
                } else {
                    mbar_expect_tx(bar, 7168);
                    tma_load_perm(dst, &maps.wd, 16 * cl, 56 * h + 14 * a + 7 * (k & 1), bar);
                }
            }
            STAMP(19);
        }
        __syncwarp();
        {
            const uint32_t fs = finish_src(sb, h, 2 * a, lane), fx = finish_dst(sb, h, 2 * a, lane);
            mbar_wait(bar0 + 8 * B_RECV, 0);
#pragma unroll 1
            for (int k = 0; k < 2; k++) {
#pragma unroll
                for (int q = 0; q < 2; q++) {
                    const uint32_t xa = (fx ^ (q << 4)) + k * 2048;
                    const uint4 x[2] = {lds128(xa), lds128(xa + 256)};
                    finish_half(fs + q * 8192 + k * 128, xa, x);
                }
                fence_async();
                __syncwarp();
                if (el) tma_store_tile(&maps.out, sb + OFF_XT + h * 32768 + (2 * a + k) * 2048, 16 * cl, 4 * a + 2 * k, 8 * h);
            }
            if (h) STAMP(59); else STAMP(20);
            const int tok = 2047 - (int)(lds32(sb + OFF_MISC + 48 + 8 * g) & 2047);
            const bool mine = (((tok >> 7) & 12) | ((tok >> 2) & 3)) == 4 * h + a;
            if (el) asm volatile("cp.async.bulk.wait_group 0;" ::: "memory");
            if (__any_sync(0xffffffffu, mine)) {
                const uint2 o0 = lds64(tile_addr(sb, tok, t));
                mbar_wait(bar0 + 8 * B_UPD, 0);
                const uint2 o1 = add_update(o0, sb + tab_off(g) + T_RED + 16 * t);
                if (mine) *reinterpret_cast<uint2*>(p.out + (size_t)tok * DM + 16 * cl + 4 * t) = o1;
            } else STAMP(62);
        }
    } else if (warp >= 4) {
        const int w = warp - 4;
        uint32_t dsk16 = ldg16(p.dsk + dch);
        cluster_arrive();
        asm volatile("setmaxnreg.inc.sync.aligned.u32 176;");
        const uint32_t vrow = sb + OFF_VT + w * VT_PITCH + VT_PAD, tab = sb + tab_off(w);
        const uint32_t rb0 = bar0 + 8 * B_RECV, rb1 = mapa(rb0, h ^ 1);
        uint32_t tpo = 80 + (g - 2 * t) * 8 - (g < 2 * t ? 16 : 0);
        uint32_t xa = sb + OFF_XT + (w & 2) * 16384 + (w >> 2) * 16384 + (w & 1) * 1024 + (g >> 1) * 2048 + (g & 1) * 128 + t * 32 + ((h ^ (g & 1)) << 4);
        uint32_t va = sb + OFF_VT + (2 * m + (r & 1)) * VT_PITCH + VT_PAD + (16 * w + (r >> 1)) * 16;
        uint32_t qa = sb + OFF_ST + 2048 * w + 128 * t + 16 * (g ^ (2 * t));
        uint32_t vmin = vrow + (m & 1) * VT_PLANE - 16, vd = vmin + 16 + (m >> 1) * 1024 + r * 16;
        uint32_t vo = vrow + VT_PLANE + 496 - (m & 1) * 512 + (m >> 1) * 128 + r * 16, vz = vrow - VT_PAD + (lane >> 1) * VT_PLANE + (lane & 1) * 16;
        pin(vmin); pin(vd); pin(vo); pin(vz);
        pin(tpo); pin(xa); pin(va); pin(qa);
        uint32_t bits = box_bits(lane), h0 = vrow + 16 * g + tok_off(2 * t - 18), h1 = vrow + 16 * g + tok_off(2 * t - 10);
        pin(bits); pin(h0); pin(h1);
        const KgenAddr ka(sb + OFF_PRIV + w * 8192, lane);
        if (__any_sync(0xffffffffu, (vmin | (vd | vo | vz) | (tpo | xa) | (va | qa) | (bits | h0 | h1) | ka.any()) & p.zero)) __trap();
        cluster_wait();
        pin(la.x); pin(la.y); pin(aim.x); pin(aim.y); pin(cre.x); pin(cre.y); pin(cim.x); pin(cim.y); pin(ldt16); pin(dsk16);
        uint4 x[8];
        auto load_x = [&]() {
            mbar_wait(bar0 + 8 * B_XT, 0);
#pragma unroll
            for (int i = 0; i < 8; i++) x[i] = lds128(xa + (i & 1) * 8192 + (i >> 1) * 256);
        };
        kgen(ka, tab, lane, la, aim, cre, cim, bf_round(ex2f(bf_lo(ldt16) * 1.4426950408889634f)), 1.f + bf_lo(dsk16), dch, [&]() {
            STAMP(21);
            if (elect_one()) mbar_arrive_n(bar0 + 8 * (B_FREE + 6 + ((w >> 1) ^ 2)), 2);
        }, [&]() {
            if ((LN_PAUSE >> w) & 1) mbar_wait(bar0 + 8 * B_LN, 0);
        });
        STAMP(1);
        const uint32_t pb = tab + T_DENSE + (g - 2 * t) * 4;
        DenseTaps dt(pb, pb + p.zero);
        {
            load_x();
            STAMP(47);
            mbar_wait(bar0 + 8 * (B_ST + (w >> 1)), 0);
            uint4 q[4];
#pragma unroll
            for (int n = 0; n < 4; n++) q[n] = lds128(qa + 512 * n);
            if (lane < 4) sts128(vz, 0, 0, 0, 0);
            STAMP(2); GSTAMP(28);
#pragma unroll
            for (int i = 0; i < 8; i++) {
                const uint32_t s0 = (i & 1) ? q[i >> 1].z : q[i >> 1].x, s1 = (i & 1) ? q[i >> 1].w : q[i >> 1].y;
                stsm4t(va + (i >> 1) * 64 + (i & 1) * VT_PLANE, normalize2(x[i].x, s0, s1), normalize2(x[i].y, s0, s1),
                       normalize2(x[i].z, s0, s1), normalize2(x[i].w, s0, s1));
            }
            __syncwarp();
            if (elect_one()) mbar_arrive(bar0 + 8 * B_V);
        }
        mbar_wait(bar0 + 8 * B_V, 0);
        STAMP(3);
        float acc[16][4];
#pragma unroll
        for (int i = 0; i < 16; i++) { acc[i][0] = acc[i][1] = acc[i][2] = acc[i][3] = 0.f; }
        bits |= dense_phase(acc, vmin, vd, vo, pb, dt, p.zero);
        const Boxes b2(bits, 0, h0, h1), b3(bits, 4, (t == 1 ? h1 : h0) - 4, t == 1 ? h0 + 12 : h1 - 4);
        STAMP(4);
        const uint32_t so = sb + OFF_XT + (8 * h + w) * 1024 + ((lane ^ ((w & 1) << 1)) << 4);
        const uint32_t dst0 = so + (h ^ 1) * 32768, dst1 = mapa(so + h * 32768, h ^ 1);
        tail_phase(acc, b2, b3, tab + T_R2 + 2 * tpo, tab + T_R3 + tpo, p.zero, [&](int j) {
            if (j == -1) {
                mbar_wait(bar0 + 8 * B_SFREE, 0);
                emit<0>(acc, h, dst0, dst1, rb0, rb1);
            }
            if (j == 3) { emit<1>(acc, h, dst0, dst1, rb0, rb1); STAMP(5); }
            if (j == 11) {
                mbar_wait(bar0 + 8 * B_XFREE, 0);
                emit<2>(acc, h, dst0, dst1, bar0 + 8 * B_OWN, rb1);
                STAMP(58);
            }
        });
        emit<3>(acc, h, dst0, dst1, bar0 + 8 * B_OWN, rb1);
        STAMP(30);
        const uint32_t fs = finish_src(sb, h, w, lane) + 16384 + h * 8192, fx = (finish_dst(sb, h, w, lane) + 16384) ^ (h << 4);
        const int tok = 2047 - (int)(lds32(sb + OFF_MISC + 48 + 8 * g) & 2047);
        const bool mine = (((tok >> 6) & 24) | ((tok >> 1) & 7)) == 16 + 8 * h + w;
        const uint32_t ta = tile_addr(sb, tok, t);
        const uint4 x0[2] = {lds128(fx), lds128(fx + 256)}, x1[2] = {lds128(fx ^ 16), lds128((fx ^ 16) + 256)};
        mbar_wait(bar0 + 8 * B_OWN, 0);
        finish_half(fs, fx, x0);
        mbar_wait(bar0 + 8 * (B_RECV + 1), 0);
        STAMP(6);
        finish_half(fs + (h ? -8192 : 8192), fx ^ 16, x1);
        __syncwarp();
        if (__any_sync(0xffffffffu, mine)) {
            const uint2 o0 = lds64(ta);
            mbar_wait(bar0 + 8 * B_UPD, 0);
            const uint2 o1 = add_update(o0, sb + tab_off(g) + T_RED + 16 * t);
            if (mine) sts64(ta, o1.x, o1.y);
        }
        fence_async();
        __syncwarp();
        if (elect_one()) {
            tma_store_tile(&maps.out, sb + OFF_XT + h * 32768 + 16384 + w * 2048, 16 * cl, 2 * w, 16 + 8 * h);
            asm volatile("cp.async.bulk.wait_group.read 0;" ::: "memory");
        }
        STAMP(7);
    } else {
        const int a = warp;
        const uint4 wq = ldg128(p.wr + 8 * tid);
        const uint32_t epoch = ld_relaxed_32(&p.sc[a].cnt[b & 96]) >> 5;
        cluster_arrive();
        asm volatile("setmaxnreg.inc.sync.aligned.u32 136;");
        const uint32_t tag = __shfl_sync(0xffffffffu, epoch, 0) + 1u, misc = sb + OFF_MISC, abar = bar0 + 8 * (B_AUX + a);
        uint32_t aph = 0;
        const Exchange* in = &p.sc[cl & (NREP - 1)];
        uint2* pub = p.sc[m >> 1].stat + 16 * b + 2 * (r ^ (2 * (b & 3))) + (m & 1);
        uint32_t* cnt_s = &p.sc[t].cnt[b & 96];
        pin(pub); pin(cnt_s);
        if (tid < 64) sts32(sb + OFF_XCH + 4 * tid, 0);
        const uint32_t wbuf = sb + OFF_LN + a * 1024, part = sb + OFF_LN + 4096;
        {
            sts128(wbuf + 16 * lane, wq.x, wq.y, wq.z, wq.w);
            sts128(wbuf + 512 + 16 * lane, 0x3f803f80u, 0x3f803f80u, 0x3f803f80u, 0x3f803f80u);
            float wsum = ((bf_lo(wq.x) + bf_hi(wq.x)) + (bf_lo(wq.y) + bf_hi(wq.y))) + ((bf_lo(wq.z) + bf_hi(wq.z)) + (bf_lo(wq.w) + bf_hi(wq.w)));
#pragma unroll
            for (int o = 16; o; o >>= 1) wsum += __shfl_xor_sync(0xffffffffu, wsum, o);
            sts32f(part + 1024 + 4 * a, wsum);
            uint32_t wf[4][4];
#pragma unroll
            for (int i = 0; i < 4; i++) ldsm4(wf[i], wbuf + ((uint32_t)(r - 1) < 2u ? 16 * (r - 1) : 512) + 32 * m + 128 * i);
            uint32_t ra = sb + OFF_VT + r * ROW_PITCH + 512 * a + 16 * m, pa = part + a * 256 + g * 16;
            cluster_wait();
            STAMP(22);
#pragma unroll 1
            for (int hf = 0; hf < 2; hf++) {
                mbar_wait(bar0 + 8 * B_ROW + 16 * hf, 0);
                mbar_wait(bar0 + 8 * B_ROW + 16 * hf + 8, 0);
                STAMP(23);
                uint32_t x[8][4];
                float cs[2][4], q[8][4];
#pragma unroll
                for (int i = 0; i < 40; i++) (i < 8 ? cs[i >> 2 & 1] : q[(i - 8) >> 2 & 7])[i & 3] = 0.f;
#pragma unroll
                for (int k = 0; k < 8; k++) ldsm4(x[k], ra + k * 64);
                const bool more = __any_sync(0xffffffffu, after_all(x, p.zero));
#pragma unroll 1
                do {
#pragma unroll
                    for (int k = 0; k < 8; k++) {
                        mma_v(cs[k & 1], x[k], wf[k >> 1][2 * (k & 1)], wf[k >> 1][2 * (k & 1) + 1]);
#pragma unroll
                        for (int i = 0; i < 4; i++) mma_bf16_k8(q[4 * (k & 1) + i], x[k][i & 2], x[k][i | 1], x[k][i]);
                    }
                } while (more);
                const float c2 = cs[0][2] + cs[1][2];
                if (t == 0) sts64f(pa, (cs[0][0] + cs[1][0]) + c2, cs[0][1] + cs[1][1]);
                if (t == 1) sts32f(pa + 12, c2);
                const float e0 = ((q[0][0] + q[2][0]) + (q[4][0] + q[6][0])) + ((q[1][2] + q[3][2]) + (q[5][2] + q[7][2]));
                const float e1 = ((q[0][1] + q[2][1]) + (q[4][1] + q[6][1])) + ((q[1][3] + q[3][3]) + (q[5][3] + q[7][3]));
                if (t == (g >> 1)) sts32f(pa + 8, (g & 1) ? e1 : e0);
                ra += 8 * ROW_PITCH; pa += 128;
            }
        }
        STAMP(31);
        named_sync(1, 128);
        if (a == 0) {
            const uint32_t pa = part + (lane & 15) * 16;
            const float4 p0 = lds128f(pa), p1 = lds128f(pa + 256), p2 = lds128f(pa + 512), p3 = lds128f(pa + 768), ws = lds128f(part + 1024);
            const float mu = ((p0.x + p1.x) + (p2.x + p3.x)) * (1.f / DM);
            float var = ((p0.z + p1.z) + (p2.z + p3.z)) * (1.f / DM) - mu * mu;
            const bool centred = __any_sync(0xffffffffu, !(mu * mu <= 4.f * var));
            if (centred) var = centred_var(sb + OFF_VT, mu, lane);
            const float ri = rcpf(bf_round(sqrtaf(bf_round(bf_round(var) + 1e-5f))));
            const uint32_t s0 = pack_bf16(mu, ri), s1 = (pack_bf16(ri - bf_hi(s0), 0.f) & 0xfffcu) | (tag & 3);
            float sc = ((((p0.y + p1.y) + (p2.y + p3.y)) + ((p0.w + p1.w) + (p2.w + p3.w))) - bf_lo(s0) * ((ws.x + ws.y) + (ws.z + ws.w))) * ri;
            if (centred) sc = centred_score(sb + OFF_VT, sb + OFF_LN, s0, s1, lane);
            const uint32_t sb16 = pack_bf16(0.f, sc);
            const uint32_t s2 = s1 | (sb16 ^ (((uint32_t)((int)sb16 >> 31) & 0x7fff0000u) | 0x80000000u));
            st_relaxed_64(pub, s0, s2);
            st_relaxed_64(pub + 2 * sizeof(Exchange) / 8, s0, s2);
            if (lane < NREP) red_add(cnt_s, 1);
            if (elect_one()) mbar_arrive(bar0 + 8 * B_LN);
            STAMP(9); GSTAMP(25);
        }
        const uint32_t slot0 = sb + OFF_RING + a * 8192, slot1 = sb + slot_off(4 + a), slot2 = sb + slot_off(8 + a), fbar = bar0 + 8 * (B_FULL + a);
        uint32_t mine = 0, row[2] = {0, 0};
        {
            uint32_t q[16];
            named_sync(1, 128);
            wait_count(&in->cnt[32 * a], 32 * tag - FEW_ST);
            STAMP(41);
#pragma unroll 1
            for (uint32_t it = 0;; spin_guard(it)) {
                if (elect_one()) {
                    mbar_expect_tx(abar, 4096);
                    bulk_g2s(sb + OFF_ST + 4096 * a, in->stat + 512 * a, 4096, abar);
                }
                mbar_wait(abar, aph);
                aph ^= 1;
                uint32_t bad = 0;
#pragma unroll
                for (int n = 0; n < 8; n++) {
                    const uint4 u = lds128v(sb + OFF_ST + 4096 * a + 512 * n + 16 * lane);
                    q[2 * n] = u.y; q[2 * n + 1] = u.w;
                    bad = or_xor(bad, u.y, tag);
                }
                const bool ok = __all_sync(0xffffffffu, (bad & 3) == 0);
                asm volatile("{ .reg .pred p; setp.ne.u32 p, %1, 0; @p mbarrier.arrive.shared::cta.b64 _, [%0]; }" ::"r"(bar0 + 8 * (B_ST + a)), "r"((uint32_t)(ok && lane == 0)) : "memory");
                if (ok) break;
            }
            STAMP(8);
            const uint32_t inv = 2047 - 512 * a - 16 * m - (r ^ (2 * m));
#pragma unroll
            for (int i = 0; i < 16; i++) asm("lop3.b32 %0, %0, %1, %2, 0x9b;" : "+r"(q[i]) : "r"(inv), "r"(0xffff0000u | (64 * (i >> 1) + 8 * (i & 1))));
            auto below = [&](uint32_t x) {
                uint32_t d[4];
#pragma unroll
                for (int i = 0; i < 16; i++) d[i & 3] = i < 4 ? x + q[i] : min(d[i & 3], x + q[i]);
                d[0] = min(min(d[0], d[1]), min(d[2], d[3]));
                return d[0] < x ? x - 1 - d[0] : 0u;
            };
            const uint32_t mx0 = ~min(min(min(min(q[0], q[1]), min(q[2], q[3])), min(min(q[4], q[5]), min(q[6], q[7]))),
                                      min(min(min(q[8], q[9]), min(q[10], q[11])), min(min(q[12], q[13]), min(q[14], q[15]))));
            const uint32_t gm = min(__reduce_max_sync(0xffffffffu, lane < 16 ? mx0 : 0u), __reduce_max_sync(0xffffffffu, lane < 16 ? 0u : mx0));
            if (lane == 0) sts32(misc + 16 + 4 * a, gm);
            named_sync(1, 128);
            STAMP(42);
            const uint4 t0 = lds128(misc + 16);
            uint32_t tau = min(min(t0.x, t0.y), min(t0.z, t0.w));
            uint32_t mx = mx0, cnt = 0, bal;
            const uint32_t list = sb + OFF_XCH + 64 * a;
#pragma unroll 1
            while ((bal = __ballot_sync(0xffffffffu, mx >= tau)) != 0) {
                const uint32_t pos = cnt + __popc(bal & ((1u << lane) - 1u));
                cnt += __popc(bal);
                if (cnt > 16) break;
                if (mx >= tau) sts32(list + 4 * pos, mx);
                mx = below(mx);
            }
            if (cnt > 16) {
                mx = mx0;
#pragma unroll 1
                for (int j = 0; j < 8; j++) {
                    const uint32_t top = __reduce_max_sync(0xffffffffu, mx), nx = below(mx);
                    if (mx == top) { sts32(list + 4 * j, mx); sts32(list + 32 + 4 * j, 0); mx = nx; }
                }
            }
            named_sync(1, 128);
            STAMP(43);
            const uint2 k = lds64(sb + OFF_XCH + 8 * lane);
            uint32_t hi = max(k.x, k.y), lo = min(k.x, k.y);
            mbar_wait(bar0 + 8 * B_V, 0);
#pragma unroll
            for (int j = 0; j < 8; j++) {
                const uint32_t top = __reduce_max_sync(0xffffffffu, hi);
                const bool won = hi == top;
                hi = won ? lo : hi;
                lo = won ? 0u : lo;
                if (g == j) mine = top;
                if (a == (j >> 1)) row[j & 1] = top;
            }
        }
        STAMP(11);
        const int tok = 2047 - (int)(mine & 2047);
        const uint32_t xs = sb + OFF_XT + (h ^ 1) * 32768 + 16384;
        if (has_gu) {
            if (elect_one()) {
                mbar_expect_tx(abar, 2048);
#pragma unroll
                for (int j = 0; j < 2; j++) bulk_g2s(xs + (2 * a + j) * 1040, p.u + (size_t)(2047 - (row[j] & 2047)) * DM + 512 * h, 1024, abar);
            }
        }
        STAMP(44);
        const uint2 st = ld_relaxed_64(in->stat + (tok & ~15) + 2 * ((tok & 7) ^ ((tok >> 3) & 6)) + ((tok >> 3) & 1));
        if (a == 0 && t == 0) sts64(misc + 48 + 8 * g, mine, __float_as_uint(bf_hi(st.x) + bf_lo(st.y)));
        if (a == 0) STAMP(45);
        if (has_gu) {
            const uint32_t mean = __shfl_sync(0xffffffffu, st.x, 8 * a + 4 * (lane >> 4)), xr = xs + (2 * a + (lane >> 4)) * 1040 + 16 * (lane & 15);
            mbar_wait(abar, aph);
            aph ^= 1;
            STAMP(46);
            uint4 x[4];
#pragma unroll
            for (int j = 0; j < 4; j++) x[j] = lds128(xr + 256 * j);
#pragma unroll
            for (int j = 0; j < 4; j++) sts128(xr + 256 * j, bsub2_lo(x[j].x, mean), bsub2_lo(x[j].y, mean), bsub2_lo(x[j].z, mean), bsub2_lo(x[j].w, mean));
            if (elect_one()) mbar_expect_tx(abar, 512);
            named_sync(1, 128);
        }
        if (lane < (has_gu ? 2 : 4)) mbar_arrive_peer(mapa(bar0 + 8 * (lane & 2 ? B_XFREE : B_SFREE), lane & 1));
        if (has_gu) {
            STAMP(12);
            float gacc[8][4];
#pragma unroll
            for (int i = 0; i < 8; i++) { gacc[i][0] = gacc[i][1] = gacc[i][2] = gacc[i][3] = 0.f; }
            uint32_t* pubh = reinterpret_cast<uint32_t*>(&p.sc[0].h[b * 32 + 8 * a + (g ^ (2 * a))]) + t;
            uint32_t* cnt_h = &p.sc[t].cnt[32 * (b / 28) + 1 + ((b / 14) & 1)];
            uint32_t ko = sb + (m & 1) * 4096 + (r + ((m >> 1) << 3)) * 128 + ((r ^ (4 * h) ^ a) << 4), kp = ko ^ 64, xb = xs + r * 1040 + m * 16;
            uint32_t xch = sb + OFF_XCH + 16 * tid, tagm = t == 3 ? 1u : 0u;
            pin(pubh); pin(cnt_h); pin(ko); pin(kp); pin(xb); pin(xch); pin(tagm);
            const float r0 = lds32f(misc + 52 + 16 * t), r1 = lds32f(misc + 60 + 16 * t);
#pragma unroll
            for (int c = 0; c < 4; c++) {
                uint32_t af[20][4];
#pragma unroll
                for (int j = 0; j < 4; j++) ldsm4(af[16 + j], xb + 256 * c + 64 * j);
                if (c == 3) mbar_wait(bar0 + 8 * B_SFREE, 0);
#pragma unroll
                for (int j = 0; j < 4; j++) {
                    mbar_wait(bar0 + 8 * (B_FULL + 4 * (c % 3) + j), c / 3);
#pragma unroll
                    for (int i = 0; i < 4; i++) ldsm4t(af[8 * (i >> 1) + 2 * j + (i & 1)], ((i & 1) ? kp : ko) + slot_off(4 * (c % 3) + j) + (i >> 1) * 2048);
                }
                STAMP(36 + c);
                __syncwarp();
                if (c < 3 && lane < 4) mbar_arrive(bar0 + 8 * (B_FREE + 4 * c + lane));
                const bool more = __any_sync(0xffffffffu, (af[6][3] | af[7][3] | af[14][3] | af[15][3]) & p.zero);
#pragma unroll 1
                do {
#pragma unroll
                    for (int i = 0; i < 16; i++) mma_v(gacc[i & 7], af[i], af[16 + ((i >> 1) & 3)][2 * (i >> 3)], af[16 + ((i >> 1) & 3)][2 * (i >> 3) + 1]);
                } while (more);
            }
            STAMP(13);
            float own[4], oth[4];
#pragma unroll
            for (int j = 0; j < 4; j++) oth[j] = (gacc[1][j] + gacc[3][j]) + (gacc[5][j] + gacc[7][j]);
            st_async128(mapa(xch, h ^ 1), __float_as_uint(oth[0]), __float_as_uint(oth[1]), __float_as_uint(oth[2]), __float_as_uint(oth[3]), mapa(abar, h ^ 1));
            STAMP(56);
#pragma unroll
            for (int j = 0; j < 4; j++) own[j] = ((gacc[0][j] + gacc[2][j]) + (gacc[4][j] + gacc[6][j])) * ((j & 1) ? r1 : r0);
            mbar_wait(abar, aph);
            aph ^= 1;
            STAMP(57);
            const float4 o4 = lds128f(xch);
            const float g0 = bf_round(fmaf(o4.x, r0, own[0])), g1 = bf_round(fmaf(o4.y, r1, own[1]));
            const float h0 = bf_round(g0 * rcpf(1.f + ex2f(-1.4426950408889634f * g0))) * bf_round(fmaf(o4.z, r0, own[2]));
            const float h1 = bf_round(g1 * rcpf(1.f + ex2f(-1.4426950408889634f * g1))) * bf_round(fmaf(o4.w, r1, own[3]));
            uint32_t hw;
            asm volatile("movmatrix.sync.aligned.m8n8.trans.b16 %0, %1;" : "=r"(hw) : "r"(pack_bf16(h0, h1)));
            hw = (hw & ~tagm) | (tag & tagm);
#pragma unroll
            for (int j = 0; j < NREP; j++) st_relaxed_32(pubh + j * (sizeof(Exchange) / 4), hw);
            if (lane < NREP) red_add(cnt_h, b % 14 < 2 ? 2 : 1);
            if (lane < 2) mbar_arrive_peer(mapa(bar0 + 8 * B_XFREE, lane));
            named_sync(1, 128);
            STAMP(14);
        }
        float dacc[4];
        const int tk = ((tid >> 1) & 6) | (tid & 1);
        uint32_t ro = 4 * tid, red = sb + tab_off(tk) + T_RED + 4 * ((tid >> 4) + 4 * (tid & 2));
        if (!has_gu) named_sync(1, 128);
        const float sg = bf_round(rcpf(1.f + ex2f(-1.4426950408889634f * __uint_as_float(unorder_key(lds32(misc + 48 + 8 * tk) >> 16) << 16))));
        pin(ro); pin(red);
        mbar_wait(bar0 + 8 * B_XFREE, 0);
        {
            uint32_t wo = (r + ((m >> 1) << 3)) * 32 + (((m & 1) ^ (r >> 2)) << 4), af[14][4];
            uint32_t ho = slot0 + 128 * t + 16 * (g ^ (2 * t));
            pin(wo); pin(ho);
            float d[7][4];
#pragma unroll
            for (int i = 0; i < 7; i++) { d[i][0] = d[i][1] = d[i][2] = d[i][3] = 0.f; }
            auto first_half = [&]() {
                mbar_wait(fbar + 32, has_gu);
#pragma unroll
                for (int j = 0; j < 14; j++) ldsm4t(af[j], slot1 + wo + j * 512);
            };
            auto fetch = [&]() {
                if (elect_one()) {
                    mbar_expect_tx(abar, 7168);
                    bulk_g2s(slot0, &in->h[(56 * h + 14 * a) * 32], 7168, abar);
                }
            };
            wait_count(&in->cnt[64 * h + 32 * (a >> 1) + 1 + (a & 1)], 64 * tag - FEW_H);
            STAMP(33);
            fetch();
            first_half();
            mbar_wait(abar, aph);
#pragma unroll
            for (int s = 0; s < 2; s++) {
                if (s) {
                    mbar_wait(fbar + 64, has_gu);
#pragma unroll
                    for (int j = 0; j < 14; j++) ldsm4t(af[j], slot2 + wo + j * 512);
                }
                uint4 hq[7];
#pragma unroll 1
                for (uint32_t it = 0;; spin_guard(it)) {
                    uint32_t bad = 0;
#pragma unroll
                    for (int j = 0; j < 7; j++) { hq[j] = lds128(ho + 512 * (7 * s + j)); bad = or_xor(bad, hq[j].w, tag); }
                    if (__all_sync(0xffffffffu, (bad & 1) == 0)) break;
                    fetch();
                    aph ^= 1;
                    mbar_wait(abar, aph);
                }
                if (s == 0) STAMP(15);
#pragma unroll
                for (int j = 0; j < 14; j++) {
                    const uint4 q = hq[j >> 1];
                    mma_v(d[j % 7], af[j], (j & 1) ? q.z : q.x, (j & 1) ? q.w : q.y);
                }
            }
#pragma unroll
            for (int j = 0; j < 4; j++) dacc[j] = ((d[0][j] + d[1][j]) + (d[2][j] + d[3][j])) + ((d[4][j] + d[5][j]) + d[6][j]);
        }
        STAMP(16);
        {
            st_async128(mapa(sb + OFF_XCH + 16 * tid, h ^ 1), __float_as_uint(dacc[0]), __float_as_uint(dacc[1]), __float_as_uint(dacc[2]), __float_as_uint(dacc[3]),
                        mapa(bar0 + 8 * B_RED, h ^ 1));
            sts128f(slot0 + 7680 + lane * 16, dacc);
            __syncwarp();
            if (elect_one()) mbar_arrive(bar0 + 8 * B_RED);
            mbar_wait(bar0 + 8 * B_RED, 0);
            const uint32_t b0 = sb + OFF_RING + 7680 + ro, b1 = sb + OFF_XCH + ro;
            const float y = ((lds32f(b0) + lds32f(b0 + 8192)) + (lds32f(b0 + 16384) + lds32f(b0 + 24576))) +
                            ((lds32f(b1) + lds32f(b1 + 512)) + (lds32f(b1 + 1024) + lds32f(b1 + 1536)));
            sts32f(red, bf_round(y) * sg);
            __syncwarp();
            if (elect_one()) mbar_arrive(bar0 + 8 * B_UPD);
        }
        STAMP(17); GSTAMP(29);
    }
}

typedef CUresult (*EncodeFn)(CUtensorMap*, CUtensorMapDataType, cuuint32_t, void*, const cuuint64_t*, const cuuint64_t*,
                             const cuuint32_t*, const cuuint32_t*, CUtensorMapInterleave, CUtensorMapSwizzle,
                             CUtensorMapL2promotion, CUtensorMapFloatOOBfill);

void make_map(EncodeFn enc, CUtensorMap* m, const void* ptr, uint64_t cols, uint64_t rows, uint32_t bc, uint32_t br,
              CUtensorMapSwizzle sw, CUtensorMapL2promotion pr) {
    cuuint64_t dims[2] = {cols, rows};
    cuuint64_t str[1] = {cols * 2};
    cuuint32_t box[2] = {bc, br};
    cuuint32_t es[2] = {1, 1};
    enc(m, CU_TENSOR_MAP_DATA_TYPE_BFLOAT16, 2, const_cast<void*>(ptr), dims, str, box, es, CU_TENSOR_MAP_INTERLEAVE_NONE, sw, pr,
        CU_TENSOR_MAP_FLOAT_OOB_FILL_NONE);
}
void make_perm_map(EncodeFn enc, CUtensorMap* m, const void* ptr, CUtensorMapL2promotion pr) {
    cuuint64_t dims[5] = {DM, 2, 4, 4, FF / 32};
    cuuint64_t str[4] = {DM * 2, 8 * DM * 2, 2 * DM * 2, 32 * DM * 2};
    cuuint32_t box[5] = {16, 2, 4, 4, 7};
    cuuint32_t es[5] = {1, 1, 1, 1, 1};
    enc(m, CU_TENSOR_MAP_DATA_TYPE_BFLOAT16, 5, const_cast<void*>(ptr), dims, str, box, es, CU_TENSOR_MAP_INTERLEAVE_NONE,
        CU_TENSOR_MAP_SWIZZLE_32B, pr, CU_TENSOR_MAP_FLOAT_OOB_FILL_NONE);
}
void make_tile_map(EncodeFn enc, CUtensorMap* m, const void* ptr) {
    cuuint64_t dims[4] = {DM, 4, 16, SEQ / 64};
    cuuint64_t str[3] = {16 * DM * 2, DM * 2, 64 * DM * 2};
    cuuint32_t box[4] = {16, 4, 2, 8};
    cuuint32_t es[4] = {1, 1, 1, 1};
    enc(m, CU_TENSOR_MAP_DATA_TYPE_BFLOAT16, 4, const_cast<void*>(ptr), dims, str, box, es, CU_TENSOR_MAP_INTERLEAVE_NONE,
        CU_TENSOR_MAP_SWIZZLE_32B, CU_TENSOR_MAP_L2_PROMOTION_NONE, CU_TENSOR_MAP_FLOAT_OOB_FILL_NONE);
}

}

extern "C" void kernel_launch(void* const* d_in, const int* in_sizes, int n_in, void* d_out, int out_size) {
    (void)in_sizes; (void)n_in; (void)out_size;
    static EncodeFn enc = nullptr;
    static void* scratch = nullptr;
    if (!enc) {
        void* fn = nullptr;
        cudaDriverEntryPointQueryResult q;
        cudaGetDriverEntryPoint("cuTensorMapEncodeTiled", &fn, cudaEnableDefault, &q);
        enc = (EncodeFn)fn;
        cudaGetSymbolAddress(&scratch, g_scratch);
        cudaFuncSetAttribute(fused_kernel, cudaFuncAttributeMaxDynamicSharedMemorySize, SMEM_BYTES);
    }
    Maps maps;
    make_tile_map(enc, &maps.u, d_in[0]);
    make_tile_map(enc, &maps.out, d_out);
    make_map(enc, &maps.wg, d_in[9], FF, DM, 64, 32, CU_TENSOR_MAP_SWIZZLE_128B, CU_TENSOR_MAP_L2_PROMOTION_L2_128B);
    make_map(enc, &maps.wu, d_in[10], FF, DM, 64, 32, CU_TENSOR_MAP_SWIZZLE_128B, CU_TENSOR_MAP_L2_PROMOTION_L2_128B);
    make_perm_map(enc, &maps.wd, d_in[11], CU_TENSOR_MAP_L2_PROMOTION_L2_64B);
    Ptrs p;
    p.sc = (Exchange*)scratch;
    p.u = (const __nv_bfloat16*)d_in[0];
    p.logA = (const __nv_bfloat16*)d_in[1];
    p.Aim = (const __nv_bfloat16*)d_in[2];
    p.Cre = (const __nv_bfloat16*)d_in[3];
    p.Cim = (const __nv_bfloat16*)d_in[4];
    p.ldt = (const __nv_bfloat16*)d_in[5];
    p.dsk = (const __nv_bfloat16*)d_in[6];
    p.wr = (const __nv_bfloat16*)d_in[8];
    p.out = (__nv_bfloat16*)d_out;
    p.zero = 0;
    fused_kernel<<<NCTA, NTHR, SMEM_BYTES, cudaStreamPerThread>>>(p, maps);
}
```

```cpp
#include <cuda_runtime.h>
#include <cuda_bf16.h>
#include <cuda_fp16.h>
#include <cuda.h>
#include <stdint.h>

namespace {

constexpr int SEQ = 2048, DM = 1024, NMODE = 128, FF = 3584;
constexpr int NCTA = 128, NTHR = 512;
constexpr int GU_CTAS = 112;
constexpr int NREP = 4;

constexpr int OFF_XT = 0;
constexpr int OFF_RING = 65536;
constexpr int OFF_PRIV = OFF_RING + 65536;
constexpr int OFF_VT = OFF_PRIV + 65536;
constexpr int VT_PAD = 32, VT_PLANE = VT_PAD + 2048, VT_PITCH = 2 * VT_PLANE, ROW_PITCH = 2064;
constexpr int OFF_BAR = OFF_VT + 8 * VT_PITCH;
constexpr int OFF_MISC = OFF_BAR + 384;
constexpr int OFF_XCH = OFF_MISC + 112;
constexpr int SMEM_BYTES = OFF_XCH + 2048;
constexpr int OFF_LN = OFF_RING + 7 * 8192;
constexpr int OFF_ST = OFF_RING + 6 * 8192;
static_assert(SMEM_BYTES <= 232448, "shared memory");

constexpr int B_ROW = 0, B_XT = 4, B_V = 5, B_LN = 6, B_SFREE = 7, B_XFREE = 8, B_OWN = 9, B_RED = 10, B_UPD = 11, B_ST = 12, B_RECV = 16, B_FREE = 20, B_FULL = 32, B_AUX = 44, NBAR = 48;

constexpr int T_DENSE = 60;
constexpr int T_PATCH = 2208;
constexpr int T_R2 = 2368;
constexpr int T_R3 = 3296;

constexpr int T_RED = 4032;
__device__ __forceinline__ bool slot_priv(int s) { return (uint32_t)(s - 6) < 4u; }
__device__ __forceinline__ uint32_t slot_off(int s) { return slot_priv(s) ? OFF_PRIV + 4096 + (s & 3) * 16384 : OFF_RING + (s < 6 ? s : s - 4) * 8192; }
__device__ __forceinline__ uint32_t tab_off(int w) { return OFF_PRIV + w * 8192 + (w & 1) * 4096; }

constexpr uint32_t SPIN_LIMIT = 1u << 20;
#define BB_UNROLL 2
constexpr int kBbUnroll = BB_UNROLL;
#define ST_T0 2250
#define ST_PER 294
#define ST_PER2 320
#define LN_PAUSE 0xf0
#define FEW_ST 10
#define FEW_H 24

struct Exchange {
    uint2 stat[SEQ];
    uint4 h[GU_CTAS * 32];
    uint32_t cnt[4 * 32];
};
__device__ __align__(128) Exchange g_scratch[NREP];

struct Ptrs {
    const __nv_bfloat16 *logA, *Aim, *Cre, *Cim, *ldt, *u;
    const __nv_bfloat16 *dsk, *wr;
    Exchange* sc;
    __nv_bfloat16* out;
    uint32_t zero;
};
struct Maps {
    CUtensorMap u, out, wg, wu, wd;
};

#define STAMP(i) do { } while (0)
#define GSTAMP(i) do { } while (0)

__device__ __forceinline__ uint32_t s_u32(const void* p) { return (uint32_t)__cvta_generic_to_shared(p); }
__device__ __forceinline__ void mbar_init(uint32_t b, uint32_t n) {
    asm volatile("mbarrier.init.shared::cta.b64 [%0], %1;" ::"r"(b), "r"(n) : "memory");
}
__device__ __forceinline__ void mbar_expect_tx(uint32_t b, uint32_t bytes) {
    asm volatile("mbarrier.arrive.expect_tx.shared::cta.b64 _, [%0], %1;" ::"r"(b), "r"(bytes) : "memory");
}
__device__ __forceinline__ void mbar_arrive(uint32_t b) {
    asm volatile("mbarrier.arrive.shared::cta.b64 _, [%0];" ::"r"(b) : "memory");
}
__device__ __forceinline__ void mbar_arrive_n(uint32_t b, uint32_t n) {
    asm volatile("mbarrier.arrive.shared::cta.b64 _, [%0], %1;" ::"r"(b), "r"(n) : "memory");
}
__device__ __forceinline__ void mbar_arrive_peer(uint32_t b_cluster) {
    asm volatile("mbarrier.arrive.relaxed.cluster.shared::cluster.b64 _, [%0];" ::"r"(b_cluster) : "memory");
}
__device__ __forceinline__ void mbar_wait(uint32_t b, uint32_t parity) {
    asm volatile("{\n\t.reg .pred p;\n\t.reg .u32 c;\n\tmov.u32 c, 0;\n"
                 "W:\n\tmbarrier.try_wait.parity.shared::cta.b64 p, [%0], %1;\n\t@p bra D;\n\t"
                 "add.u32 c, c, 1;\n\tsetp.lt.u32 p, c, 1048576;\n\t@p bra W;\n\ttrap;\nD:\n\t}"
                 ::"r"(b), "r"(parity) : "memory");
}
__device__ __forceinline__ bool elect_one() {
    uint32_t p;
    asm volatile("{ .reg .pred P; elect.sync _|P, 0xffffffff; selp.u32 %0, 1, 0, P; }" : "=r"(p));
    return p != 0;
}
__device__ __forceinline__ uint32_t mapa(uint32_t a, uint32_t rank) {
    uint32_t r;
    asm("mapa.shared::cluster.u32 %0, %1, %2;" : "=r"(r) : "r"(a), "r"(rank));
    return r;
}
__device__ __forceinline__ void cluster_arrive() { asm volatile("barrier.cluster.arrive.relaxed.aligned;" ::: "memory"); }
__device__ __forceinline__ void cluster_wait() { asm volatile("barrier.cluster.wait.acquire.aligned;" ::: "memory"); }
__device__ __forceinline__ void tma_load_2d(uint32_t dst, const CUtensorMap* m, int c0, int c1, uint32_t bar) {
    asm volatile("cp.async.bulk.tensor.2d.shared::cluster.global.mbarrier::complete_tx::bytes [%0], [%1, {%3, %4}], [%2];"
                 ::"r"(dst), "l"(m), "r"(bar), "r"(c0), "r"(c1) : "memory");
}
__device__ __forceinline__ void tma_load_perm(uint32_t dst, const CUtensorMap* m, int c0, int blk, uint32_t bar) {
    asm volatile("cp.async.bulk.tensor.5d.shared::cluster.global.mbarrier::complete_tx::bytes [%0], [%1, {%3, %4, %4, %4, %5}], [%2];"
                 ::"r"(dst), "l"(m), "r"(bar), "r"(c0), "r"(0), "r"(blk) : "memory");
}
__device__ __forceinline__ void tma_load_tile(uint32_t dst, const CUtensorMap* m, int c0, int c2, int c3, uint32_t bar) {
    asm volatile("cp.async.bulk.tensor.4d.shared::cluster.global.mbarrier::complete_tx::bytes.multicast::cluster [%0], [%1, {%3, %4, %5, %6}], [%2], %7;"
                 ::"r"(dst), "l"(m), "r"(bar), "r"(c0), "r"(0), "r"(c2), "r"(c3), "h"((uint16_t)3) : "memory");
}
__device__ __forceinline__ void tma_store_tile(const CUtensorMap* m, uint32_t src, int c0, int c2, int c3) {
    asm volatile("cp.async.bulk.tensor.4d.global.shared::cta.bulk_group [%0, {%2, %3, %4, %5}], [%1];"
                 ::"l"(m), "r"(src), "r"(c0), "r"(0), "r"(c2), "r"(c3) : "memory");
    asm volatile("cp.async.bulk.commit_group;" ::: "memory");
}
__device__ __forceinline__ void bulk_g2s(uint32_t dst, const void* src, uint32_t bytes, uint32_t bar) {
    asm volatile("cp.async.bulk.shared::cluster.global.mbarrier::complete_tx::bytes [%0], [%1], %2, [%3];"
                 ::"r"(dst), "l"(src), "r"(bytes), "r"(bar) : "memory");
}
__device__ __forceinline__ void st_async128(uint32_t dst_cluster, uint32_t x, uint32_t y, uint32_t z, uint32_t w, uint32_t bar_cluster) {
    asm volatile("st.async.weak.shared::cluster.mbarrier::complete_tx::bytes.v4.b32 [%0], {%1,%2,%3,%4}, [%5];"
                 ::"r"(dst_cluster), "r"(x), "r"(y), "r"(z), "r"(w), "r"(bar_cluster) : "memory");
}
__device__ __forceinline__ void fence_async() { asm volatile("fence.proxy.async.shared::cta;" ::: "memory"); }
__device__ __forceinline__ void named_sync(int id, int n) { asm volatile("bar.sync %0, %1;" ::"r"(id), "r"(n) : "memory"); }

__device__ __forceinline__ void ldsm4(uint32_t* r, uint32_t a) {
    asm volatile("ldmatrix.sync.aligned.m8n8.x4.shared.b16 {%0,%1,%2,%3}, [%4];"
                 : "=r"(r[0]), "=r"(r[1]), "=r"(r[2]), "=r"(r[3]) : "r"(a));
}
__device__ __forceinline__ void ldsm4t(uint32_t* r, uint32_t a) {
    asm volatile("ldmatrix.sync.aligned.m8n8.x4.trans.shared.b16 {%0,%1,%2,%3}, [%4];"
                 : "=r"(r[0]), "=r"(r[1]), "=r"(r[2]), "=r"(r[3]) : "r"(a));
}
__device__ __forceinline__ void stsm4t(uint32_t a, uint32_t x, uint32_t y, uint32_t z, uint32_t w) {
    asm volatile("stmatrix.sync.aligned.m8n8.x4.trans.shared.b16 [%0], {%1,%2,%3,%4};"
                 ::"r"(a), "r"(x), "r"(y), "r"(z), "r"(w) : "memory");
}
__device__ __forceinline__ uint32_t lds32(uint32_t a) { uint32_t v; asm volatile("ld.shared.u32 %0, [%1];" : "=r"(v) : "r"(a)); return v; }
__device__ __forceinline__ float lds32f(uint32_t a) { float v; asm volatile("ld.shared.f32 %0, [%1];" : "=f"(v) : "r"(a)); return v; }
__device__ __forceinline__ uint2 lds64(uint32_t a) { uint2 v; asm volatile("ld.shared.v2.u32 {%0,%1}, [%2];" : "=r"(v.x), "=r"(v.y) : "r"(a)); return v; }
__device__ __forceinline__ uint4 lds128(uint32_t a) {
    uint4 v; asm volatile("ld.shared.v4.u32 {%0,%1,%2,%3}, [%4];" : "=r"(v.x), "=r"(v.y), "=r"(v.z), "=r"(v.w) : "r"(a)); return v;
}
__device__ __forceinline__ uint4 lds128v(uint32_t a) {
    uint4 v; asm volatile("ld.volatile.shared.v4.u32 {%0,%1,%2,%3}, [%4];" : "=r"(v.x), "=r"(v.y), "=r"(v.z), "=r"(v.w) : "r"(a)); return v;
}
__device__ __forceinline__ uint32_t or_xor(uint32_t a, uint32_t b, uint32_t c) {
    uint32_t r; asm("lop3.b32 %0, %1, %2, %3, 0xf6;" : "=r"(r) : "r"(a), "r"(b), "r"(c)); return r;
}
__device__ __forceinline__ float4 lds128f(uint32_t a) {
    float4 v; asm volatile("ld.shared.v4.f32 {%0,%1,%2,%3}, [%4];" : "=f"(v.x), "=f"(v.y), "=f"(v.z), "=f"(v.w) : "r"(a)); return v;
}
__device__ __forceinline__ void sts32(uint32_t a, uint32_t v) { asm volatile("st.shared.u32 [%0], %1;" ::"r"(a), "r"(v) : "memory"); }
__device__ __forceinline__ void sts32f(uint32_t a, float v) { asm volatile("st.shared.f32 [%0], %1;" ::"r"(a), "f"(v) : "memory"); }
__device__ __forceinline__ void sts64(uint32_t a, uint32_t x, uint32_t y) { asm volatile("st.shared.v2.u32 [%0], {%1,%2};" ::"r"(a), "r"(x), "r"(y) : "memory"); }
__device__ __forceinline__ void sts64f(uint32_t a, float x, float y) { asm volatile("st.shared.v2.f32 [%0], {%1,%2};" ::"r"(a), "f"(x), "f"(y) : "memory"); }
__device__ __forceinline__ void sts128(uint32_t a, uint32_t x, uint32_t y, uint32_t z, uint32_t w) {
    asm volatile("st.shared.v4.u32 [%0], {%1,%2,%3,%4};" ::"r"(a), "r"(x), "r"(y), "r"(z), "r"(w) : "memory");
}
__device__ __forceinline__ void sts128f(uint32_t a, const float* v) {
    asm volatile("st.shared.v4.f32 [%0], {%1,%2,%3,%4};" ::"r"(a), "f"(v[0]), "f"(v[1]), "f"(v[2]), "f"(v[3]) : "memory");
}
__device__ __forceinline__ uint4 ldg128(const void* p) {
    uint4 v; asm volatile("ld.global.nc.L1::no_allocate.v4.u32 {%0,%1,%2,%3}, [%4];" : "=r"(v.x), "=r"(v.y), "=r"(v.z), "=r"(v.w) : "l"(p)); return v;
}
__device__ __forceinline__ uint2 ldg64(const void* p) {
    uint2 v; asm volatile("ld.global.nc.L1::no_allocate.v2.u32 {%0,%1}, [%2];" : "=r"(v.x), "=r"(v.y) : "l"(p)); return v;
}
__device__ __forceinline__ uint32_t ldg16(const void* p) {
    uint32_t v; asm volatile("ld.global.nc.u16 %0, [%1];" : "=r"(v) : "l"(p)); return v;
}
__device__ __forceinline__ uint2 ld_relaxed_64(const void* p) {
    uint2 v; asm volatile("ld.relaxed.gpu.global.v2.u32 {%0,%1}, [%2];" : "=r"(v.x), "=r"(v.y) : "l"(p) : "memory"); return v;
}
__device__ __forceinline__ uint32_t ld_relaxed_32(const void* p) {
    uint32_t v; asm volatile("ld.relaxed.gpu.global.u32 %0, [%1];" : "=r"(v) : "l"(p) : "memory"); return v;
}
__device__ __forceinline__ void st_relaxed_64(void* p, uint32_t x, uint32_t y) {
    asm volatile("st.relaxed.gpu.global.v2.u32 [%0], {%1,%2};" ::"l"(p), "r"(x), "r"(y) : "memory");
}
__device__ __forceinline__ void st_relaxed_32(void* p, uint32_t v) {
    asm volatile("st.relaxed.gpu.global.u32 [%0], %1;" ::"l"(p), "r"(v) : "memory");
}
__device__ __forceinline__ void red_add(void* p, uint32_t v) { asm volatile("red.relaxed.gpu.global.add.u32 [%0], %1;" ::"l"(p), "r"(v) : "memory"); }
__device__ __forceinline__ uint32_t now_ns() { uint32_t t; asm volatile("mov.u32 %0, %%globaltimer_lo;" : "=r"(t) :: "memory"); return t; }
__device__ __forceinline__ void sleep_until(uint32_t t) {
#pragma unroll 1
    for (int left; (left = (int)(t - now_ns())) > 0;) __nanosleep(left >> 1);
}
__device__ __forceinline__ void spin_guard(uint32_t& it) { if (++it > SPIN_LIMIT) __trap(); }
__device__ __forceinline__ void wait_count(const uint32_t* p, uint32_t target) {
#pragma unroll 1
    for (uint32_t it = 0; __any_sync(0xffffffffu, (int)(ld_relaxed_32(p) - target) < 0); spin_guard(it)) { }
}
__device__ __forceinline__ void mma_bf16_k8(float* c, uint32_t a0, uint32_t a1, uint32_t b0) {
    asm("mma.sync.aligned.m16n8k8.row.col.f32.bf16.bf16.f32 {%0,%1,%2,%3}, {%4,%5}, {%6}, {%0,%1,%2,%3};"
                 : "+f"(c[0]), "+f"(c[1]), "+f"(c[2]), "+f"(c[3]) : "r"(a0), "r"(a1), "r"(b0));
}
__device__ __forceinline__ void mma_v(float* c, const uint32_t* a, uint32_t b0, uint32_t b1) {
    asm volatile("mma.sync.aligned.m16n8k16.row.col.f32.bf16.bf16.f32 {%0,%1,%2,%3}, {%4,%5,%6,%7}, {%8,%9}, {%0,%1,%2,%3};"
                 : "+f"(c[0]), "+f"(c[1]), "+f"(c[2]), "+f"(c[3]) : "r"(a[0]), "r"(a[1]), "r"(a[2]), "r"(a[3]), "r"(b0), "r"(b1));
}
__device__ __forceinline__ void mma_bf16_z(float* c, uint32_t a0, uint32_t a1, uint32_t a2, uint32_t a3, uint32_t b0, uint32_t b1) {
    asm volatile("mma.sync.aligned.m16n8k16.row.col.f32.bf16.bf16.f32 {%0,%1,%2,%3}, {%4,%5,%6,%7}, {%8,%9}, {%10,%10,%10,%10};"
        : "=f"(c[0]), "=f"(c[1]), "=f"(c[2]), "=f"(c[3]) : "r"(a0), "r"(a1), "r"(a2), "r"(a3), "r"(b0), "r"(b1), "f"(0.f));
}
__device__ __forceinline__ void mma_f16(float* c, uint32_t a0, uint32_t a1, uint32_t a2, uint32_t a3, uint32_t b0, uint32_t b1) {
    asm("mma.sync.aligned.m16n8k16.row.col.f32.f16.f16.f32 {%0,%1,%2,%3}, {%4,%5,%6,%7}, {%8,%9}, {%0,%1,%2,%3};"
                 : "+f"(c[0]), "+f"(c[1]), "+f"(c[2]), "+f"(c[3]) : "r"(a0), "r"(a1), "r"(a2), "r"(a3), "r"(b0), "r"(b1));
}
__device__ __forceinline__ uint32_t pack_bf16(float lo, float hi) {
    uint32_t r; asm("cvt.rn.bf16x2.f32 %0, %1, %2;" : "=r"(r) : "f"(hi), "f"(lo)); return r;
}
__device__ __forceinline__ uint32_t pack_v(float lo, float hi) {
    uint32_t r; asm volatile("cvt.rn.bf16x2.f32 %0, %1, %2;" : "=r"(r) : "f"(hi), "f"(lo)); return r;
}
__device__ __forceinline__ uint32_t pack_w(float lo, float hi) {
    uint32_t r; asm volatile("cvt.rn.satfinite.bf16x2.f32 %0, %1, %2;" : "=r"(r) : "f"(hi), "f"(lo)); return r;
}
template <int N> __device__ __forceinline__ uint32_t after_all(const uint32_t (&f)[N][4], uint32_t zero) {
    uint32_t d[3] = {0, 0, 0};
#pragma unroll
    for (int i = 0; i < N; i++) d[i % 3] |= f[i][3];
    return (d[0] | d[1] | d[2]) & zero;
}
__device__ __forceinline__ void pin(uint32_t& x) { asm volatile("" : "+r"(x)); }
template <class T> __device__ __forceinline__ void pin(T*& x) { asm volatile("" : "+l"(x)); }
__device__ __forceinline__ uint32_t pack_f16(float lo, float hi) {
    uint32_t r; asm("cvt.rn.f16x2.f32 %0, %1, %2;" : "=r"(r) : "f"(hi), "f"(lo)); return r;
}
__device__ __forceinline__ float bf_lo(uint32_t v) { return __uint_as_float(v << 16); }
__device__ __forceinline__ float bf_hi(uint32_t v) { return __uint_as_float(v & 0xffff0000u); }
__device__ __forceinline__ float bf_round(float x) { return __uint_as_float(pack_bf16(0.f, x)); }
__device__ __forceinline__ uint32_t badd2(uint32_t a, uint32_t b) { uint32_t r; asm("add.rn.bf16x2 %0, %1, %2;" : "=r"(r) : "r"(a), "r"(b)); return r; }
__device__ __forceinline__ uint32_t bsub2_lo(uint32_t a, uint32_t b) {
    uint32_t r; asm("{ .reg .b16 m, h; .reg .b32 m2; mov.b32 {m, h}, %2; mov.b32 m2, {m, m}; sub.rn.bf16x2 %0, %1, m2; }" : "=r"(r) : "r"(a), "r"(b)); return r;
}
__device__ __forceinline__ uint32_t bmax2(uint32_t a, uint32_t b) { uint32_t r; asm("max.bf16x2 %0, %1, %2;" : "=r"(r) : "r"(a), "r"(b)); return r; }
__device__ __forceinline__ uint32_t normalize2(uint32_t x, uint32_t s0, uint32_t s1) {
    uint32_t r;
    asm("{ .reg .b16 m, h, l, k; .reg .b32 m2, h2, l2, d, t;\n\t"
        "mov.b32 {m, h}, %2; mov.b32 {l, k}, %3; mov.b32 m2, {m, m}; mov.b32 h2, {h, h}; mov.b32 l2, {l, l};\n\t"
        "sub.rn.bf16x2 d, %1, m2; mul.rn.bf16x2 t, d, l2; fma.rn.bf16x2 %0, d, h2, t; }" : "=r"(r) : "r"(x), "r"(s0), "r"(s1));
    return r;
}
__device__ __forceinline__ float rcpf(float x) { float r; asm("rcp.approx.ftz.f32 %0, %1;" : "=f"(r) : "f"(x)); return r; }
__device__ __forceinline__ float sqrtaf(float x) { float r; asm("sqrt.approx.ftz.f32 %0, %1;" : "=f"(r) : "f"(x)); return r; }
__device__ __forceinline__ float ex2f(float x) { float r; asm("ex2.approx.ftz.f32 %0, %1;" : "=f"(r) : "f"(x)); return r; }

__device__ __forceinline__ int tok_off(int t) { return ((t >> 3) & 1) * VT_PLANE + (t >> 4) * 16 + (t & 7) * 2; }

__device__ __forceinline__ uint32_t unorder_key(uint32_t k16) { return k16 ^ ((k16 & 0x8000u) ? 0x8000u : 0xffffu); }

struct cplx { float r, i; };
struct hc { uint32_t r, i; };
template <bool CONJ> __device__ __forceinline__ cplx csq(cplx a) {
    float im;
    asm("{ .reg .f32 t; mul.ftz.f32 t, %1, %2; mul.ftz.f32 %0, t, 0f40000000; }" : "=f"(im) : "f"(CONJ ? -a.r : a.r), "f"(a.i));
    return {fmaf(a.r, a.r, -(a.i * a.i)), im};
}
__device__ __forceinline__ cplx cexpp(float a2, float ai) {
    float m = ex2f(a2), s, c;
    __sincosf(ai, &s, &c);
    return {m * c, m * s};
}
__device__ __forceinline__ __half2 as_h2(uint32_t x) { return *reinterpret_cast<__half2*>(&x); }
__device__ __forceinline__ uint32_t as_u(__half2 x) { return *reinterpret_cast<uint32_t*>(&x); }
__device__ __forceinline__ hc hmul(hc a, hc b) {
    return {as_u(__hfma2(as_h2(a.r), as_h2(b.r), __hneg2(__hmul2(as_h2(a.i), as_h2(b.i))))),
            as_u(__hfma2(as_h2(a.r), as_h2(b.i), __hmul2(as_h2(a.i), as_h2(b.r))))};
}
__device__ __forceinline__ hc hpack(cplx a, cplx b) { return {pack_f16(a.r, b.r), pack_f16(a.i, b.i)}; }
__device__ __forceinline__ void sts16(uint32_t a, uint32_t v) { asm volatile("st.shared.u16 [%0], %1;" ::"r"(a), "r"(v) : "memory"); }

struct KgenAddr {
    uint32_t l, h, m2, m3, m4, z, w, wz;
    __device__ __forceinline__ KgenAddr(uint32_t scr, int lane) {
        const int g = lane >> 2, t = lane & 3;
        const uint32_t rec = scr + t * 480;
        l = rec + 16 * g; h = rec + 128 + 8 * g; m2 = rec + 192 + 8 * (g & 1); m3 = rec + 208 + 4 * (g & 2); m4 = rec + 224 + 2 * (g & 4);
        z = scr + 7680 + 16 * t; w = scr + 240 * lane; wz = scr + 7680 + 8 * lane;
        pin(l); pin(h); pin(m2); pin(m3); pin(m4); pin(z); pin(w); pin(wz);
    }
    __device__ __forceinline__ uint32_t any() const { return (l | h | m2) | (m3 | m4 | z) | (w | wz); }
};
template <class Hook, class Hook2>
__device__ __forceinline__ void kgen(const KgenAddr& ad, uint32_t tab, int lane, uint2 la, uint2 aim, uint2 cre, uint2 cim, float dt, float skip, int dch, Hook main_done, Hook2 half_done) {
    const int g = lane >> 2, t = lane & 3;
    const float dt2 = 2.f * dt;
    const uint32_t am = bmax2(bmax2(cre.x & 0x7fff7fffu, cre.y & 0x7fff7fffu), bmax2(cim.x & 0x7fff7fffu, cim.y & 0x7fff7fffu));
    const float mx = dt2 * fmaxf(bf_lo(am), bf_hi(am));
    const uint32_t eb = min(max(__reduce_max_sync(0xffffffffu, __float_as_uint(mx)) >> 23, 1u), 252u);
    const float cscale = dt2 * __uint_as_float((253u - eb) << 23);
    const float scale_inv = __uint_as_float((eb + 1u) << 23);
    float k0 = (bf_lo(cre.x) + bf_hi(cre.x)) + (bf_lo(cre.y) + bf_hi(cre.y));
#pragma unroll
    for (int o = 16; o; o >>= 1) k0 += __shfl_xor_sync(0xffffffffu, k0, o);
    const float ndt = -1.4426950408889634f * dt;
    STAMP(40);

    float acc[5][4];
#pragma unroll
    for (int i = 0; i < 5; i++) { acc[i][0] = acc[i][1] = acc[i][2] = acc[i][3] = 0.f; }

#pragma unroll kBbUnroll
    for (int bb = 0; bb < 2; bb++) {
        cplx z[2][11], cz[2];
#pragma unroll
        for (int e = 0; e < 2; e++) {
            const float lg = e ? bf_hi(la.x) : bf_lo(la.x), ai = (e ? bf_hi(aim.x) : bf_lo(aim.x)) * dt;
            const float cr = (e ? bf_hi(cre.x) : bf_lo(cre.x)) * cscale, ci = (e ? bf_hi(cim.x) : bf_lo(cim.x)) * cscale;
            const float a2 = bf_round(ex2f(lg * 1.4426950408889634f)) * ndt;
            z[e][0] = cexpp(a2, ai);
            z[e][5] = cexpp(a2 * 32.f, ai * -32.f);
#pragma unroll
            for (int i = 1; i < 11; i++) if (i != 5) z[e][i] = (i == 3 || i == 7) ? csq<true>(z[e][i - 1]) : csq<false>(z[e][i - 1]);
            cz[e] = {fmaf(cr, z[e][0].r, -(ci * z[e][0].i)), fmaf(cr, z[e][0].i, ci * z[e][0].r)};
        }
        la.x = la.y; aim.x = aim.y; cre.x = cre.y; cim.x = cim.y;
        const hc z1 = hpack(z[0][0], z[1][0]), z2 = hpack(z[0][1], z[1][1]), z4 = hpack(z[0][2], z[1][2]);
        hc L[8], H[8];
        L[1] = hpack(z[0][3], z[1][3]); L[2] = hpack(z[0][4], z[1][4]); L[4] = hpack(z[0][5], z[1][5]);
        const hc y64 = hpack(z[0][6], z[1][6]), z128 = hpack(z[0][7], z[1][7]), z256 = hpack(z[0][8], z[1][8]);
        const hc z512 = hpack(z[0][9], z[1][9]), z1024 = hpack(z[0][10], z[1][10]);
        H[0] = hpack(cz[0], cz[1]);
        H[1] = hmul(H[0], z1); H[2] = hmul(H[0], z2); H[3] = hmul(H[1], z2);
        L[3] = hmul(L[1], L[2]);
#pragma unroll
        for (int i = 0; i < 4; i++) { H[4 + i] = hmul(H[i], z4); if (i) L[4 + i] = hmul(L[i], L[4]); }
        __syncwarp();
        sts128(ad.w, 0x3c003c00u, y64.r, 0u, y64.i);
#pragma unroll
        for (int i = 1; i < 8; i++) { const hc q = hmul(L[i], y64); sts128(ad.w + 16 * i, L[i].r, q.r, L[i].i, q.i); }
#pragma unroll
        for (int i = 0; i < 4; i++) sts128(ad.w + 128 + 16 * i, H[2 * i].r, H[2 * i].i, H[2 * i + 1].r, H[2 * i + 1].i);
        {
            const hc a = hmul(z256, z1), b = hmul(z256, z128), c = hmul(z256, z2), d = hmul(z512, z4);
            sts128(ad.w + 192, a.r, a.i, b.r, b.i);
            sts128(ad.w + 208, c.r, c.i, z512.r, z512.i);
            sts128(ad.w + 224, d.r, d.i, z1024.r, z1024.i);
            sts64(ad.wz, z128.r, z128.i);
        }
        __syncwarp();

#pragma unroll
        for (int k2 = 0; k2 < 4; k2++) {
#pragma unroll
            for (uint32_t s = 0; s < 2; s++) {
                const uint32_t o = k2 * 1920 + s * 240;
                const uint4 l = lds128(ad.l + o);
                const uint2 h0 = lds64(ad.h + o), m2 = lds64(ad.m2 + o), m3 = lds64(ad.m3 + o), m4 = lds64(ad.m4 + o), mz = lds64(ad.z + k2 * 64 + s * 8);
                const hc H0 = {h0.x, h0.y};
                const hc H1 = hmul(H0, {mz.x, mz.y}), H2 = hmul(H0, {m2.x, m2.y}), H3 = hmul(H2, {m3.x, m3.y}), H4 = hmul(H3, {m4.x, m4.y});
                mma_f16(acc[0], l.x, l.y, l.z, l.w, H0.r, H0.i);
                mma_f16(acc[1], l.x, l.y, l.z, l.w, H1.r, H1.i);
                mma_f16(acc[2], l.x, l.y, l.z, l.w, H2.r, H2.i);
                mma_f16(acc[3], l.x, l.y, l.z, l.w, H3.r, H3.i);
                mma_f16(acc[4], l.x, l.y, l.z, l.w, H4.r, H4.i);
            }
        }

        if (bb == 0) half_done();
    }
    __syncwarp();
    main_done();

#pragma unroll
    for (int i = 0; i < 4; i++) sts128(tab + 2048 + 512 * i + 16 * lane, 0, 0, 0, 0);
    if (lane < 15) sts32(tab + 4 * lane, 0);
    __syncwarp();
    const uint32_t d0 = tab + T_DENSE + 4 + 8 * lane, src = (lane + 31) & 31;
    const uint32_t p0 = pack_bf16(fmaf(k0, dt2, skip), 0.f);
    uint32_t prev = p0;
#pragma unroll
    for (int i = 0; i < 4; i++) {
        const uint32_t pk = pack_bf16(acc[i >> 1][2 * (i & 1) + 1] * scale_inv, acc[i >> 1][2 * (i & 1)] * scale_inv);
        sts64(d0 + 256 * i, __byte_perm(pk, __shfl_sync(0xffffffffu, lane == 31 ? prev : pk, src), 0x5432), pk);
        prev = pk;
    }
    const uint32_t w0 = pack_bf16(acc[2][0] * scale_inv, acc[2][1] * scale_inv), w1 = pack_bf16(acc[2][2] * scale_inv, acc[2][3] * scale_inv);
    const uint32_t sa = (lane & 1) ? 0x5410u : 0x5454u, sb2 = (lane & 1) ? 0x1010u : 0x5410u;
#pragma unroll
    for (int hf = 0; hf < 2; hf++) {
        const uint32_t w = hf ? w1 : w0;
        const uint32_t pv = __shfl_sync(0xffffffffu, lane != 31 ? w : hf ? w0 : __byte_perm(prev, w1, 0x5410), src);
        sts64(d0 + 1024 + 256 * hf, __byte_perm(w, pv, sa), __byte_perm(w, pv, sb2));
        sts64(d0 + 1536 + 256 * hf, __byte_perm(w, pv, sa + 0x2222u), __byte_perm(w, pv, sb2 + 0x2222u));
    }
    const uint32_t d3 = tab + T_R2 + 160 + 320 * (t & 1) + 16 * (g >> 1) + 8 * (g & 1) + 4 * (t >> 1), d3n = d3 + (g >= 6 ? 32 : 0);
    const uint32_t d4 = tab + T_R3 + 80 + 160 * t + 4 * g, d4n = d4 + (g >= 6 ? 16 : 0);
    uint32_t p3;
#pragma unroll
    for (int hf = 0; hf < 2; hf++)
#pragma unroll
        for (int e = 0; e < 2; e++) {
            const float v3 = acc[3][2 * hf + e] * scale_inv;
            const uint32_t p4 = pack_bf16(acc[4][2 * hf + e] * scale_inv, 0.f);
            p3 = pack_bf16(v3, v3);
            sts16(d3 + 64 * hf + 160 * e, p3);
            sts16((hf ? d3n : d3) + 64 * hf + 160 * e + 18, p3);
            sts16(d4 + 32 * hf + 80 * e, p4);
            sts16((hf ? d4n : d4) + 32 * hf + 80 * e + 10, p4);
        }
    if (lane == 31) {
        const uint32_t k512 = __byte_perm(w1, 0, 0x3232);
        sts32(tab + T_DENSE, p0);
        sts64(tab + T_DENSE + 4 * 513, k512, k512); sts16(tab + T_DENSE + 4 * 515 + 2, k512);
        sts16(tab + T_PATCH + 4 * 17, p3); sts32(tab + T_PATCH + 4 * 18, p3); sts16(tab + T_PATCH + 4 * 19 + 2, p3);
    }
    __syncwarp();
}

__device__ __forceinline__ void load_toep(uint32_t* a, uint32_t p, uint32_t pz) {
    a[0] = lds32(p); a[1] = lds32(p + 32); a[2] = lds32(pz - 32); a[3] = lds32(pz);
}
template <int F>
__device__ __forceinline__ void ffa_step(float (&acc)[16][4], float (&W)[8][4], uint32_t (&R)[8][4], uint32_t (&A)[4][4],
                                         uint32_t va, uint32_t vmin, uint32_t pb, uint32_t pz) {
    constexpr int S = F ^ 1;
    auto load = [&](int sh) {
#pragma unroll
        for (int i = S; i < 8; i += 2) ldsm4(R[i], i == 0 ? max(va - 16 * sh, vmin) : va - 16 * sh + i * 128);
#pragma unroll
        for (int k = S; k < 4; k += 2) load_toep(A[k], pb + 64 * sh + k * 512, pz + 64 * sh + k * 512);
    };
    auto prod = [&](int par, int dst) {
#pragma unroll
        for (int k = 0; k < 2; k++)
#pragma unroll
            for (int m = k; m < 8; m++) {
                const uint32_t* x = &R[2 * ((m - k) & 3) + par][2 * ((m - k) >> 2)];
                mma_v(dst == 1 ? W[m] : acc[2 * m + (dst >> 1)], A[2 * k + par], x[0], x[1]);
            }
    };
    load(0);
    prod(F, F);
    prod(S, S);
#pragma unroll
    for (int i = 0; i < 8; i++) A[(i >> 2) * 2 + F][i & 3] = badd2(A[(i >> 2) * 2][i & 3], A[(i >> 2) * 2 + 1][i & 3]);
#pragma unroll
    for (int i = 0; i < 16; i++) R[(i >> 2) * 2 + F][i & 3] = badd2(R[(i >> 2) * 2][i & 3], R[(i >> 2) * 2 + 1][i & 3]);
    load(1);
    prod(F, 2);
}
struct DenseTaps {
    uint32_t A[4][4], E[4], F[4], G[4];
    __device__ __forceinline__ DenseTaps(uint32_t pb, uint32_t pz) {
        constexpr int PP = T_PATCH - T_DENSE + 56;
        load_toep(E, pb + 2048, pz + 2048);
        load_toep(F, pb + PP, pz + PP);
        G[0] = lds32(pz + 2048 + 32); G[1] = lds32(pb + 2048 + 64); G[2] = lds32(pz + PP + 32); G[3] = lds32(pb + PP + 64);
    }
};
__device__ __forceinline__ uint32_t dense_phase(float (&acc)[16][4], uint32_t vmin, uint32_t va, uint32_t vo, uint32_t pb, DenseTaps& tp, uint32_t zero) {
    uint32_t R[8][4];
    uint32_t pz = pb + zero;
    {
        uint32_t H[4][4];
#pragma unroll
        for (int i = 0; i < 4; i++) ldsm4(H[i], vo + i * 256);
#pragma unroll
        for (int i = 0; i < 8; i++) ldsm4(R[i], va + i * 128);
#pragma unroll
        for (int i = 0; i < 4; i += 2) load_toep(tp.A[i], pb + 512 * i, pz + 512 * i);
#pragma unroll
        for (int i = 0; i < 4; i++) mma_bf16_k8(acc[i + 4], tp.G[0], tp.G[1], H[i >> 1][2 * (i & 1) + 1]);
#pragma unroll
        for (int i = 0; i < 8; i++) mma_v(acc[i + 8], tp.G, H[i >> 1][2 * (i & 1)], H[i >> 1][2 * (i & 1) + 1]);
#pragma unroll
        for (int i = 0; i < 12; i++) mma_v(acc[i + 4], tp.E, R[i & 7][2 * (i >> 3)], R[i & 7][2 * (i >> 3) + 1]);
#pragma unroll
        for (int i = 0; i < 8; i++) mma_v(acc[i + 8], tp.F, R[i][0], R[i][1]);
    }
    float W[8][4];
#pragma unroll
    for (int i = 0; i < 32; i++) { W[i >> 2][i & 3] = 0.f; if (i >= 8) acc[2 * (i >> 2) + 1][i & 3] += acc[2 * (i >> 2)][i & 3]; }
#pragma unroll 1
    for (int rho = 0; rho < 8; rho += 2) {
        ffa_step<0>(acc, W, R, tp.A, va, vmin, pb, pz);
        ffa_step<1>(acc, W, R, tp.A, va - 16, vmin, pb + 64, pz + 64);
        pb += 128; pz += 128; va -= 32;
    }
#pragma unroll
    for (int i = 0; i < 32; i++) {
        const int m = i >> 2, j = i & 3;
        acc[2 * m + 1][j] = (acc[2 * m + 1][j] - acc[2 * m][j]) - W[m][j];
        if (m) acc[2 * m][j] += W[m - 1][j];
    }
    return __float_as_uint(W[7][0]) & zero;
}
__device__ __forceinline__ uint32_t ones2(int c, int lo, int hi) {
    return (((uint32_t)(c - lo) <= (uint32_t)(hi - lo)) ? 1u : 0u) | (((uint32_t)(c + 1 - lo) <= (uint32_t)(hi - lo)) ? 0x10000u : 0u);
}
__device__ __forceinline__ uint32_t box_bits(int lane) {
    const int d = 2 * (lane & 3) - (lane >> 2);
    auto four = [&](int L1, int H1, int L2, int H2) { return ones2(d, L1, H1) | ones2(d, L2, H2) << 1 | ones2(d + 8, L1, H1) << 2 | ones2(d + 8, L2, H2) << 3; };
    return four(5, 7, 0, 4) | four(1, 7, 0, 8) << 4;
}
struct Boxes {
    uint32_t q[4], ha[2];
    __device__ __forceinline__ Boxes(uint32_t bits, int k0, uint32_t h0, uint32_t h1) {
#pragma unroll
        for (int i = 0; i < 4; i++) q[i] = (bits & (0x10001u << (k0 + i))) * (0x3f80u >> (k0 + i));
        ha[0] = h0; ha[1] = h1;
    }
    __device__ __forceinline__ void load(int j, uint32_t* v, uint32_t zero) const {
        const uint32_t o = j * 128;
        v[0] = lds32(ha[0] + o); v[1] = lds32(ha[1] + zero + o); v[2] = lds32(ha[1] + o);
        v[3] = lds32(ha[0] + zero + o + 16); v[4] = lds32(ha[0] + o + 16); v[5] = lds32(ha[1] + o + 16);
    }
    __device__ __forceinline__ void sums(const uint32_t* v, float* Z, float* X, float* Y) const {
        mma_bf16_z(Z, q[0], q[1], q[2], q[3], v[0], v[1]);
        mma_bf16_z(X, q[0], q[1], q[2], q[3], v[2], v[3]);
        mma_bf16_z(Y, q[0], q[1], q[2], q[3], v[4], v[5]);
    }
};
__host__ __device__ constexpr int tail_step(int n) { return n < 8 ? n : n < 12 ? n + 4 : (n & 1) ? 11 - (n - 13) / 2 : 19 - (n - 12) / 2; }
template <class After>
__device__ __forceinline__ void tail_phase(float (&acc)[16][4], const Boxes& b2, const Boxes& b3, uint32_t tp2, uint32_t tp3, uint32_t zero, After after) {
    uint4 t2[5];
    uint2 t3[8];
    uint32_t v[6], a0[4], a1[4];
    float Z[4], X[4], Y[4];
    b2.load(0, v, zero);
#pragma unroll
    for (int i = 0; i < 5; i++) t2[i] = lds128(tp2 + 160 * i);
#pragma unroll
    for (int n = -1; n < 20; n++) {
        const int j = tail_step(n), j1 = tail_step(n + 1), j2 = tail_step(n + 2);
        if (n < 19) {
            (j1 < 12 ? b2 : b3).sums(v, Z, X, Y);
            if (n < 18) { if (j2 < 12) b2.load(j2, v, zero); else b3.load(j2 - 12, v, zero); }
        }
        if (n >= 0 && j < 12) {
#pragma unroll
            for (int b = 0; b < 5; b++) if (j + 4 + b < 16) mma_v(acc[j + 4 + b], a1, t2[b].z, t2[b].w);
        }
        if (n < 19 && j1 < 12) { a1[0] = pack_v(Z[0], Z[1]); a1[1] = pack_w(X[0], X[1]); a1[2] = pack_v(Z[2], Z[3]); a1[3] = pack_w(X[2], X[3]); }
        if (n == 6) {
#pragma unroll
            for (int b = 0; b < 8; b++) t3[b] = lds64(tp3 + 80 * b);
        }
        if (n >= 0 && j < 12) {
#pragma unroll
            for (int b = 0; b < 5; b++) if (j + 4 + b < 16) mma_v(acc[j + 4 + b], a0, t2[b].x, t2[b].y);
        } else if (n >= 0) {
#pragma unroll
            for (int b = 0; b < 8; b++) if (j - 4 + b < 16) mma_v(acc[j - 4 + b], a0, t3[b].x, t3[b].y);
        }
        if (n < 19) {
            if (j1 < 12) { a0[0] = pack_v(X[0], X[1]); a0[1] = pack_v(Y[0], Y[1]); a0[2] = pack_v(X[2], X[3]); a0[3] = pack_v(Y[2], Y[3]); }
            else { a0[0] = pack_v(X[0], X[1]); a0[1] = pack_v(Y[0], Y[1]); a0[2] = pack_v(Z[2], Z[3]); a0[3] = pack_v(X[2], X[3]); }
        }
        after(n);
    }
}
template <int Q>
__device__ __forceinline__ void emit(const float (&acc)[16][4], int h, uint32_t own, uint32_t peer, uint32_t bar, uint32_t bar_peer) {
    constexpr int n = 4 * Q;
#pragma unroll
    for (int hf = 0; hf < 2; hf++)
        asm volatile("{ .reg .pred p; setp.eq.u32 p, %7, %8;\n\t@p st.shared.v4.u32 [%0], {%1,%2,%3,%4};\n\t"
                     "@!p st.async.weak.shared::cluster.mbarrier::complete_tx::bytes.v4.b32 [%5], {%1,%2,%3,%4}, [%6]; }"
                     ::"r"(own + Q * 8192), "r"(pack_bf16(acc[n][2 * hf], acc[n][2 * hf + 1])), "r"(pack_bf16(acc[n + 1][2 * hf], acc[n + 1][2 * hf + 1])),
                     "r"(pack_bf16(acc[n + 2][2 * hf], acc[n + 2][2 * hf + 1])), "r"(pack_bf16(acc[n + 3][2 * hf], acc[n + 3][2 * hf + 1])),
                     "r"(peer + Q * 8192), "r"(bar_peer + 8 * Q), "r"(h), "r"(hf) : "memory");
    __syncwarp();
    if (elect_one()) mbar_arrive(bar);
}
__device__ __forceinline__ uint32_t finish_src(uint32_t sb, int h, int j, int lane) {
    const int m = lane >> 3, r = lane & 7;
    return sb + OFF_XT + (h ^ 1) * 32768 + (2 * m + (r & 1)) * 512 + (((8 * j + (r & 4) + ((r >> 1) & 1)) ^ ((r & 1) << 1)) << 4);
}
__device__ __forceinline__ uint32_t finish_dst(uint32_t sb, int h, int j, int lane) {
    const int g = lane >> 2, t = lane & 3;
    return sb + OFF_XT + h * 32768 + j * 2048 + (g >> 1) * 512 + (t >> 1) * 144 + (2 * (t & 1) + (g & 1)) * 32;
}
__device__ __forceinline__ uint32_t tile_addr(uint32_t sb, int tok, int t) {
    return sb + OFF_XT + (tok & 8) * 4096 + (tok >> 9) * 8192 + (tok & 6) * 1024 + (tok & 448) * 4 + (tok & 1) * 128 + (tok & 48) * 2 + (((t >> 1) ^ (tok & 1)) << 4) + (t & 1) * 8;
}
__device__ __forceinline__ uint2 add_update(uint2 o, uint32_t upd) {
    const float4 u = lds128f(upd);
    return make_uint2(badd2(o.x, pack_bf16(u.x, u.y)), badd2(o.y, pack_bf16(u.z, u.w)));
}
__device__ __forceinline__ void finish_half(uint32_t src, uint32_t xa, const uint4 (&x)[2]) {
    uint32_t s[2][4];
#pragma unroll
    for (int i = 0; i < 2; i++) ldsm4t(s[i], src ^ (i << 5));
#pragma unroll
    for (int i = 0; i < 2; i++) sts128(xa + i * 256, badd2(x[i].x, s[i][0]), badd2(x[i].y, s[i][1]), badd2(x[i].z, s[i][2]), badd2(x[i].w, s[i][3]));
}

__device__ __noinline__ float centred_var(uint32_t rows, float mu, int lane) {
    float var = 0.f;
#pragma unroll 1
    for (int rr = 0; rr < 16; rr++) {
        const float c0 = __shfl_sync(0xffffffffu, mu, rr);
        float c = 0.f;
#pragma unroll 1
        for (int k = 0; k < 16; k++) {
            const uint32_t q = lds32(rows + rr * ROW_PITCH + k * 128 + lane * 4);
            const float d0 = bf_lo(q) - c0, d1 = bf_hi(q) - c0;
            c = fmaf(d0, d0, fmaf(d1, d1, c));
        }
#pragma unroll 1
        for (int o = 16; o; o >>= 1) c += __shfl_xor_sync(0xffffffffu, c, o);
        if ((lane & 15) == rr) var = c * (1.f / DM);
    }
    return var;
}
__device__ __noinline__ float centred_score(uint32_t rows, uint32_t wbuf, uint32_t s0, uint32_t s1, int lane) {
    float sc = 0.f;
#pragma unroll 1
    for (int rr = 0; rr < 16; rr++) {
        const uint32_t t0 = __shfl_sync(0xffffffffu, s0, rr), t1 = __shfl_sync(0xffffffffu, s1, rr);
        float c = 0.f;
#pragma unroll 1
        for (int k = 0; k < 16; k++) {
            const uint32_t xn = normalize2(lds32(rows + rr * ROW_PITCH + k * 128 + lane * 4), t0, t1);
            const uint32_t wq = lds32(wbuf + (k >> 2) * 1024 + (k & 3) * 128 + lane * 4);
            c = fmaf(bf_lo(xn), bf_lo(wq), fmaf(bf_hi(xn), bf_hi(wq), c));
        }
#pragma unroll 1
        for (int o = 16; o; o >>= 1) c += __shfl_xor_sync(0xffffffffu, c, o);
        if ((lane & 15) == rr) sc = c;
    }
    return sc;
}

__device__ __forceinline__ void issue_rows(const __nv_bfloat16* u, uint32_t sb, int b) {
    if (elect_one()) {
        const uint32_t bar = sb + OFF_BAR + 8 * B_ROW;
#pragma unroll
        for (int j = 0; j < 4; j++) mbar_init(bar + 8 * j, 1);
        asm volatile("fence.mbarrier_init.release.cluster;" ::: "memory");
        fence_async();
#pragma unroll 1
        for (int j = 0; j < 4; j++) {
            mbar_expect_tx(bar + 8 * j, 8192);
#pragma unroll
            for (int i = 0; i < 4; i++) bulk_g2s(sb + OFF_VT + (4 * j + i) * ROW_PITCH, u + (size_t)(16 * b + 4 * j + i) * DM, 2048, bar + 8 * j);
        }
    }
    __syncwarp();
}

__global__ void __cluster_dims__(2, 1, 1) __launch_bounds__(NTHR, 1)
fused_kernel(const __grid_constant__ Ptrs p, const __grid_constant__ Maps maps) {
    extern __shared__ __align__(1024) unsigned char smem[];
    const int tid = threadIdx.x, lane = tid & 31;
    const int c_ = ((blockIdx.x >> 1) + 60) & 63, b = 2 * ((c_ & 32) | ((c_ & 7) << 2) | ((c_ >> 3) & 3)) + (blockIdx.x & 1);
    const int dch = 8 * b + (tid >> 5) - 4;
    uint2 la, aim, cre, cim;
    uint32_t ldt16;
    if ((uint32_t)(tid - 128) < 256u) {
        la = ldg64(p.logA + dch * NMODE + 4 * lane); aim = ldg64(p.Aim + dch * NMODE + 4 * lane);
        cre = ldg64(p.Cre + dch * NMODE + 4 * lane); cim = ldg64(p.Cim + dch * NMODE + 4 * lane);
        ldt16 = ldg16(p.ldt + dch);
    }
    const uint32_t sb = s_u32(smem), bar0 = sb + OFF_BAR;
    const int warp = __shfl_sync(0xffffffffu, tid >> 5, 0);
    const int h = b & 1, cl = b >> 1;
    const int m = lane >> 3, r = lane & 7, g = lane >> 2, t = lane & 3;
    const bool has_gu = b < GU_CTAS;
    if (warp == 4) { STAMP(0); GSTAMP(24); }

    if (warp >= 12) {
        asm volatile("setmaxnreg.dec.sync.aligned.u32 24;");
        const int a = warp - 12;
        uint32_t due = now_ns() + ST_T0 + (uint32_t)(2 * a + h) * (ST_PER / 2) + (has_gu ? 0 : 12 * ST_PER + 4 * ST_PER2);
        const bool el = elect_one();
        if (a == 1) issue_rows(p.u, sb, b);
        if (a == 2 && el) {
#pragma unroll
            for (int i = B_XT; i < NBAR; i++) mbar_init(bar0 + 8 * i, (i == B_V || i == B_SFREE || i == B_XFREE || i == B_OWN) ? 8 : (i >= B_RECV && i < B_RECV + 3) ? 9 : i == B_RED ? 5 : (i == B_UPD || (i >= B_FREE && i < B_FULL)) ? 4 : 1);
            asm volatile("fence.mbarrier_init.release.cluster;" ::: "memory");
            fence_async();
            mbar_expect_tx(bar0 + 8 * B_XT, 65536);
#pragma unroll
            for (int i = 0; i < 4; i++) mbar_expect_tx(bar0 + 8 * (B_RECV + i), 4096);
            mbar_expect_tx(bar0 + 8 * B_RED, 2048);
        }
        if (a == 3 && el) {
#pragma unroll
            for (int i = 0; i < 5; i++) asm volatile("prefetch.tensormap [%0];" ::"l"(&maps.u + i) : "memory");
        }
        __syncwarp();
        cluster_arrive();
        cluster_wait();
        STAMP(18);
        mbar_wait(bar0 + 8 * (B_ROW + a), 0);
        if (el) {
#pragma unroll
            for (int i = 0; i < 4; i++)
                tma_load_tile(sb + OFF_XT + (a >> 1) * 32768 + (a & 1) * 4096 + h * 8192 + (i & 1) * 16384 + (i >> 1) * 2048, &maps.u, 16 * cl, 4 * a + (i & 2), 16 * (i & 1) + 8 * h, bar0 + 8 * B_XT);
        }
        if (el) {
#pragma unroll 1
            for (int k = has_gu ? 0 : 4; k < 6; k++) {
                const int i = 4 * k + a, s = k < 3 ? i : i - 12;
                sleep_until(due);
                due += k < 3 ? 4 * ST_PER : 4 * ST_PER2;
                const bool again = k >= 3 && has_gu;
                if (s >= 6 || again) mbar_wait(bar0 + 8 * (s < 10 || again ? B_FREE + s : B_V), slot_priv(s) && again);
                const uint32_t dst = sb + slot_off(s), bar = bar0 + 8 * (B_FULL + s);
                if (k < 4) {
                    mbar_expect_tx(bar, 8192);
                    tma_load_2d(dst, &maps.wg, 64 * cl, 512 * h + 32 * i, bar);
                    tma_load_2d(dst + 4096, &maps.wu, 64 * cl, 512 * h + 32 * i, bar);
                } else {
                    mbar_expect_tx(bar, 7168);
                    tma_load_perm(dst, &maps.wd, 16 * cl, 56 * h + 14 * a + 7 * (k & 1), bar);
                }
            }
            STAMP(19);
        }
        __syncwarp();
        {
            uint32_t fs = finish_src(sb, h, a, lane), fx = finish_dst(sb, h, a, lane);
#pragma unroll 1
            for (int Q = 0; Q < 3; Q++) {
                mbar_wait(bar0 + 8 * (B_RECV + Q), 0);
#pragma unroll
                for (int q = 0; q < 2; q++) {
                    const uint4 x[2] = {lds128(fx ^ (q << 4)), lds128((fx ^ (q << 4)) + 256)};
                    finish_half(fs + q * 4096, fx ^ (q << 4), x);
                }
                fence_async();
                __syncwarp();
                if (el) tma_store_tile(&maps.out, sb + OFF_XT + h * 32768 + Q * 8192 + a * 2048, 16 * cl, 8 * h + 2 * a, 8 * Q);
                fs += 8192; fx += 8192;
                STAMP(Q ? 58 + Q : 20);
            }
            const int tok = 2047 - (int)(lds32(sb + OFF_MISC + 48 + 8 * g) & 2047);
            const bool mine = ((tok >> 1) & 7) == 4 * h + a && tok < 1536;
            if (el) asm volatile("cp.async.bulk.wait_group 0;" ::: "memory");
            if (__any_sync(0xffffffffu, mine)) {
                const uint2 o0 = lds64(tile_addr(sb, tok, t));
                mbar_wait(bar0 + 8 * B_UPD, 0);
                const uint2 o1 = add_update(o0, sb + tab_off(g) + T_RED + 16 * t);
                if (mine) *reinterpret_cast<uint2*>(p.out + (size_t)tok * DM + 16 * cl + 4 * t) = o1;
            } else STAMP(62);
        }
    } else if (warp >= 4) {
        const int w = warp - 4;
        uint32_t dsk16 = ldg16(p.dsk + dch);
        cluster_arrive();
        asm volatile("setmaxnreg.inc.sync.aligned.u32 176;");
        const uint32_t vrow = sb + OFF_VT + w * VT_PITCH + VT_PAD, tab = sb + tab_off(w);
        const uint32_t rb0 = bar0 + 8 * B_RECV, rb1 = mapa(rb0, h ^ 1);
        uint32_t tpo = 80 + (g - 2 * t) * 8 - (g < 2 * t ? 16 : 0);
        uint32_t xa = sb + OFF_XT + (w >> 1) * 8192 + (w & 1) * 1024 + (g >> 1) * 2048 + (g & 1) * 128 + t * 32 + ((h ^ (g & 1)) << 4);
        uint32_t va = sb + OFF_VT + (2 * m + (r & 1)) * VT_PITCH + VT_PAD + (16 * w + (r >> 1)) * 16;
        uint32_t qa = sb + OFF_ST + 2048 * w + 128 * t + 16 * (g ^ (2 * t));
        uint32_t vmin = vrow + (m & 1) * VT_PLANE - 16, vd = vmin + 16 + (m >> 1) * 1024 + r * 16;
        uint32_t vo = vrow + VT_PLANE + 496 - (m & 1) * 512 + (m >> 1) * 128 + r * 16, vz = vrow - VT_PAD + (lane >> 1) * VT_PLANE + (lane & 1) * 16;
        pin(vmin); pin(vd); pin(vo); pin(vz);
        pin(tpo); pin(xa); pin(va); pin(qa);
        uint32_t bits = box_bits(lane), h0 = vrow + 16 * g + tok_off(2 * t - 18), h1 = vrow + 16 * g + tok_off(2 * t - 10);
        pin(bits); pin(h0); pin(h1);
        const KgenAddr ka(sb + OFF_PRIV + w * 8192, lane);
        if (__any_sync(0xffffffffu, (vmin | (vd | vo | vz) | (tpo | xa) | (va | qa) | (bits | h0 | h1) | ka.any()) & p.zero)) __trap();
        cluster_wait();
        pin(la.x); pin(la.y); pin(aim.x); pin(aim.y); pin(cre.x); pin(cre.y); pin(cim.x); pin(cim.y); pin(ldt16); pin(dsk16);
        uint4 x[8];
        auto load_x = [&]() {
            mbar_wait(bar0 + 8 * B_XT, 0);
#pragma unroll
            for (int i = 0; i < 8; i++) x[i] = lds128(xa + (i & 1) * 32768 + (i >> 1) * 256);
        };
        kgen(ka, tab, lane, la, aim, cre, cim, bf_round(ex2f(bf_lo(ldt16) * 1.4426950408889634f)), 1.f + bf_lo(dsk16), dch, [&]() {
            STAMP(21);
            if (elect_one()) mbar_arrive_n(bar0 + 8 * (B_FREE + 6 + ((w >> 1) ^ 2)), 2);
        }, [&]() {
            if ((LN_PAUSE >> w) & 1) mbar_wait(bar0 + 8 * B_LN, 0);
        });
        STAMP(1);
        const uint32_t pb = tab + T_DENSE + (g - 2 * t) * 4;
        DenseTaps dt(pb, pb + p.zero);
        {
            load_x();
            STAMP(47);
            mbar_wait(bar0 + 8 * (B_ST + (w >> 1)), 0);
            uint4 q[4];
#pragma unroll
            for (int n = 0; n < 4; n++) q[n] = lds128(qa + 512 * n);
            if (lane < 4) sts128(vz, 0, 0, 0, 0);
            STAMP(2); GSTAMP(28);
#pragma unroll
            for (int i = 0; i < 8; i++) {
                const uint32_t s0 = (i & 1) ? q[i >> 1].z : q[i >> 1].x, s1 = (i & 1) ? q[i >> 1].w : q[i >> 1].y;
                stsm4t(va + (i >> 1) * 64 + (i & 1) * VT_PLANE, normalize2(x[i].x, s0, s1), normalize2(x[i].y, s0, s1),
                       normalize2(x[i].z, s0, s1), normalize2(x[i].w, s0, s1));
            }
            __syncwarp();
            if (elect_one()) mbar_arrive(bar0 + 8 * B_V);
        }
        mbar_wait(bar0 + 8 * B_V, 0);
        STAMP(3);
        float acc[16][4];
#pragma unroll
        for (int i = 0; i < 16; i++) { acc[i][0] = acc[i][1] = acc[i][2] = acc[i][3] = 0.f; }
        bits |= dense_phase(acc, vmin, vd, vo, pb, dt, p.zero);
        const Boxes b2(bits, 0, h0, h1), b3(bits, 4, (t == 1 ? h1 : h0) - 4, t == 1 ? h0 + 12 : h1 - 4);
        STAMP(4);
        const uint32_t so = sb + OFF_XT + (8 * h + w) * 512 + ((lane ^ ((w & 1) << 1)) << 4);
        const uint32_t dst0 = so + (h ^ 1) * 32768, dst1 = mapa(so + h * 32768, h ^ 1);
        tail_phase(acc, b2, b3, tab + T_R2 + 2 * tpo, tab + T_R3 + tpo, p.zero, [&](int j) {
            if (j == -1) {
                mbar_wait(bar0 + 8 * B_SFREE, 0);
                emit<0>(acc, h, dst0, dst1, rb0, rb1);
            }
            if (j == 3) { emit<1>(acc, h, dst0, dst1, rb0 + 8, rb1); STAMP(5); }
            if (j == 11) {
                mbar_wait(bar0 + 8 * B_XFREE, 0);
                emit<2>(acc, h, dst0, dst1, rb0 + 16, rb1);
                STAMP(58);
            }
        });
        emit<3>(acc, h, dst0, dst1, bar0 + 8 * B_OWN, rb1);
        STAMP(30);
        if (w < 4) {
            const uint32_t fs = finish_src(sb, h, w, lane) + 24576 + h * 4096, fx = (finish_dst(sb, h, w, lane) + 24576) ^ (h << 4);
            const int tok = 2047 - (int)(lds32(sb + OFF_MISC + 48 + 8 * g) & 2047);
            const bool mine = ((tok >> 1) & 7) == 4 * h + w && tok >= 1536;
            const uint32_t ta = tile_addr(sb, tok, t);
            const uint4 x0[2] = {lds128(fx), lds128(fx + 256)}, x1[2] = {lds128(fx ^ 16), lds128((fx ^ 16) + 256)};
            mbar_wait(bar0 + 8 * B_OWN, 0);
            finish_half(fs, fx, x0);
            mbar_wait(bar0 + 8 * (B_RECV + 3), 0);
            STAMP(6);
            finish_half(fs + (h ? -4096 : 4096), fx ^ 16, x1);
            __syncwarp();
            if (__any_sync(0xffffffffu, mine)) {
                const uint2 o0 = lds64(ta);
                mbar_wait(bar0 + 8 * B_UPD, 0);
                const uint2 o1 = add_update(o0, sb + tab_off(g) + T_RED + 16 * t);
                if (mine) sts64(ta, o1.x, o1.y);
            }
            fence_async();
            __syncwarp();
            if (elect_one()) {
                tma_store_tile(&maps.out, sb + OFF_XT + h * 32768 + 24576 + w * 2048, 16 * cl, 8 * h + 2 * w, 24);
                if (w == 3) STAMP(61);
                asm volatile("cp.async.bulk.wait_group.read 0;" ::: "memory");
            }
        }
        STAMP(7);
    } else {
        const int a = warp;
        const uint4 wq = ldg128(p.wr + 8 * tid);
        const uint32_t epoch = ld_relaxed_32(&p.sc[a].cnt[b & 96]) >> 5;
        cluster_arrive();
        asm volatile("setmaxnreg.inc.sync.aligned.u32 136;");
        const uint32_t tag = __shfl_sync(0xffffffffu, epoch, 0) + 1u, misc = sb + OFF_MISC, abar = bar0 + 8 * (B_AUX + a);
        uint32_t aph = 0;
        const Exchange* in = &p.sc[cl & (NREP - 1)];
        uint2* pub = p.sc[m >> 1].stat + 16 * b + 2 * (r ^ (2 * (b & 3))) + (m & 1);
        uint32_t* cnt_s = &p.sc[t].cnt[b & 96];
        pin(pub); pin(cnt_s);
        if (tid < 64) sts32(sb + OFF_XCH + 4 * tid, 0);
        const uint32_t wbuf = sb + OFF_LN + a * 1024, part = sb + OFF_LN + 4096;
        {
            sts128(wbuf + 16 * lane, wq.x, wq.y, wq.z, wq.w);
            sts128(wbuf + 512 + 16 * lane, 0x3f803f80u, 0x3f803f80u, 0x3f803f80u, 0x3f803f80u);
            float wsum = ((bf_lo(wq.x) + bf_hi(wq.x)) + (bf_lo(wq.y) + bf_hi(wq.y))) + ((bf_lo(wq.z) + bf_hi(wq.z)) + (bf_lo(wq.w) + bf_hi(wq.w)));
#pragma unroll
            for (int o = 16; o; o >>= 1) wsum += __shfl_xor_sync(0xffffffffu, wsum, o);
            sts32f(part + 1024 + 4 * a, wsum);
            uint32_t wf[4][4];
#pragma unroll
            for (int i = 0; i < 4; i++) ldsm4(wf[i], wbuf + ((uint32_t)(r - 1) < 2u ? 16 * (r - 1) : 512) + 32 * m + 128 * i);
            uint32_t ra = sb + OFF_VT + r * ROW_PITCH + 512 * a + 16 * m, pa = part + a * 256 + g * 16;
            cluster_wait();
            STAMP(22);
#pragma unroll 1
            for (int hf = 0; hf < 2; hf++) {
                mbar_wait(bar0 + 8 * B_ROW + 16 * hf, 0);
                mbar_wait(bar0 + 8 * B_ROW + 16 * hf + 8, 0);
                STAMP(23);
                uint32_t x[8][4];
                float cs[2][4], q[8][4];
#pragma unroll
                for (int i = 0; i < 40; i++) (i < 8 ? cs[i >> 2 & 1] : q[(i - 8) >> 2 & 7])[i & 3] = 0.f;
#pragma unroll
                for (int k = 0; k < 8; k++) ldsm4(x[k], ra + k * 64);
                const bool more = __any_sync(0xffffffffu, after_all(x, p.zero));
#pragma unroll 1
                do {
#pragma unroll
                    for (int k = 0; k < 8; k++) {
                        mma_v(cs[k & 1], x[k], wf[k >> 1][2 * (k & 1)], wf[k >> 1][2 * (k & 1) + 1]);
#pragma unroll
                        for (int i = 0; i < 4; i++) mma_bf16_k8(q[4 * (k & 1) + i], x[k][i & 2], x[k][i | 1], x[k][i]);
                    }
                } while (more);
                const float c2 = cs[0][2] + cs[1][2];
                if (t == 0) sts64f(pa, (cs[0][0] + cs[1][0]) + c2, cs[0][1] + cs[1][1]);
                if (t == 1) sts32f(pa + 12, c2);
                const float e0 = ((q[0][0] + q[2][0]) + (q[4][0] + q[6][0])) + ((q[1][2] + q[3][2]) + (q[5][2] + q[7][2]));
                const float e1 = ((q[0][1] + q[2][1]) + (q[4][1] + q[6][1])) + ((q[1][3] + q[3][3]) + (q[5][3] + q[7][3]));
                if (t == (g >> 1)) sts32f(pa + 8, (g & 1) ? e1 : e0);
                ra += 8 * ROW_PITCH; pa += 128;
            }
        }
        STAMP(31);
        named_sync(1, 128);
        if (a == 0) {
            const uint32_t pa = part + (lane & 15) * 16;
            const float4 p0 = lds128f(pa), p1 = lds128f(pa + 256), p2 = lds128f(pa + 512), p3 = lds128f(pa + 768), ws = lds128f(part + 1024);
            const float mu = ((p0.x + p1.x) + (p2.x + p3.x)) * (1.f / DM);
            float var = ((p0.z + p1.z) + (p2.z + p3.z)) * (1.f / DM) - mu * mu;
            const bool centred = __any_sync(0xffffffffu, !(mu * mu <= 4.f * var));
            if (centred) var = centred_var(sb + OFF_VT, mu, lane);
            const float ri = rcpf(bf_round(sqrtaf(bf_round(bf_round(var) + 1e-5f))));
            const uint32_t s0 = pack_bf16(mu, ri), s1 = (pack_bf16(ri - bf_hi(s0), 0.f) & 0xfffcu) | (tag & 3);
            float sc = ((((p0.y + p1.y) + (p2.y + p3.y)) + ((p0.w + p1.w) + (p2.w + p3.w))) - bf_lo(s0) * ((ws.x + ws.y) + (ws.z + ws.w))) * ri;
            if (centred) sc = centred_score(sb + OFF_VT, sb + OFF_LN, s0, s1, lane);
            const uint32_t sb16 = pack_bf16(0.f, sc);
            const uint32_t s2 = s1 | (sb16 ^ (((uint32_t)((int)sb16 >> 31) & 0x7fff0000u) | 0x80000000u));
            st_relaxed_64(pub, s0, s2);
            st_relaxed_64(pub + 2 * sizeof(Exchange) / 8, s0, s2);
            if (lane < NREP) red_add(cnt_s, 1);
            if (elect_one()) mbar_arrive(bar0 + 8 * B_LN);
            STAMP(9); GSTAMP(25);
        }
        const uint32_t slot0 = sb + OFF_RING + a * 8192, slot1 = sb + slot_off(4 + a), slot2 = sb + slot_off(8 + a), fbar = bar0 + 8 * (B_FULL + a);
        uint32_t mine = 0, row[2] = {0, 0};
        {
            uint32_t q[16];
            named_sync(1, 128);
            wait_count(&in->cnt[32 * a], 32 * tag - FEW_ST);
            STAMP(41);
#pragma unroll 1
            for (uint32_t it = 0;; spin_guard(it)) {
                if (elect_one()) {
                    mbar_expect_tx(abar, 4096);
                    bulk_g2s(sb + OFF_ST + 4096 * a, in->stat + 512 * a, 4096, abar);
                }
                mbar_wait(abar, aph);
                aph ^= 1;
                uint32_t bad = 0;
#pragma unroll
                for (int n = 0; n < 8; n++) {
                    const uint4 u = lds128v(sb + OFF_ST + 4096 * a + 512 * n + 16 * lane);
                    q[2 * n] = u.y; q[2 * n + 1] = u.w;
                    bad = or_xor(bad, u.y, tag);
                }
                const bool ok = __all_sync(0xffffffffu, (bad & 3) == 0);
                asm volatile("{ .reg .pred p; setp.ne.u32 p, %1, 0; @p mbarrier.arrive.shared::cta.b64 _, [%0]; }" ::"r"(bar0 + 8 * (B_ST + a)), "r"((uint32_t)(ok && lane == 0)) : "memory");
                if (ok) break;
            }
            STAMP(8);
            const uint32_t inv = 2047 - 512 * a - 16 * m - (r ^ (2 * m));
#pragma unroll
            for (int i = 0; i < 16; i++) asm("lop3.b32 %0, %0, %1, %2, 0x9b;" : "+r"(q[i]) : "r"(inv), "r"(0xffff0000u | (64 * (i >> 1) + 8 * (i & 1))));
            auto below = [&](uint32_t x) {
                uint32_t d[4];
#pragma unroll
                for (int i = 0; i < 16; i++) d[i & 3] = i < 4 ? x + q[i] : min(d[i & 3], x + q[i]);
                d[0] = min(min(d[0], d[1]), min(d[2], d[3]));
                return d[0] < x ? x - 1 - d[0] : 0u;
            };
            const uint32_t mx0 = ~min(min(min(min(q[0], q[1]), min(q[2], q[3])), min(min(q[4], q[5]), min(q[6], q[7]))),
                                      min(min(min(q[8], q[9]), min(q[10], q[11])), min(min(q[12], q[13]), min(q[14], q[15]))));
            const uint32_t gm = min(__reduce_max_sync(0xffffffffu, lane < 16 ? mx0 : 0u), __reduce_max_sync(0xffffffffu, lane < 16 ? 0u : mx0));
            if (lane == 0) sts32(misc + 16 + 4 * a, gm);
            named_sync(1, 128);
            STAMP(42);
            const uint4 t0 = lds128(misc + 16);
            uint32_t tau = min(min(t0.x, t0.y), min(t0.z, t0.w));
            uint32_t mx = mx0, cnt = 0, bal;
            const uint32_t list = sb + OFF_XCH + 64 * a;
#pragma unroll 1
            while ((bal = __ballot_sync(0xffffffffu, mx >= tau)) != 0) {
                const uint32_t pos = cnt + __popc(bal & ((1u << lane) - 1u));
                cnt += __popc(bal);
                if (cnt > 16) break;
                if (mx >= tau) sts32(list + 4 * pos, mx);
                mx = below(mx);
            }
            if (cnt > 16) {
                mx = mx0;
#pragma unroll 1
                for (int j = 0; j < 8; j++) {
                    const uint32_t top = __reduce_max_sync(0xffffffffu, mx), nx = below(mx);
                    if (mx == top) { sts32(list + 4 * j, mx); sts32(list + 32 + 4 * j, 0); mx = nx; }
                }
            }
            named_sync(1, 128);
            STAMP(43);
            const uint2 k = lds64(sb + OFF_XCH + 8 * lane);
            uint32_t hi = max(k.x, k.y), lo = min(k.x, k.y);
            mbar_wait(bar0 + 8 * B_V, 0);
#pragma unroll
            for (int j = 0; j < 8; j++) {
                const uint32_t top = __reduce_max_sync(0xffffffffu, hi);
                const bool won = hi == top;
                hi = won ? lo : hi;
                lo = won ? 0u : lo;
                if (g == j) mine = top;
                if (a == (j >> 1)) row[j & 1] = top;
            }
        }
        STAMP(11);
        const int tok = 2047 - (int)(mine & 2047);
        const uint32_t xs = sb + OFF_XT + (h ^ 1) * 32768 + 16384;
        if (has_gu) {
            if (elect_one()) {
                mbar_expect_tx(abar, 2048);
#pragma unroll
                for (int j = 0; j < 2; j++) bulk_g2s(xs + (2 * a + j) * 1040, p.u + (size_t)(2047 - (row[j] & 2047)) * DM + 512 * h, 1024, abar);
            }
        }
        STAMP(44);
        const uint2 st = ld_relaxed_64(in->stat + (tok & ~15) + 2 * ((tok & 7) ^ ((tok >> 3) & 6)) + ((tok >> 3) & 1));
        if (a == 0 && t == 0) sts64(misc + 48 + 8 * g, mine, __float_as_uint(bf_hi(st.x) + bf_lo(st.y)));
        if (a == 0) STAMP(45);
        if (has_gu) {
            const uint32_t mean = __shfl_sync(0xffffffffu, st.x, 8 * a + 4 * (lane >> 4)), xr = xs + (2 * a + (lane >> 4)) * 1040 + 16 * (lane & 15);
            mbar_wait(abar, aph);
            aph ^= 1;
            STAMP(46);
            uint4 x[4];
#pragma unroll
            for (int j = 0; j < 4; j++) x[j] = lds128(xr + 256 * j);
#pragma unroll
            for (int j = 0; j < 4; j++) sts128(xr + 256 * j, bsub2_lo(x[j].x, mean), bsub2_lo(x[j].y, mean), bsub2_lo(x[j].z, mean), bsub2_lo(x[j].w, mean));
            if (elect_one()) mbar_expect_tx(abar, 512);
            named_sync(1, 128);
        }
        if (lane < (has_gu ? 2 : 4)) mbar_arrive_peer(mapa(bar0 + 8 * (lane & 2 ? B_XFREE : B_SFREE), lane & 1));
        if (has_gu) {
            STAMP(12);
            float gacc[8][4];
#pragma unroll
            for (int i = 0; i < 8; i++) { gacc[i][0] = gacc[i][1] = gacc[i][2] = gacc[i][3] = 0.f; }
            uint32_t* pubh = reinterpret_cast<uint32_t*>(&p.sc[0].h[b * 32 + 8 * a + (g ^ (2 * a))]) + t;
            uint32_t* cnt_h = &p.sc[t].cnt[32 * (b / 28) + 1 + ((b / 14) & 1)];
            uint32_t ko = sb + (m & 1) * 4096 + (r + ((m >> 1) << 3)) * 128 + ((r ^ (4 * h) ^ a) << 4), kp = ko ^ 64, xb = xs + r * 1040 + m * 16;
            uint32_t xch = sb + OFF_XCH + 16 * tid, tagm = t == 3 ? 1u : 0u;
            pin(pubh); pin(cnt_h); pin(ko); pin(kp); pin(xb); pin(xch); pin(tagm);
            const float r0 = lds32f(misc + 52 + 16 * t), r1 = lds32f(misc + 60 + 16 * t);
#pragma unroll
            for (int c = 0; c < 4; c++) {
                uint32_t af[20][4];
#pragma unroll
                for (int j = 0; j < 4; j++) ldsm4(af[16 + j], xb + 256 * c + 64 * j);
                if (c == 3) mbar_wait(bar0 + 8 * B_SFREE, 0);
#pragma unroll
                for (int j = 0; j < 4; j++) {
                    mbar_wait(bar0 + 8 * (B_FULL + 4 * (c % 3) + j), c / 3);
#pragma unroll
                    for (int i = 0; i < 4; i++) ldsm4t(af[8 * (i >> 1) + 2 * j + (i & 1)], ((i & 1) ? kp : ko) + slot_off(4 * (c % 3) + j) + (i >> 1) * 2048);
                }
                STAMP(36 + c);
                __syncwarp();
                if (c < 3 && lane < 4) mbar_arrive(bar0 + 8 * (B_FREE + 4 * c + lane));
                const bool more = __any_sync(0xffffffffu, (af[6][3] | af[7][3] | af[14][3] | af[15][3]) & p.zero);
#pragma unroll 1
                do {
#pragma unroll
                    for (int i = 0; i < 16; i++) mma_v(gacc[i & 7], af[i], af[16 + ((i >> 1) & 3)][2 * (i >> 3)], af[16 + ((i >> 1) & 3)][2 * (i >> 3) + 1]);
                } while (more);
            }
            STAMP(13);
            float own[4], oth[4];
#pragma unroll
            for (int j = 0; j < 4; j++) oth[j] = (gacc[1][j] + gacc[3][j]) + (gacc[5][j] + gacc[7][j]);
            st_async128(mapa(xch, h ^ 1), __float_as_uint(oth[0]), __float_as_uint(oth[1]), __float_as_uint(oth[2]), __float_as_uint(oth[3]), mapa(abar, h ^ 1));
            STAMP(56);
#pragma unroll
            for (int j = 0; j < 4; j++) own[j] = ((gacc[0][j] + gacc[2][j]) + (gacc[4][j] + gacc[6][j])) * ((j & 1) ? r1 : r0);
            mbar_wait(abar, aph);
            aph ^= 1;
            STAMP(57);
            const float4 o4 = lds128f(xch);
            const float g0 = bf_round(fmaf(o4.x, r0, own[0])), g1 = bf_round(fmaf(o4.y, r1, own[1]));
            const float h0 = bf_round(g0 * rcpf(1.f + ex2f(-1.4426950408889634f * g0))) * bf_round(fmaf(o4.z, r0, own[2]));
            const float h1 = bf_round(g1 * rcpf(1.f + ex2f(-1.4426950408889634f * g1))) * bf_round(fmaf(o4.w, r1, own[3]));
            uint32_t hw;
            asm volatile("movmatrix.sync.aligned.m8n8.trans.b16 %0, %1;" : "=r"(hw) : "r"(pack_bf16(h0, h1)));
            hw = (hw & ~tagm) | (tag & tagm);
#pragma unroll
            for (int j = 0; j < NREP; j++) st_relaxed_32(pubh + j * (sizeof(Exchange) / 4), hw);
            if (lane < NREP) red_add(cnt_h, b % 14 < 2 ? 2 : 1);
            if (lane < 2) mbar_arrive_peer(mapa(bar0 + 8 * B_XFREE, lane));
            named_sync(1, 128);
            STAMP(14);
        }
        float dacc[4];
        const int tk = ((tid >> 1) & 6) | (tid & 1);
        uint32_t ro = 4 * tid, red = sb + tab_off(tk) + T_RED + 4 * ((tid >> 4) + 4 * (tid & 2));
        if (!has_gu) named_sync(1, 128);
        const float sg = bf_round(rcpf(1.f + ex2f(-1.4426950408889634f * __uint_as_float(unorder_key(lds32(misc + 48 + 8 * tk) >> 16) << 16))));
        pin(ro); pin(red);
        mbar_wait(bar0 + 8 * B_XFREE, 0);
        {
            uint32_t wo = (r + ((m >> 1) << 3)) * 32 + (((m & 1) ^ (r >> 2)) << 4), af[14][4];
            uint32_t ho = slot0 + 128 * t + 16 * (g ^ (2 * t));
            pin(wo); pin(ho);
            float d[7][4];
#pragma unroll
            for (int i = 0; i < 7; i++) { d[i][0] = d[i][1] = d[i][2] = d[i][3] = 0.f; }
            auto first_half = [&]() {
                mbar_wait(fbar + 32, has_gu);
#pragma unroll
                for (int j = 0; j < 14; j++) ldsm4t(af[j], slot1 + wo + j * 512);
            };
            auto fetch = [&]() {
                if (elect_one()) {
                    mbar_expect_tx(abar, 7168);
                    bulk_g2s(slot0, &in->h[(56 * h + 14 * a) * 32], 7168, abar);
                }
            };
            wait_count(&in->cnt[64 * h + 32 * (a >> 1) + 1 + (a & 1)], 64 * tag - FEW_H);
            STAMP(33);
            fetch();
            first_half();
            mbar_wait(abar, aph);
#pragma unroll
            for (int s = 0; s < 2; s++) {
                if (s) {
                    mbar_wait(fbar + 64, has_gu);
#pragma unroll
                    for (int j = 0; j < 14; j++) ldsm4t(af[j], slot2 + wo + j * 512);
                }
                uint4 hq[7];
#pragma unroll 1
                for (uint32_t it = 0;; spin_guard(it)) {
                    uint32_t bad = 0;
#pragma unroll
                    for (int j = 0; j < 7; j++) { hq[j] = lds128(ho + 512 * (7 * s + j)); bad = or_xor(bad, hq[j].w, tag); }
                    if (__all_sync(0xffffffffu, (bad & 1) == 0)) break;
                    fetch();
                    aph ^= 1;
                    mbar_wait(abar, aph);
                }
                if (s == 0) STAMP(15);
#pragma unroll
                for (int j = 0; j < 14; j++) {
                    const uint4 q = hq[j >> 1];
                    mma_v(d[j % 7], af[j], (j & 1) ? q.z : q.x, (j & 1) ? q.w : q.y);
                }
            }
#pragma unroll
            for (int j = 0; j < 4; j++) dacc[j] = ((d[0][j] + d[1][j]) + (d[2][j] + d[3][j])) + ((d[4][j] + d[5][j]) + d[6][j]);
        }
        STAMP(16);
        {
            st_async128(mapa(sb + OFF_XCH + 16 * tid, h ^ 1), __float_as_uint(dacc[0]), __float_as_uint(dacc[1]), __float_as_uint(dacc[2]), __float_as_uint(dacc[3]),
                        mapa(bar0 + 8 * B_RED, h ^ 1));
            sts128f(slot0 + 7680 + lane * 16, dacc);
            __syncwarp();
            if (elect_one()) mbar_arrive(bar0 + 8 * B_RED);
            mbar_wait(bar0 + 8 * B_RED, 0);
            const uint32_t b0 = sb + OFF_RING + 7680 + ro, b1 = sb + OFF_XCH + ro;
            const float y = ((lds32f(b0) + lds32f(b0 + 8192)) + (lds32f(b0 + 16384) + lds32f(b0 + 24576))) +
                            ((lds32f(b1) + lds32f(b1 + 512)) + (lds32f(b1 + 1024) + lds32f(b1 + 1536)));
            sts32f(red, bf_round(y) * sg);
            __syncwarp();
            if (elect_one()) mbar_arrive(bar0 + 8 * B_UPD);
        }
        STAMP(17); GSTAMP(29);
    }
}

typedef CUresult (*EncodeFn)(CUtensorMap*, CUtensorMapDataType, cuuint32_t, void*, const cuuint64_t*, const cuuint64_t*,
                             const cuuint32_t*, const cuuint32_t*, CUtensorMapInterleave, CUtensorMapSwizzle,
                             CUtensorMapL2promotion, CUtensorMapFloatOOBfill);

void make_map(EncodeFn enc, CUtensorMap* m, const void* ptr, uint64_t cols, uint64_t rows, uint32_t bc, uint32_t br,
              CUtensorMapSwizzle sw, CUtensorMapL2promotion pr) {
    cuuint64_t dims[2] = {cols, rows};
    cuuint64_t str[1] = {cols * 2};
    cuuint32_t box[2] = {bc, br};
    cuuint32_t es[2] = {1, 1};
    enc(m, CU_TENSOR_MAP_DATA_TYPE_BFLOAT16, 2, const_cast<void*>(ptr), dims, str, box, es, CU_TENSOR_MAP_INTERLEAVE_NONE, sw, pr,
        CU_TENSOR_MAP_FLOAT_OOB_FILL_NONE);
}
void make_perm_map(EncodeFn enc, CUtensorMap* m, const void* ptr, CUtensorMapL2promotion pr) {
    cuuint64_t dims[5] = {DM, 2, 4, 4, FF / 32};
    cuuint64_t str[4] = {DM * 2, 8 * DM * 2, 2 * DM * 2, 32 * DM * 2};
    cuuint32_t box[5] = {16, 2, 4, 4, 7};
    cuuint32_t es[5] = {1, 1, 1, 1, 1};
    enc(m, CU_TENSOR_MAP_DATA_TYPE_BFLOAT16, 5, const_cast<void*>(ptr), dims, str, box, es, CU_TENSOR_MAP_INTERLEAVE_NONE,
        CU_TENSOR_MAP_SWIZZLE_32B, pr, CU_TENSOR_MAP_FLOAT_OOB_FILL_NONE);
}
void make_tile_map(EncodeFn enc, CUtensorMap* m, const void* ptr) {
    cuuint64_t dims[4] = {DM, 4, 16, SEQ / 64};
    cuuint64_t str[3] = {16 * DM * 2, DM * 2, 64 * DM * 2};
    cuuint32_t box[4] = {16, 4, 2, 8};
    cuuint32_t es[4] = {1, 1, 1, 1};
    enc(m, CU_TENSOR_MAP_DATA_TYPE_BFLOAT16, 4, const_cast<void*>(ptr), dims, str, box, es, CU_TENSOR_MAP_INTERLEAVE_NONE,
        CU_TENSOR_MAP_SWIZZLE_32B, CU_TENSOR_MAP_L2_PROMOTION_NONE, CU_TENSOR_MAP_FLOAT_OOB_FILL_NONE);
}

}

extern "C" void kernel_launch(void* const* d_in, const int* in_sizes, int n_in, void* d_out, int out_size) {
    (void)in_sizes; (void)n_in; (void)out_size;
    static EncodeFn enc = nullptr;
    static void* scratch = nullptr;
    if (!enc) {
        void* fn = nullptr;
        cudaDriverEntryPointQueryResult q;
        cudaGetDriverEntryPoint("cuTensorMapEncodeTiled", &fn, cudaEnableDefault, &q);
        enc = (EncodeFn)fn;
        cudaGetSymbolAddress(&scratch, g_scratch);
        cudaFuncSetAttribute(fused_kernel, cudaFuncAttributeMaxDynamicSharedMemorySize, SMEM_BYTES);
    }
    Maps maps;
    make_tile_map(enc, &maps.u, d_in[0]);
    make_tile_map(enc, &maps.out, d_out);
    make_map(enc, &maps.wg, d_in[9], FF, DM, 64, 32, CU_TENSOR_MAP_SWIZZLE_128B, CU_TENSOR_MAP_L2_PROMOTION_L2_128B);
    make_map(enc, &maps.wu, d_in[10], FF, DM, 64, 32, CU_TENSOR_MAP_SWIZZLE_128B, CU_TENSOR_MAP_L2_PROMOTION_L2_128B);
    make_perm_map(enc, &maps.wd, d_in[11], CU_TENSOR_MAP_L2_PROMOTION_L2_64B);
    Ptrs p;
    p.sc = (Exchange*)scratch;
    p.u = (const __nv_bfloat16*)d_in[0];
    p.logA = (const __nv_bfloat16*)d_in[1];
    p.Aim = (const __nv_bfloat16*)d_in[2];
    p.Cre = (const __nv_bfloat16*)d_in[3];
    p.Cim = (const __nv_bfloat16*)d_in[4];
    p.ldt = (const __nv_bfloat16*)d_in[5];
    p.dsk = (const __nv_bfloat16*)d_in[6];
    p.wr = (const __nv_bfloat16*)d_in[8];
    p.out = (__nv_bfloat16*)d_out;
    p.zero = 0;
    fused_kernel<<<NCTA, NTHR, SMEM_BYTES, cudaStreamPerThread>>>(p, maps);
}
```

```cpp
#include <cuda_runtime.h>
#include <cuda_bf16.h>
#include <cuda_fp16.h>
#include <cuda.h>
#include <stdint.h>

namespace {

constexpr int SEQ = 2048, DM = 1024, NMODE = 128, FF = 3584;
constexpr int NCTA = 128, NTHR = 512;
constexpr int GU_CTAS = 112;
constexpr int NREP = 4;

constexpr int OFF_XT = 0;
constexpr int OFF_RING = 65536;
constexpr int OFF_PRIV = OFF_RING + 65536;
constexpr int OFF_VT = OFF_PRIV + 65536;
constexpr int VT_PAD = 32, VT_PLANE = VT_PAD + 2048, VT_PITCH = 2 * VT_PLANE, ROW_PITCH = 2064;
constexpr int OFF_BAR = OFF_VT + 8 * VT_PITCH;
constexpr int OFF_MISC = OFF_BAR + 384;
constexpr int OFF_XCH = OFF_MISC + 112;
constexpr int SMEM_BYTES = OFF_XCH + 2048;
constexpr int OFF_LN = OFF_RING + 7 * 8192;
constexpr int OFF_ST = OFF_RING + 6 * 8192;
static_assert(SMEM_BYTES <= 232448, "shared memory");

constexpr int B_ROW = 0, B_XT = 4, B_V = 5, B_LN = 6, B_SFREE = 7, B_XFREE = 8, B_OWN = 9, B_RED = 10, B_UPD = 11, B_ST = 12, B_RECV = 16, B_FREE = 20, B_FULL = 32, B_AUX = 44, NBAR = 48;

constexpr int T_DENSE = 60;
constexpr int T_PATCH = 2208;
constexpr int T_R2 = 2368;
constexpr int T_R3 = 3296;

constexpr int T_RED = 4032;
__device__ __forceinline__ bool slot_priv(int s) { return (uint32_t)(s - 6) < 4u; }
__device__ __forceinline__ uint32_t slot_off(int s) { return slot_priv(s) ? OFF_PRIV + 4096 + (s & 3) * 16384 : OFF_RING + (s < 6 ? s : s - 4) * 8192; }
__device__ __forceinline__ uint32_t tab_off(int w) { return OFF_PRIV + w * 8192 + (w & 1) * 4096; }

constexpr uint32_t SPIN_LIMIT = 1u << 20;
#define BB_UNROLL 2
constexpr int kBbUnroll = BB_UNROLL;
#define ST_T0 2150
#define ST_PER 294
#define ST_PER2 320
#define LN_PAUSE 0xf0
#define FEW_ST 10
#define FEW_H 24

struct Exchange {
    uint2 stat[SEQ];
    uint4 h[GU_CTAS * 32];
    uint32_t cnt[4 * 32];
};
__device__ __align__(128) Exchange g_scratch[NREP];

struct Ptrs {
    const __nv_bfloat16 *logA, *Aim, *Cre, *Cim, *ldt, *u;
    const __nv_bfloat16 *dsk, *wr;
    Exchange* sc;
    __nv_bfloat16* out;
    uint32_t zero;
};
struct Maps {
    CUtensorMap u, out, wg, wu, wd;
};

#define STAMP(i) do { } while (0)
#define GSTAMP(i) do { } while (0)

__device__ __forceinline__ uint32_t s_u32(const void* p) { return (uint32_t)__cvta_generic_to_shared(p); }
__device__ __forceinline__ void mbar_init(uint32_t b, uint32_t n) {
    asm volatile("mbarrier.init.shared::cta.b64 [%0], %1;" ::"r"(b), "r"(n) : "memory");
}
__device__ __forceinline__ void mbar_expect_tx(uint32_t b, uint32_t bytes) {
    asm volatile("mbarrier.arrive.expect_tx.shared::cta.b64 _, [%0], %1;" ::"r"(b), "r"(bytes) : "memory");
}
__device__ __forceinline__ void mbar_arrive(uint32_t b) {
    asm volatile("mbarrier.arrive.shared::cta.b64 _, [%0];" ::"r"(b) : "memory");
}
__device__ __forceinline__ void mbar_arrive_n(uint32_t b, uint32_t n) {
    asm volatile("mbarrier.arrive.shared::cta.b64 _, [%0], %1;" ::"r"(b), "r"(n) : "memory");
}
__device__ __forceinline__ void mbar_arrive_peer(uint32_t b_cluster) {
    asm volatile("mbarrier.arrive.relaxed.cluster.shared::cluster.b64 _, [%0];" ::"r"(b_cluster) : "memory");
}
__device__ __forceinline__ void mbar_wait(uint32_t b, uint32_t parity) {
    asm volatile("{\n\t.reg .pred p;\n\t.reg .u32 c;\n\tmov.u32 c, 0;\n"
                 "W:\n\tmbarrier.try_wait.parity.shared::cta.b64 p, [%0], %1;\n\t@p bra D;\n\t"
                 "add.u32 c, c, 1;\n\tsetp.lt.u32 p, c, 1048576;\n\t@p bra W;\n\ttrap;\nD:\n\t}"
                 ::"r"(b), "r"(parity) : "memory");
}
__device__ __forceinline__ bool elect_one() {
    uint32_t p;
    asm volatile("{ .reg .pred P; elect.sync _|P, 0xffffffff; selp.u32 %0, 1, 0, P; }" : "=r"(p));
    return p != 0;
}
__device__ __forceinline__ uint32_t mapa(uint32_t a, uint32_t rank) {
    uint32_t r;
    asm("mapa.shared::cluster.u32 %0, %1, %2;" : "=r"(r) : "r"(a), "r"(rank));
    return r;
}
__device__ __forceinline__ void cluster_arrive() { asm volatile("barrier.cluster.arrive.relaxed.aligned;" ::: "memory"); }
__device__ __forceinline__ void cluster_wait() { asm volatile("barrier.cluster.wait.acquire.aligned;" ::: "memory"); }
__device__ __forceinline__ void tma_load_2d(uint32_t dst, const CUtensorMap* m, int c0, int c1, uint32_t bar) {
    asm volatile("cp.async.bulk.tensor.2d.shared::cluster.global.mbarrier::complete_tx::bytes [%0], [%1, {%3, %4}], [%2];"
                 ::"r"(dst), "l"(m), "r"(bar), "r"(c0), "r"(c1) : "memory");
}
__device__ __forceinline__ void tma_load_perm(uint32_t dst, const CUtensorMap* m, int c0, int blk, uint32_t bar) {
    asm volatile("cp.async.bulk.tensor.5d.shared::cluster.global.mbarrier::complete_tx::bytes [%0], [%1, {%3, %4, %4, %4, %5}], [%2];"
                 ::"r"(dst), "l"(m), "r"(bar), "r"(c0), "r"(0), "r"(blk) : "memory");
}
__device__ __forceinline__ void tma_load_tile(uint32_t dst, const CUtensorMap* m, int c0, int c2, int c3, uint32_t bar) {
    asm volatile("cp.async.bulk.tensor.4d.shared::cluster.global.mbarrier::complete_tx::bytes.multicast::cluster [%0], [%1, {%3, %4, %5, %6}], [%2], %7;"
                 ::"r"(dst), "l"(m), "r"(bar), "r"(c0), "r"(0), "r"(c2), "r"(c3), "h"((uint16_t)3) : "memory");
}
__device__ __forceinline__ void tma_store_tile(const CUtensorMap* m, uint32_t src, int c0, int c2, int c3) {
    asm volatile("cp.async.bulk.tensor.4d.global.shared::cta.bulk_group [%0, {%2, %3, %4, %5}], [%1];"
                 ::"l"(m), "r"(src), "r"(c0), "r"(0), "r"(c2), "r"(c3) : "memory");
    asm volatile("cp.async.bulk.commit_group;" ::: "memory");
}
__device__ __forceinline__ void bulk_g2s(uint32_t dst, const void* src, uint32_t bytes, uint32_t bar) {
    asm volatile("cp.async.bulk.shared::cluster.global.mbarrier::complete_tx::bytes [%0], [%1], %2, [%3];"
                 ::"r"(dst), "l"(src), "r"(bytes), "r"(bar) : "memory");
}
__device__ __forceinline__ void st_async128(uint32_t dst_cluster, uint32_t x, uint32_t y, uint32_t z, uint32_t w, uint32_t bar_cluster) {
    asm volatile("st.async.weak.shared::cluster.mbarrier::complete_tx::bytes.v4.b32 [%0], {%1,%2,%3,%4}, [%5];"
                 ::"r"(dst_cluster), "r"(x), "r"(y), "r"(z), "r"(w), "r"(bar_cluster) : "memory");
}
__device__ __forceinline__ void fence_async() { asm volatile("fence.proxy.async.shared::cta;" ::: "memory"); }
__device__ __forceinline__ void named_sync(int id, int n) { asm volatile("bar.sync %0, %1;" ::"r"(id), "r"(n) : "memory"); }

__device__ __forceinline__ void ldsm4(uint32_t* r, uint32_t a) {
    asm volatile("ldmatrix.sync.aligned.m8n8.x4.shared.b16 {%0,%1,%2,%3}, [%4];"
                 : "=r"(r[0]), "=r"(r[1]), "=r"(r[2]), "=r"(r[3]) : "r"(a));
}
__device__ __forceinline__ void ldsm4t(uint32_t* r, uint32_t a) {
    asm volatile("ldmatrix.sync.aligned.m8n8.x4.trans.shared.b16 {%0,%1,%2,%3}, [%4];"
                 : "=r"(r[0]), "=r"(r[1]), "=r"(r[2]), "=r"(r[3]) : "r"(a));
}
__device__ __forceinline__ void stsm4t(uint32_t a, uint32_t x, uint32_t y, uint32_t z, uint32_t w) {
    asm volatile("stmatrix.sync.aligned.m8n8.x4.trans.shared.b16 [%0], {%1,%2,%3,%4};"
                 ::"r"(a), "r"(x), "r"(y), "r"(z), "r"(w) : "memory");
}
__device__ __forceinline__ uint32_t lds32(uint32_t a) { uint32_t v; asm volatile("ld.shared.u32 %0, [%1];" : "=r"(v) : "r"(a)); return v; }
__device__ __forceinline__ float lds32f(uint32_t a) { float v; asm volatile("ld.shared.f32 %0, [%1];" : "=f"(v) : "r"(a)); return v; }
__device__ __forceinline__ uint2 lds64(uint32_t a) { uint2 v; asm volatile("ld.shared.v2.u32 {%0,%1}, [%2];" : "=r"(v.x), "=r"(v.y) : "r"(a)); return v; }
__device__ __forceinline__ uint4 lds128(uint32_t a) {
    uint4 v; asm volatile("ld.shared.v4.u32 {%0,%1,%2,%3}, [%4];" : "=r"(v.x), "=r"(v.y), "=r"(v.z), "=r"(v.w) : "r"(a)); return v;
}
__device__ __forceinline__ uint4 lds128v(uint32_t a) {
    uint4 v; asm volatile("ld.volatile.shared.v4.u32 {%0,%1,%2,%3}, [%4];" : "=r"(v.x), "=r"(v.y), "=r"(v.z), "=r"(v.w) : "r"(a)); return v;
}
__device__ __forceinline__ uint32_t or_xor(uint32_t a, uint32_t b, uint32_t c) {
    uint32_t r; asm("lop3.b32 %0, %1, %2, %3, 0xf6;" : "=r"(r) : "r"(a), "r"(b), "r"(c)); return r;
}
__device__ __forceinline__ float4 lds128f(uint32_t a) {
    float4 v; asm volatile("ld.shared.v4.f32 {%0,%1,%2,%3}, [%4];" : "=f"(v.x), "=f"(v.y), "=f"(v.z), "=f"(v.w) : "r"(a)); return v;
}
__device__ __forceinline__ void sts32(uint32_t a, uint32_t v) { asm volatile("st.shared.u32 [%0], %1;" ::"r"(a), "r"(v) : "memory"); }
__device__ __forceinline__ void sts32f(uint32_t a, float v) { asm volatile("st.shared.f32 [%0], %1;" ::"r"(a), "f"(v) : "memory"); }
__device__ __forceinline__ void sts64(uint32_t a, uint32_t x, uint32_t y) { asm volatile("st.shared.v2.u32 [%0], {%1,%2};" ::"r"(a), "r"(x), "r"(y) : "memory"); }
__device__ __forceinline__ void sts64f(uint32_t a, float x, float y) { asm volatile("st.shared.v2.f32 [%0], {%1,%2};" ::"r"(a), "f"(x), "f"(y) : "memory"); }
__device__ __forceinline__ void sts128(uint32_t a, uint32_t x, uint32_t y, uint32_t z, uint32_t w) {
    asm volatile("st.shared.v4.u32 [%0], {%1,%2,%3,%4};" ::"r"(a), "r"(x), "r"(y), "r"(z), "r"(w) : "memory");
}
__device__ __forceinline__ void sts128f(uint32_t a, const float* v) {
    asm volatile("st.shared.v4.f32 [%0], {%1,%2,%3,%4};" ::"r"(a), "f"(v[0]), "f"(v[1]), "f"(v[2]), "f"(v[3]) : "memory");
}
__device__ __forceinline__ uint4 ldg128(const void* p) {
    uint4 v; asm volatile("ld.global.nc.L1::no_allocate.v4.u32 {%0,%1,%2,%3}, [%4];" : "=r"(v.x), "=r"(v.y), "=r"(v.z), "=r"(v.w) : "l"(p)); return v;
}
__device__ __forceinline__ uint2 ldg64(const void* p) {
    uint2 v; asm volatile("ld.global.nc.L1::no_allocate.v2.u32 {%0,%1}, [%2];" : "=r"(v.x), "=r"(v.y) : "l"(p)); return v;
}
__device__ __forceinline__ uint32_t ldg16(const void* p) {
    uint32_t v; asm volatile("ld.global.nc.u16 %0, [%1];" : "=r"(v) : "l"(p)); return v;
}
__device__ __forceinline__ uint2 ld_relaxed_64(const void* p) {
    uint2 v; asm volatile("ld.relaxed.gpu.global.v2.u32 {%0,%1}, [%2];" : "=r"(v.x), "=r"(v.y) : "l"(p) : "memory"); return v;
}
__device__ __forceinline__ uint32_t ld_relaxed_32(const void* p) {
    uint32_t v; asm volatile("ld.relaxed.gpu.global.u32 %0, [%1];" : "=r"(v) : "l"(p) : "memory"); return v;
}
__device__ __forceinline__ void st_relaxed_64(void* p, uint32_t x, uint32_t y) {
    asm volatile("st.relaxed.gpu.global.v2.u32 [%0], {%1,%2};" ::"l"(p), "r"(x), "r"(y) : "memory");
}
__device__ __forceinline__ void st_relaxed_32(void* p, uint32_t v) {
    asm volatile("st.relaxed.gpu.global.u32 [%0], %1;" ::"l"(p), "r"(v) : "memory");
}
__device__ __forceinline__ void red_add(void* p, uint32_t v) { asm volatile("red.relaxed.gpu.global.add.u32 [%0], %1;" ::"l"(p), "r"(v) : "memory"); }
__device__ __forceinline__ uint32_t now_ns() { uint32_t t; asm volatile("mov.u32 %0, %%globaltimer_lo;" : "=r"(t) :: "memory"); return t; }
__device__ __forceinline__ void sleep_until(uint32_t t) {
#pragma unroll 1
    for (int left; (left = (int)(t - now_ns())) > 0;) __nanosleep(left >> 1);
}
__device__ __forceinline__ void spin_guard(uint32_t& it) { if (++it > SPIN_LIMIT) __trap(); }
__device__ __forceinline__ void wait_count(const uint32_t* p, uint32_t target) {
#pragma unroll 1
    for (uint32_t it = 0; __any_sync(0xffffffffu, (int)(ld_relaxed_32(p) - target) < 0); spin_guard(it)) { }
}
__device__ __forceinline__ void mma_bf16_k8(float* c, uint32_t a0, uint32_t a1, uint32_t b0) {
    asm("mma.sync.aligned.m16n8k8.row.col.f32.bf16.bf16.f32 {%0,%1,%2,%3}, {%4,%5}, {%6}, {%0,%1,%2,%3};"
                 : "+f"(c[0]), "+f"(c[1]), "+f"(c[2]), "+f"(c[3]) : "r"(a0), "r"(a1), "r"(b0));
}
__device__ __forceinline__ void mma_v(float* c, const uint32_t* a, uint32_t b0, uint32_t b1) {
    asm volatile("mma.sync.aligned.m16n8k16.row.col.f32.bf16.bf16.f32 {%0,%1,%2,%3}, {%4,%5,%6,%7}, {%8,%9}, {%0,%1,%2,%3};"
                 : "+f"(c[0]), "+f"(c[1]), "+f"(c[2]), "+f"(c[3]) : "r"(a[0]), "r"(a[1]), "r"(a[2]), "r"(a[3]), "r"(b0), "r"(b1));
}
__device__ __forceinline__ void mma_bf16_z(float* c, uint32_t a0, uint32_t a1, uint32_t a2, uint32_t a3, uint32_t b0, uint32_t b1) {
    asm volatile("mma.sync.aligned.m16n8k16.row.col.f32.bf16.bf16.f32 {%0,%1,%2,%3}, {%4,%5,%6,%7}, {%8,%9}, {%10,%10,%10,%10};"
        : "=f"(c[0]), "=f"(c[1]), "=f"(c[2]), "=f"(c[3]) : "r"(a0), "r"(a1), "r"(a2), "r"(a3), "r"(b0), "r"(b1), "f"(0.f));
}
__device__ __forceinline__ void mma_f16(float* c, uint32_t a0, uint32_t a1, uint32_t a2, uint32_t a3, uint32_t b0, uint32_t b1) {
    asm("mma.sync.aligned.m16n8k16.row.col.f32.f16.f16.f32 {%0,%1,%2,%3}, {%4,%5,%6,%7}, {%8,%9}, {%0,%1,%2,%3};"
                 : "+f"(c[0]), "+f"(c[1]), "+f"(c[2]), "+f"(c[3]) : "r"(a0), "r"(a1), "r"(a2), "r"(a3), "r"(b0), "r"(b1));
}
__device__ __forceinline__ uint32_t pack_bf16(float lo, float hi) {
    uint32_t r; asm("cvt.rn.bf16x2.f32 %0, %1, %2;" : "=r"(r) : "f"(hi), "f"(lo)); return r;
}
__device__ __forceinline__ uint32_t pack_v(float lo, float hi) {
    uint32_t r; asm volatile("cvt.rn.bf16x2.f32 %0, %1, %2;" : "=r"(r) : "f"(hi), "f"(lo)); return r;
}
__device__ __forceinline__ uint32_t pack_w(float lo, float hi) {
    uint32_t r; asm volatile("cvt.rn.satfinite.bf16x2.f32 %0, %1, %2;" : "=r"(r) : "f"(hi), "f"(lo)); return r;
}
template <int N> __device__ __forceinline__ uint32_t after_all(const uint32_t (&f)[N][4], uint32_t zero) {
    uint32_t d[3] = {0, 0, 0};
#pragma unroll
    for (int i = 0; i < N; i++) d[i % 3] |= f[i][3];
    return (d[0] | d[1] | d[2]) & zero;
}
__device__ __forceinline__ void pin(uint32_t& x) { asm volatile("" : "+r"(x)); }
template <class T> __device__ __forceinline__ void pin(T*& x) { asm volatile("" : "+l"(x)); }
__device__ __forceinline__ uint32_t pack_f16(float lo, float hi) {
    uint32_t r; asm("cvt.rn.f16x2.f32 %0, %1, %2;" : "=r"(r) : "f"(hi), "f"(lo)); return r;
}
__device__ __forceinline__ float bf_lo(uint32_t v) { return __uint_as_float(v << 16); }
__device__ __forceinline__ float bf_hi(uint32_t v) { return __uint_as_float(v & 0xffff0000u); }
__device__ __forceinline__ float bf_round(float x) { return __uint_as_float(pack_bf16(0.f, x)); }
__device__ __forceinline__ uint32_t badd2(uint32_t a, uint32_t b) { uint32_t r; asm("add.rn.bf16x2 %0, %1, %2;" : "=r"(r) : "r"(a), "r"(b)); return r; }
__device__ __forceinline__ uint32_t bsub2_lo(uint32_t a, uint32_t b) {
    uint32_t r; asm("{ .reg .b16 m, h; .reg .b32 m2; mov.b32 {m, h}, %2; mov.b32 m2, {m, m}; sub.rn.bf16x2 %0, %1, m2; }" : "=r"(r) : "r"(a), "r"(b)); return r;
}
__device__ __forceinline__ uint32_t bmax2(uint32_t a, uint32_t b) { uint32_t r; asm("max.bf16x2 %0, %1, %2;" : "=r"(r) : "r"(a), "r"(b)); return r; }
__device__ __forceinline__ uint32_t normalize2(uint32_t x, uint32_t s0, uint32_t s1) {
    uint32_t r;
    asm("{ .reg .b16 m, h, l, k; .reg .b32 m2, h2, l2, d, t;\n\t"
        "mov.b32 {m, h}, %2; mov.b32 {l, k}, %3; mov.b32 m2, {m, m}; mov.b32 h2, {h, h}; mov.b32 l2, {l, l};\n\t"
        "sub.rn.bf16x2 d, %1, m2; mul.rn.bf16x2 t, d, l2; fma.rn.bf16x2 %0, d, h2, t; }" : "=r"(r) : "r"(x), "r"(s0), "r"(s1));
    return r;
}
__device__ __forceinline__ float rcpf(float x) { float r; asm("rcp.approx.ftz.f32 %0, %1;" : "=f"(r) : "f"(x)); return r; }
__device__ __forceinline__ float sqrtaf(float x) { float r; asm("sqrt.approx.ftz.f32 %0, %1;" : "=f"(r) : "f"(x)); return r; }
__device__ __forceinline__ float ex2f(float x) { float r; asm("ex2.approx.ftz.f32 %0, %1;" : "=f"(r) : "f"(x)); return r; }

__device__ __forceinline__ int tok_off(int t) { return ((t >> 3) & 1) * VT_PLANE + (t >> 4) * 16 + (t & 7) * 2; }

__device__ __forceinline__ uint32_t unorder_key(uint32_t k16) { return k16 ^ ((k16 & 0x8000u) ? 0x8000u : 0xffffu); }

struct cplx { float r, i; };
struct hc { uint32_t r, i; };
template <bool CONJ> __device__ __forceinline__ cplx csq(cplx a) {
    float im;
    asm("{ .reg .f32 t; mul.ftz.f32 t, %1, %2; mul.ftz.f32 %0, t, 0f40000000; }" : "=f"(im) : "f"(CONJ ? -a.r : a.r), "f"(a.i));
    return {fmaf(a.r, a.r, -(a.i * a.i)), im};
}
__device__ __forceinline__ cplx cexpp(float a2, float ai) {
    float m = ex2f(a2), s, c;
    __sincosf(ai, &s, &c);
    return {m * c, m * s};
}
__device__ __forceinline__ __half2 as_h2(uint32_t x) { return *reinterpret_cast<__half2*>(&x); }
__device__ __forceinline__ uint32_t as_u(__half2 x) { return *reinterpret_cast<uint32_t*>(&x); }
__device__ __forceinline__ hc hmul(hc a, hc b) {
    return {as_u(__hfma2(as_h2(a.r), as_h2(b.r), __hneg2(__hmul2(as_h2(a.i), as_h2(b.i))))),
            as_u(__hfma2(as_h2(a.r), as_h2(b.i), __hmul2(as_h2(a.i), as_h2(b.r))))};
}
__device__ __forceinline__ hc hpack(cplx a, cplx b) { return {pack_f16(a.r, b.r), pack_f16(a.i, b.i)}; }
__device__ __forceinline__ void sts16(uint32_t a, uint32_t v) { asm volatile("st.shared.u16 [%0], %1;" ::"r"(a), "r"(v) : "memory"); }

struct KgenAddr {
    uint32_t l, h, m2, m3, m4, z, w, wz;
    __device__ __forceinline__ KgenAddr(uint32_t scr, int lane) {
        const int g = lane >> 2, t = lane & 3;
        const uint32_t rec = scr + t * 480;
        l = rec + 16 * g; h = rec + 128 + 8 * g; m2 = rec + 192 + 8 * (g & 1); m3 = rec + 208 + 4 * (g & 2); m4 = rec + 224 + 2 * (g & 4);
        z = scr + 7680 + 16 * t; w = scr + 240 * lane; wz = scr + 7680 + 8 * lane;
        pin(l); pin(h); pin(m2); pin(m3); pin(m4); pin(z); pin(w); pin(wz);
    }
    __device__ __forceinline__ uint32_t any() const { return (l | h | m2) | (m3 | m4 | z) | (w | wz); }
};
template <class Hook, class Hook2>
__device__ __forceinline__ void kgen(const KgenAddr& ad, uint32_t tab, int lane, uint2 la, uint2 aim, uint2 cre, uint2 cim, float dt, float skip, int dch, Hook main_done, Hook2 half_done) {
    const int g = lane >> 2, t = lane & 3;
    const float dt2 = 2.f * dt;
    const uint32_t am = bmax2(bmax2(cre.x & 0x7fff7fffu, cre.y & 0x7fff7fffu), bmax2(cim.x & 0x7fff7fffu, cim.y & 0x7fff7fffu));
    const float mx = dt2 * fmaxf(bf_lo(am), bf_hi(am));
    const uint32_t eb = min(max(__reduce_max_sync(0xffffffffu, __float_as_uint(mx)) >> 23, 1u), 252u);
    const float cscale = dt2 * __uint_as_float((253u - eb) << 23);
    const float scale_inv = __uint_as_float((eb + 1u) << 23);
    float k0 = (bf_lo(cre.x) + bf_hi(cre.x)) + (bf_lo(cre.y) + bf_hi(cre.y));
#pragma unroll
    for (int o = 16; o; o >>= 1) k0 += __shfl_xor_sync(0xffffffffu, k0, o);
    const float ndt = -1.4426950408889634f * dt;
    STAMP(40);

    float acc[5][4];
#pragma unroll
    for (int i = 0; i < 5; i++) { acc[i][0] = acc[i][1] = acc[i][2] = acc[i][3] = 0.f; }

#pragma unroll kBbUnroll
    for (int bb = 0; bb < 2; bb++) {
        cplx z[2][11], cz[2];
#pragma unroll
        for (int e = 0; e < 2; e++) {
            const float lg = e ? bf_hi(la.x) : bf_lo(la.x), ai = (e ? bf_hi(aim.x) : bf_lo(aim.x)) * dt;
            const float cr = (e ? bf_hi(cre.x) : bf_lo(cre.x)) * cscale, ci = (e ? bf_hi(cim.x) : bf_lo(cim.x)) * cscale;
            const float a2 = bf_round(ex2f(lg * 1.4426950408889634f)) * ndt;
            z[e][0] = cexpp(a2, ai);
            z[e][5] = cexpp(a2 * 32.f, ai * -32.f);
#pragma unroll
            for (int i = 1; i < 11; i++) if (i != 5) z[e][i] = (i == 3 || i == 7) ? csq<true>(z[e][i - 1]) : csq<false>(z[e][i - 1]);
            cz[e] = {fmaf(cr, z[e][0].r, -(ci * z[e][0].i)), fmaf(cr, z[e][0].i, ci * z[e][0].r)};
        }
        la.x = la.y; aim.x = aim.y; cre.x = cre.y; cim.x = cim.y;
        const hc z1 = hpack(z[0][0], z[1][0]), z2 = hpack(z[0][1], z[1][1]), z4 = hpack(z[0][2], z[1][2]);
        hc L[8], H[8];
        L[1] = hpack(z[0][3], z[1][3]); L[2] = hpack(z[0][4], z[1][4]); L[4] = hpack(z[0][5], z[1][5]);
        const hc y64 = hpack(z[0][6], z[1][6]), z128 = hpack(z[0][7], z[1][7]), z256 = hpack(z[0][8], z[1][8]);
        const hc z512 = hpack(z[0][9], z[1][9]), z1024 = hpack(z[0][10], z[1][10]);
        H[0] = hpack(cz[0], cz[1]);
        H[1] = hmul(H[0], z1); H[2] = hmul(H[0], z2); H[3] = hmul(H[1], z2);
        L[3] = hmul(L[1], L[2]);
#pragma unroll
        for (int i = 0; i < 4; i++) { H[4 + i] = hmul(H[i], z4); if (i) L[4 + i] = hmul(L[i], L[4]); }
        __syncwarp();
        sts128(ad.w, 0x3c003c00u, y64.r, 0u, y64.i);
#pragma unroll
        for (int i = 1; i < 8; i++) { const hc q = hmul(L[i], y64); sts128(ad.w + 16 * i, L[i].r, q.r, L[i].i, q.i); }
#pragma unroll
        for (int i = 0; i < 4; i++) sts128(ad.w + 128 + 16 * i, H[2 * i].r, H[2 * i].i, H[2 * i + 1].r, H[2 * i + 1].i);
        {
            const hc a = hmul(z256, z1), b = hmul(z256, z128), c = hmul(z256, z2), d = hmul(z512, z4);
            sts128(ad.w + 192, a.r, a.i, b.r, b.i);
            sts128(ad.w + 208, c.r, c.i, z512.r, z512.i);
            sts128(ad.w + 224, d.r, d.i, z1024.r, z1024.i);
            sts64(ad.wz, z128.r, z128.i);
        }
        __syncwarp();

#pragma unroll
        for (int k2 = 0; k2 < 4; k2++) {
#pragma unroll
            for (uint32_t s = 0; s < 2; s++) {
                const uint32_t o = k2 * 1920 + s * 240;
                const uint4 l = lds128(ad.l + o);
                const uint2 h0 = lds64(ad.h + o), m2 = lds64(ad.m2 + o), m3 = lds64(ad.m3 + o), m4 = lds64(ad.m4 + o), mz = lds64(ad.z + k2 * 64 + s * 8);
                const hc H0 = {h0.x, h0.y};
                const hc H1 = hmul(H0, {mz.x, mz.y}), H2 = hmul(H0, {m2.x, m2.y}), H3 = hmul(H2, {m3.x, m3.y}), H4 = hmul(H3, {m4.x, m4.y});
                mma_f16(acc[0], l.x, l.y, l.z, l.w, H0.r, H0.i);
                mma_f16(acc[1], l.x, l.y, l.z, l.w, H1.r, H1.i);
                mma_f16(acc[2], l.x, l.y, l.z, l.w, H2.r, H2.i);
                mma_f16(acc[3], l.x, l.y, l.z, l.w, H3.r, H3.i);
                mma_f16(acc[4], l.x, l.y, l.z, l.w, H4.r, H4.i);
            }
        }

        if (bb == 0) half_done();
    }
    __syncwarp();
    main_done();

#pragma unroll
    for (int i = 0; i < 4; i++) sts128(tab + 2048 + 512 * i + 16 * lane, 0, 0, 0, 0);
    if (lane < 15) sts32(tab + 4 * lane, 0);
    __syncwarp();
    const uint32_t d0 = tab + T_DENSE + 4 + 8 * lane, src = (lane + 31) & 31;
    const uint32_t p0 = pack_bf16(fmaf(k0, dt2, skip), 0.f);
    uint32_t prev = p0;
#pragma unroll
    for (int i = 0; i < 4; i++) {
        const uint32_t pk = pack_bf16(acc[i >> 1][2 * (i & 1) + 1] * scale_inv, acc[i >> 1][2 * (i & 1)] * scale_inv);
        sts64(d0 + 256 * i, __byte_perm(pk, __shfl_sync(0xffffffffu, lane == 31 ? prev : pk, src), 0x5432), pk);
        prev = pk;
    }
    const uint32_t w0 = pack_bf16(acc[2][0] * scale_inv, acc[2][1] * scale_inv), w1 = pack_bf16(acc[2][2] * scale_inv, acc[2][3] * scale_inv);
    const uint32_t sa = (lane & 1) ? 0x5410u : 0x5454u, sb2 = (lane & 1) ? 0x1010u : 0x5410u;
#pragma unroll
    for (int hf = 0; hf < 2; hf++) {
        const uint32_t w = hf ? w1 : w0;
        const uint32_t pv = __shfl_sync(0xffffffffu, lane != 31 ? w : hf ? w0 : __byte_perm(prev, w1, 0x5410), src);
        sts64(d0 + 1024 + 256 * hf, __byte_perm(w, pv, sa), __byte_perm(w, pv, sb2));
        sts64(d0 + 1536 + 256 * hf, __byte_perm(w, pv, sa + 0x2222u), __byte_perm(w, pv, sb2 + 0x2222u));
    }
    const uint32_t d3 = tab + T_R2 + 160 + 320 * (t & 1) + 16 * (g >> 1) + 8 * (g & 1) + 4 * (t >> 1), d3n = d3 + (g >= 6 ? 32 : 0);
    const uint32_t d4 = tab + T_R3 + 80 + 160 * t + 4 * g, d4n = d4 + (g >= 6 ? 16 : 0);
    uint32_t p3;
#pragma unroll
    for (int hf = 0; hf < 2; hf++)
#pragma unroll
        for (int e = 0; e < 2; e++) {
            const float v3 = acc[3][2 * hf + e] * scale_inv;
            const uint32_t p4 = pack_bf16(acc[4][2 * hf + e] * scale_inv, 0.f);
            p3 = pack_bf16(v3, v3);
            sts16(d3 + 64 * hf + 160 * e, p3);
            sts16((hf ? d3n : d3) + 64 * hf + 160 * e + 18, p3);
            sts16(d4 + 32 * hf + 80 * e, p4);
            sts16((hf ? d4n : d4) + 32 * hf + 80 * e + 10, p4);
        }
    if (lane == 31) {
        const uint32_t k512 = __byte_perm(w1, 0, 0x3232);
        sts32(tab + T_DENSE, p0);
        sts64(tab + T_DENSE + 4 * 513, k512, k512); sts16(tab + T_DENSE + 4 * 515 + 2, k512);
        sts16(tab + T_PATCH + 4 * 17, p3); sts32(tab + T_PATCH + 4 * 18, p3); sts16(tab + T_PATCH + 4 * 19 + 2, p3);
    }
    __syncwarp();
}

__device__ __forceinline__ void load_toep(uint32_t* a, uint32_t p, uint32_t pz) {
    a[0] = lds32(p); a[1] = lds32(p + 32); a[2] = lds32(pz - 32); a[3] = lds32(pz);
}
template <int F>
__device__ __forceinline__ void ffa_step(float (&acc)[16][4], float (&W)[8][4], uint32_t (&R)[8][4], uint32_t (&A)[4][4],
                                         uint32_t va, uint32_t vmin, uint32_t pb, uint32_t pz) {
    constexpr int S = F ^ 1;
    auto load = [&](int sh) {
#pragma unroll
        for (int i = S; i < 8; i += 2) ldsm4(R[i], i == 0 ? max(va - 16 * sh, vmin) : va - 16 * sh + i * 128);
#pragma unroll
        for (int k = S; k < 4; k += 2) load_toep(A[k], pb + 64 * sh + k * 512, pz + 64 * sh + k * 512);
    };
    auto prod = [&](int par, int dst) {
#pragma unroll
        for (int k = 0; k < 2; k++)
#pragma unroll
            for (int m = k; m < 8; m++) {
                const uint32_t* x = &R[2 * ((m - k) & 3) + par][2 * ((m - k) >> 2)];
                mma_v(dst == 1 ? W[m] : acc[2 * m + (dst >> 1)], A[2 * k + par], x[0], x[1]);
            }
    };
    load(0);
    prod(F, F);
    prod(S, S);
#pragma unroll
    for (int i = 0; i < 8; i++) A[(i >> 2) * 2 + F][i & 3] = badd2(A[(i >> 2) * 2][i & 3], A[(i >> 2) * 2 + 1][i & 3]);
#pragma unroll
    for (int i = 0; i < 16; i++) R[(i >> 2) * 2 + F][i & 3] = badd2(R[(i >> 2) * 2][i & 3], R[(i >> 2) * 2 + 1][i & 3]);
    load(1);
    prod(F, 2);
}
struct DenseTaps {
    uint32_t A[4][4], E[4], F[4], G[4];
    __device__ __forceinline__ DenseTaps(uint32_t pb, uint32_t pz) {
        constexpr int PP = T_PATCH - T_DENSE + 56;
        load_toep(E, pb + 2048, pz + 2048);
        load_toep(F, pb + PP, pz + PP);
        G[0] = lds32(pz + 2048 + 32); G[1] = lds32(pb + 2048 + 64); G[2] = lds32(pz + PP + 32); G[3] = lds32(pb + PP + 64);
    }
};
__device__ __forceinline__ uint32_t dense_phase(float (&acc)[16][4], uint32_t vmin, uint32_t va, uint32_t vo, uint32_t pb, DenseTaps& tp, uint32_t zero) {
    uint32_t R[8][4];
    uint32_t pz = pb + zero;
    {
        uint32_t H[4][4];
#pragma unroll
        for (int i = 0; i < 4; i++) ldsm4(H[i], vo + i * 256);
#pragma unroll
        for (int i = 0; i < 8; i++) ldsm4(R[i], va + i * 128);
#pragma unroll
        for (int i = 0; i < 4; i += 2) load_toep(tp.A[i], pb + 512 * i, pz + 512 * i);
#pragma unroll
        for (int i = 0; i < 4; i++) mma_bf16_k8(acc[i + 4], tp.G[0], tp.G[1], H[i >> 1][2 * (i & 1) + 1]);
#pragma unroll
        for (int i = 0; i < 8; i++) mma_v(acc[i + 8], tp.G, H[i >> 1][2 * (i & 1)], H[i >> 1][2 * (i & 1) + 1]);
#pragma unroll
        for (int i = 0; i < 12; i++) mma_v(acc[i + 4], tp.E, R[i & 7][2 * (i >> 3)], R[i & 7][2 * (i >> 3) + 1]);
#pragma unroll
        for (int i = 0; i < 8; i++) mma_v(acc[i + 8], tp.F, R[i][0], R[i][1]);
    }
    float W[8][4];
#pragma unroll
    for (int i = 0; i < 32; i++) { W[i >> 2][i & 3] = 0.f; if (i >= 8) acc[2 * (i >> 2) + 1][i & 3] += acc[2 * (i >> 2)][i & 3]; }
#pragma unroll 1
    for (int rho = 0; rho < 8; rho += 2) {
        ffa_step<0>(acc, W, R, tp.A, va, vmin, pb, pz);
        ffa_step<1>(acc, W, R, tp.A, va - 16, vmin, pb + 64, pz + 64);
        pb += 128; pz += 128; va -= 32;
    }
#pragma unroll
    for (int i = 0; i < 32; i++) {
        const int m = i >> 2, j = i & 3;
        acc[2 * m + 1][j] = (acc[2 * m + 1][j] - acc[2 * m][j]) - W[m][j];
        if (m) acc[2 * m][j] += W[m - 1][j];
    }
    return __float_as_uint(W[7][0]) & zero;
}
__device__ __forceinline__ uint32_t ones2(int c, int lo, int hi) {
    return (((uint32_t)(c - lo) <= (uint32_t)(hi - lo)) ? 1u : 0u) | (((uint32_t)(c + 1 - lo) <= (uint32_t)(hi - lo)) ? 0x10000u : 0u);
}
__device__ __forceinline__ uint32_t box_bits(int lane) {
    const int d = 2 * (lane & 3) - (lane >> 2);
    auto four = [&](int L1, int H1, int L2, int H2) { return ones2(d, L1, H1) | ones2(d, L2, H2) << 1 | ones2(d + 8, L1, H1) << 2 | ones2(d + 8, L2, H2) << 3; };
    return four(5, 7, 0, 4) | four(1, 7, 0, 8) << 4;
}
struct Boxes {
    uint32_t q[4], ha[2];
    __device__ __forceinline__ Boxes(uint32_t bits, int k0, uint32_t h0, uint32_t h1) {
#pragma unroll
        for (int i = 0; i < 4; i++) q[i] = (bits & (0x10001u << (k0 + i))) * (0x3f80u >> (k0 + i));
        ha[0] = h0; ha[1] = h1;
    }
    __device__ __forceinline__ void load(int j, uint32_t* v, uint32_t zero) const {
        const uint32_t o = j * 128;
        v[0] = lds32(ha[0] + o); v[1] = lds32(ha[1] + zero + o); v[2] = lds32(ha[1] + o);
        v[3] = lds32(ha[0] + zero + o + 16); v[4] = lds32(ha[0] + o + 16); v[5] = lds32(ha[1] + o + 16);
    }
    __device__ __forceinline__ void sums(const uint32_t* v, float* Z, float* X, float* Y) const {
        mma_bf16_z(Z, q[0], q[1], q[2], q[3], v[0], v[1]);
        mma_bf16_z(X, q[0], q[1], q[2], q[3], v[2], v[3]);
        mma_bf16_z(Y, q[0], q[1], q[2], q[3], v[4], v[5]);
    }
};
__host__ __device__ constexpr int tail_step(int n) { return n < 8 ? n : n < 12 ? n + 4 : (n & 1) ? 11 - (n - 13) / 2 : 19 - (n - 12) / 2; }
template <class After>
__device__ __forceinline__ void tail_phase(float (&acc)[16][4], const Boxes& b2, const Boxes& b3, uint32_t tp2, uint32_t tp3, uint32_t zero, After after) {
    uint4 t2[5];
    uint2 t3[8];
    uint32_t v[6], a0[4], a1[4];
    float Z[4], X[4], Y[4];
    b2.load(0, v, zero);
#pragma unroll
    for (int i = 0; i < 5; i++) t2[i] = lds128(tp2 + 160 * i);
#pragma unroll
    for (int n = -1; n < 20; n++) {
        const int j = tail_step(n), j1 = tail_step(n + 1), j2 = tail_step(n + 2);
        if (n < 19) {
            (j1 < 12 ? b2 : b3).sums(v, Z, X, Y);
            if (n < 18) { if (j2 < 12) b2.load(j2, v, zero); else b3.load(j2 - 12, v, zero); }
        }
        if (n >= 0 && j < 12) {
#pragma unroll
            for (int b = 0; b < 5; b++) if (j + 4 + b < 16) mma_v(acc[j + 4 + b], a1, t2[b].z, t2[b].w);
        }
        if (n < 19 && j1 < 12) { a1[0] = pack_v(Z[0], Z[1]); a1[1] = pack_w(X[0], X[1]); a1[2] = pack_v(Z[2], Z[3]); a1[3] = pack_w(X[2], X[3]); }
        if (n == 6) {
#pragma unroll
            for (int b = 0; b < 8; b++) t3[b] = lds64(tp3 + 80 * b);
        }
        if (n >= 0 && j < 12) {
#pragma unroll
            for (int b = 0; b < 5; b++) if (j + 4 + b < 16) mma_v(acc[j + 4 + b], a0, t2[b].x, t2[b].y);
        } else if (n >= 0) {
#pragma unroll
            for (int b = 0; b < 8; b++) if (j - 4 + b < 16) mma_v(acc[j - 4 + b], a0, t3[b].x, t3[b].y);
        }
        if (n < 19) {
            if (j1 < 12) { a0[0] = pack_v(X[0], X[1]); a0[1] = pack_v(Y[0], Y[1]); a0[2] = pack_v(X[2], X[3]); a0[3] = pack_v(Y[2], Y[3]); }
            else { a0[0] = pack_v(X[0], X[1]); a0[1] = pack_v(Y[0], Y[1]); a0[2] = pack_v(Z[2], Z[3]); a0[3] = pack_v(X[2], X[3]); }
        }
        after(n);
    }
}
template <int Q>
__device__ __forceinline__ void emit(const float (&acc)[16][4], int h, uint32_t own, uint32_t peer, uint32_t bar, uint32_t bar_peer) {
    constexpr int n = 4 * Q;
#pragma unroll
    for (int hf = 0; hf < 2; hf++)
        asm volatile("{ .reg .pred p; setp.eq.u32 p, %7, %8;\n\t@p st.shared.v4.u32 [%0], {%1,%2,%3,%4};\n\t"
                     "@!p st.async.weak.shared::cluster.mbarrier::complete_tx::bytes.v4.b32 [%5], {%1,%2,%3,%4}, [%6]; }"
                     ::"r"(own + Q * 8192), "r"(pack_bf16(acc[n][2 * hf], acc[n][2 * hf + 1])), "r"(pack_bf16(acc[n + 1][2 * hf], acc[n + 1][2 * hf + 1])),
                     "r"(pack_bf16(acc[n + 2][2 * hf], acc[n + 2][2 * hf + 1])), "r"(pack_bf16(acc[n + 3][2 * hf], acc[n + 3][2 * hf + 1])),
                     "r"(peer + Q * 8192), "r"(bar_peer + 8 * Q), "r"(h), "r"(hf) : "memory");
    __syncwarp();
    if (elect_one()) mbar_arrive(bar);
}
__device__ __forceinline__ uint32_t finish_src(uint32_t sb, int h, int j, int lane) {
    const int m = lane >> 3, r = lane & 7;
    return sb + OFF_XT + (h ^ 1) * 32768 + (2 * m + (r & 1)) * 512 + (((8 * j + (r & 4) + ((r >> 1) & 1)) ^ ((r & 1) << 1)) << 4);
}
__device__ __forceinline__ uint32_t finish_dst(uint32_t sb, int h, int j, int lane) {
    const int g = lane >> 2, t = lane & 3;
    return sb + OFF_XT + h * 32768 + j * 2048 + (g >> 1) * 512 + (t >> 1) * 144 + (2 * (t & 1) + (g & 1)) * 32;
}
__device__ __forceinline__ uint32_t tile_addr(uint32_t sb, int tok, int t) {
    return sb + OFF_XT + (tok & 8) * 4096 + (tok >> 9) * 8192 + (tok & 6) * 1024 + (tok & 448) * 4 + (tok & 1) * 128 + (tok & 48) * 2 + (((t >> 1) ^ (tok & 1)) << 4) + (t & 1) * 8;
}
__device__ __forceinline__ uint2 add_update(uint2 o, uint32_t upd) {
    const float4 u = lds128f(upd);
    return make_uint2(badd2(o.x, pack_bf16(u.x, u.y)), badd2(o.y, pack_bf16(u.z, u.w)));
}
__device__ __forceinline__ void finish_half(uint32_t src, uint32_t xa, const uint4 (&x)[2]) {
    uint32_t s[2][4];
#pragma unroll
    for (int i = 0; i < 2; i++) ldsm4t(s[i], src ^ (i << 5));
#pragma unroll
    for (int i = 0; i < 2; i++) sts128(xa + i * 256, badd2(x[i].x, s[i][0]), badd2(x[i].y, s[i][1]), badd2(x[i].z, s[i][2]), badd2(x[i].w, s[i][3]));
}

__device__ __noinline__ float centred_var(uint32_t rows, float mu, int lane) {
    float var = 0.f;
#pragma unroll 1
    for (int rr = 0; rr < 16; rr++) {
        const float c0 = __shfl_sync(0xffffffffu, mu, rr);
        float c = 0.f;
#pragma unroll 1
        for (int k = 0; k < 16; k++) {
            const uint32_t q = lds32(rows + rr * ROW_PITCH + k * 128 + lane * 4);
            const float d0 = bf_lo(q) - c0, d1 = bf_hi(q) - c0;
            c = fmaf(d0, d0, fmaf(d1, d1, c));
        }
#pragma unroll 1
        for (int o = 16; o; o >>= 1) c += __shfl_xor_sync(0xffffffffu, c, o);
        if ((lane & 15) == rr) var = c * (1.f / DM);
    }
    return var;
}
__device__ __noinline__ float centred_score(uint32_t rows, uint32_t wbuf, uint32_t s0, uint32_t s1, int lane) {
    float sc = 0.f;
#pragma unroll 1
    for (int rr = 0; rr < 16; rr++) {
        const uint32_t t0 = __shfl_sync(0xffffffffu, s0, rr), t1 = __shfl_sync(0xffffffffu, s1, rr);
        float c = 0.f;
#pragma unroll 1
        for (int k = 0; k < 16; k++) {
            const uint32_t xn = normalize2(lds32(rows + rr * ROW_PITCH + k * 128 + lane * 4), t0, t1);
            const uint32_t wq = lds32(wbuf + (k >> 2) * 1024 + (k & 3) * 128 + lane * 4);
            c = fmaf(bf_lo(xn), bf_lo(wq), fmaf(bf_hi(xn), bf_hi(wq), c));
        }
#pragma unroll 1
        for (int o = 16; o; o >>= 1) c += __shfl_xor_sync(0xffffffffu, c, o);
        if ((lane & 15) == rr) sc = c;
    }
    return sc;
}

__device__ __forceinline__ void issue_rows(const __nv_bfloat16* u, uint32_t sb, int b) {
    if (elect_one()) {
        const uint32_t bar = sb + OFF_BAR + 8 * B_ROW;
#pragma unroll
        for (int j = 0; j < 4; j++) mbar_init(bar + 8 * j, 1);
        asm volatile("fence.mbarrier_init.release.cluster;" ::: "memory");
        fence_async();
#pragma unroll 1
        for (int j = 0; j < 4; j++) {
            mbar_expect_tx(bar + 8 * j, 8192);
#pragma unroll
            for (int i = 0; i < 4; i++) bulk_g2s(sb + OFF_VT + (4 * j + i) * ROW_PITCH, u + (size_t)(16 * b + 4 * j + i) * DM, 2048, bar + 8 * j);
        }
    }
    __syncwarp();
}

__global__ void __cluster_dims__(2, 1, 1) __launch_bounds__(NTHR, 1)
fused_kernel(const __grid_constant__ Ptrs p, const __grid_constant__ Maps maps) {
    extern __shared__ __align__(1024) unsigned char smem[];
    const int tid = threadIdx.x, lane = tid & 31;
    const int c_ = ((blockIdx.x >> 1) + 60) & 63, b = 2 * ((c_ & 32) | ((c_ & 7) << 2) | ((c_ >> 3) & 3)) + (blockIdx.x & 1);
    const int dch = 8 * b + (tid >> 5) - 4;
    uint2 la, aim, cre, cim;
    uint32_t ldt16;
    if ((uint32_t)(tid - 128) < 256u) {
        la = ldg64(p.logA + dch * NMODE + 4 * lane); aim = ldg64(p.Aim + dch * NMODE + 4 * lane);
        cre = ldg64(p.Cre + dch * NMODE + 4 * lane); cim = ldg64(p.Cim + dch * NMODE + 4 * lane);
        ldt16 = ldg16(p.ldt + dch);
    }
    const uint32_t sb = s_u32(smem), bar0 = sb + OFF_BAR;
    const int warp = __shfl_sync(0xffffffffu, tid >> 5, 0);
    const int h = b & 1, cl = b >> 1;
    const int m = lane >> 3, r = lane & 7, g = lane >> 2, t = lane & 3;
    const bool has_gu = b < GU_CTAS;
    if (warp == 4) { STAMP(0); GSTAMP(24); }

    if (warp >= 12) {
        asm volatile("setmaxnreg.dec.sync.aligned.u32 24;");
        const int a = warp - 12;
        uint32_t due = now_ns() + ST_T0 + (uint32_t)(2 * a + h) * (ST_PER / 2) + (has_gu ? 0 : 12 * ST_PER + 4 * ST_PER2);
        const bool el = elect_one();
        if (a == 1) issue_rows(p.u, sb, b);
        if (a == 2 && el) {
#pragma unroll
            for (int i = B_XT; i < NBAR; i++) mbar_init(bar0 + 8 * i, (i == B_V || i == B_SFREE || i == B_XFREE || i == B_OWN) ? 8 : (i >= B_RECV && i < B_RECV + 3) ? 9 : i == B_RED ? 5 : (i == B_UPD || (i >= B_FREE && i < B_FULL)) ? 4 : 1);
            asm volatile("fence.mbarrier_init.release.cluster;" ::: "memory");
            fence_async();
            mbar_expect_tx(bar0 + 8 * B_XT, 65536);
#pragma unroll
            for (int i = 0; i < 4; i++) mbar_expect_tx(bar0 + 8 * (B_RECV + i), 4096);
            mbar_expect_tx(bar0 + 8 * B_RED, 2048);
        }
        if (a == 3 && el) {
#pragma unroll
            for (int i = 0; i < 5; i++) asm volatile("prefetch.tensormap [%0];" ::"l"(&maps.u + i) : "memory");
        }
        __syncwarp();
        cluster_arrive();
        cluster_wait();
        STAMP(18);
        uint32_t fs = finish_src(sb, h, a, lane), fx = finish_dst(sb, h, a, lane);
        pin(fs); pin(fx);
        mbar_wait(bar0 + 8 * (B_ROW + a), 0);
        if (el) {
#pragma unroll
            for (int i = 0; i < 4; i++)
                tma_load_tile(sb + OFF_XT + (a >> 1) * 32768 + (a & 1) * 4096 + h * 8192 + (i & 1) * 16384 + (i >> 1) * 2048, &maps.u, 16 * cl, 4 * a + (i & 2), 16 * (i & 1) + 8 * h, bar0 + 8 * B_XT);
        }
        if (el) {
#pragma unroll 1
            for (int k = has_gu ? 0 : 4; k < 6; k++) {
                const int i = 4 * k + a, s = k < 3 ? i : i - 12;
                sleep_until(due);
                due += k < 3 ? 4 * ST_PER : 4 * ST_PER2;
                const bool again = k >= 3 && has_gu;
                if (s >= 6 || again) mbar_wait(bar0 + 8 * (s < 10 || again ? B_FREE + s : B_V), slot_priv(s) && again);
                if (k == 5 && a >= 2) mbar_wait(bar0 + 8 * B_LN, 1);
                const uint32_t dst = sb + slot_off(s), bar = bar0 + 8 * (B_FULL + s);
                if (k < 4) {
                    mbar_expect_tx(bar, 8192);
                    tma_load_2d(dst, &maps.wg, 64 * cl, 512 * h + 32 * i, bar);
                    tma_load_2d(dst + 4096, &maps.wu, 64 * cl, 512 * h + 32 * i, bar);
                } else {
                    mbar_expect_tx(bar, 7168);
                    tma_load_perm(dst, &maps.wd, 16 * cl, 56 * h + 14 * a + 7 * (k & 1), bar);
                }
            }
            STAMP(19);
        }
        __syncwarp();
        {
            mbar_wait(bar0 + 8 * B_XT, 0);
#pragma unroll 1
            for (int Q = 0; Q < 3; Q++) {
#pragma unroll
                for (int q = 0; q < 2; q++) {
                    const uint4 x[2] = {lds128(fx ^ (q << 4)), lds128((fx ^ (q << 4)) + 256)};
                    if (q == 0) mbar_wait(bar0 + 8 * (B_RECV + Q), 0);
                    finish_half(fs + q * 4096, fx ^ (q << 4), x);
                }
                fence_async();
                __syncwarp();
                if (el) tma_store_tile(&maps.out, sb + OFF_XT + h * 32768 + Q * 8192 + a * 2048, 16 * cl, 8 * h + 2 * a, 8 * Q);
                fs += 8192; fx += 8192;
                STAMP(Q ? 58 + Q : 20);
            }
            const int tok = 2047 - (int)(lds32(sb + OFF_MISC + 48 + 8 * g) & 2047);
            const bool mine = ((tok >> 1) & 7) == 4 * h + a && tok < 1536;
            if (el) asm volatile("cp.async.bulk.wait_group 0;" ::: "memory");
            if (__any_sync(0xffffffffu, mine)) {
                const uint2 o0 = lds64(tile_addr(sb, tok, t));
                mbar_wait(bar0 + 8 * B_UPD, 0);
                const uint2 o1 = add_update(o0, sb + tab_off(g) + T_RED + 16 * t);
                if (mine) *reinterpret_cast<uint2*>(p.out + (size_t)tok * DM + 16 * cl + 4 * t) = o1;
            } else STAMP(62);
        }
    } else if (warp >= 4) {
        const int w = warp - 4;
        uint32_t dsk16 = ldg16(p.dsk + dch);
        cluster_arrive();
        asm volatile("setmaxnreg.inc.sync.aligned.u32 176;");
        const uint32_t vrow = sb + OFF_VT + w * VT_PITCH + VT_PAD, tab = sb + tab_off(w);
        const uint32_t rb0 = bar0 + 8 * B_RECV, rb1 = mapa(rb0, h ^ 1);
        uint32_t tpo = 80 + (g - 2 * t) * 8 - (g < 2 * t ? 16 : 0);
        uint32_t xa = sb + OFF_XT + (w >> 1) * 8192 + (w & 1) * 1024 + (g >> 1) * 2048 + (g & 1) * 128 + t * 32 + ((h ^ (g & 1)) << 4);
        uint32_t va = sb + OFF_VT + (2 * m + (r & 1)) * VT_PITCH + VT_PAD + (16 * w + (r >> 1)) * 16;
        uint32_t qa = sb + OFF_ST + 2048 * w + 128 * t + 16 * (g ^ (2 * t));
        uint32_t vmin = vrow + (m & 1) * VT_PLANE - 16, vd = vmin + 16 + (m >> 1) * 1024 + r * 16;
        uint32_t vo = vrow + VT_PLANE + 496 - (m & 1) * 512 + (m >> 1) * 128 + r * 16, vz = vrow - VT_PAD + (lane >> 1) * VT_PLANE + (lane & 1) * 16;
        pin(vmin); pin(vd); pin(vo); pin(vz);
        pin(tpo); pin(xa); pin(va); pin(qa);
        uint32_t bits = box_bits(lane), h0 = vrow + 16 * g + tok_off(2 * t - 18), h1 = vrow + 16 * g + tok_off(2 * t - 10);
        pin(bits); pin(h0); pin(h1);
        const KgenAddr ka(sb + OFF_PRIV + w * 8192, lane);
        if (__any_sync(0xffffffffu, (vmin | (vd | vo | vz) | (tpo | xa) | (va | qa) | (bits | h0 | h1) | ka.any()) & p.zero)) __trap();
        cluster_wait();
        pin(la.x); pin(la.y); pin(aim.x); pin(aim.y); pin(cre.x); pin(cre.y); pin(cim.x); pin(cim.y); pin(ldt16); pin(dsk16);
        uint4 x[8];
        auto load_x = [&]() {
            mbar_wait(bar0 + 8 * B_XT, 0);
#pragma unroll
            for (int i = 0; i < 8; i++) x[i] = lds128(xa + (i & 1) * 32768 + (i >> 1) * 256);
        };
        kgen(ka, tab, lane, la, aim, cre, cim, bf_round(ex2f(bf_lo(ldt16) * 1.4426950408889634f)), 1.f + bf_lo(dsk16), dch, [&]() {
            STAMP(21);
            if (elect_one()) mbar_arrive_n(bar0 + 8 * (B_FREE + 6 + ((w >> 1) ^ 2)), 2);
        }, [&]() {
            if ((LN_PAUSE >> w) & 1) mbar_wait(bar0 + 8 * B_LN, 0);
        });
        STAMP(1);
        const uint32_t pb = tab + T_DENSE + (g - 2 * t) * 4;
        DenseTaps dt(pb, pb + p.zero);
        {
            load_x();
            STAMP(47);
            mbar_wait(bar0 + 8 * (B_ST + (w >> 1)), 0);
            uint4 q[4];
#pragma unroll
            for (int n = 0; n < 4; n++) q[n] = lds128(qa + 512 * n);
            if (lane < 4) sts128(vz, 0, 0, 0, 0);
            STAMP(2); GSTAMP(28);
#pragma unroll
            for (int i = 0; i < 8; i++) {
                const uint32_t s0 = (i & 1) ? q[i >> 1].z : q[i >> 1].x, s1 = (i & 1) ? q[i >> 1].w : q[i >> 1].y;
                stsm4t(va + (i >> 1) * 64 + (i & 1) * VT_PLANE, normalize2(x[i].x, s0, s1), normalize2(x[i].y, s0, s1),
                       normalize2(x[i].z, s0, s1), normalize2(x[i].w, s0, s1));
            }
            __syncwarp();
            if (elect_one()) mbar_arrive(bar0 + 8 * B_V);
        }
        mbar_wait(bar0 + 8 * B_V, 0);
        STAMP(3);
        float acc[16][4];
#pragma unroll
        for (int i = 0; i < 16; i++) { acc[i][0] = acc[i][1] = acc[i][2] = acc[i][3] = 0.f; }
        bits |= dense_phase(acc, vmin, vd, vo, pb, dt, p.zero);
        const Boxes b2(bits, 0, h0, h1), b3(bits, 4, (t == 1 ? h1 : h0) - 4, t == 1 ? h0 + 12 : h1 - 4);
        STAMP(4);
        const uint32_t so = sb + OFF_XT + (8 * h + w) * 512 + ((lane ^ ((w & 1) << 1)) << 4);
        const uint32_t dst0 = so + (h ^ 1) * 32768, dst1 = mapa(so + h * 32768, h ^ 1);
        tail_phase(acc, b2, b3, tab + T_R2 + 2 * tpo, tab + T_R3 + tpo, p.zero, [&](int j) {
            if (j == -1) {
                mbar_wait(bar0 + 8 * B_SFREE, 0);
                emit<0>(acc, h, dst0, dst1, rb0, rb1);
            }
            if (j == 3) { emit<1>(acc, h, dst0, dst1, rb0 + 8, rb1); STAMP(5); }
            if (j == 11) {
                mbar_wait(bar0 + 8 * B_XFREE, 0);
                emit<2>(acc, h, dst0, dst1, rb0 + 16, rb1);
                STAMP(58);
            }
        });
        emit<3>(acc, h, dst0, dst1, bar0 + 8 * B_OWN, rb1);
        STAMP(30);
        if (w < 4) {
            const uint32_t fs = finish_src(sb, h, w, lane) + 24576 + h * 4096, fx = (finish_dst(sb, h, w, lane) + 24576) ^ (h << 4);
            const int tok = 2047 - (int)(lds32(sb + OFF_MISC + 48 + 8 * g) & 2047);
            const bool mine = ((tok >> 1) & 7) == 4 * h + w && tok >= 1536;
            const uint32_t ta = tile_addr(sb, tok, t);
            const uint4 x0[2] = {lds128(fx), lds128(fx + 256)}, x1[2] = {lds128(fx ^ 16), lds128((fx ^ 16) + 256)};
            mbar_wait(bar0 + 8 * B_OWN, 0);
            finish_half(fs, fx, x0);
            mbar_wait(bar0 + 8 * (B_RECV + 3), 0);
            STAMP(6);
            finish_half(fs + (h ? -4096 : 4096), fx ^ 16, x1);
            __syncwarp();
            if (__any_sync(0xffffffffu, mine)) {
                const uint2 o0 = lds64(ta);
                mbar_wait(bar0 + 8 * B_UPD, 0);
                const uint2 o1 = add_update(o0, sb + tab_off(g) + T_RED + 16 * t);
                if (mine) sts64(ta, o1.x, o1.y);
            }
            fence_async();
            __syncwarp();
            if (elect_one()) {
                tma_store_tile(&maps.out, sb + OFF_XT + h * 32768 + 24576 + w * 2048, 16 * cl, 8 * h + 2 * w, 24);
                if (w == 3) STAMP(61);
                asm volatile("cp.async.bulk.wait_group.read 0;" ::: "memory");
            }
        }
        STAMP(7);
    } else {
        const int a = warp;
        const uint4 wq = ldg128(p.wr + 8 * tid);
        const uint32_t epoch = ld_relaxed_32(&p.sc[a].cnt[b & 96]) >> 5;
        cluster_arrive();
        asm volatile("setmaxnreg.inc.sync.aligned.u32 136;");
        const uint32_t tag = __shfl_sync(0xffffffffu, epoch, 0) + 1u, misc = sb + OFF_MISC, abar = bar0 + 8 * (B_AUX + a);
        uint32_t aph = 0;
        const Exchange* in = &p.sc[cl & (NREP - 1)];
        uint2* pub = p.sc[m >> 1].stat + 16 * b + 2 * (r ^ (2 * (b & 3))) + (m & 1);
        uint32_t* cnt_s = &p.sc[t].cnt[b & 96];
        pin(pub); pin(cnt_s);
        if (tid < 64) sts32(sb + OFF_XCH + 4 * tid, 0);
        const uint32_t wbuf = sb + OFF_LN + a * 1024, part = sb + OFF_LN + 4096;
        {
            sts128(wbuf + 16 * lane, wq.x, wq.y, wq.z, wq.w);
            sts128(wbuf + 512 + 16 * lane, 0x3f803f80u, 0x3f803f80u, 0x3f803f80u, 0x3f803f80u);
            float wsum = ((bf_lo(wq.x) + bf_hi(wq.x)) + (bf_lo(wq.y) + bf_hi(wq.y))) + ((bf_lo(wq.z) + bf_hi(wq.z)) + (bf_lo(wq.w) + bf_hi(wq.w)));
#pragma unroll
            for (int o = 16; o; o >>= 1) wsum += __shfl_xor_sync(0xffffffffu, wsum, o);
            sts32f(part + 1024 + 4 * a, wsum);
            uint32_t wf[4][4];
#pragma unroll
            for (int i = 0; i < 4; i++) ldsm4(wf[i], wbuf + ((uint32_t)(r - 1) < 2u ? 16 * (r - 1) : 512) + 32 * m + 128 * i);
            uint32_t ra = sb + OFF_VT + r * ROW_PITCH + 512 * a + 16 * m, pa = part + a * 256 + g * 16;
            cluster_wait();
            STAMP(22);
#pragma unroll 1
            for (int hf = 0; hf < 2; hf++) {
                mbar_wait(bar0 + 8 * B_ROW + 16 * hf, 0);
                mbar_wait(bar0 + 8 * B_ROW + 16 * hf + 8, 0);
                STAMP(23);
                uint32_t x[8][4];
                float cs[2][4], q[8][4];
#pragma unroll
                for (int i = 0; i < 40; i++) (i < 8 ? cs[i >> 2 & 1] : q[(i - 8) >> 2 & 7])[i & 3] = 0.f;
#pragma unroll
                for (int k = 0; k < 8; k++) ldsm4(x[k], ra + k * 64);
                const bool more = __any_sync(0xffffffffu, after_all(x, p.zero));
#pragma unroll 1
                do {
#pragma unroll
                    for (int k = 0; k < 8; k++) {
                        mma_v(cs[k & 1], x[k], wf[k >> 1][2 * (k & 1)], wf[k >> 1][2 * (k & 1) + 1]);
#pragma unroll
                        for (int i = 0; i < 4; i++) mma_bf16_k8(q[4 * (k & 1) + i], x[k][i & 2], x[k][i | 1], x[k][i]);
                    }
                } while (more);
                const float c2 = cs[0][2] + cs[1][2];
                if (t == 0) sts64f(pa, (cs[0][0] + cs[1][0]) + c2, cs[0][1] + cs[1][1]);
                if (t == 1) sts32f(pa + 12, c2);
                const float e0 = ((q[0][0] + q[2][0]) + (q[4][0] + q[6][0])) + ((q[1][2] + q[3][2]) + (q[5][2] + q[7][2]));
                const float e1 = ((q[0][1] + q[2][1]) + (q[4][1] + q[6][1])) + ((q[1][3] + q[3][3]) + (q[5][3] + q[7][3]));
                if (t == (g >> 1)) sts32f(pa + 8, (g & 1) ? e1 : e0);
                ra += 8 * ROW_PITCH; pa += 128;
            }
        }
        STAMP(31);
        named_sync(1, 128);
        if (a == 0) {
            const uint32_t pa = part + (lane & 15) * 16;
            const float4 p0 = lds128f(pa), p1 = lds128f(pa + 256), p2 = lds128f(pa + 512), p3 = lds128f(pa + 768), ws = lds128f(part + 1024);
            const float mu = ((p0.x + p1.x) + (p2.x + p3.x)) * (1.f / DM);
            float var = ((p0.z + p1.z) + (p2.z + p3.z)) * (1.f / DM) - mu * mu;
            const bool centred = __any_sync(0xffffffffu, !(mu * mu <= 4.f * var));
            if (centred) var = centred_var(sb + OFF_VT, mu, lane);
            const float ri = rcpf(bf_round(sqrtaf(bf_round(bf_round(var) + 1e-5f))));
            const uint32_t s0 = pack_bf16(mu, ri), s1 = (pack_bf16(ri - bf_hi(s0), 0.f) & 0xfffcu) | (tag & 3);
            float sc = ((((p0.y + p1.y) + (p2.y + p3.y)) + ((p0.w + p1.w) + (p2.w + p3.w))) - bf_lo(s0) * ((ws.x + ws.y) + (ws.z + ws.w))) * ri;
            if (centred) sc = centred_score(sb + OFF_VT, sb + OFF_LN, s0, s1, lane);
            const uint32_t sb16 = pack_bf16(0.f, sc);
            const uint32_t s2 = s1 | (sb16 ^ (((uint32_t)((int)sb16 >> 31) & 0x7fff0000u) | 0x80000000u));
            st_relaxed_64(pub, s0, s2);
            st_relaxed_64(pub + 2 * sizeof(Exchange) / 8, s0, s2);
            if (lane < NREP) red_add(cnt_s, 1);
            if (elect_one()) mbar_arrive(bar0 + 8 * B_LN);
            STAMP(9); GSTAMP(25);
        }
        const uint32_t slot0 = sb + OFF_RING + a * 8192, slot1 = sb + slot_off(4 + a), slot2 = sb + slot_off(8 + a), fbar = bar0 + 8 * (B_FULL + a);
        uint32_t mine = 0, row[2] = {0, 0};
        {
            uint32_t q[16];
            named_sync(1, 128);
            wait_count(&in->cnt[32 * a], 32 * tag - FEW_ST);
            STAMP(41);
#pragma unroll 1
            for (uint32_t it = 0;; spin_guard(it)) {
                if (elect_one()) {
                    mbar_expect_tx(abar, 4096);
                    bulk_g2s(sb + OFF_ST + 4096 * a, in->stat + 512 * a, 4096, abar);
                }
                mbar_wait(abar, aph);
                aph ^= 1;
                uint32_t bad = 0;
#pragma unroll
                for (int n = 0; n < 8; n++) {
                    const uint4 u = lds128v(sb + OFF_ST + 4096 * a + 512 * n + 16 * lane);
                    q[2 * n] = u.y; q[2 * n + 1] = u.w;
                    bad = or_xor(bad, u.y, tag);
                }
                const bool ok = __all_sync(0xffffffffu, (bad & 3) == 0);
                asm volatile("{ .reg .pred p; setp.ne.u32 p, %1, 0; @p mbarrier.arrive.shared::cta.b64 _, [%0]; }" ::"r"(bar0 + 8 * (B_ST + a)), "r"((uint32_t)(ok && lane == 0)) : "memory");
                if (ok) break;
            }
            STAMP(8);
            const uint32_t inv = 2047 - 512 * a - 16 * m - (r ^ (2 * m));
#pragma unroll
            for (int i = 0; i < 16; i++) asm("lop3.b32 %0, %0, %1, %2, 0x9b;" : "+r"(q[i]) : "r"(inv), "r"(0xffff0000u | (64 * (i >> 1) + 8 * (i & 1))));
            auto below = [&](uint32_t x) {
                uint32_t d[4];
#pragma unroll
                for (int i = 0; i < 16; i++) d[i & 3] = i < 4 ? x + q[i] : min(d[i & 3], x + q[i]);
                d[0] = min(min(d[0], d[1]), min(d[2], d[3]));
                return d[0] < x ? x - 1 - d[0] : 0u;
            };
            const uint32_t mx0 = ~min(min(min(min(q[0], q[1]), min(q[2], q[3])), min(min(q[4], q[5]), min(q[6], q[7]))),
                                      min(min(min(q[8], q[9]), min(q[10], q[11])), min(min(q[12], q[13]), min(q[14], q[15]))));
            const uint32_t gm = min(__reduce_max_sync(0xffffffffu, lane < 16 ? mx0 : 0u), __reduce_max_sync(0xffffffffu, lane < 16 ? 0u : mx0));
            if (lane == 0) sts32(misc + 16 + 4 * a, gm);
            named_sync(1, 128);
            STAMP(42);
            const uint4 t0 = lds128(misc + 16);
            uint32_t tau = min(min(t0.x, t0.y), min(t0.z, t0.w));
            uint32_t mx = mx0, cnt = 0, bal;
            const uint32_t list = sb + OFF_XCH + 64 * a;
#pragma unroll 1
            while ((bal = __ballot_sync(0xffffffffu, mx >= tau)) != 0) {
                const uint32_t pos = cnt + __popc(bal & ((1u << lane) - 1u));
                cnt += __popc(bal);
                if (cnt > 16) break;
                if (mx >= tau) sts32(list + 4 * pos, mx);
                mx = below(mx);
            }
            if (cnt > 16) {
                mx = mx0;
#pragma unroll 1
                for (int j = 0; j < 8; j++) {
                    const uint32_t top = __reduce_max_sync(0xffffffffu, mx), nx = below(mx);
                    if (mx == top) { sts32(list + 4 * j, mx); sts32(list + 32 + 4 * j, 0); mx = nx; }
                }
            }
            named_sync(1, 128);
            STAMP(43);
            const uint2 k = lds64(sb + OFF_XCH + 8 * lane);
            uint32_t hi = max(k.x, k.y), lo = min(k.x, k.y);
            mbar_wait(bar0 + 8 * B_V, 0);
#pragma unroll
            for (int j = 0; j < 8; j++) {
                const uint32_t top = __reduce_max_sync(0xffffffffu, hi);
                const bool won = hi == top;
                hi = won ? lo : hi;
                lo = won ? 0u : lo;
                if (g == j) mine = top;
                if (a == (j >> 1)) row[j & 1] = top;
            }
        }
        STAMP(11);
        const int tok = 2047 - (int)(mine & 2047);
        const uint32_t xs = sb + OFF_XT + (h ^ 1) * 32768 + 16384;
        if (has_gu) {
            if (elect_one()) {
                mbar_expect_tx(abar, 2048);
#pragma unroll
                for (int j = 0; j < 2; j++) bulk_g2s(xs + (2 * a + j) * 1040, p.u + (size_t)(2047 - (row[j] & 2047)) * DM + 512 * h, 1024, abar);
            }
        }
        STAMP(44);
        const uint2 st = ld_relaxed_64(in->stat + (tok & ~15) + 2 * ((tok & 7) ^ ((tok >> 3) & 6)) + ((tok >> 3) & 1));
        if (a == 0 && t == 0) sts64(misc + 48 + 8 * g, mine, __float_as_uint(bf_hi(st.x) + bf_lo(st.y)));
        if (a == 0) STAMP(45);
        if (has_gu) {
            const uint32_t mean = __shfl_sync(0xffffffffu, st.x, 8 * a + 4 * (lane >> 4)), xr = xs + (2 * a + (lane >> 4)) * 1040 + 16 * (lane & 15);
            mbar_wait(abar, aph);
            aph ^= 1;
            STAMP(46);
            uint4 x[4];
#pragma unroll
            for (int j = 0; j < 4; j++) x[j] = lds128(xr + 256 * j);
#pragma unroll
            for (int j = 0; j < 4; j++) sts128(xr + 256 * j, bsub2_lo(x[j].x, mean), bsub2_lo(x[j].y, mean), bsub2_lo(x[j].z, mean), bsub2_lo(x[j].w, mean));
            if (elect_one()) mbar_expect_tx(abar, 512);
            named_sync(1, 128);
        }
        if (lane < (has_gu ? 2 : 4)) mbar_arrive_peer(mapa(bar0 + 8 * (lane & 2 ? B_XFREE : B_SFREE), lane & 1));
        if (has_gu) {
            STAMP(12);
            float gacc[8][4];
#pragma unroll
            for (int i = 0; i < 8; i++) { gacc[i][0] = gacc[i][1] = gacc[i][2] = gacc[i][3] = 0.f; }
            uint32_t* pubh = reinterpret_cast<uint32_t*>(&p.sc[0].h[b * 32 + 8 * a + (g ^ (2 * a))]) + t;
            uint32_t* cnt_h = &p.sc[t].cnt[32 * (b / 28) + 1 + ((b / 14) & 1)];
            uint32_t ko = sb + (m & 1) * 4096 + (r + ((m >> 1) << 3)) * 128 + ((r ^ (4 * h) ^ a) << 4), kp = ko ^ 64, xb = xs + r * 1040 + m * 16;
            uint32_t xch = sb + OFF_XCH + 16 * tid, tagm = t == 3 ? 1u : 0u;
            pin(pubh); pin(cnt_h); pin(ko); pin(kp); pin(xb); pin(xch); pin(tagm);
            const float r0 = lds32f(misc + 52 + 16 * t), r1 = lds32f(misc + 60 + 16 * t);
#pragma unroll
            for (int c = 0; c < 4; c++) {
                uint32_t af[20][4];
#pragma unroll
                for (int j = 0; j < 4; j++) ldsm4(af[16 + j], xb + 256 * c + 64 * j);
                if (c == 3) mbar_wait(bar0 + 8 * B_SFREE, 0);
#pragma unroll
                for (int j = 0; j < 4; j++) {
                    mbar_wait(bar0 + 8 * (B_FULL + 4 * (c % 3) + j), c / 3);
#pragma unroll
                    for (int i = 0; i < 4; i++) ldsm4t(af[8 * (i >> 1) + 2 * j + (i & 1)], ((i & 1) ? kp : ko) + slot_off(4 * (c % 3) + j) + (i >> 1) * 2048);
                }
                STAMP(36 + c);
                __syncwarp();
                if (c < 3 && lane < 4) mbar_arrive(bar0 + 8 * (B_FREE + 4 * c + lane));
                const bool more = __any_sync(0xffffffffu, (af[6][3] | af[7][3] | af[14][3] | af[15][3]) & p.zero);
#pragma unroll 1
                do {
#pragma unroll
                    for (int i = 0; i < 16; i++) mma_v(gacc[i & 7], af[i], af[16 + ((i >> 1) & 3)][2 * (i >> 3)], af[16 + ((i >> 1) & 3)][2 * (i >> 3) + 1]);
                } while (more);
            }
            STAMP(13);
            float own[4], oth[4];
#pragma unroll
            for (int j = 0; j < 4; j++) oth[j] = (gacc[1][j] + gacc[3][j]) + (gacc[5][j] + gacc[7][j]);
            st_async128(mapa(xch, h ^ 1), __float_as_uint(oth[0]), __float_as_uint(oth[1]), __float_as_uint(oth[2]), __float_as_uint(oth[3]), mapa(abar, h ^ 1));
            STAMP(56);
#pragma unroll
            for (int j = 0; j < 4; j++) own[j] = ((gacc[0][j] + gacc[2][j]) + (gacc[4][j] + gacc[6][j])) * ((j & 1) ? r1 : r0);
            mbar_wait(abar, aph);
            aph ^= 1;
            STAMP(57);
            const float4 o4 = lds128f(xch);
            const float g0 = bf_round(fmaf(o4.x, r0, own[0])), g1 = bf_round(fmaf(o4.y, r1, own[1]));
            const float h0 = bf_round(g0 * rcpf(1.f + ex2f(-1.4426950408889634f * g0))) * bf_round(fmaf(o4.z, r0, own[2]));
            const float h1 = bf_round(g1 * rcpf(1.f + ex2f(-1.4426950408889634f * g1))) * bf_round(fmaf(o4.w, r1, own[3]));
            uint32_t hw;
            asm volatile("movmatrix.sync.aligned.m8n8.trans.b16 %0, %1;" : "=r"(hw) : "r"(pack_bf16(h0, h1)));
            hw = (hw & ~tagm) | (tag & tagm);
#pragma unroll
            for (int j = 0; j < NREP; j++) st_relaxed_32(pubh + j * (sizeof(Exchange) / 4), hw);
            if (lane < NREP) red_add(cnt_h, b % 14 < 2 ? 2 : 1);
            if (lane < 2) mbar_arrive_peer(mapa(bar0 + 8 * B_XFREE, lane));
            named_sync(1, 128);
            STAMP(14);
        }
        float dacc[4];
        const int tk = ((tid >> 1) & 6) | (tid & 1);
        uint32_t ro = 4 * tid, red = sb + tab_off(tk) + T_RED + 4 * ((tid >> 4) + 4 * (tid & 2));
        if (!has_gu) named_sync(1, 128);
        const float sg = bf_round(rcpf(1.f + ex2f(-1.4426950408889634f * __uint_as_float(unorder_key(lds32(misc + 48 + 8 * tk) >> 16) << 16))));
        pin(ro); pin(red);
        mbar_wait(bar0 + 8 * B_XFREE, 0);
        {
            uint32_t wo = (r + ((m >> 1) << 3)) * 32 + (((m & 1) ^ (r >> 2)) << 4), af[14][4];
            uint32_t ho = slot0 + 128 * t + 16 * (g ^ (2 * t));
            pin(wo); pin(ho);
            float d[7][4];
#pragma unroll
            for (int i = 0; i < 7; i++) { d[i][0] = d[i][1] = d[i][2] = d[i][3] = 0.f; }
            auto first_half = [&]() {
                mbar_wait(fbar + 32, has_gu);
#pragma unroll
                for (int j = 0; j < 14; j++) ldsm4t(af[j], slot1 + wo + j * 512);
            };
            auto fetch = [&]() {
                if (elect_one()) {
                    mbar_expect_tx(abar, 7168);
                    bulk_g2s(slot0, &in->h[(56 * h + 14 * a) * 32], 7168, abar);
                }
            };
            wait_count(&in->cnt[64 * h + 32 * (a >> 1) + 1 + (a & 1)], 64 * tag - FEW_H);
            STAMP(33);
            fetch();
            if (a == 3 && elect_one()) mbar_arrive(bar0 + 8 * B_LN);
            first_half();
            mbar_wait(abar, aph);
#pragma unroll
            for (int s = 0; s < 2; s++) {
                if (s) {
                    mbar_wait(fbar + 64, has_gu);
#pragma unroll
                    for (int j = 0; j < 14; j++) ldsm4t(af[j], slot2 + wo + j * 512);
                }
                uint4 hq[7];
#pragma unroll 1
                for (uint32_t it = 0;; spin_guard(it)) {
                    uint32_t bad = 0;
#pragma unroll
                    for (int j = 0; j < 7; j++) { hq[j] = lds128(ho + 512 * (7 * s + j)); bad = or_xor(bad, hq[j].w, tag); }
                    if (__all_sync(0xffffffffu, (bad & 1) == 0)) break;
                    fetch();
                    aph ^= 1;
                    mbar_wait(abar, aph);
                }
                if (s == 0) STAMP(15);
#pragma unroll
                for (int j = 0; j < 14; j++) {
                    const uint4 q = hq[j >> 1];
                    mma_v(d[j % 7], af[j], (j & 1) ? q.z : q.x, (j & 1) ? q.w : q.y);
                }
            }
#pragma unroll
            for (int j = 0; j < 4; j++) dacc[j] = ((d[0][j] + d[1][j]) + (d[2][j] + d[3][j])) + ((d[4][j] + d[5][j]) + d[6][j]);
        }
        STAMP(16);
        {
            st_async128(mapa(sb + OFF_XCH + 16 * tid, h ^ 1), __float_as_uint(dacc[0]), __float_as_uint(dacc[1]), __float_as_uint(dacc[2]), __float_as_uint(dacc[3]),
                        mapa(bar0 + 8 * B_RED, h ^ 1));
            sts128f(slot0 + 7680 + lane * 16, dacc);
            __syncwarp();
            if (elect_one()) mbar_arrive(bar0 + 8 * B_RED);
            mbar_wait(bar0 + 8 * B_RED, 0);
            const uint32_t b0 = sb + OFF_RING + 7680 + ro, b1 = sb + OFF_XCH + ro;
            const float y = ((lds32f(b0) + lds32f(b0 + 8192)) + (lds32f(b0 + 16384) + lds32f(b0 + 24576))) +
                            ((lds32f(b1) + lds32f(b1 + 512)) + (lds32f(b1 + 1024) + lds32f(b1 + 1536)));
            sts32f(red, bf_round(y) * sg);
            __syncwarp();
            if (elect_one()) mbar_arrive(bar0 + 8 * B_UPD);
        }
        STAMP(17); GSTAMP(29);
    }
}

typedef CUresult (*EncodeFn)(CUtensorMap*, CUtensorMapDataType, cuuint32_t, void*, const cuuint64_t*, const cuuint64_t*,
                             const cuuint32_t*, const cuuint32_t*, CUtensorMapInterleave, CUtensorMapSwizzle,
                             CUtensorMapL2promotion, CUtensorMapFloatOOBfill);

void make_map(EncodeFn enc, CUtensorMap* m, const void* ptr, uint64_t cols, uint64_t rows, uint32_t bc, uint32_t br,
              CUtensorMapSwizzle sw, CUtensorMapL2promotion pr) {
    cuuint64_t dims[2] = {cols, rows};
    cuuint64_t str[1] = {cols * 2};
    cuuint32_t box[2] = {bc, br};
    cuuint32_t es[2] = {1, 1};
    enc(m, CU_TENSOR_MAP_DATA_TYPE_BFLOAT16, 2, const_cast<void*>(ptr), dims, str, box, es, CU_TENSOR_MAP_INTERLEAVE_NONE, sw, pr,
        CU_TENSOR_MAP_FLOAT_OOB_FILL_NONE);
}
void make_perm_map(EncodeFn enc, CUtensorMap* m, const void* ptr, CUtensorMapL2promotion pr) {
    cuuint64_t dims[5] = {DM, 2, 4, 4, FF / 32};
    cuuint64_t str[4] = {DM * 2, 8 * DM * 2, 2 * DM * 2, 32 * DM * 2};
    cuuint32_t box[5] = {16, 2, 4, 4, 7};
    cuuint32_t es[5] = {1, 1, 1, 1, 1};
    enc(m, CU_TENSOR_MAP_DATA_TYPE_BFLOAT16, 5, const_cast<void*>(ptr), dims, str, box, es, CU_TENSOR_MAP_INTERLEAVE_NONE,
        CU_TENSOR_MAP_SWIZZLE_32B, pr, CU_TENSOR_MAP_FLOAT_OOB_FILL_NONE);
}
void make_tile_map(EncodeFn enc, CUtensorMap* m, const void* ptr) {
    cuuint64_t dims[4] = {DM, 4, 16, SEQ / 64};
    cuuint64_t str[3] = {16 * DM * 2, DM * 2, 64 * DM * 2};
    cuuint32_t box[4] = {16, 4, 2, 8};
    cuuint32_t es[4] = {1, 1, 1, 1};
    enc(m, CU_TENSOR_MAP_DATA_TYPE_BFLOAT16, 4, const_cast<void*>(ptr), dims, str, box, es, CU_TENSOR_MAP_INTERLEAVE_NONE,
        CU_TENSOR_MAP_SWIZZLE_32B, CU_TENSOR_MAP_L2_PROMOTION_NONE, CU_TENSOR_MAP_FLOAT_OOB_FILL_NONE);
}

}

extern "C" void kernel_launch(void* const* d_in, const int* in_sizes, int n_in, void* d_out, int out_size) {
    (void)in_sizes; (void)n_in; (void)out_size;
    static EncodeFn enc = nullptr;
    static void* scratch = nullptr;
    if (!enc) {
        void* fn = nullptr;
        cudaDriverEntryPointQueryResult q;
        cudaGetDriverEntryPoint("cuTensorMapEncodeTiled", &fn, cudaEnableDefault, &q);
        enc = (EncodeFn)fn;
        cudaGetSymbolAddress(&scratch, g_scratch);
        cudaFuncSetAttribute(fused_kernel, cudaFuncAttributeMaxDynamicSharedMemorySize, SMEM_BYTES);
    }
    Maps maps;
    make_tile_map(enc, &maps.u, d_in[0]);
    make_tile_map(enc, &maps.out, d_out);
    make_map(enc, &maps.wg, d_in[9], FF, DM, 64, 32, CU_TENSOR_MAP_SWIZZLE_128B, CU_TENSOR_MAP_L2_PROMOTION_L2_128B);
    make_map(enc, &maps.wu, d_in[10], FF, DM, 64, 32, CU_TENSOR_MAP_SWIZZLE_128B, CU_TENSOR_MAP_L2_PROMOTION_L2_128B);
    make_perm_map(enc, &maps.wd, d_in[11], CU_TENSOR_MAP_L2_PROMOTION_L2_64B);
    Ptrs p;
    p.sc = (Exchange*)scratch;
    p.u = (const __nv_bfloat16*)d_in[0];
    p.logA = (const __nv_bfloat16*)d_in[1];
    p.Aim = (const __nv_bfloat16*)d_in[2];
    p.Cre = (const __nv_bfloat16*)d_in[3];
    p.Cim = (const __nv_bfloat16*)d_in[4];
    p.ldt = (const __nv_bfloat16*)d_in[5];
    p.dsk = (const __nv_bfloat16*)d_in[6];
    p.wr = (const __nv_bfloat16*)d_in[8];
    p.out = (__nv_bfloat16*)d_out;
    p.zero = 0;
    fused_kernel<<<NCTA, NTHR, SMEM_BYTES, cudaStreamPerThread>>>(p, maps);
}
```

```cpp
#include <cuda_runtime.h>
#include <cuda_bf16.h>
#include <cuda_fp16.h>
#include <cuda.h>
#include <stdint.h>

namespace {

constexpr int SEQ = 2048, DM = 1024, NMODE = 128, FF = 3584;
constexpr int NCTA = 128, NTHR = 512;
constexpr int GU_CTAS = 112;
constexpr int NREP = 4;

constexpr int OFF_XT = 0;
constexpr int OFF_RING = 65536;
constexpr int OFF_PRIV = OFF_RING + 65536;
constexpr int OFF_VT = OFF_PRIV + 65536;
constexpr int VT_PAD = 32, VT_PLANE = VT_PAD + 2048, VT_PITCH = 2 * VT_PLANE, ROW_PITCH = 2064;
constexpr int OFF_BAR = OFF_VT + 8 * VT_PITCH;
constexpr int OFF_MISC = OFF_BAR + 384;
constexpr int OFF_XCH = OFF_MISC + 112;
constexpr int SMEM_BYTES = OFF_XCH + 2048;
constexpr int OFF_LN = OFF_RING + 7 * 8192;
constexpr int OFF_ST = OFF_RING + 6 * 8192;
static_assert(SMEM_BYTES <= 232448, "shared memory");

constexpr int B_ROW = 0, B_XT = 4, B_V = 5, B_LN = 6, B_SFREE = 7, B_XFREE = 8, B_OWN = 9, B_RED = 10, B_UPD = 11, B_ST = 12, B_RECV = 16, B_FREE = 20, B_FULL = 32, B_AUX = 44, NBAR = 48;

constexpr int T_DENSE = 60;
constexpr int T_PATCH = 2208;
constexpr int T_R2 = 2368;
constexpr int T_R3 = 3296;

constexpr int T_RED = 4032;
__device__ __forceinline__ bool slot_priv(int s) { return (uint32_t)(s - 6) < 4u; }
__device__ __forceinline__ uint32_t slot_off(int s) { return slot_priv(s) ? OFF_PRIV + 4096 + (s & 3) * 16384 : OFF_RING + (s < 6 ? s : s - 4) * 8192; }
__device__ __forceinline__ uint32_t tab_off(int w) { return OFF_PRIV + w * 8192 + (w & 1) * 4096; }

constexpr uint32_t SPIN_LIMIT = 1u << 20;
#define BB_UNROLL 2
constexpr int kBbUnroll = BB_UNROLL;
#define ST_T0 2250
#define ST_PER 286
#define ST_PER2 320
#define LN_PAUSE 0xf0
#define FEW_ST 10
#define FEW_H 24

struct Exchange {
    uint2 stat[SEQ];
    uint4 h[GU_CTAS * 32];
    uint32_t cnt[4 * 32];
};
__device__ __align__(128) Exchange g_scratch[NREP];

struct Ptrs {
    const __nv_bfloat16 *logA, *Aim, *Cre, *Cim, *ldt, *u;
    const __nv_bfloat16 *dsk, *wr;
    Exchange* sc;
    __nv_bfloat16* out;
    uint32_t zero;
};
struct Maps {
    CUtensorMap u, out, wg, wu, wd;
};

#define STAMP(i) do { } while (0)
#define GSTAMP(i) do { } while (0)

__device__ __forceinline__ uint32_t s_u32(const void* p) { return (uint32_t)__cvta_generic_to_shared(p); }
__device__ __forceinline__ void mbar_init(uint32_t b, uint32_t n) {
    asm volatile("mbarrier.init.shared::cta.b64 [%0], %1;" ::"r"(b), "r"(n) : "memory");
}
__device__ __forceinline__ void mbar_expect_tx(uint32_t b, uint32_t bytes) {
    asm volatile("mbarrier.arrive.expect_tx.shared::cta.b64 _, [%0], %1;" ::"r"(b), "r"(bytes) : "memory");
}
__device__ __forceinline__ void mbar_arrive(uint32_t b) {
    asm volatile("mbarrier.arrive.shared::cta.b64 _, [%0];" ::"r"(b) : "memory");
}
__device__ __forceinline__ void mbar_arrive_n(uint32_t b, uint32_t n) {
    asm volatile("mbarrier.arrive.shared::cta.b64 _, [%0], %1;" ::"r"(b), "r"(n) : "memory");
}
__device__ __forceinline__ void mbar_arrive_peer(uint32_t b_cluster) {
    asm volatile("mbarrier.arrive.relaxed.cluster.shared::cluster.b64 _, [%0];" ::"r"(b_cluster) : "memory");
}
__device__ __forceinline__ void mbar_wait(uint32_t b, uint32_t parity) {
    asm volatile("{\n\t.reg .pred p;\n\t.reg .u32 c;\n\tmov.u32 c, 0;\n"
                 "W:\n\tmbarrier.try_wait.parity.shared::cta.b64 p, [%0], %1;\n\t@p bra D;\n\t"
                 "add.u32 c, c, 1;\n\tsetp.lt.u32 p, c, 1048576;\n\t@p bra W;\n\ttrap;\nD:\n\t}"
                 ::"r"(b), "r"(parity) : "memory");
}
__device__ __forceinline__ bool elect_one() {
    uint32_t p;
    asm volatile("{ .reg .pred P; elect.sync _|P, 0xffffffff; selp.u32 %0, 1, 0, P; }" : "=r"(p));
    return p != 0;
}
__device__ __forceinline__ uint32_t mapa(uint32_t a, uint32_t rank) {
    uint32_t r;
    asm("mapa.shared::cluster.u32 %0, %1, %2;" : "=r"(r) : "r"(a), "r"(rank));
    return r;
}
__device__ __forceinline__ void cluster_arrive() { asm volatile("barrier.cluster.arrive.relaxed.aligned;" ::: "memory"); }
__device__ __forceinline__ void cluster_wait() { asm volatile("barrier.cluster.wait.acquire.aligned;" ::: "memory"); }
__device__ __forceinline__ void tma_load_2d(uint32_t dst, const CUtensorMap* m, int c0, int c1, uint32_t bar) {
    asm volatile("cp.async.bulk.tensor.2d.shared::cluster.global.mbarrier::complete_tx::bytes [%0], [%1, {%3, %4}], [%2];"
                 ::"r"(dst), "l"(m), "r"(bar), "r"(c0), "r"(c1) : "memory");
}
__device__ __forceinline__ void tma_load_perm(uint32_t dst, const CUtensorMap* m, int c0, int blk, uint32_t bar) {
    asm volatile("cp.async.bulk.tensor.5d.shared::cluster.global.mbarrier::complete_tx::bytes [%0], [%1, {%3, %4, %4, %4, %5}], [%2];"
                 ::"r"(dst), "l"(m), "r"(bar), "r"(c0), "r"(0), "r"(blk) : "memory");
}
__device__ __forceinline__ void tma_load_tile(uint32_t dst, const CUtensorMap* m, int c0, int c2, int c3, uint32_t bar) {
    asm volatile("cp.async.bulk.tensor.4d.shared::cluster.global.mbarrier::complete_tx::bytes.multicast::cluster [%0], [%1, {%3, %4, %5, %6}], [%2], %7;"
                 ::"r"(dst), "l"(m), "r"(bar), "r"(c0), "r"(0), "r"(c2), "r"(c3), "h"((uint16_t)3) : "memory");
}
__device__ __forceinline__ void tma_store_tile(const CUtensorMap* m, uint32_t src, int c0, int c2, int c3) {
    asm volatile("cp.async.bulk.tensor.4d.global.shared::cta.bulk_group [%0, {%2, %3, %4, %5}], [%1];"
                 ::"l"(m), "r"(src), "r"(c0), "r"(0), "r"(c2), "r"(c3) : "memory");
    asm volatile("cp.async.bulk.commit_group;" ::: "memory");
}
__device__ __forceinline__ void bulk_g2s(uint32_t dst, const void* src, uint32_t bytes, uint32_t bar) {
    asm volatile("cp.async.bulk.shared::cluster.global.mbarrier::complete_tx::bytes [%0], [%1], %2, [%3];"
                 ::"r"(dst), "l"(src), "r"(bytes), "r"(bar) : "memory");
}
__device__ __forceinline__ void st_async128(uint32_t dst_cluster, uint32_t x, uint32_t y, uint32_t z, uint32_t w, uint32_t bar_cluster) {
    asm volatile("st.async.weak.shared::cluster.mbarrier::complete_tx::bytes.v4.b32 [%0], {%1,%2,%3,%4}, [%5];"
                 ::"r"(dst_cluster), "r"(x), "r"(y), "r"(z), "r"(w), "r"(bar_cluster) : "memory");
}
__device__ __forceinline__ void fence_async() { asm volatile("fence.proxy.async.shared::cta;" ::: "memory"); }
__device__ __forceinline__ void named_sync(int id, int n) { asm volatile("bar.sync %0, %1;" ::"r"(id), "r"(n) : "memory"); }

__device__ __forceinline__ void ldsm4(uint32_t* r, uint32_t a) {
    asm volatile("ldmatrix.sync.aligned.m8n8.x4.shared.b16 {%0,%1,%2,%3}, [%4];"
                 : "=r"(r[0]), "=r"(r[1]), "=r"(r[2]), "=r"(r[3]) : "r"(a));
}
__device__ __forceinline__ void ldsm4t(uint32_t* r, uint32_t a) {
    asm volatile("ldmatrix.sync.aligned.m8n8.x4.trans.shared.b16 {%0,%1,%2,%3}, [%4];"
                 : "=r"(r[0]), "=r"(r[1]), "=r"(r[2]), "=r"(r[3]) : "r"(a));
}
__device__ __forceinline__ void stsm4t(uint32_t a, uint32_t x, uint32_t y, uint32_t z, uint32_t w) {
    asm volatile("stmatrix.sync.aligned.m8n8.x4.trans.shared.b16 [%0], {%1,%2,%3,%4};"
                 ::"r"(a), "r"(x), "r"(y), "r"(z), "r"(w) : "memory");
}
__device__ __forceinline__ uint32_t lds32(uint32_t a) { uint32_t v; asm volatile("ld.shared.u32 %0, [%1];" : "=r"(v) : "r"(a)); return v; }
__device__ __forceinline__ float lds32f(uint32_t a) { float v; asm volatile("ld.shared.f32 %0, [%1];" : "=f"(v) : "r"(a)); return v; }
__device__ __forceinline__ uint2 lds64(uint32_t a) { uint2 v; asm volatile("ld.shared.v2.u32 {%0,%1}, [%2];" : "=r"(v.x), "=r"(v.y) : "r"(a)); return v; }
__device__ __forceinline__ uint4 lds128(uint32_t a) {
    uint4 v; asm volatile("ld.shared.v4.u32 {%0,%1,%2,%3}, [%4];" : "=r"(v.x), "=r"(v.y), "=r"(v.z), "=r"(v.w) : "r"(a)); return v;
}
__device__ __forceinline__ uint4 lds128v(uint32_t a) {
    uint4 v; asm volatile("ld.volatile.shared.v4.u32 {%0,%1,%2,%3}, [%4];" : "=r"(v.x), "=r"(v.y), "=r"(v.z), "=r"(v.w) : "r"(a)); return v;
}
__device__ __forceinline__ uint32_t or_xor(uint32_t a, uint32_t b, uint32_t c) {
    uint32_t r; asm("lop3.b32 %0, %1, %2, %3, 0xf6;" : "=r"(r) : "r"(a), "r"(b), "r"(c)); return r;
}
__device__ __forceinline__ float4 lds128f(uint32_t a) {
    float4 v; asm volatile("ld.shared.v4.f32 {%0,%1,%2,%3}, [%4];" : "=f"(v.x), "=f"(v.y), "=f"(v.z), "=f"(v.w) : "r"(a)); return v;
}
__device__ __forceinline__ void sts32(uint32_t a, uint32_t v) { asm volatile("st.shared.u32 [%0], %1;" ::"r"(a), "r"(v) : "memory"); }
__device__ __forceinline__ void sts32f(uint32_t a, float v) { asm volatile("st.shared.f32 [%0], %1;" ::"r"(a), "f"(v) : "memory"); }
__device__ __forceinline__ void sts64(uint32_t a, uint32_t x, uint32_t y) { asm volatile("st.shared.v2.u32 [%0], {%1,%2};" ::"r"(a), "r"(x), "r"(y) : "memory"); }
__device__ __forceinline__ void sts64f(uint32_t a, float x, float y) { asm volatile("st.shared.v2.f32 [%0], {%1,%2};" ::"r"(a), "f"(x), "f"(y) : "memory"); }
__device__ __forceinline__ void sts128(uint32_t a, uint32_t x, uint32_t y, uint32_t z, uint32_t w) {
    asm volatile("st.shared.v4.u32 [%0], {%1,%2,%3,%4};" ::"r"(a), "r"(x), "r"(y), "r"(z), "r"(w) : "memory");
}
__device__ __forceinline__ void sts128f(uint32_t a, const float* v) {
    asm volatile("st.shared.v4.f32 [%0], {%1,%2,%3,%4};" ::"r"(a), "f"(v[0]), "f"(v[1]), "f"(v[2]), "f"(v[3]) : "memory");
}
__device__ __forceinline__ uint4 ldg128(const void* p) {
    uint4 v; asm volatile("ld.global.nc.L1::no_allocate.v4.u32 {%0,%1,%2,%3}, [%4];" : "=r"(v.x), "=r"(v.y), "=r"(v.z), "=r"(v.w) : "l"(p)); return v;
}
__device__ __forceinline__ uint2 ldg64(const void* p) {
    uint2 v; asm volatile("ld.global.nc.L1::no_allocate.v2.u32 {%0,%1}, [%2];" : "=r"(v.x), "=r"(v.y) : "l"(p)); return v;
}
__device__ __forceinline__ uint32_t ldg16(const void* p) {
    uint32_t v; asm volatile("ld.global.nc.u16 %0, [%1];" : "=r"(v) : "l"(p)); return v;
}
__device__ __forceinline__ uint2 ld_relaxed_64(const void* p) {
    uint2 v; asm volatile("ld.relaxed.gpu.global.v2.u32 {%0,%1}, [%2];" : "=r"(v.x), "=r"(v.y) : "l"(p) : "memory"); return v;
}
__device__ __forceinline__ uint32_t ld_relaxed_32(const void* p) {
    uint32_t v; asm volatile("ld.relaxed.gpu.global.u32 %0, [%1];" : "=r"(v) : "l"(p) : "memory"); return v;
}
__device__ __forceinline__ void st_relaxed_64(void* p, uint32_t x, uint32_t y) {
    asm volatile("st.relaxed.gpu.global.v2.u32 [%0], {%1,%2};" ::"l"(p), "r"(x), "r"(y) : "memory");
}
__device__ __forceinline__ void st_relaxed_32(void* p, uint32_t v) {
    asm volatile("st.relaxed.gpu.global.u32 [%0], %1;" ::"l"(p), "r"(v) : "memory");
}
__device__ __forceinline__ void red_add(void* p, uint32_t v) { asm volatile("red.relaxed.gpu.global.add.u32 [%0], %1;" ::"l"(p), "r"(v) : "memory"); }
__device__ __forceinline__ uint32_t now_ns() { uint32_t t; asm volatile("mov.u32 %0, %%globaltimer_lo;" : "=r"(t) :: "memory"); return t; }
__device__ __forceinline__ void sleep_until(uint32_t t) {
#pragma unroll 1
    for (int left; (left = (int)(t - now_ns())) > 0;) __nanosleep(left >> 1);
}
__device__ __forceinline__ void spin_guard(uint32_t& it) { if (++it > SPIN_LIMIT) __trap(); }
__device__ __forceinline__ void wait_count(const uint32_t* p, uint32_t target) {
#pragma unroll 1
    for (uint32_t it = 0; __any_sync(0xffffffffu, (int)(ld_relaxed_32(p) - target) < 0); spin_guard(it)) { }
}
__device__ __forceinline__ void mma_bf16_k8(float* c, uint32_t a0, uint32_t a1, uint32_t b0) {
    asm("mma.sync.aligned.m16n8k8.row.col.f32.bf16.bf16.f32 {%0,%1,%2,%3}, {%4,%5}, {%6}, {%0,%1,%2,%3};"
                 : "+f"(c[0]), "+f"(c[1]), "+f"(c[2]), "+f"(c[3]) : "r"(a0), "r"(a1), "r"(b0));
}
__device__ __forceinline__ void mma_v(float* c, const uint32_t* a, uint32_t b0, uint32_t b1) {
    asm volatile("mma.sync.aligned.m16n8k16.row.col.f32.bf16.bf16.f32 {%0,%1,%2,%3}, {%4,%5,%6,%7}, {%8,%9}, {%0,%1,%2,%3};"
                 : "+f"(c[0]), "+f"(c[1]), "+f"(c[2]), "+f"(c[3]) : "r"(a[0]), "r"(a[1]), "r"(a[2]), "r"(a[3]), "r"(b0), "r"(b1));
}
__device__ __forceinline__ void mma_bf16_z(float* c, uint32_t a0, uint32_t a1, uint32_t a2, uint32_t a3, uint32_t b0, uint32_t b1) {
    asm volatile("mma.sync.aligned.m16n8k16.row.col.f32.bf16.bf16.f32 {%0,%1,%2,%3}, {%4,%5,%6,%7}, {%8,%9}, {%10,%10,%10,%10};"
        : "=f"(c[0]), "=f"(c[1]), "=f"(c[2]), "=f"(c[3]) : "r"(a0), "r"(a1), "r"(a2), "r"(a3), "r"(b0), "r"(b1), "f"(0.f));
}
__device__ __forceinline__ void mma_f16(float* c, uint32_t a0, uint32_t a1, uint32_t a2, uint32_t a3, uint32_t b0, uint32_t b1) {
    asm("mma.sync.aligned.m16n8k16.row.col.f32.f16.f16.f32 {%0,%1,%2,%3}, {%4,%5,%6,%7}, {%8,%9}, {%0,%1,%2,%3};"
                 : "+f"(c[0]), "+f"(c[1]), "+f"(c[2]), "+f"(c[3]) : "r"(a0), "r"(a1), "r"(a2), "r"(a3), "r"(b0), "r"(b1));
}
__device__ __forceinline__ uint32_t pack_bf16(float lo, float hi) {
    uint32_t r; asm("cvt.rn.bf16x2.f32 %0, %1, %2;" : "=r"(r) : "f"(hi), "f"(lo)); return r;
}
__device__ __forceinline__ uint32_t pack_v(float lo, float hi) {
    uint32_t r; asm volatile("cvt.rn.bf16x2.f32 %0, %1, %2;" : "=r"(r) : "f"(hi), "f"(lo)); return r;
}
__device__ __forceinline__ uint32_t pack_w(float lo, float hi) {
    uint32_t r; asm volatile("cvt.rn.satfinite.bf16x2.f32 %0, %1, %2;" : "=r"(r) : "f"(hi), "f"(lo)); return r;
}
template <int N> __device__ __forceinline__ uint32_t after_all(const uint32_t (&f)[N][4], uint32_t zero) {
    uint32_t d[3] = {0, 0, 0};
#pragma unroll
    for (int i = 0; i < N; i++) d[i % 3] |= f[i][3];
    return (d[0] | d[1] | d[2]) & zero;
}
__device__ __forceinline__ void pin(uint32_t& x) { asm volatile("" : "+r"(x)); }
template <class T> __device__ __forceinline__ void pin(T*& x) { asm volatile("" : "+l"(x)); }
__device__ __forceinline__ uint32_t pack_f16(float lo, float hi) {
    uint32_t r; asm("cvt.rn.f16x2.f32 %0, %1, %2;" : "=r"(r) : "f"(hi), "f"(lo)); return r;
}
__device__ __forceinline__ float bf_lo(uint32_t v) { return __uint_as_float(v << 16); }
__device__ __forceinline__ float bf_hi(uint32_t v) { return __uint_as_float(v & 0xffff0000u); }
__device__ __forceinline__ float bf_round(float x) { return __uint_as_float(pack_bf16(0.f, x)); }
__device__ __forceinline__ uint32_t badd2(uint32_t a, uint32_t b) { uint32_t r; asm("add.rn.bf16x2 %0, %1, %2;" : "=r"(r) : "r"(a), "r"(b)); return r; }
__device__ __forceinline__ uint32_t bsub2_lo(uint32_t a, uint32_t b) {
    uint32_t r; asm("{ .reg .b16 m, h; .reg .b32 m2; mov.b32 {m, h}, %2; mov.b32 m2, {m, m}; sub.rn.bf16x2 %0, %1, m2; }" : "=r"(r) : "r"(a), "r"(b)); return r;
}
__device__ __forceinline__ uint32_t bmax2(uint32_t a, uint32_t b) { uint32_t r; asm("max.bf16x2 %0, %1, %2;" : "=r"(r) : "r"(a), "r"(b)); return r; }
__device__ __forceinline__ uint32_t normalize2(uint32_t x, uint32_t s0, uint32_t s1) {
    uint32_t r;
    asm("{ .reg .b16 m, h, l, k; .reg .b32 m2, h2, l2, d, t;\n\t"
        "mov.b32 {m, h}, %2; mov.b32 {l, k}, %3; mov.b32 m2, {m, m}; mov.b32 h2, {h, h}; mov.b32 l2, {l, l};\n\t"
        "sub.rn.bf16x2 d, %1, m2; mul.rn.bf16x2 t, d, l2; fma.rn.bf16x2 %0, d, h2, t; }" : "=r"(r) : "r"(x), "r"(s0), "r"(s1));
    return r;
}
__device__ __forceinline__ float rcpf(float x) { float r; asm("rcp.approx.ftz.f32 %0, %1;" : "=f"(r) : "f"(x)); return r; }
__device__ __forceinline__ float sqrtaf(float x) { float r; asm("sqrt.approx.ftz.f32 %0, %1;" : "=f"(r) : "f"(x)); return r; }
__device__ __forceinline__ float ex2f(float x) { float r; asm("ex2.approx.ftz.f32 %0, %1;" : "=f"(r) : "f"(x)); return r; }

__device__ __forceinline__ int tok_off(int t) { return ((t >> 3) & 1) * VT_PLANE + (t >> 4) * 16 + (t & 7) * 2; }

__device__ __forceinline__ uint32_t unorder_key(uint32_t k16) { return k16 ^ ((k16 & 0x8000u) ? 0x8000u : 0xffffu); }

struct cplx { float r, i; };
struct hc { uint32_t r, i; };
template <bool CONJ> __device__ __forceinline__ cplx csq(cplx a) {
    float im;
    asm("{ .reg .f32 t; mul.ftz.f32 t, %1, %2; mul.ftz.f32 %0, t, 0f40000000; }" : "=f"(im) : "f"(CONJ ? -a.r : a.r), "f"(a.i));
    return {fmaf(a.r, a.r, -(a.i * a.i)), im};
}
__device__ __forceinline__ cplx cexpp(float a2, float ai) {
    float m = ex2f(a2), s, c;
    __sincosf(ai, &s, &c);
    return {m * c, m * s};
}
__device__ __forceinline__ __half2 as_h2(uint32_t x) { return *reinterpret_cast<__half2*>(&x); }
__device__ __forceinline__ uint32_t as_u(__half2 x) { return *reinterpret_cast<uint32_t*>(&x); }
__device__ __forceinline__ hc hmul(hc a, hc b) {
    return {as_u(__hfma2(as_h2(a.r), as_h2(b.r), __hneg2(__hmul2(as_h2(a.i), as_h2(b.i))))),
            as_u(__hfma2(as_h2(a.r), as_h2(b.i), __hmul2(as_h2(a.i), as_h2(b.r))))};
}
__device__ __forceinline__ hc hpack(cplx a, cplx b) { return {pack_f16(a.r, b.r), pack_f16(a.i, b.i)}; }
__device__ __forceinline__ void sts16(uint32_t a, uint32_t v) { asm volatile("st.shared.u16 [%0], %1;" ::"r"(a), "r"(v) : "memory"); }

struct KgenAddr {
    uint32_t l, h, m2, m3, m4, z, w, wz;
    __device__ __forceinline__ KgenAddr(uint32_t scr, int lane) {
        const int g = lane >> 2, t = lane & 3;
        const uint32_t rec = scr + t * 480;
        l = rec + 16 * g; h = rec + 128 + 8 * g; m2 = rec + 192 + 8 * (g & 1); m3 = rec + 208 + 4 * (g & 2); m4 = rec + 224 + 2 * (g & 4);
        z = scr + 7680 + 16 * t; w = scr + 240 * lane; wz = scr + 7680 + 8 * lane;
        pin(l); pin(h); pin(m2); pin(m3); pin(m4); pin(z); pin(w); pin(wz);
    }
    __device__ __forceinline__ uint32_t any() const { return (l | h | m2) | (m3 | m4 | z) | (w | wz); }
};
template <class Hook, class Hook2>
__device__ __forceinline__ void kgen(const KgenAddr& ad, uint32_t tab, int lane, uint2 la, uint2 aim, uint2 cre, uint2 cim, float dt, float skip, int dch, Hook main_done, Hook2 half_done) {
    const int g = lane >> 2, t = lane & 3;
    const float dt2 = 2.f * dt;
    const uint32_t am = bmax2(bmax2(cre.x & 0x7fff7fffu, cre.y & 0x7fff7fffu), bmax2(cim.x & 0x7fff7fffu, cim.y & 0x7fff7fffu));
    const float mx = dt2 * fmaxf(bf_lo(am), bf_hi(am));
    const uint32_t eb = min(max(__reduce_max_sync(0xffffffffu, __float_as_uint(mx)) >> 23, 1u), 252u);
    const float cscale = dt2 * __uint_as_float((253u - eb) << 23);
    const float scale_inv = __uint_as_float((eb + 1u) << 23);
    float k0 = (bf_lo(cre.x) + bf_hi(cre.x)) + (bf_lo(cre.y) + bf_hi(cre.y));
#pragma unroll
    for (int o = 16; o; o >>= 1) k0 += __shfl_xor_sync(0xffffffffu, k0, o);
    const float ndt = -1.4426950408889634f * dt;
    STAMP(40);

    float acc[5][4];
#pragma unroll
    for (int i = 0; i < 5; i++) { acc[i][0] = acc[i][1] = acc[i][2] = acc[i][3] = 0.f; }

#pragma unroll kBbUnroll
    for (int bb = 0; bb < 2; bb++) {
        cplx z[2][11], cz[2];
#pragma unroll
        for (int e = 0; e < 2; e++) {
            const float lg = e ? bf_hi(la.x) : bf_lo(la.x), ai = (e ? bf_hi(aim.x) : bf_lo(aim.x)) * dt;
            const float cr = (e ? bf_hi(cre.x) : bf_lo(cre.x)) * cscale, ci = (e ? bf_hi(cim.x) : bf_lo(cim.x)) * cscale;
            const float a2 = bf_round(ex2f(lg * 1.4426950408889634f)) * ndt;
            z[e][0] = cexpp(a2, ai);
            z[e][5] = cexpp(a2 * 32.f, ai * -32.f);
#pragma unroll
            for (int i = 1; i < 11; i++) if (i != 5) z[e][i] = (i == 3 || i == 7) ? csq<true>(z[e][i - 1]) : csq<false>(z[e][i - 1]);
            cz[e] = {fmaf(cr, z[e][0].r, -(ci * z[e][0].i)), fmaf(cr, z[e][0].i, ci * z[e][0].r)};
        }
        la.x = la.y; aim.x = aim.y; cre.x = cre.y; cim.x = cim.y;
        const hc z1 = hpack(z[0][0], z[1][0]), z2 = hpack(z[0][1], z[1][1]), z4 = hpack(z[0][2], z[1][2]);
        hc L[8], H[8];
        L[1] = hpack(z[0][3], z[1][3]); L[2] = hpack(z[0][4], z[1][4]); L[4] = hpack(z[0][5], z[1][5]);
        const hc y64 = hpack(z[0][6], z[1][6]), z128 = hpack(z[0][7], z[1][7]), z256 = hpack(z[0][8], z[1][8]);
        const hc z512 = hpack(z[0][9], z[1][9]), z1024 = hpack(z[0][10], z[1][10]);
        H[0] = hpack(cz[0], cz[1]);
        H[1] = hmul(H[0], z1); H[2] = hmul(H[0], z2); H[3] = hmul(H[1], z2);
        L[3] = hmul(L[1], L[2]);
#pragma unroll
        for (int i = 0; i < 4; i++) { H[4 + i] = hmul(H[i], z4); if (i) L[4 + i] = hmul(L[i], L[4]); }
        __syncwarp();
        sts128(ad.w, 0x3c003c00u, y64.r, 0u, y64.i);
#pragma unroll
        for (int i = 1; i < 8; i++) { const hc q = hmul(L[i], y64); sts128(ad.w + 16 * i, L[i].r, q.r, L[i].i, q.i); }
#pragma unroll
        for (int i = 0; i < 4; i++) sts128(ad.w + 128 + 16 * i, H[2 * i].r, H[2 * i].i, H[2 * i + 1].r, H[2 * i + 1].i);
        {
            const hc a = hmul(z256, z1), b = hmul(z256, z128), c = hmul(z256, z2), d = hmul(z512, z4);
            sts128(ad.w + 192, a.r, a.i, b.r, b.i);
            sts128(ad.w + 208, c.r, c.i, z512.r, z512.i);
            sts128(ad.w + 224, d.r, d.i, z1024.r, z1024.i);
            sts64(ad.wz, z128.r, z128.i);
        }
        __syncwarp();

#pragma unroll
        for (int k2 = 0; k2 < 4; k2++) {
#pragma unroll
            for (uint32_t s = 0; s < 2; s++) {
                const uint32_t o = k2 * 1920 + s * 240;
                const uint4 l = lds128(ad.l + o);
                const uint2 h0 = lds64(ad.h + o), m2 = lds64(ad.m2 + o), m3 = lds64(ad.m3 + o), m4 = lds64(ad.m4 + o), mz = lds64(ad.z + k2 * 64 + s * 8);
                const hc H0 = {h0.x, h0.y};
                const hc H1 = hmul(H0, {mz.x, mz.y}), H2 = hmul(H0, {m2.x, m2.y}), H3 = hmul(H2, {m3.x, m3.y}), H4 = hmul(H3, {m4.x, m4.y});
                mma_f16(acc[0], l.x, l.y, l.z, l.w, H0.r, H0.i);
                mma_f16(acc[1], l.x, l.y, l.z, l.w, H1.r, H1.i);
                mma_f16(acc[2], l.x, l.y, l.z, l.w, H2.r, H2.i);
                mma_f16(acc[3], l.x, l.y, l.z, l.w, H3.r, H3.i);
                mma_f16(acc[4], l.x, l.y, l.z, l.w, H4.r, H4.i);
            }
        }

        if (bb == 0) half_done();
    }
    __syncwarp();
    main_done();

#pragma unroll
    for (int i = 0; i < 4; i++) sts128(tab + 2048 + 512 * i + 16 * lane, 0, 0, 0, 0);
    if (lane < 15) sts32(tab + 4 * lane, 0);
    __syncwarp();
    const uint32_t d0 = tab + T_DENSE + 4 + 8 * lane, src = (lane + 31) & 31;
    const uint32_t p0 = pack_bf16(fmaf(k0, dt2, skip), 0.f);
    uint32_t prev = p0;
#pragma unroll
    for (int i = 0; i < 4; i++) {
        const uint32_t pk = pack_bf16(acc[i >> 1][2 * (i & 1) + 1] * scale_inv, acc[i >> 1][2 * (i & 1)] * scale_inv);
        sts64(d0 + 256 * i, __byte_perm(pk, __shfl_sync(0xffffffffu, lane == 31 ? prev : pk, src), 0x5432), pk);
        prev = pk;
    }
    const uint32_t w0 = pack_bf16(acc[2][0] * scale_inv, acc[2][1] * scale_inv), w1 = pack_bf16(acc[2][2] * scale_inv, acc[2][3] * scale_inv);
    const uint32_t sa = (lane & 1) ? 0x5410u : 0x5454u, sb2 = (lane & 1) ? 0x1010u : 0x5410u;
#pragma unroll
    for (int hf = 0; hf < 2; hf++) {
        const uint32_t w = hf ? w1 : w0;
        const uint32_t pv = __shfl_sync(0xffffffffu, lane != 31 ? w : hf ? w0 : __byte_perm(prev, w1, 0x5410), src);
        sts64(d0 + 1024 + 256 * hf, __byte_perm(w, pv, sa), __byte_perm(w, pv, sb2));
        sts64(d0 + 1536 + 256 * hf, __byte_perm(w, pv, sa + 0x2222u), __byte_perm(w, pv, sb2 + 0x2222u));
    }
    const uint32_t d3 = tab + T_R2 + 160 + 320 * (t & 1) + 16 * (g >> 1) + 8 * (g & 1) + 4 * (t >> 1), d3n = d3 + (g >= 6 ? 32 : 0);
    const uint32_t d4 = tab + T_R3 + 80 + 160 * t + 4 * g, d4n = d4 + (g >= 6 ? 16 : 0);
    uint32_t p3;
#pragma unroll
    for (int hf = 0; hf < 2; hf++)
#pragma unroll
        for (int e = 0; e < 2; e++) {
            const float v3 = acc[3][2 * hf + e] * scale_inv;
            const uint32_t p4 = pack_bf16(acc[4][2 * hf + e] * scale_inv, 0.f);
            p3 = pack_bf16(v3, v3);
            sts16(d3 + 64 * hf + 160 * e, p3);
            sts16((hf ? d3n : d3) + 64 * hf + 160 * e + 18, p3);
            sts16(d4 + 32 * hf + 80 * e, p4);
            sts16((hf ? d4n : d4) + 32 * hf + 80 * e + 10, p4);
        }
    if (lane == 31) {
        const uint32_t k512 = __byte_perm(w1, 0, 0x3232);
        sts32(tab + T_DENSE, p0);
        sts64(tab + T_DENSE + 4 * 513, k512, k512); sts16(tab + T_DENSE + 4 * 515 + 2, k512);
        sts16(tab + T_PATCH + 4 * 17, p3); sts32(tab + T_PATCH + 4 * 18, p3); sts16(tab + T_PATCH + 4 * 19 + 2, p3);
    }
    __syncwarp();
}

__device__ __forceinline__ void load_toep(uint32_t* a, uint32_t p, uint32_t pz) {
    a[0] = lds32(p); a[1] = lds32(p + 32); a[2] = lds32(pz - 32); a[3] = lds32(pz);
}
template <int F>
__device__ __forceinline__ void ffa_step(float (&acc)[16][4], float (&W)[8][4], uint32_t (&R)[8][4], uint32_t (&A)[4][4],
                                         uint32_t va, uint32_t vmin, uint32_t pb, uint32_t pz) {
    constexpr int S = F ^ 1;
    auto load = [&](int sh) {
#pragma unroll
        for (int i = S; i < 8; i += 2) ldsm4(R[i], i == 0 ? max(va - 16 * sh, vmin) : va - 16 * sh + i * 128);
#pragma unroll
        for (int k = S; k < 4; k += 2) load_toep(A[k], pb + 64 * sh + k * 512, pz + 64 * sh + k * 512);
    };
    auto prod = [&](int par, int dst) {
#pragma unroll
        for (int k = 0; k < 2; k++)
#pragma unroll
            for (int m = k; m < 8; m++) {
                const uint32_t* x = &R[2 * ((m - k) & 3) + par][2 * ((m - k) >> 2)];
                mma_v(dst == 1 ? W[m] : acc[2 * m + (dst >> 1)], A[2 * k + par], x[0], x[1]);
            }
    };
    load(0);
    prod(F, F);
    prod(S, S);
#pragma unroll
    for (int i = 0; i < 8; i++) A[(i >> 2) * 2 + F][i & 3] = badd2(A[(i >> 2) * 2][i & 3], A[(i >> 2) * 2 + 1][i & 3]);
#pragma unroll
    for (int i = 0; i < 16; i++) R[(i >> 2) * 2 + F][i & 3] = badd2(R[(i >> 2) * 2][i & 3], R[(i >> 2) * 2 + 1][i & 3]);
    load(1);
    prod(F, 2);
}
struct DenseTaps {
    uint32_t A[4][4], E[4], F[4], G[4];
    __device__ __forceinline__ DenseTaps(uint32_t pb, uint32_t pz) {
        constexpr int PP = T_PATCH - T_DENSE + 56;
        load_toep(E, pb + 2048, pz + 2048);
        load_toep(F, pb + PP, pz + PP);
        G[0] = lds32(pz + 2048 + 32); G[1] = lds32(pb + 2048 + 64); G[2] = lds32(pz + PP + 32); G[3] = lds32(pb + PP + 64);
    }
};
__device__ __forceinline__ uint32_t dense_phase(float (&acc)[16][4], uint32_t vmin, uint32_t va, uint32_t vo, uint32_t pb, DenseTaps& tp, uint32_t zero) {
    uint32_t R[8][4];
    uint32_t pz = pb + zero;
    {
        uint32_t H[4][4];
#pragma unroll
        for (int i = 0; i < 4; i++) ldsm4(H[i], vo + i * 256);
#pragma unroll
        for (int i = 0; i < 8; i++) ldsm4(R[i], va + i * 128);
#pragma unroll
        for (int i = 0; i < 4; i += 2) load_toep(tp.A[i], pb + 512 * i, pz + 512 * i);
#pragma unroll
        for (int i = 0; i < 4; i++) mma_bf16_k8(acc[i + 4], tp.G[0], tp.G[1], H[i >> 1][2 * (i & 1) + 1]);
#pragma unroll
        for (int i = 0; i < 8; i++) mma_v(acc[i + 8], tp.G, H[i >> 1][2 * (i & 1)], H[i >> 1][2 * (i & 1) + 1]);
#pragma unroll
        for (int i = 0; i < 12; i++) mma_v(acc[i + 4], tp.E, R[i & 7][2 * (i >> 3)], R[i & 7][2 * (i >> 3) + 1]);
#pragma unroll
        for (int i = 0; i < 8; i++) mma_v(acc[i + 8], tp.F, R[i][0], R[i][1]);
    }
    float W[8][4];
#pragma unroll
    for (int i = 0; i < 32; i++) { W[i >> 2][i & 3] = 0.f; if (i >= 8) acc[2 * (i >> 2) + 1][i & 3] += acc[2 * (i >> 2)][i & 3]; }
#pragma unroll 1
    for (int rho = 0; rho < 8; rho += 2) {
        ffa_step<0>(acc, W, R, tp.A, va, vmin, pb, pz);
        ffa_step<1>(acc, W, R, tp.A, va - 16, vmin, pb + 64, pz + 64);
        pb += 128; pz += 128; va -= 32;
    }
#pragma unroll
    for (int i = 0; i < 32; i++) {
        const int m = i >> 2, j = i & 3;
        acc[2 * m + 1][j] = (acc[2 * m + 1][j] - acc[2 * m][j]) - W[m][j];
        if (m) acc[2 * m][j] += W[m - 1][j];
    }
    return __float_as_uint(W[7][0]) & zero;
}
__device__ __forceinline__ uint32_t ones2(int c, int lo, int hi) {
    return (((uint32_t)(c - lo) <= (uint32_t)(hi - lo)) ? 1u : 0u) | (((uint32_t)(c + 1 - lo) <= (uint32_t)(hi - lo)) ? 0x10000u : 0u);
}
__device__ __forceinline__ uint32_t box_bits(int lane) {
    const int d = 2 * (lane & 3) - (lane >> 2);
    auto four = [&](int L1, int H1, int L2, int H2) { return ones2(d, L1, H1) | ones2(d, L2, H2) << 1 | ones2(d + 8, L1, H1) << 2 | ones2(d + 8, L2, H2) << 3; };
    return four(5, 7, 0, 4) | four(1, 7, 0, 8) << 4;
}
struct Boxes {
    uint32_t q[4], ha[2];
    __device__ __forceinline__ Boxes(uint32_t bits, int k0, uint32_t h0, uint32_t h1) {
#pragma unroll
        for (int i = 0; i < 4; i++) q[i] = (bits & (0x10001u << (k0 + i))) * (0x3f80u >> (k0 + i));
        ha[0] = h0; ha[1] = h1;
    }
    __device__ __forceinline__ void load(int j, uint32_t* v, uint32_t zero) const {
        const uint32_t o = j * 128;
        v[0] = lds32(ha[0] + o); v[1] = lds32(ha[1] + zero + o); v[2] = lds32(ha[1] + o);
        v[3] = lds32(ha[0] + zero + o + 16); v[4] = lds32(ha[0] + o + 16); v[5] = lds32(ha[1] + o + 16);
    }
    __device__ __forceinline__ void sums(const uint32_t* v, float* Z, float* X, float* Y) const {
        mma_bf16_z(Z, q[0], q[1], q[2], q[3], v[0], v[1]);
        mma_bf16_z(X, q[0], q[1], q[2], q[3], v[2], v[3]);
        mma_bf16_z(Y, q[0], q[1], q[2], q[3], v[4], v[5]);
    }
};
__host__ __device__ constexpr int tail_step(int n) { return n < 8 ? n : n < 12 ? n + 4 : (n & 1) ? 11 - (n - 13) / 2 : 19 - (n - 12) / 2; }
template <class After>
__device__ __forceinline__ void tail_phase(float (&acc)[16][4], const Boxes& b2, const Boxes& b3, uint32_t tp2, uint32_t tp3, uint32_t zero, After after) {
    uint4 t2[5];
    uint2 t3[8];
    uint32_t v[6], a0[4], a1[4];
    float Z[4], X[4], Y[4];
    b2.load(0, v, zero);
#pragma unroll
    for (int i = 0; i < 5; i++) t2[i] = lds128(tp2 + 160 * i);
#pragma unroll
    for (int n = -1; n < 20; n++) {
        const int j = tail_step(n), j1 = tail_step(n + 1), j2 = tail_step(n + 2);
        if (n < 19) {
            (j1 < 12 ? b2 : b3).sums(v, Z, X, Y);
            if (n < 18) { if (j2 < 12) b2.load(j2, v, zero); else b3.load(j2 - 12, v, zero); }
        }
        if (n >= 0 && j < 12) {
#pragma unroll
            for (int b = 0; b < 5; b++) if (j + 4 + b < 16) mma_v(acc[j + 4 + b], a1, t2[b].z, t2[b].w);
        }
        if (n < 19 && j1 < 12) { a1[0] = pack_v(Z[0], Z[1]); a1[1] = pack_w(X[0], X[1]); a1[2] = pack_v(Z[2], Z[3]); a1[3] = pack_w(X[2], X[3]); }
        if (n == 6) {
#pragma unroll
            for (int b = 0; b < 8; b++) t3[b] = lds64(tp3 + 80 * b);
        }
        if (n >= 0 && j < 12) {
#pragma unroll
            for (int b = 0; b < 5; b++) if (j + 4 + b < 16) mma_v(acc[j + 4 + b], a0, t2[b].x, t2[b].y);
        } else if (n >= 0) {
#pragma unroll
            for (int b = 0; b < 8; b++) if (j - 4 + b < 16) mma_v(acc[j - 4 + b], a0, t3[b].x, t3[b].y);
        }
        if (n < 19) {
            if (j1 < 12) { a0[0] = pack_v(X[0], X[1]); a0[1] = pack_v(Y[0], Y[1]); a0[2] = pack_v(X[2], X[3]); a0[3] = pack_v(Y[2], Y[3]); }
            else { a0[0] = pack_v(X[0], X[1]); a0[1] = pack_v(Y[0], Y[1]); a0[2] = pack_v(Z[2], Z[3]); a0[3] = pack_v(X[2], X[3]); }
        }
        after(n);
    }
}
template <int Q>
__device__ __forceinline__ void emit(const float (&acc)[16][4], int h, uint32_t own, uint32_t peer, uint32_t bar, uint32_t bar_peer) {
    constexpr int n = 4 * Q;
#pragma unroll
    for (int hf = 0; hf < 2; hf++)
        asm volatile("{ .reg .pred p; setp.eq.u32 p, %7, %8;\n\t@p st.shared.v4.u32 [%0], {%1,%2,%3,%4};\n\t"
                     "@!p st.async.weak.shared::cluster.mbarrier::complete_tx::bytes.v4.b32 [%5], {%1,%2,%3,%4}, [%6]; }"
                     ::"r"(own + Q * 8192), "r"(pack_bf16(acc[n][2 * hf], acc[n][2 * hf + 1])), "r"(pack_bf16(acc[n + 1][2 * hf], acc[n + 1][2 * hf + 1])),
                     "r"(pack_bf16(acc[n + 2][2 * hf], acc[n + 2][2 * hf + 1])), "r"(pack_bf16(acc[n + 3][2 * hf], acc[n + 3][2 * hf + 1])),
                     "r"(peer + Q * 8192), "r"(bar_peer + 8 * Q), "r"(h), "r"(hf) : "memory");
    __syncwarp();
    if (elect_one()) mbar_arrive(bar);
}
__device__ __forceinline__ uint32_t finish_src(uint32_t sb, int h, int j, int lane) {
    const int m = lane >> 3, r = lane & 7;
    return sb + OFF_XT + (h ^ 1) * 32768 + (2 * m + (r & 1)) * 512 + (((8 * j + (r & 4) + ((r >> 1) & 1)) ^ ((r & 1) << 1)) << 4);
}
__device__ __forceinline__ uint32_t finish_dst(uint32_t sb, int h, int j, int lane) {
    const int g = lane >> 2, t = lane & 3;
    return sb + OFF_XT + h * 32768 + j * 2048 + (g >> 1) * 512 + (t >> 1) * 144 + (2 * (t & 1) + (g & 1)) * 32;
}
__device__ __forceinline__ uint32_t tile_addr(uint32_t sb, int tok, int t) {
    return sb + OFF_XT + (tok & 8) * 4096 + (tok >> 9) * 8192 + (tok & 6) * 1024 + (tok & 448) * 4 + (tok & 1) * 128 + (tok & 48) * 2 + (((t >> 1) ^ (tok & 1)) << 4) + (t & 1) * 8;
}
__device__ __forceinline__ uint2 add_update(uint2 o, uint32_t upd) {
    const float4 u = lds128f(upd);
    return make_uint2(badd2(o.x, pack_bf16(u.x, u.y)), badd2(o.y, pack_bf16(u.z, u.w)));
}
__device__ __forceinline__ void finish_half(uint32_t src, uint32_t xa, const uint4 (&x)[2]) {
    uint32_t s[2][4];
#pragma unroll
    for (int i = 0; i < 2; i++) ldsm4t(s[i], src ^ (i << 5));
#pragma unroll
    for (int i = 0; i < 2; i++) sts128(xa + i * 256, badd2(x[i].x, s[i][0]), badd2(x[i].y, s[i][1]), badd2(x[i].z, s[i][2]), badd2(x[i].w, s[i][3]));
}

__device__ __noinline__ float centred_var(uint32_t rows, float mu, int lane) {
    float var = 0.f;
#pragma unroll 1
    for (int rr = 0; rr < 16; rr++) {
        const float c0 = __shfl_sync(0xffffffffu, mu, rr);
        float c = 0.f;
#pragma unroll 1
        for (int k = 0; k < 16; k++) {
            const uint32_t q = lds32(rows + rr * ROW_PITCH + k * 128 + lane * 4);
            const float d0 = bf_lo(q) - c0, d1 = bf_hi(q) - c0;
            c = fmaf(d0, d0, fmaf(d1, d1, c));
        }
#pragma unroll 1
        for (int o = 16; o; o >>= 1) c += __shfl_xor_sync(0xffffffffu, c, o);
        if ((lane & 15) == rr) var = c * (1.f / DM);
    }
    return var;
}
__device__ __noinline__ float centred_score(uint32_t rows, uint32_t wbuf, uint32_t s0, uint32_t s1, int lane) {
    float sc = 0.f;
#pragma unroll 1
    for (int rr = 0; rr < 16; rr++) {
        const uint32_t t0 = __shfl_sync(0xffffffffu, s0, rr), t1 = __shfl_sync(0xffffffffu, s1, rr);
        float c = 0.f;
#pragma unroll 1
        for (int k = 0; k < 16; k++) {
            const uint32_t xn = normalize2(lds32(rows + rr * ROW_PITCH + k * 128 + lane * 4), t0, t1);
            const uint32_t wq = lds32(wbuf + (k >> 2) * 1024 + (k & 3) * 128 + lane * 4);
            c = fmaf(bf_lo(xn), bf_lo(wq), fmaf(bf_hi(xn), bf_hi(wq), c));
        }
#pragma unroll 1
        for (int o = 16; o; o >>= 1) c += __shfl_xor_sync(0xffffffffu, c, o);
        if ((lane & 15) == rr) sc = c;
    }
    return sc;
}

__device__ __forceinline__ void issue_rows(const __nv_bfloat16* u, uint32_t sb, int b) {
    if (elect_one()) {
        const uint32_t bar = sb + OFF_BAR + 8 * B_ROW;
#pragma unroll
        for (int j = 0; j < 4; j++) mbar_init(bar + 8 * j, 1);
        asm volatile("fence.mbarrier_init.release.cluster;" ::: "memory");
        fence_async();
#pragma unroll 1
        for (int j = 0; j < 4; j++) {
            mbar_expect_tx(bar + 8 * j, 8192);
#pragma unroll
            for (int i = 0; i < 4; i++) bulk_g2s(sb + OFF_VT + (4 * j + i) * ROW_PITCH, u + (size_t)(16 * b + 4 * j + i) * DM, 2048, bar + 8 * j);
        }
    }
    __syncwarp();
}

__global__ void __cluster_dims__(2, 1, 1) __launch_bounds__(NTHR, 1)
fused_kernel(const __grid_constant__ Ptrs p, const __grid_constant__ Maps maps) {
    extern __shared__ __align__(1024) unsigned char smem[];
    const int tid = threadIdx.x, lane = tid & 31;
    const int c_ = ((blockIdx.x >> 1) + 60) & 63, b = 2 * ((c_ & 32) | ((c_ & 7) << 2) | ((c_ >> 3) & 3)) + (blockIdx.x & 1);
    const int dch = 8 * b + (tid >> 5) - 4;
    uint2 la, aim, cre, cim;
    uint32_t ldt16;
    if ((uint32_t)(tid - 128) < 256u) {
        la = ldg64(p.logA + dch * NMODE + 4 * lane); aim = ldg64(p.Aim + dch * NMODE + 4 * lane);
        cre = ldg64(p.Cre + dch * NMODE + 4 * lane); cim = ldg64(p.Cim + dch * NMODE + 4 * lane);
        ldt16 = ldg16(p.ldt + dch);
    }
    const uint32_t sb = s_u32(smem), bar0 = sb + OFF_BAR;
    const int warp = __shfl_sync(0xffffffffu, tid >> 5, 0);
    const int h = b & 1, cl = b >> 1;
    const int m = lane >> 3, r = lane & 7, g = lane >> 2, t = lane & 3;
    const bool has_gu = b < GU_CTAS;
    if (warp == 4) { STAMP(0); GSTAMP(24); }

    if (warp >= 12) {
        asm volatile("setmaxnreg.dec.sync.aligned.u32 24;");
        const int a = warp - 12;
        uint32_t due = now_ns() + ST_T0 + (uint32_t)(2 * a + h) * (ST_PER / 2) + (has_gu ? 0 : 12 * ST_PER + 4 * ST_PER2);
        const bool el = elect_one();
        if (a == 1) issue_rows(p.u, sb, b);
        if (a == 2 && el) {
#pragma unroll
            for (int i = B_XT; i < NBAR; i++) mbar_init(bar0 + 8 * i, (i == B_V || i == B_SFREE || i == B_XFREE || i == B_OWN) ? 8 : (i >= B_RECV && i < B_RECV + 3) ? 9 : i == B_RED ? 5 : (i == B_UPD || (i >= B_FREE && i < B_FULL)) ? 4 : 1);
            asm volatile("fence.mbarrier_init.release.cluster;" ::: "memory");
            fence_async();
            mbar_expect_tx(bar0 + 8 * B_XT, 65536);
#pragma unroll
            for (int i = 0; i < 4; i++) mbar_expect_tx(bar0 + 8 * (B_RECV + i), 4096);
            mbar_expect_tx(bar0 + 8 * B_RED, 2048);
        }
        if (a == 3 && el) {
#pragma unroll
            for (int i = 0; i < 5; i++) asm volatile("prefetch.tensormap [%0];" ::"l"(&maps.u + i) : "memory");
        }
        __syncwarp();
        cluster_arrive();
        cluster_wait();
        STAMP(18);
        uint32_t fs = finish_src(sb, h, a, lane), fx = finish_dst(sb, h, a, lane);
        pin(fs); pin(fx);
        mbar_wait(bar0 + 8 * (B_ROW + a), 0);
        if (el) {
#pragma unroll
            for (int i = 0; i < 4; i++)
                tma_load_tile(sb + OFF_XT + (a >> 1) * 32768 + (a & 1) * 4096 + h * 8192 + (i & 1) * 16384 + (i >> 1) * 2048, &maps.u, 16 * cl, 4 * a + (i & 2), 16 * (i & 1) + 8 * h, bar0 + 8 * B_XT);
        }
        if (el) {
#pragma unroll 1
            for (int k = has_gu ? 0 : 4; k < 6; k++) {
                const int i = 4 * k + a, s = k < 3 ? i : i - 12;
                sleep_until(due);
                due += k < 3 ? 4 * ST_PER : 4 * ST_PER2;
                const bool again = k >= 3 && has_gu;
                if (s >= 6 || again) mbar_wait(bar0 + 8 * (s < 10 || again ? B_FREE + s : B_V), slot_priv(s) && again);
                if (k == 5 && a >= 2) mbar_wait(bar0 + 8 * B_LN, 1);
                const uint32_t dst = sb + slot_off(s), bar = bar0 + 8 * (B_FULL + s);
                if (k < 4) {
                    mbar_expect_tx(bar, 8192);
                    tma_load_2d(dst, &maps.wg, 64 * cl, 512 * h + 32 * i, bar);
                    tma_load_2d(dst + 4096, &maps.wu, 64 * cl, 512 * h + 32 * i, bar);
                } else {
                    mbar_expect_tx(bar, 7168);
                    tma_load_perm(dst, &maps.wd, 16 * cl, 56 * h + 14 * a + 7 * (k & 1), bar);
                }
            }
            STAMP(19);
        }
        __syncwarp();
        {
            mbar_wait(bar0 + 8 * B_XT, 0);
#pragma unroll 1
            for (int Q = 0; Q < 3; Q++) {
#pragma unroll
                for (int q = 0; q < 2; q++) {
                    const uint4 x[2] = {lds128(fx ^ (q << 4)), lds128((fx ^ (q << 4)) + 256)};
                    if (q == 0) mbar_wait(bar0 + 8 * (B_RECV + Q), 0);
                    finish_half(fs + q * 4096, fx ^ (q << 4), x);
                }
                fence_async();
                __syncwarp();
                if (el) tma_store_tile(&maps.out, sb + OFF_XT + h * 32768 + Q * 8192 + a * 2048, 16 * cl, 8 * h + 2 * a, 8 * Q);
                fs += 8192; fx += 8192;
                STAMP(Q ? 58 + Q : 20);
            }
            const int tok = 2047 - (int)(lds32(sb + OFF_MISC + 48 + 8 * g) & 2047);
            const bool mine = ((tok >> 1) & 7) == 4 * h + a && tok < 1536;
            if (el) asm volatile("cp.async.bulk.wait_group 0;" ::: "memory");
            if (__any_sync(0xffffffffu, mine)) {
                const uint2 o0 = lds64(tile_addr(sb, tok, t));
                mbar_wait(bar0 + 8 * B_UPD, 0);
                const uint2 o1 = add_update(o0, sb + tab_off(g) + T_RED + 16 * t);
                if (mine) *reinterpret_cast<uint2*>(p.out + (size_t)tok * DM + 16 * cl + 4 * t) = o1;
            } else STAMP(62);
        }
    } else if (warp >= 4) {
        const int w = warp - 4;
        uint32_t dsk16 = ldg16(p.dsk + dch);
        cluster_arrive();
        asm volatile("setmaxnreg.inc.sync.aligned.u32 176;");
        const uint32_t vrow = sb + OFF_VT + w * VT_PITCH + VT_PAD, tab = sb + tab_off(w);
        const uint32_t rb0 = bar0 + 8 * B_RECV, rb1 = mapa(rb0, h ^ 1);
        uint32_t tpo = 80 + (g - 2 * t) * 8 - (g < 2 * t ? 16 : 0);
        uint32_t xa = sb + OFF_XT + (w >> 1) * 8192 + (w & 1) * 1024 + (g >> 1) * 2048 + (g & 1) * 128 + t * 32 + ((h ^ (g & 1)) << 4);
        uint32_t va = sb + OFF_VT + (2 * m + (r & 1)) * VT_PITCH + VT_PAD + (16 * w + (r >> 1)) * 16;
        uint32_t qa = sb + OFF_ST + 2048 * w + 128 * t + 16 * (g ^ (2 * t));
        uint32_t vmin = vrow + (m & 1) * VT_PLANE - 16, vd = vmin + 16 + (m >> 1) * 1024 + r * 16;
        uint32_t vo = vrow + VT_PLANE + 496 - (m & 1) * 512 + (m >> 1) * 128 + r * 16, vz = vrow - VT_PAD + (lane >> 1) * VT_PLANE + (lane & 1) * 16;
        pin(vmin); pin(vd); pin(vo); pin(vz);
        pin(tpo); pin(xa); pin(va); pin(qa);
        uint32_t bits = box_bits(lane), h0 = vrow + 16 * g + tok_off(2 * t - 18), h1 = vrow + 16 * g + tok_off(2 * t - 10);
        pin(bits); pin(h0); pin(h1);
        const KgenAddr ka(sb + OFF_PRIV + w * 8192, lane);
        if (__any_sync(0xffffffffu, (vmin | (vd | vo | vz) | (tpo | xa) | (va | qa) | (bits | h0 | h1) | ka.any()) & p.zero)) __trap();
        cluster_wait();
        pin(la.x); pin(la.y); pin(aim.x); pin(aim.y); pin(cre.x); pin(cre.y); pin(cim.x); pin(cim.y); pin(ldt16); pin(dsk16);
        uint4 x[8];
        auto load_x = [&]() {
            mbar_wait(bar0 + 8 * B_XT, 0);
#pragma unroll
            for (int i = 0; i < 8; i++) x[i] = lds128(xa + (i & 1) * 32768 + (i >> 1) * 256);
        };
        kgen(ka, tab, lane, la, aim, cre, cim, bf_round(ex2f(bf_lo(ldt16) * 1.4426950408889634f)), 1.f + bf_lo(dsk16), dch, [&]() {
            STAMP(21);
            if (elect_one()) mbar_arrive_n(bar0 + 8 * (B_FREE + 6 + ((w >> 1) ^ 2)), 2);
        }, [&]() {
            if ((LN_PAUSE >> w) & 1) mbar_wait(bar0 + 8 * B_LN, 0);
        });
        STAMP(1);
        const uint32_t pb = tab + T_DENSE + (g - 2 * t) * 4;
        DenseTaps dt(pb, pb + p.zero);
        {
            load_x();
            STAMP(47);
            mbar_wait(bar0 + 8 * (B_ST + (w >> 1)), 0);
            uint4 q[4];
#pragma unroll
            for (int n = 0; n < 4; n++) q[n] = lds128(qa + 512 * n);
            if (lane < 4) sts128(vz, 0, 0, 0, 0);
            STAMP(2); GSTAMP(28);
#pragma unroll
            for (int i = 0; i < 8; i++) {
                const uint32_t s0 = (i & 1) ? q[i >> 1].z : q[i >> 1].x, s1 = (i & 1) ? q[i >> 1].w : q[i >> 1].y;
                stsm4t(va + (i >> 1) * 64 + (i & 1) * VT_PLANE, normalize2(x[i].x, s0, s1), normalize2(x[i].y, s0, s1),
                       normalize2(x[i].z, s0, s1), normalize2(x[i].w, s0, s1));
            }
            __syncwarp();
            if (elect_one()) mbar_arrive(bar0 + 8 * B_V);
        }
        mbar_wait(bar0 + 8 * B_V, 0);
        STAMP(3);
        float acc[16][4];
#pragma unroll
        for (int i = 0; i < 16; i++) { acc[i][0] = acc[i][1] = acc[i][2] = acc[i][3] = 0.f; }
        bits |= dense_phase(acc, vmin, vd, vo, pb, dt, p.zero);
        const Boxes b2(bits, 0, h0, h1), b3(bits, 4, (t == 1 ? h1 : h0) - 4, t == 1 ? h0 + 12 : h1 - 4);
        STAMP(4);
        const uint32_t so = sb + OFF_XT + (8 * h + w) * 512 + ((lane ^ ((w & 1) << 1)) << 4);
        const uint32_t dst0 = so + (h ^ 1) * 32768, dst1 = mapa(so + h * 32768, h ^ 1);
        tail_phase(acc, b2, b3, tab + T_R2 + 2 * tpo, tab + T_R3 + tpo, p.zero, [&](int j) {
            if (j == -1) {
                mbar_wait(bar0 + 8 * B_SFREE, 0);
                emit<0>(acc, h, dst0, dst1, rb0, rb1);
            }
            if (j == 3) { emit<1>(acc, h, dst0, dst1, rb0 + 8, rb1); STAMP(5); }
            if (j == 11) {
                mbar_wait(bar0 + 8 * B_XFREE, 0);
                emit<2>(acc, h, dst0, dst1, rb0 + 16, rb1);
                STAMP(58);
            }
        });
        emit<3>(acc, h, dst0, dst1, bar0 + 8 * B_OWN, rb1);
        STAMP(30);
        if (w < 4) {
            const uint32_t fs = finish_src(sb, h, w, lane) + 24576 + h * 4096, fx = (finish_dst(sb, h, w, lane) + 24576) ^ (h << 4);
            const int tok = 2047 - (int)(lds32(sb + OFF_MISC + 48 + 8 * g) & 2047);
            const bool mine = ((tok >> 1) & 7) == 4 * h + w && tok >= 1536;
            const uint32_t ta = tile_addr(sb, tok, t);
            const uint4 x0[2] = {lds128(fx), lds128(fx + 256)}, x1[2] = {lds128(fx ^ 16), lds128((fx ^ 16) + 256)};
            mbar_wait(bar0 + 8 * B_OWN, 0);
            finish_half(fs, fx, x0);
            mbar_wait(bar0 + 8 * (B_RECV + 3), 0);
            STAMP(6);
            finish_half(fs + (h ? -4096 : 4096), fx ^ 16, x1);
            __syncwarp();
            if (__any_sync(0xffffffffu, mine)) {
                const uint2 o0 = lds64(ta);
                mbar_wait(bar0 + 8 * B_UPD, 0);
                const uint2 o1 = add_update(o0, sb + tab_off(g) + T_RED + 16 * t);
                if (mine) sts64(ta, o1.x, o1.y);
            }
            fence_async();
            __syncwarp();
            if (elect_one()) {
                tma_store_tile(&maps.out, sb + OFF_XT + h * 32768 + 24576 + w * 2048, 16 * cl, 8 * h + 2 * w, 24);
                if (w == 3) STAMP(61);
                asm volatile("cp.async.bulk.wait_group.read 0;" ::: "memory");
            }
        }
        STAMP(7);
    } else {
        const int a = warp;
        const uint4 wq = ldg128(p.wr + 8 * tid);
        const uint32_t epoch = ld_relaxed_32(&p.sc[a].cnt[b & 96]) >> 5;
        cluster_arrive();
        asm volatile("setmaxnreg.inc.sync.aligned.u32 136;");
        const uint32_t tag = __shfl_sync(0xffffffffu, epoch, 0) + 1u, misc = sb + OFF_MISC, abar = bar0 + 8 * (B_AUX + a);
        uint32_t aph = 0;
        const Exchange* in = &p.sc[cl & (NREP - 1)];
        uint2* pub = p.sc[m >> 1].stat + 16 * b + 2 * (r ^ (2 * (b & 3))) + (m & 1);
        uint32_t* cnt_s = &p.sc[t].cnt[b & 96];
        pin(pub); pin(cnt_s);
        if (tid < 32) sts32(sb + OFF_XCH + 4 * tid, 0);
        const uint32_t wbuf = sb + OFF_LN + a * 1024, part = sb + OFF_LN + 4096;
        {
            sts128(wbuf + 16 * lane, wq.x, wq.y, wq.z, wq.w);
            sts128(wbuf + 512 + 16 * lane, 0x3f803f80u, 0x3f803f80u, 0x3f803f80u, 0x3f803f80u);
            float wsum = ((bf_lo(wq.x) + bf_hi(wq.x)) + (bf_lo(wq.y) + bf_hi(wq.y))) + ((bf_lo(wq.z) + bf_hi(wq.z)) + (bf_lo(wq.w) + bf_hi(wq.w)));
#pragma unroll
            for (int o = 16; o; o >>= 1) wsum += __shfl_xor_sync(0xffffffffu, wsum, o);
            sts32f(part + 1024 + 4 * a, wsum);
            uint32_t wf[4][4];
#pragma unroll
            for (int i = 0; i < 4; i++) ldsm4(wf[i], wbuf + ((uint32_t)(r - 1) < 2u ? 16 * (r - 1) : 512) + 32 * m + 128 * i);
            uint32_t ra = sb + OFF_VT + r * ROW_PITCH + 512 * a + 16 * m, pa = part + a * 256 + g * 16;
            cluster_wait();
            STAMP(22);
#pragma unroll 1
            for (int hf = 0; hf < 2; hf++) {
                mbar_wait(bar0 + 8 * B_ROW + 16 * hf, 0);
                mbar_wait(bar0 + 8 * B_ROW + 16 * hf + 8, 0);
                STAMP(23);
                uint32_t x[8][4];
                float cs[2][4], q[8][4];
#pragma unroll
                for (int i = 0; i < 40; i++) (i < 8 ? cs[i >> 2 & 1] : q[(i - 8) >> 2 & 7])[i & 3] = 0.f;
#pragma unroll
                for (int k = 0; k < 8; k++) ldsm4(x[k], ra + k * 64);
                const bool more = __any_sync(0xffffffffu, after_all(x, p.zero));
#pragma unroll 1
                do {
#pragma unroll
                    for (int k = 0; k < 8; k++) {
                        mma_v(cs[k & 1], x[k], wf[k >> 1][2 * (k & 1)], wf[k >> 1][2 * (k & 1) + 1]);
#pragma unroll
                        for (int i = 0; i < 4; i++) mma_bf16_k8(q[4 * (k & 1) + i], x[k][i & 2], x[k][i | 1], x[k][i]);
                    }
                } while (more);
                const float c2 = cs[0][2] + cs[1][2];
                if (t == 0) sts64f(pa, (cs[0][0] + cs[1][0]) + c2, cs[0][1] + cs[1][1]);
                if (t == 1) sts32f(pa + 12, c2);
                const float e0 = ((q[0][0] + q[2][0]) + (q[4][0] + q[6][0])) + ((q[1][2] + q[3][2]) + (q[5][2] + q[7][2]));
                const float e1 = ((q[0][1] + q[2][1]) + (q[4][1] + q[6][1])) + ((q[1][3] + q[3][3]) + (q[5][3] + q[7][3]));
                if (t == (g >> 1)) sts32f(pa + 8, (g & 1) ? e1 : e0);
                ra += 8 * ROW_PITCH; pa += 128;
            }
        }
        STAMP(31);
        named_sync(1, 128);
        if (a == 0) {
            const uint32_t pa = part + (lane & 15) * 16;
            const float4 p0 = lds128f(pa), p1 = lds128f(pa + 256), p2 = lds128f(pa + 512), p3 = lds128f(pa + 768), ws = lds128f(part + 1024);
            const float mu = ((p0.x + p1.x) + (p2.x + p3.x)) * (1.f / DM);
            float var = ((p0.z + p1.z) + (p2.z + p3.z)) * (1.f / DM) - mu * mu;
            const bool centred = __any_sync(0xffffffffu, !(mu * mu <= 4.f * var));
            if (centred) var = centred_var(sb + OFF_VT, mu, lane);
            const float ri = rcpf(bf_round(sqrtaf(bf_round(bf_round(var) + 1e-5f))));
            const uint32_t s0 = pack_bf16(mu, ri), s1 = (pack_bf16(ri - bf_hi(s0), 0.f) & 0xfffcu) | (tag & 3);
            float sc = ((((p0.y + p1.y) + (p2.y + p3.y)) + ((p0.w + p1.w) + (p2.w + p3.w))) - bf_lo(s0) * ((ws.x + ws.y) + (ws.z + ws.w))) * ri;
            if (centred) sc = centred_score(sb + OFF_VT, sb + OFF_LN, s0, s1, lane);
            const uint32_t sb16 = pack_bf16(0.f, sc);
            const uint32_t s2 = s1 | (sb16 ^ (((uint32_t)((int)sb16 >> 31) & 0x7fff0000u) | 0x80000000u));
            st_relaxed_64(pub, s0, s2);
            st_relaxed_64(pub + 2 * sizeof(Exchange) / 8, s0, s2);
            if (lane < NREP) red_add(cnt_s, 1);
            if (elect_one()) mbar_arrive(bar0 + 8 * B_LN);
            STAMP(9); GSTAMP(25);
        }
        const uint32_t slot0 = sb + OFF_RING + a * 8192, slot1 = sb + slot_off(4 + a), slot2 = sb + slot_off(8 + a), fbar = bar0 + 8 * (B_FULL + a);
        uint32_t mine, row[2];
        {
            uint32_t q[16];
            named_sync(1, 128);
            wait_count(&in->cnt[32 * a], 32 * tag - FEW_ST);
            STAMP(41);
#pragma unroll 1
            for (uint32_t it = 0;; spin_guard(it)) {
                if (elect_one()) {
                    mbar_expect_tx(abar, 4096);
                    bulk_g2s(sb + OFF_ST + 4096 * a, in->stat + 512 * a, 4096, abar);
                }
                mbar_wait(abar, aph);
                aph ^= 1;
                uint32_t bad = 0;
#pragma unroll
                for (int n = 0; n < 8; n++) {
                    const uint4 u = lds128v(sb + OFF_ST + 4096 * a + 512 * n + 16 * lane);
                    q[2 * n] = u.y; q[2 * n + 1] = u.w;
                    bad = or_xor(bad, u.y, tag);
                }
                const bool ok = __all_sync(0xffffffffu, (bad & 3) == 0);
                asm volatile("{ .reg .pred p; setp.ne.u32 p, %1, 0; @p mbarrier.arrive.shared::cta.b64 _, [%0]; }" ::"r"(bar0 + 8 * (B_ST + a)), "r"((uint32_t)(ok && lane == 0)) : "memory");
                if (ok) break;
            }
            STAMP(8);
            const uint32_t inv = 2047 - 512 * a - 16 * m - (r ^ (2 * m));
#pragma unroll
            for (int i = 0; i < 16; i++) asm("lop3.b32 %0, %0, %1, %2, 0x9b;" : "+r"(q[i]) : "r"(inv), "r"(0xffff0000u | (64 * (i >> 1) + 8 * (i & 1))));
            auto below = [&](uint32_t x) {
                uint32_t d[4];
#pragma unroll
                for (int i = 0; i < 16; i++) d[i & 3] = i < 4 ? x + q[i] : min(d[i & 3], x + q[i]);
                d[0] = min(min(d[0], d[1]), min(d[2], d[3]));
                return d[0] < x ? x - 1 - d[0] : 0u;
            };
            const uint32_t mx0 = ~min(min(min(min(q[0], q[1]), min(q[2], q[3])), min(min(q[4], q[5]), min(q[6], q[7]))),
                                      min(min(min(q[8], q[9]), min(q[10], q[11])), min(min(q[12], q[13]), min(q[14], q[15]))));
            const uint32_t gm = __reduce_max_sync(0xffffffffu, mx0 == __reduce_max_sync(0xffffffffu, mx0) ? 0u : mx0);
            if (lane == 0) sts32(misc + 16 + 4 * a, gm);
            named_sync(1, 128);
            STAMP(42);
            const uint4 t0 = lds128(misc + 16);
            uint32_t tau = min(min(t0.x, t0.y), min(t0.z, t0.w));
            uint32_t mx = mx0, cnt = 0, bal;
            const uint32_t list = sb + OFF_XCH + 32 * a;
#pragma unroll 1
            while ((bal = __ballot_sync(0xffffffffu, mx >= tau)) != 0) {
                const uint32_t pos = cnt + __popc(bal & ((1u << lane) - 1u));
                cnt += __popc(bal);
                if (cnt > 8) break;
                if (mx >= tau) sts32(list + 4 * pos, mx);
                mx = below(mx);
            }
            if (cnt > 8) {
                mx = mx0;
#pragma unroll 1
                for (int j = 0; j < 8; j++) {
                    const uint32_t top = __reduce_max_sync(0xffffffffu, mx), nx = below(mx);
                    if (mx == top) { sts32(list + 4 * j, mx); mx = nx; }
                }
            }
            named_sync(1, 128);
            STAMP(43);
            const uint32_t k = lds32(sb + OFF_XCH + 4 * lane);
            uint32_t rk[4] = {misc + 48, 0, 0, 0};
#pragma unroll
            for (int j = 0; j < 8; j++) {
                const uint4 c = lds128(sb + OFF_XCH + 16 * j);
                asm("{ .reg .pred p, q, r, s; setp.gt.u32 p, %4, %8; setp.gt.u32 q, %5, %8; setp.gt.u32 r, %6, %8; setp.gt.u32 s, %7, %8;\n\t"
                    "@p add.u32 %0, %0, 8; @q add.u32 %1, %1, 8; @r add.u32 %2, %2, 8; @s add.u32 %3, %3, 8; }"
                    : "+r"(rk[0]), "+r"(rk[1]), "+r"(rk[2]), "+r"(rk[3]) : "r"(c.x), "r"(c.y), "r"(c.z), "r"(c.w), "r"(k));
            }
            rk[0] = (rk[0] + rk[1]) + (rk[2] + rk[3]);
            if (rk[0] < misc + 112) sts32(rk[0], k);
            __syncwarp();
            mine = lds32(misc + 48 + 8 * g);
            const uint4 two = lds128v(misc + 48 + 16 * a);
            row[0] = two.x; row[1] = two.z;
            mbar_wait(bar0 + 8 * B_V, 0);
        }
        STAMP(11);
        const int tok = 2047 - (int)(mine & 2047);
        const uint32_t xs = sb + OFF_XT + (h ^ 1) * 32768 + 16384;
        if (has_gu) {
            if (elect_one()) {
                mbar_expect_tx(abar, 2048);
#pragma unroll
                for (int j = 0; j < 2; j++) bulk_g2s(xs + (2 * a + j) * 1040, p.u + (size_t)(2047 - (row[j] & 2047)) * DM + 512 * h, 1024, abar);
            }
        }
        STAMP(44);
        uint32_t af[20][4], ko = sb + (m & 1) * 4096 + (r + ((m >> 1) << 3)) * 128 + ((r ^ (4 * h) ^ a) << 4);
        auto load_level = [&](int c) {
#pragma unroll
            for (int j = 0; j < 4; j++) {
                mbar_wait(bar0 + 8 * (B_FULL + 4 * (c % 3) + j), c / 3);
#pragma unroll
                for (int i = 0; i < 4; i++) ldsm4t(af[8 * (i >> 1) + 2 * j + (i & 1)], (ko ^ ((i & 1) << 6)) + slot_off(4 * (c % 3) + j) + (i >> 1) * 2048);
            }
            STAMP(36 + c);
            __syncwarp();
            if (c < 3 && lane < 4) mbar_arrive(bar0 + 8 * (B_FREE + 4 * c + lane));
        };
        const uint2 st = ld_relaxed_64(in->stat + (tok & ~15) + 2 * ((tok & 7) ^ ((tok >> 3) & 6)) + ((tok >> 3) & 1));
        if (has_gu) load_level(0);
        if (a == 0 && t == 0) sts32f(misc + 52 + 8 * g, bf_hi(st.x) + bf_lo(st.y));
        if (a == 0) STAMP(45);
        if (has_gu) {
            const uint32_t mean = __shfl_sync(0xffffffffu, st.x, 8 * a + 4 * (lane >> 4)), xr = xs + (2 * a + (lane >> 4)) * 1040 + 16 * (lane & 15);
            mbar_wait(abar, aph);
            aph ^= 1;
            STAMP(46);
            uint4 x[4];
#pragma unroll
            for (int j = 0; j < 4; j++) x[j] = lds128(xr + 256 * j);
#pragma unroll
            for (int j = 0; j < 4; j++) sts128(xr + 256 * j, bsub2_lo(x[j].x, mean), bsub2_lo(x[j].y, mean), bsub2_lo(x[j].z, mean), bsub2_lo(x[j].w, mean));
            if (elect_one()) mbar_expect_tx(abar, 512);
            named_sync(1, 128);
        }
        if (lane < (has_gu ? 2 : 4)) mbar_arrive_peer(mapa(bar0 + 8 * (lane & 2 ? B_XFREE : B_SFREE), lane & 1));
        if (has_gu) {
            STAMP(12);
            float gacc[8][4];
#pragma unroll
            for (int i = 0; i < 8; i++) { gacc[i][0] = gacc[i][1] = gacc[i][2] = gacc[i][3] = 0.f; }
            uint32_t* pubh = reinterpret_cast<uint32_t*>(&p.sc[0].h[b * 32 + 8 * a + (g ^ (2 * a))]) + t;
            uint32_t* cnt_h = &p.sc[t].cnt[32 * (b / 28) + 1 + ((b / 14) & 1)];
            uint32_t xb = xs + r * 1040 + m * 16;
            uint32_t xch = sb + OFF_XCH + 16 * tid, tagm = t == 3 ? 1u : 0u;
            pin(pubh); pin(cnt_h); pin(xb); pin(xch); pin(tagm);
            const float r0 = lds32f(misc + 52 + 16 * t), r1 = lds32f(misc + 60 + 16 * t);
#pragma unroll
            for (int c = 0; c < 4; c++) {
#pragma unroll
                for (int j = 0; j < 4; j++) ldsm4(af[16 + j], xb + 256 * c + 64 * j);
                if (c == 3) mbar_wait(bar0 + 8 * B_SFREE, 0);
                if (c) load_level(c);
                const bool more = __any_sync(0xffffffffu, (c ? af[6][3] | af[7][3] | af[14][3] | af[15][3] : af[16][3] | af[17][3] | af[18][3] | af[19][3]) & p.zero);
#pragma unroll 1
                do {
#pragma unroll
                    for (int i = 0; i < 16; i++) mma_v(gacc[i & 7], af[i], af[16 + ((i >> 1) & 3)][2 * (i >> 3)], af[16 + ((i >> 1) & 3)][2 * (i >> 3) + 1]);
                } while (more);
            }
            STAMP(13);
            float own[4], oth[4];
#pragma unroll
            for (int j = 0; j < 4; j++) oth[j] = (gacc[1][j] + gacc[3][j]) + (gacc[5][j] + gacc[7][j]);
            st_async128(mapa(xch, h ^ 1), __float_as_uint(oth[0]), __float_as_uint(oth[1]), __float_as_uint(oth[2]), __float_as_uint(oth[3]), mapa(abar, h ^ 1));
            STAMP(56);
#pragma unroll
            for (int j = 0; j < 4; j++) own[j] = ((gacc[0][j] + gacc[2][j]) + (gacc[4][j] + gacc[6][j])) * ((j & 1) ? r1 : r0);
            mbar_wait(abar, aph);
            aph ^= 1;
            STAMP(57);
            const float4 o4 = lds128f(xch);
            const float g0 = bf_round(fmaf(o4.x, r0, own[0])), g1 = bf_round(fmaf(o4.y, r1, own[1]));
            const float h0 = bf_round(g0 * rcpf(1.f + ex2f(-1.4426950408889634f * g0))) * bf_round(fmaf(o4.z, r0, own[2]));
            const float h1 = bf_round(g1 * rcpf(1.f + ex2f(-1.4426950408889634f * g1))) * bf_round(fmaf(o4.w, r1, own[3]));
            uint32_t hw;
            asm volatile("movmatrix.sync.aligned.m8n8.trans.b16 %0, %1;" : "=r"(hw) : "r"(pack_bf16(h0, h1)));
            hw = (hw & ~tagm) | (tag & tagm);
#pragma unroll
            for (int j = 0; j < NREP; j++) st_relaxed_32(pubh + j * (sizeof(Exchange) / 4), hw);
            if (lane < NREP) red_add(cnt_h, b % 14 < 2 ? 2 : 1);
            if (lane < 2) mbar_arrive_peer(mapa(bar0 + 8 * B_XFREE, lane));
            named_sync(1, 128);
            STAMP(14);
        }
        float dacc[4];
        const int tk = ((tid >> 1) & 6) | (tid & 1);
        uint32_t ro = 4 * tid, red = sb + tab_off(tk) + T_RED + 4 * ((tid >> 4) + 4 * (tid & 2));
        if (!has_gu) named_sync(1, 128);
        const float sg = bf_round(rcpf(1.f + ex2f(-1.4426950408889634f * __uint_as_float(unorder_key(lds32(misc + 48 + 8 * tk) >> 16) << 16))));
        pin(ro); pin(red);
        mbar_wait(bar0 + 8 * B_XFREE, 0);
        {
            uint32_t wo = (r + ((m >> 1) << 3)) * 32 + (((m & 1) ^ (r >> 2)) << 4), af[14][4];
            uint32_t ho = slot0 + 128 * t + 16 * (g ^ (2 * t));
            pin(wo); pin(ho);
            float d[7][4];
#pragma unroll
            for (int i = 0; i < 7; i++) { d[i][0] = d[i][1] = d[i][2] = d[i][3] = 0.f; }
            auto first_half = [&]() {
                mbar_wait(fbar + 32, has_gu);
#pragma unroll
                for (int j = 0; j < 14; j++) ldsm4t(af[j], slot1 + wo + j * 512);
            };
            auto fetch = [&]() {
                if (elect_one()) {
                    mbar_expect_tx(abar, 7168);
                    bulk_g2s(slot0, &in->h[(56 * h + 14 * a) * 32], 7168, abar);
                }
            };
            wait_count(&in->cnt[64 * h + 32 * (a >> 1) + 1 + (a & 1)], 64 * tag - FEW_H);
            STAMP(33);
            fetch();
            if (a == 3 && elect_one()) mbar_arrive(bar0 + 8 * B_LN);
            first_half();
            mbar_wait(abar, aph);
#pragma unroll
            for (int s = 0; s < 2; s++) {
                if (s) {
                    mbar_wait(fbar + 64, has_gu);
#pragma unroll
                    for (int j = 0; j < 14; j++) ldsm4t(af[j], slot2 + wo + j * 512);
                }
                uint4 hq[7];
#pragma unroll 1
                for (uint32_t it = 0;; spin_guard(it)) {
                    uint32_t bad = 0;
#pragma unroll
                    for (int j = 0; j < 7; j++) { hq[j] = lds128(ho + 512 * (7 * s + j)); bad = or_xor(bad, hq[j].w, tag); }
                    if (__all_sync(0xffffffffu, (bad & 1) == 0)) break;
                    fetch();
                    aph ^= 1;
                    mbar_wait(abar, aph);
                }
                if (s == 0) STAMP(15);
#pragma unroll
                for (int j = 0; j < 14; j++) {
                    const uint4 q = hq[j >> 1];
                    mma_v(d[j % 7], af[j], (j & 1) ? q.z : q.x, (j & 1) ? q.w : q.y);
                }
            }
#pragma unroll
            for (int j = 0; j < 4; j++) dacc[j] = ((d[0][j] + d[1][j]) + (d[2][j] + d[3][j])) + ((d[4][j] + d[5][j]) + d[6][j]);
        }
        STAMP(16);
        {
            st_async128(mapa(sb + OFF_XCH + 16 * tid, h ^ 1), __float_as_uint(dacc[0]), __float_as_uint(dacc[1]), __float_as_uint(dacc[2]), __float_as_uint(dacc[3]),
                        mapa(bar0 + 8 * B_RED, h ^ 1));
            sts128f(slot0 + 7680 + lane * 16, dacc);
            __syncwarp();
            if (elect_one()) mbar_arrive(bar0 + 8 * B_RED);
            mbar_wait(bar0 + 8 * B_RED, 0);
            const uint32_t b0 = sb + OFF_RING + 7680 + ro, b1 = sb + OFF_XCH + ro;
            const float y = ((lds32f(b0) + lds32f(b0 + 8192)) + (lds32f(b0 + 16384) + lds32f(b0 + 24576))) +
                            ((lds32f(b1) + lds32f(b1 + 512)) + (lds32f(b1 + 1024) + lds32f(b1 + 1536)));
            sts32f(red, bf_round(y) * sg);
            __syncwarp();
            if (elect_one()) mbar_arrive(bar0 + 8 * B_UPD);
        }
        STAMP(17); GSTAMP(29);
    }
}

typedef CUresult (*EncodeFn)(CUtensorMap*, CUtensorMapDataType, cuuint32_t, void*, const cuuint64_t*, const cuuint64_t*,
                             const cuuint32_t*, const cuuint32_t*, CUtensorMapInterleave, CUtensorMapSwizzle,
                             CUtensorMapL2promotion, CUtensorMapFloatOOBfill);

void make_map(EncodeFn enc, CUtensorMap* m, const void* ptr, uint64_t cols, uint64_t rows, uint32_t bc, uint32_t br,
              CUtensorMapSwizzle sw, CUtensorMapL2promotion pr) {
    cuuint64_t dims[2] = {cols, rows};
    cuuint64_t str[1] = {cols * 2};
    cuuint32_t box[2] = {bc, br};
    cuuint32_t es[2] = {1, 1};
    enc(m, CU_TENSOR_MAP_DATA_TYPE_BFLOAT16, 2, const_cast<void*>(ptr), dims, str, box, es, CU_TENSOR_MAP_INTERLEAVE_NONE, sw, pr,
        CU_TENSOR_MAP_FLOAT_OOB_FILL_NONE);
}
void make_perm_map(EncodeFn enc, CUtensorMap* m, const void* ptr, CUtensorMapL2promotion pr) {
    cuuint64_t dims[5] = {DM, 2, 4, 4, FF / 32};
    cuuint64_t str[4] = {DM * 2, 8 * DM * 2, 2 * DM * 2, 32 * DM * 2};
    cuuint32_t box[5] = {16, 2, 4, 4, 7};
    cuuint32_t es[5] = {1, 1, 1, 1, 1};
    enc(m, CU_TENSOR_MAP_DATA_TYPE_BFLOAT16, 5, const_cast<void*>(ptr), dims, str, box, es, CU_TENSOR_MAP_INTERLEAVE_NONE,
        CU_TENSOR_MAP_SWIZZLE_32B, pr, CU_TENSOR_MAP_FLOAT_OOB_FILL_NONE);
}
void make_tile_map(EncodeFn enc, CUtensorMap* m, const void* ptr) {
    cuuint64_t dims[4] = {DM, 4, 16, SEQ / 64};
    cuuint64_t str[3] = {16 * DM * 2, DM * 2, 64 * DM * 2};
    cuuint32_t box[4] = {16, 4, 2, 8};
    cuuint32_t es[4] = {1, 1, 1, 1};
    enc(m, CU_TENSOR_MAP_DATA_TYPE_BFLOAT16, 4, const_cast<void*>(ptr), dims, str, box, es, CU_TENSOR_MAP_INTERLEAVE_NONE,
        CU_TENSOR_MAP_SWIZZLE_32B, CU_TENSOR_MAP_L2_PROMOTION_NONE, CU_TENSOR_MAP_FLOAT_OOB_FILL_NONE);
}

}

extern "C" void kernel_launch(void* const* d_in, const int* in_sizes, int n_in, void* d_out, int out_size) {
    (void)in_sizes; (void)n_in; (void)out_size;
    static EncodeFn enc = nullptr;
    static void* scratch = nullptr;
    if (!enc) {
        void* fn = nullptr;
        cudaDriverEntryPointQueryResult q;
        cudaGetDriverEntryPoint("cuTensorMapEncodeTiled", &fn, cudaEnableDefault, &q);
        enc = (EncodeFn)fn;
        cudaGetSymbolAddress(&scratch, g_scratch);
        cudaFuncSetAttribute(fused_kernel, cudaFuncAttributeMaxDynamicSharedMemorySize, SMEM_BYTES);
    }
    Maps maps;
    make_tile_map(enc, &maps.u, d_in[0]);
    make_tile_map(enc, &maps.out, d_out);
    make_map(enc, &maps.wg, d_in[9], FF, DM, 64, 32, CU_TENSOR_MAP_SWIZZLE_128B, CU_TENSOR_MAP_L2_PROMOTION_L2_128B);
    make_map(enc, &maps.wu, d_in[10], FF, DM, 64, 32, CU_TENSOR_MAP_SWIZZLE_128B, CU_TENSOR_MAP_L2_PROMOTION_L2_128B);
    make_perm_map(enc, &maps.wd, d_in[11], CU_TENSOR_MAP_L2_PROMOTION_L2_64B);
    Ptrs p;
    p.sc = (Exchange*)scratch;
    p.u = (const __nv_bfloat16*)d_in[0];
    p.logA = (const __nv_bfloat16*)d_in[1];
    p.Aim = (const __nv_bfloat16*)d_in[2];
    p.Cre = (const __nv_bfloat16*)d_in[3];
    p.Cim = (const __nv_bfloat16*)d_in[4];
    p.ldt = (const __nv_bfloat16*)d_in[5];
    p.dsk = (const __nv_bfloat16*)d_in[6];
    p.wr = (const __nv_bfloat16*)d_in[8];
    p.out = (__nv_bfloat16*)d_out;
    p.zero = 0;
    fused_kernel<<<NCTA, NTHR, SMEM_BYTES, cudaStreamPerThread>>>(p, maps);
}
```

```cpp
#include <cuda_runtime.h>
#include <cuda_bf16.h>
#include <cuda_fp16.h>
#include <cuda.h>
#include <stdint.h>

namespace {

constexpr int SEQ = 2048, DM = 1024, NMODE = 128, FF = 3584;
constexpr int NCTA = 128, NTHR = 512;
constexpr int GU_CTAS = 112;
constexpr int NREP = 4;

constexpr int OFF_XT = 0;
constexpr int OFF_RING = 65536;
constexpr int OFF_PRIV = OFF_RING + 65536;
constexpr int OFF_VT = OFF_PRIV + 65536;
constexpr int VT_PAD = 32, VT_PLANE = VT_PAD + 2048, VT_PITCH = 2 * VT_PLANE, ROW_PITCH = 2064;
constexpr int OFF_BAR = OFF_VT + 8 * VT_PITCH;
constexpr int OFF_MISC = OFF_BAR + 384;
constexpr int OFF_XCH = OFF_MISC + 112;
constexpr int SMEM_BYTES = OFF_XCH + 2048;
constexpr int OFF_LN = OFF_RING + 7 * 8192;
constexpr int OFF_ST = OFF_RING + 6 * 8192;
static_assert(SMEM_BYTES <= 232448, "shared memory");

constexpr int B_ROW = 0, B_XT = 4, B_V = 5, B_LN = 6, B_SFREE = 7, B_XFREE = 8, B_OWN = 9, B_RED = 10, B_UPD = 11, B_ST = 12, B_RECV = 16, B_FREE = 20, B_FULL = 32, B_AUX = 44, NBAR = 48;

constexpr int T_DENSE = 60;
constexpr int T_PATCH = 2208;
constexpr int T_R2 = 2368;
constexpr int T_R3 = 3296;

constexpr int T_RED = 4032;
__device__ __forceinline__ bool slot_priv(int s) { return (uint32_t)(s - 6) < 4u; }
__device__ __forceinline__ uint32_t slot_off(int s) { return slot_priv(s) ? OFF_PRIV + 4096 + (s & 3) * 16384 : OFF_RING + (s < 6 ? s : s - 4) * 8192; }
__device__ __forceinline__ uint32_t tab_off(int w) { return OFF_PRIV + w * 8192 + (w & 1) * 4096; }

constexpr uint32_t SPIN_LIMIT = 1u << 20;
#define BB_UNROLL 2
constexpr int kBbUnroll = BB_UNROLL;
#define ST_T0 2200
#define ST_PER 286
#define ST_PER2 320
#define LN_PAUSE 0xf0
#define FEW_ST 10
#define FEW_H 24

struct Exchange {
    uint2 stat[SEQ];
    uint4 h[GU_CTAS * 32];
    uint32_t cnt[4 * 32];
};
__device__ __align__(128) Exchange g_scratch[NREP];

struct Ptrs {
    const __nv_bfloat16 *logA, *Aim, *Cre, *Cim, *ldt, *u;
    const __nv_bfloat16 *dsk, *wr;
    Exchange* sc;
    __nv_bfloat16* out;
    uint32_t zero;
};
struct Maps {
    CUtensorMap u, out, wg, wu, wd;
};

#define STAMP(i) do { } while (0)
#define GSTAMP(i) do { } while (0)

__device__ __forceinline__ uint32_t s_u32(const void* p) { return (uint32_t)__cvta_generic_to_shared(p); }
__device__ __forceinline__ void mbar_init(uint32_t b, uint32_t n) {
    asm volatile("mbarrier.init.shared::cta.b64 [%0], %1;" ::"r"(b), "r"(n) : "memory");
}
__device__ __forceinline__ void mbar_expect_tx(uint32_t b, uint32_t bytes) {
    asm volatile("mbarrier.arrive.expect_tx.shared::cta.b64 _, [%0], %1;" ::"r"(b), "r"(bytes) : "memory");
}
__device__ __forceinline__ void mbar_arrive(uint32_t b) {
    asm volatile("mbarrier.arrive.shared::cta.b64 _, [%0];" ::"r"(b) : "memory");
}
__device__ __forceinline__ void mbar_arrive_n(uint32_t b, uint32_t n) {
    asm volatile("mbarrier.arrive.shared::cta.b64 _, [%0], %1;" ::"r"(b), "r"(n) : "memory");
}
__device__ __forceinline__ void mbar_arrive_peer(uint32_t b_cluster) {
    asm volatile("mbarrier.arrive.relaxed.cluster.shared::cluster.b64 _, [%0];" ::"r"(b_cluster) : "memory");
}
__device__ __forceinline__ void mbar_wait(uint32_t b, uint32_t parity) {
    asm volatile("{\n\t.reg .pred p;\n\t.reg .u32 c;\n\tmov.u32 c, 0;\n"
                 "W:\n\tmbarrier.try_wait.parity.shared::cta.b64 p, [%0], %1;\n\t@p bra D;\n\t"
                 "add.u32 c, c, 1;\n\tsetp.lt.u32 p, c, 1048576;\n\t@p bra W;\n\ttrap;\nD:\n\t}"
                 ::"r"(b), "r"(parity) : "memory");
}
__device__ __forceinline__ bool elect_one() {
    uint32_t p;
    asm volatile("{ .reg .pred P; elect.sync _|P, 0xffffffff; selp.u32 %0, 1, 0, P; }" : "=r"(p));
    return p != 0;
}
__device__ __forceinline__ uint32_t mapa(uint32_t a, uint32_t rank) {
    uint32_t r;
    asm("mapa.shared::cluster.u32 %0, %1, %2;" : "=r"(r) : "r"(a), "r"(rank));
    return r;
}
__device__ __forceinline__ void cluster_arrive() { asm volatile("barrier.cluster.arrive.relaxed.aligned;" ::: "memory"); }
__device__ __forceinline__ void cluster_wait() { asm volatile("barrier.cluster.wait.acquire.aligned;" ::: "memory"); }
__device__ __forceinline__ void tma_load_2d(uint32_t dst, const CUtensorMap* m, int c0, int c1, uint32_t bar) {
    asm volatile("cp.async.bulk.tensor.2d.shared::cluster.global.mbarrier::complete_tx::bytes [%0], [%1, {%3, %4}], [%2];"
                 ::"r"(dst), "l"(m), "r"(bar), "r"(c0), "r"(c1) : "memory");
}
__device__ __forceinline__ void tma_load_perm(uint32_t dst, const CUtensorMap* m, int c0, int blk, uint32_t bar) {
    asm volatile("cp.async.bulk.tensor.5d.shared::cluster.global.mbarrier::complete_tx::bytes [%0], [%1, {%3, %4, %4, %4, %5}], [%2];"
                 ::"r"(dst), "l"(m), "r"(bar), "r"(c0), "r"(0), "r"(blk) : "memory");
}
__device__ __forceinline__ void tma_load_tile(uint32_t dst, const CUtensorMap* m, int c0, int c2, int c3, uint32_t bar) {
    asm volatile("cp.async.bulk.tensor.4d.shared::cluster.global.mbarrier::complete_tx::bytes.multicast::cluster [%0], [%1, {%3, %4, %5, %6}], [%2], %7;"
                 ::"r"(dst), "l"(m), "r"(bar), "r"(c0), "r"(0), "r"(c2), "r"(c3), "h"((uint16_t)3) : "memory");
}
__device__ __forceinline__ void tma_store_tile(const CUtensorMap* m, uint32_t src, int c0, int c2, int c3) {
    asm volatile("cp.async.bulk.tensor.4d.global.shared::cta.bulk_group [%0, {%2, %3, %4, %5}], [%1];"
                 ::"l"(m), "r"(src), "r"(c0), "r"(0), "r"(c2), "r"(c3) : "memory");
    asm volatile("cp.async.bulk.commit_group;" ::: "memory");
}
__device__ __forceinline__ void bulk_g2s(uint32_t dst, const void* src, uint32_t bytes, uint32_t bar) {
    asm volatile("cp.async.bulk.shared::cluster.global.mbarrier::complete_tx::bytes [%0], [%1], %2, [%3];"
                 ::"r"(dst), "l"(src), "r"(bytes), "r"(bar) : "memory");
}
__device__ __forceinline__ void st_async128(uint32_t dst_cluster, uint32_t x, uint32_t y, uint32_t z, uint32_t w, uint32_t bar_cluster) {
    asm volatile("st.async.weak.shared::cluster.mbarrier::complete_tx::bytes.v4.b32 [%0], {%1,%2,%3,%4}, [%5];"
                 ::"r"(dst_cluster), "r"(x), "r"(y), "r"(z), "r"(w), "r"(bar_cluster) : "memory");
}
__device__ __forceinline__ void fence_async() { asm volatile("fence.proxy.async.shared::cta;" ::: "memory"); }
__device__ __forceinline__ void named_sync(int id, int n) { asm volatile("bar.sync %0, %1;" ::"r"(id), "r"(n) : "memory"); }

__device__ __forceinline__ void ldsm4(uint32_t* r, uint32_t a) {
    asm volatile("ldmatrix.sync.aligned.m8n8.x4.shared.b16 {%0,%1,%2,%3}, [%4];"
                 : "=r"(r[0]), "=r"(r[1]), "=r"(r[2]), "=r"(r[3]) : "r"(a));
}
__device__ __forceinline__ void ldsm4t(uint32_t* r, uint32_t a) {
    asm volatile("ldmatrix.sync.aligned.m8n8.x4.trans.shared.b16 {%0,%1,%2,%3}, [%4];"
                 : "=r"(r[0]), "=r"(r[1]), "=r"(r[2]), "=r"(r[3]) : "r"(a));
}
__device__ __forceinline__ void stsm4t(uint32_t a, uint32_t x, uint32_t y, uint32_t z, uint32_t w) {
    asm volatile("stmatrix.sync.aligned.m8n8.x4.trans.shared.b16 [%0], {%1,%2,%3,%4};"
                 ::"r"(a), "r"(x), "r"(y), "r"(z), "r"(w) : "memory");
}
__device__ __forceinline__ uint32_t lds32(uint32_t a) { uint32_t v; asm volatile("ld.shared.u32 %0, [%1];" : "=r"(v) : "r"(a)); return v; }
__device__ __forceinline__ float lds32f(uint32_t a) { float v; asm volatile("ld.shared.f32 %0, [%1];" : "=f"(v) : "r"(a)); return v; }
__device__ __forceinline__ uint2 lds64(uint32_t a) { uint2 v; asm volatile("ld.shared.v2.u32 {%0,%1}, [%2];" : "=r"(v.x), "=r"(v.y) : "r"(a)); return v; }
__device__ __forceinline__ uint4 lds128(uint32_t a) {
    uint4 v; asm volatile("ld.shared.v4.u32 {%0,%1,%2,%3}, [%4];" : "=r"(v.x), "=r"(v.y), "=r"(v.z), "=r"(v.w) : "r"(a)); return v;
}
__device__ __forceinline__ uint4 lds128v(uint32_t a) {
    uint4 v; asm volatile("ld.volatile.shared.v4.u32 {%0,%1,%2,%3}, [%4];" : "=r"(v.x), "=r"(v.y), "=r"(v.z), "=r"(v.w) : "r"(a)); return v;
}
__device__ __forceinline__ uint32_t or_xor(uint32_t a, uint32_t b, uint32_t c) {
    uint32_t r; asm("lop3.b32 %0, %1, %2, %3, 0xf6;" : "=r"(r) : "r"(a), "r"(b), "r"(c)); return r;
}
__device__ __forceinline__ float4 lds128f(uint32_t a) {
    float4 v; asm volatile("ld.shared.v4.f32 {%0,%1,%2,%3}, [%4];" : "=f"(v.x), "=f"(v.y), "=f"(v.z), "=f"(v.w) : "r"(a)); return v;
}
__device__ __forceinline__ void sts32(uint32_t a, uint32_t v) { asm volatile("st.shared.u32 [%0], %1;" ::"r"(a), "r"(v) : "memory"); }
__device__ __forceinline__ void sts32f(uint32_t a, float v) { asm volatile("st.shared.f32 [%0], %1;" ::"r"(a), "f"(v) : "memory"); }
__device__ __forceinline__ void sts64(uint32_t a, uint32_t x, uint32_t y) { asm volatile("st.shared.v2.u32 [%0], {%1,%2};" ::"r"(a), "r"(x), "r"(y) : "memory"); }
__device__ __forceinline__ void sts64f(uint32_t a, float x, float y) { asm volatile("st.shared.v2.f32 [%0], {%1,%2};" ::"r"(a), "f"(x), "f"(y) : "memory"); }
__device__ __forceinline__ void sts128(uint32_t a, uint32_t x, uint32_t y, uint32_t z, uint32_t w) {
    asm volatile("st.shared.v4.u32 [%0], {%1,%2,%3,%4};" ::"r"(a), "r"(x), "r"(y), "r"(z), "r"(w) : "memory");
}
__device__ __forceinline__ void sts128f(uint32_t a, const float* v) {
    asm volatile("st.shared.v4.f32 [%0], {%1,%2,%3,%4};" ::"r"(a), "f"(v[0]), "f"(v[1]), "f"(v[2]), "f"(v[3]) : "memory");
}
__device__ __forceinline__ uint4 ldg128(const void* p) {
    uint4 v; asm volatile("ld.global.nc.L1::no_allocate.v4.u32 {%0,%1,%2,%3}, [%4];" : "=r"(v.x), "=r"(v.y), "=r"(v.z), "=r"(v.w) : "l"(p)); return v;
}
__device__ __forceinline__ uint2 ldg64(const void* p) {
    uint2 v; asm volatile("ld.global.nc.L1::no_allocate.v2.u32 {%0,%1}, [%2];" : "=r"(v.x), "=r"(v.y) : "l"(p)); return v;
}
__device__ __forceinline__ uint32_t ldg16(const void* p) {
    uint32_t v; asm volatile("ld.global.nc.u16 %0, [%1];" : "=r"(v) : "l"(p)); return v;
}
__device__ __forceinline__ uint2 ld_relaxed_64(const void* p) {
    uint2 v; asm volatile("ld.relaxed.gpu.global.v2.u32 {%0,%1}, [%2];" : "=r"(v.x), "=r"(v.y) : "l"(p) : "memory"); return v;
}
__device__ __forceinline__ uint32_t ld_relaxed_32(const void* p) {
    uint32_t v; asm volatile("ld.relaxed.gpu.global.u32 %0, [%1];" : "=r"(v) : "l"(p) : "memory"); return v;
}
__device__ __forceinline__ void st_relaxed_64(void* p, uint32_t x, uint32_t y) {
    asm volatile("st.relaxed.gpu.global.v2.u32 [%0], {%1,%2};" ::"l"(p), "r"(x), "r"(y) : "memory");
}
__device__ __forceinline__ void st_relaxed_32(void* p, uint32_t v) {
    asm volatile("st.relaxed.gpu.global.u32 [%0], %1;" ::"l"(p), "r"(v) : "memory");
}
__device__ __forceinline__ void red_add(void* p, uint32_t v) { asm volatile("red.relaxed.gpu.global.add.u32 [%0], %1;" ::"l"(p), "r"(v) : "memory"); }
__device__ __forceinline__ uint32_t now_ns() { uint32_t t; asm volatile("mov.u32 %0, %%globaltimer_lo;" : "=r"(t) :: "memory"); return t; }
__device__ __forceinline__ void sleep_until(uint32_t t) {
#pragma unroll 1
    for (int left; (left = (int)(t - now_ns())) > 0;) __nanosleep(left >> 1);
}
__device__ __forceinline__ void spin_guard(uint32_t& it) { if (++it > SPIN_LIMIT) __trap(); }
__device__ __forceinline__ void wait_count(const uint32_t* p, uint32_t target) {
#pragma unroll 1
    for (uint32_t it = 0; __any_sync(0xffffffffu, (int)(ld_relaxed_32(p) - target) < 0); spin_guard(it)) { }
}
__device__ __forceinline__ void mma_bf16_k8(float* c, uint32_t a0, uint32_t a1, uint32_t b0) {
    asm("mma.sync.aligned.m16n8k8.row.col.f32.bf16.bf16.f32 {%0,%1,%2,%3}, {%4,%5}, {%6}, {%0,%1,%2,%3};"
                 : "+f"(c[0]), "+f"(c[1]), "+f"(c[2]), "+f"(c[3]) : "r"(a0), "r"(a1), "r"(b0));
}
__device__ __forceinline__ void mma_v(float* c, const uint32_t* a, uint32_t b0, uint32_t b1) {
    asm volatile("mma.sync.aligned.m16n8k16.row.col.f32.bf16.bf16.f32 {%0,%1,%2,%3}, {%4,%5,%6,%7}, {%8,%9}, {%0,%1,%2,%3};"
                 : "+f"(c[0]), "+f"(c[1]), "+f"(c[2]), "+f"(c[3]) : "r"(a[0]), "r"(a[1]), "r"(a[2]), "r"(a[3]), "r"(b0), "r"(b1));
}
__device__ __forceinline__ void mma_bf16_z(float* c, uint32_t a0, uint32_t a1, uint32_t a2, uint32_t a3, uint32_t b0, uint32_t b1) {
    asm volatile("mma.sync.aligned.m16n8k16.row.col.f32.bf16.bf16.f32 {%0,%1,%2,%3}, {%4,%5,%6,%7}, {%8,%9}, {%10,%10,%10,%10};"
        : "=f"(c[0]), "=f"(c[1]), "=f"(c[2]), "=f"(c[3]) : "r"(a0), "r"(a1), "r"(a2), "r"(a3), "r"(b0), "r"(b1), "f"(0.f));
}
__device__ __forceinline__ void mma_f16(float* c, uint32_t a0, uint32_t a1, uint32_t a2, uint32_t a3, uint32_t b0, uint32_t b1) {
    asm("mma.sync.aligned.m16n8k16.row.col.f32.f16.f16.f32 {%0,%1,%2,%3}, {%4,%5,%6,%7}, {%8,%9}, {%0,%1,%2,%3};"
                 : "+f"(c[0]), "+f"(c[1]), "+f"(c[2]), "+f"(c[3]) : "r"(a0), "r"(a1), "r"(a2), "r"(a3), "r"(b0), "r"(b1));
}
__device__ __forceinline__ uint32_t pack_bf16(float lo, float hi) {
    uint32_t r; asm("cvt.rn.bf16x2.f32 %0, %1, %2;" : "=r"(r) : "f"(hi), "f"(lo)); return r;
}
__device__ __forceinline__ uint32_t pack_v(float lo, float hi) {
    uint32_t r; asm volatile("cvt.rn.bf16x2.f32 %0, %1, %2;" : "=r"(r) : "f"(hi), "f"(lo)); return r;
}
__device__ __forceinline__ uint32_t pack_w(float lo, float hi) {
    uint32_t r; asm volatile("cvt.rn.satfinite.bf16x2.f32 %0, %1, %2;" : "=r"(r) : "f"(hi), "f"(lo)); return r;
}
template <int N> __device__ __forceinline__ uint32_t after_all(const uint32_t (&f)[N][4], uint32_t zero) {
    uint32_t d[3] = {0, 0, 0};
#pragma unroll
    for (int i = 0; i < N; i++) d[i % 3] |= f[i][3];
    return (d[0] | d[1] | d[2]) & zero;
}
__device__ __forceinline__ void pin(uint32_t& x) { asm volatile("" : "+r"(x)); }
template <class T> __device__ __forceinline__ void pin(T*& x) { asm volatile("" : "+l"(x)); }
__device__ __forceinline__ uint32_t pack_f16(float lo, float hi) {
    uint32_t r; asm("cvt.rn.f16x2.f32 %0, %1, %2;" : "=r"(r) : "f"(hi), "f"(lo)); return r;
}
__device__ __forceinline__ float bf_lo(uint32_t v) { return __uint_as_float(v << 16); }
__device__ __forceinline__ float bf_hi(uint32_t v) { return __uint_as_float(v & 0xffff0000u); }
__device__ __forceinline__ float bf_round(float x) { return __uint_as_float(pack_bf16(0.f, x)); }
__device__ __forceinline__ uint32_t badd2(uint32_t a, uint32_t b) { uint32_t r; asm("add.rn.bf16x2 %0, %1, %2;" : "=r"(r) : "r"(a), "r"(b)); return r; }
__device__ __forceinline__ uint32_t bsub2_lo(uint32_t a, uint32_t b) {
    uint32_t r; asm("{ .reg .b16 m, h; .reg .b32 m2; mov.b32 {m, h}, %2; mov.b32 m2, {m, m}; sub.rn.bf16x2 %0, %1, m2; }" : "=r"(r) : "r"(a), "r"(b)); return r;
}
__device__ __forceinline__ uint32_t bmax2(uint32_t a, uint32_t b) { uint32_t r; asm("max.bf16x2 %0, %1, %2;" : "=r"(r) : "r"(a), "r"(b)); return r; }
__device__ __forceinline__ uint32_t normalize2(uint32_t x, uint32_t s0, uint32_t s1) {
    uint32_t r;
    asm("{ .reg .b16 m, h, l, k; .reg .b32 m2, h2, l2, d, t;\n\t"
        "mov.b32 {m, h}, %2; mov.b32 {l, k}, %3; mov.b32 m2, {m, m}; mov.b32 h2, {h, h}; mov.b32 l2, {l, l};\n\t"
        "sub.rn.bf16x2 d, %1, m2; mul.rn.bf16x2 t, d, l2; fma.rn.bf16x2 %0, d, h2, t; }" : "=r"(r) : "r"(x), "r"(s0), "r"(s1));
    return r;
}
__device__ __forceinline__ float rcpf(float x) { float r; asm("rcp.approx.ftz.f32 %0, %1;" : "=f"(r) : "f"(x)); return r; }
__device__ __forceinline__ float sqrtaf(float x) { float r; asm("sqrt.approx.ftz.f32 %0, %1;" : "=f"(r) : "f"(x)); return r; }
__device__ __forceinline__ float ex2f(float x) { float r; asm("ex2.approx.ftz.f32 %0, %1;" : "=f"(r) : "f"(x)); return r; }

__device__ __forceinline__ int tok_off(int t) { return ((t >> 3) & 1) * VT_PLANE + (t >> 4) * 16 + (t & 7) * 2; }

__device__ __forceinline__ uint32_t unorder_key(uint32_t k16) { return k16 ^ ((k16 & 0x8000u) ? 0x8000u : 0xffffu); }

struct cplx { float r, i; };
struct hc { uint32_t r, i; };
template <bool CONJ> __device__ __forceinline__ cplx csq(cplx a) {
    float im;
    asm("{ .reg .f32 t; mul.ftz.f32 t, %1, %2; mul.ftz.f32 %0, t, 0f40000000; }" : "=f"(im) : "f"(CONJ ? -a.r : a.r), "f"(a.i));
    return {fmaf(a.r, a.r, -(a.i * a.i)), im};
}
__device__ __forceinline__ cplx cexpp(float a2, float ai) {
    float m = ex2f(a2), s, c;
    __sincosf(ai, &s, &c);
    return {m * c, m * s};
}
__device__ __forceinline__ __half2 as_h2(uint32_t x) { return *reinterpret_cast<__half2*>(&x); }
__device__ __forceinline__ uint32_t as_u(__half2 x) { return *reinterpret_cast<uint32_t*>(&x); }
__device__ __forceinline__ hc hmul(hc a, hc b) {
    return {as_u(__hfma2(as_h2(a.r), as_h2(b.r), __hneg2(__hmul2(as_h2(a.i), as_h2(b.i))))),
            as_u(__hfma2(as_h2(a.r), as_h2(b.i), __hmul2(as_h2(a.i), as_h2(b.r))))};
}
__device__ __forceinline__ hc hpack(cplx a, cplx b) { return {pack_f16(a.r, b.r), pack_f16(a.i, b.i)}; }
__device__ __forceinline__ void sts16(uint32_t a, uint32_t v) { asm volatile("st.shared.u16 [%0], %1;" ::"r"(a), "r"(v) : "memory"); }

struct KgenAddr {
    uint32_t l, h, m2, m3, m4, z, w, wz;
    __device__ __forceinline__ KgenAddr(uint32_t scr, int lane) {
        const int g = lane >> 2, t = lane & 3;
        const uint32_t rec = scr + t * 480;
        l = rec + 16 * g; h = rec + 128 + 8 * g; m2 = rec + 192 + 8 * (g & 1); m3 = rec + 208 + 4 * (g & 2); m4 = rec + 224 + 2 * (g & 4);
        z = scr + 7680 + 16 * t; w = scr + 240 * lane; wz = scr + 7680 + 8 * lane;
        pin(l); pin(h); pin(m2); pin(m3); pin(m4); pin(z); pin(w); pin(wz);
    }
    __device__ __forceinline__ uint32_t any() const { return (l | h | m2) | (m3 | m4 | z) | (w | wz); }
};
template <class Hook, class Hook2>
__device__ __forceinline__ void kgen(const KgenAddr& ad, uint32_t tab, int lane, uint2 la, uint2 aim, uint2 cre, uint2 cim, float dt, float skip, int dch, Hook main_done, Hook2 half_done) {
    const int g = lane >> 2, t = lane & 3;
    const float dt2 = 2.f * dt;
    const uint32_t am = bmax2(bmax2(cre.x & 0x7fff7fffu, cre.y & 0x7fff7fffu), bmax2(cim.x & 0x7fff7fffu, cim.y & 0x7fff7fffu));
    const float mx = dt2 * fmaxf(bf_lo(am), bf_hi(am));
    const uint32_t eb = min(max(__reduce_max_sync(0xffffffffu, __float_as_uint(mx)) >> 23, 1u), 252u);
    const float cscale = dt2 * __uint_as_float((253u - eb) << 23);
    const float scale_inv = __uint_as_float((eb + 1u) << 23);
    float k0 = (bf_lo(cre.x) + bf_hi(cre.x)) + (bf_lo(cre.y) + bf_hi(cre.y));
#pragma unroll
    for (int o = 16; o; o >>= 1) k0 += __shfl_xor_sync(0xffffffffu, k0, o);
    const float ndt = -1.4426950408889634f * dt;
    STAMP(40);

    float acc[5][4];
#pragma unroll
    for (int i = 0; i < 5; i++) { acc[i][0] = acc[i][1] = acc[i][2] = acc[i][3] = 0.f; }

#pragma unroll kBbUnroll
    for (int bb = 0; bb < 2; bb++) {
        cplx z[2][11], cz[2];
#pragma unroll
        for (int e = 0; e < 2; e++) {
            const float lg = e ? bf_hi(la.x) : bf_lo(la.x), ai = (e ? bf_hi(aim.x) : bf_lo(aim.x)) * dt;
            const float cr = (e ? bf_hi(cre.x) : bf_lo(cre.x)) * cscale, ci = (e ? bf_hi(cim.x) : bf_lo(cim.x)) * cscale;
            const float a2 = bf_round(ex2f(lg * 1.4426950408889634f)) * ndt;
            z[e][0] = cexpp(a2, ai);
            z[e][5] = cexpp(a2 * 32.f, ai * -32.f);
#pragma unroll
            for (int i = 1; i < 11; i++) if (i != 5) z[e][i] = (i == 3 || i == 7) ? csq<true>(z[e][i - 1]) : csq<false>(z[e][i - 1]);
            cz[e] = {fmaf(cr, z[e][0].r, -(ci * z[e][0].i)), fmaf(cr, z[e][0].i, ci * z[e][0].r)};
        }
        la.x = la.y; aim.x = aim.y; cre.x = cre.y; cim.x = cim.y;
        const hc z1 = hpack(z[0][0], z[1][0]), z2 = hpack(z[0][1], z[1][1]), z4 = hpack(z[0][2], z[1][2]);
        hc L[8], H[8];
        L[1] = hpack(z[0][3], z[1][3]); L[2] = hpack(z[0][4], z[1][4]); L[4] = hpack(z[0][5], z[1][5]);
        const hc y64 = hpack(z[0][6], z[1][6]), z128 = hpack(z[0][7], z[1][7]), z256 = hpack(z[0][8], z[1][8]);
        const hc z512 = hpack(z[0][9], z[1][9]), z1024 = hpack(z[0][10], z[1][10]);
        H[0] = hpack(cz[0], cz[1]);
        H[1] = hmul(H[0], z1); H[2] = hmul(H[0], z2); H[3] = hmul(H[1], z2);
        L[3] = hmul(L[1], L[2]);
#pragma unroll
        for (int i = 0; i < 4; i++) { H[4 + i] = hmul(H[i], z4); if (i) L[4 + i] = hmul(L[i], L[4]); }
        __syncwarp();
        sts128(ad.w, 0x3c003c00u, y64.r, 0u, y64.i);
#pragma unroll
        for (int i = 1; i < 8; i++) { const hc q = hmul(L[i], y64); sts128(ad.w + 16 * i, L[i].r, q.r, L[i].i, q.i); }
#pragma unroll
        for (int i = 0; i < 4; i++) sts128(ad.w + 128 + 16 * i, H[2 * i].r, H[2 * i].i, H[2 * i + 1].r, H[2 * i + 1].i);
        {
            const hc a = hmul(z256, z1), b = hmul(z256, z128), c = hmul(z256, z2), d = hmul(z512, z4);
            sts128(ad.w + 192, a.r, a.i, b.r, b.i);
            sts128(ad.w + 208, c.r, c.i, z512.r, z512.i);
            sts128(ad.w + 224, d.r, d.i, z1024.r, z1024.i);
            sts64(ad.wz, z128.r, z128.i);
        }
        __syncwarp();

#pragma unroll
        for (int k2 = 0; k2 < 4; k2++) {
#pragma unroll
            for (uint32_t s = 0; s < 2; s++) {
                const uint32_t o = k2 * 1920 + s * 240;
                const uint4 l = lds128(ad.l + o);
                const uint2 h0 = lds64(ad.h + o), m2 = lds64(ad.m2 + o), m3 = lds64(ad.m3 + o), m4 = lds64(ad.m4 + o), mz = lds64(ad.z + k2 * 64 + s * 8);
                const hc H0 = {h0.x, h0.y};
                const hc H1 = hmul(H0, {mz.x, mz.y}), H2 = hmul(H0, {m2.x, m2.y}), H3 = hmul(H2, {m3.x, m3.y}), H4 = hmul(H3, {m4.x, m4.y});
                mma_f16(acc[0], l.x, l.y, l.z, l.w, H0.r, H0.i);
                mma_f16(acc[1], l.x, l.y, l.z, l.w, H1.r, H1.i);
                mma_f16(acc[2], l.x, l.y, l.z, l.w, H2.r, H2.i);
                mma_f16(acc[3], l.x, l.y, l.z, l.w, H3.r, H3.i);
                mma_f16(acc[4], l.x, l.y, l.z, l.w, H4.r, H4.i);
            }
        }

        if (bb == 0) half_done();
    }
    __syncwarp();
    main_done();

#pragma unroll
    for (int i = 0; i < 4; i++) sts128(tab + 2048 + 512 * i + 16 * lane, 0, 0, 0, 0);
    if (lane < 15) sts32(tab + 4 * lane, 0);
    __syncwarp();
    const uint32_t d0 = tab + T_DENSE + 4 + 8 * lane, src = (lane + 31) & 31;
    const uint32_t p0 = pack_bf16(fmaf(k0, dt2, skip), 0.f);
    uint32_t prev = p0;
#pragma unroll
    for (int i = 0; i < 4; i++) {
        const uint32_t pk = pack_bf16(acc[i >> 1][2 * (i & 1) + 1] * scale_inv, acc[i >> 1][2 * (i & 1)] * scale_inv);
        sts64(d0 + 256 * i, __byte_perm(pk, __shfl_sync(0xffffffffu, lane == 31 ? prev : pk, src), 0x5432), pk);
        prev = pk;
    }
    const uint32_t w0 = pack_bf16(acc[2][0] * scale_inv, acc[2][1] * scale_inv), w1 = pack_bf16(acc[2][2] * scale_inv, acc[2][3] * scale_inv);
    const uint32_t sa = (lane & 1) ? 0x5410u : 0x5454u, sb2 = (lane & 1) ? 0x1010u : 0x5410u;
#pragma unroll
    for (int hf = 0; hf < 2; hf++) {
        const uint32_t w = hf ? w1 : w0;
        const uint32_t pv = __shfl_sync(0xffffffffu, lane != 31 ? w : hf ? w0 : __byte_perm(prev, w1, 0x5410), src);
        sts64(d0 + 1024 + 256 * hf, __byte_perm(w, pv, sa), __byte_perm(w, pv, sb2));
        sts64(d0 + 1536 + 256 * hf, __byte_perm(w, pv, sa + 0x2222u), __byte_perm(w, pv, sb2 + 0x2222u));
    }
    const uint32_t d3 = tab + T_R2 + 160 + 320 * (t & 1) + 16 * (g >> 1) + 8 * (g & 1) + 4 * (t >> 1), d3n = d3 + (g >= 6 ? 32 : 0);
    const uint32_t d4 = tab + T_R3 + 80 + 160 * t + 4 * g, d4n = d4 + (g >= 6 ? 16 : 0);
    uint32_t p3;
#pragma unroll
    for (int hf = 0; hf < 2; hf++)
#pragma unroll
        for (int e = 0; e < 2; e++) {
            const float v3 = acc[3][2 * hf + e] * scale_inv;
            const uint32_t p4 = pack_bf16(acc[4][2 * hf + e] * scale_inv, 0.f);
            p3 = pack_bf16(v3, v3);
            sts16(d3 + 64 * hf + 160 * e, p3);
            sts16((hf ? d3n : d3) + 64 * hf + 160 * e + 18, p3);
            sts16(d4 + 32 * hf + 80 * e, p4);
            sts16((hf ? d4n : d4) + 32 * hf + 80 * e + 10, p4);
        }
    if (lane == 31) {
        const uint32_t k512 = __byte_perm(w1, 0, 0x3232);
        sts32(tab + T_DENSE, p0);
        sts64(tab + T_DENSE + 4 * 513, k512, k512); sts16(tab + T_DENSE + 4 * 515 + 2, k512);
        sts16(tab + T_PATCH + 4 * 17, p3); sts32(tab + T_PATCH + 4 * 18, p3); sts16(tab + T_PATCH + 4 * 19 + 2, p3);
    }
    __syncwarp();
}

__device__ __forceinline__ void load_toep(uint32_t* a, uint32_t p, uint32_t pz) {
    a[0] = lds32(p); a[1] = lds32(p + 32); a[2] = lds32(pz - 32); a[3] = lds32(pz);
}
template <int F>
__device__ __forceinline__ void ffa_step(float (&acc)[16][4], float (&W)[8][4], uint32_t (&R)[8][4], uint32_t (&A)[4][4],
                                         uint32_t va, uint32_t vn, uint32_t vmin, uint32_t pb, uint32_t pz) {
    constexpr int S = F ^ 1;
    auto load = [&](int sh) {
#pragma unroll
        for (int i = S; i < 8; i += 2) ldsm4(R[i], i == 0 ? max(sh ? vn : va, vmin) : (sh ? vn : va) + i * 128);
#pragma unroll
        for (int k = S; k < 4; k += 2) load_toep(A[k], pb + 64 * sh + k * 512, pz + 64 * sh + k * 512);
    };
    auto prod = [&](int par, int dst) {
#pragma unroll
        for (int k = 0; k < 2; k++)
#pragma unroll
            for (int m = k; m < 8; m++) {
                const uint32_t* x = &R[2 * ((m - k) & 3) + par][2 * ((m - k) >> 2)];
                mma_v(dst == 1 ? W[m] : acc[2 * m + (dst >> 1)], A[2 * k + par], x[0], x[1]);
            }
    };
    load(0);
    prod(F, F);
    prod(S, S);
#pragma unroll
    for (int i = 0; i < 8; i++) A[(i >> 2) * 2 + F][i & 3] = badd2(A[(i >> 2) * 2][i & 3], A[(i >> 2) * 2 + 1][i & 3]);
#pragma unroll
    for (int i = 0; i < 16; i++) R[(i >> 2) * 2 + F][i & 3] = badd2(R[(i >> 2) * 2][i & 3], R[(i >> 2) * 2 + 1][i & 3]);
    load(1);
    prod(F, 2);
}
__device__ __forceinline__ uint32_t dense_phase(float (&acc)[16][4], float (&W)[8][4], uint32_t (&A)[4][4], uint32_t vmin, uint32_t va, uint32_t pb, uint32_t zero, int lane,
                                                uint32_t vbar) {
    uint32_t R[8][4], pz = pb + zero;
#pragma unroll 1
    for (int rho = 0; rho < 8; rho += 2) {
        if (rho == (int)zero) {
            mbar_wait(vbar, 0);
            STAMP(3);
#pragma unroll
            for (int i = 0; i < 8; i += 2) ldsm4(R[i], va + i * 128);
        }
        ffa_step<0>(acc, W, R, A, va, va - 16, vmin, pb, pz);
        ffa_step<1>(acc, W, R, A, va - 16, rho == 6 ? va + 96 : va - 32, vmin, pb + 64, pz + 64);
        pb += 128; pz += 128; va -= 32;
    }
    constexpr int PE = 2048 - 512, PP = T_PATCH - T_DENSE + 56 - 512;
    uint32_t E[4], F[4], G[4], H[4][4];
    const uint32_t vo = va + 128 + VT_PLANE + 496 - ((lane >> 3) & 1) * (512 + VT_PLANE) - (lane >> 4) * 896;
    load_toep(E, pb + PE, pz + PE);
#pragma unroll
    for (int i = 1; i < 8; i += 2) ldsm4(R[i], va + 128 + i * 128);
    load_toep(F, pb + PP, pz + PP);
    G[0] = lds32(pz + PE + 32); G[1] = lds32(pb + PE + 64); G[2] = lds32(pz + PP + 32); G[3] = lds32(pb + PP + 64);
#pragma unroll
    for (int i = 0; i < 4; i++) ldsm4(H[i], vo + i * 256);
#pragma unroll
    for (int i = 0; i < 32; i++) {
        const int m = i >> 2, j = i & 3;
        acc[2 * m + 1][j] = (acc[2 * m + 1][j] - acc[2 * m][j]) - W[m][j];
        if (m) acc[2 * m][j] += W[m - 1][j];
    }
#pragma unroll
    for (int i = 0; i < 12; i++) mma_v(acc[i + 4], E, R[i & 7][2 * (i >> 3)], R[i & 7][2 * (i >> 3) + 1]);
#pragma unroll
    for (int i = 0; i < 8; i++) mma_v(acc[i + 8], F, R[i][0], R[i][1]);
#pragma unroll
    for (int i = 0; i < 4; i++) mma_bf16_k8(acc[i + 4], G[0], G[1], H[i >> 1][2 * (i & 1) + 1]);
#pragma unroll
    for (int i = 0; i < 8; i++) mma_v(acc[i + 8], G, H[i >> 1][2 * (i & 1)], H[i >> 1][2 * (i & 1) + 1]);
    return __float_as_uint(W[7][0]) & zero;
}
__device__ __forceinline__ uint32_t ones2(int c, int lo, int hi) {
    return (((uint32_t)(c - lo) <= (uint32_t)(hi - lo)) ? 1u : 0u) | (((uint32_t)(c + 1 - lo) <= (uint32_t)(hi - lo)) ? 0x10000u : 0u);
}
__device__ __forceinline__ uint32_t box_bits(int lane) {
    const int d = 2 * (lane & 3) - (lane >> 2);
    auto four = [&](int L1, int H1, int L2, int H2) { return ones2(d, L1, H1) | ones2(d, L2, H2) << 1 | ones2(d + 8, L1, H1) << 2 | ones2(d + 8, L2, H2) << 3; };
    return four(5, 7, 0, 4) | four(1, 7, 0, 8) << 4;
}
struct Boxes {
    uint32_t q[4], ha[2];
    __device__ __forceinline__ Boxes(uint32_t bits, int k0, uint32_t h0, uint32_t h1) {
#pragma unroll
        for (int i = 0; i < 4; i++) q[i] = (bits & (0x10001u << (k0 + i))) * (0x3f80u >> (k0 + i));
        ha[0] = h0; ha[1] = h1;
    }
    __device__ __forceinline__ void load(int j, uint32_t* v, uint32_t zero) const {
        const uint32_t o = j * 128;
        v[0] = lds32(ha[0] + o); v[1] = lds32(ha[1] + zero + o); v[2] = lds32(ha[1] + o);
        v[3] = lds32(ha[0] + zero + o + 16); v[4] = lds32(ha[0] + o + 16); v[5] = lds32(ha[1] + o + 16);
    }
    __device__ __forceinline__ void sums(const uint32_t* v, float* Z, float* X, float* Y) const {
        mma_bf16_z(Z, q[0], q[1], q[2], q[3], v[0], v[1]);
        mma_bf16_z(X, q[0], q[1], q[2], q[3], v[2], v[3]);
        mma_bf16_z(Y, q[0], q[1], q[2], q[3], v[4], v[5]);
    }
};
__host__ __device__ constexpr int tail_step(int n) { return n < 8 ? n : n < 12 ? n + 4 : (n & 1) ? 11 - (n - 13) / 2 : 19 - (n - 12) / 2; }
template <class After>
__device__ __forceinline__ void tail_phase(float (&acc)[16][4], const Boxes& b2, const Boxes& b3, uint32_t tp2, uint32_t tp3, uint32_t zero, After after) {
    uint4 t2[5];
    uint2 t3[8];
    uint32_t v[6], a0[4], a1[4];
    float Z[4], X[4], Y[4];
    b2.load(0, v, zero);
#pragma unroll
    for (int i = 0; i < 5; i++) t2[i] = lds128(tp2 + 160 * i);
#pragma unroll
    for (int n = -1; n < 20; n++) {
        const int j = tail_step(n), j1 = tail_step(n + 1), j2 = tail_step(n + 2);
        if (n < 19) {
            (j1 < 12 ? b2 : b3).sums(v, Z, X, Y);
            if (n < 18) { if (j2 < 12) b2.load(j2, v, zero); else b3.load(j2 - 12, v, zero); }
        }
        if (n >= 0 && j < 12) {
#pragma unroll
            for (int b = 0; b < 5; b++) if (j + 4 + b < 16) mma_v(acc[j + 4 + b], a1, t2[b].z, t2[b].w);
        }
        if (n < 19 && j1 < 12) { a1[0] = pack_v(Z[0], Z[1]); a1[1] = pack_w(X[0], X[1]); a1[2] = pack_v(Z[2], Z[3]); a1[3] = pack_w(X[2], X[3]); }
        if (n == 6) {
#pragma unroll
            for (int b = 0; b < 8; b++) t3[b] = lds64(tp3 + 80 * b);
        }
        if (n >= 0 && j < 12) {
#pragma unroll
            for (int b = 0; b < 5; b++) if (j + 4 + b < 16) mma_v(acc[j + 4 + b], a0, t2[b].x, t2[b].y);
        } else if (n >= 0) {
#pragma unroll
            for (int b = 0; b < 8; b++) if (j - 4 + b < 16) mma_v(acc[j - 4 + b], a0, t3[b].x, t3[b].y);
        }
        if (n < 19) {
            if (j1 < 12) { a0[0] = pack_v(X[0], X[1]); a0[1] = pack_v(Y[0], Y[1]); a0[2] = pack_v(X[2], X[3]); a0[3] = pack_v(Y[2], Y[3]); }
            else { a0[0] = pack_v(X[0], X[1]); a0[1] = pack_v(Y[0], Y[1]); a0[2] = pack_v(Z[2], Z[3]); a0[3] = pack_v(X[2], X[3]); }
        }
        after(n);
    }
}
template <int Q>
__device__ __forceinline__ void emit(const float (&acc)[16][4], int h, uint32_t own, uint32_t peer, uint32_t bar, uint32_t bar_peer) {
    constexpr int n = 4 * Q;
#pragma unroll
    for (int hf = 0; hf < 2; hf++)
        asm volatile("{ .reg .pred p; setp.eq.u32 p, %7, %8;\n\t@p st.shared.v4.u32 [%0], {%1,%2,%3,%4};\n\t"
                     "@!p st.async.weak.shared::cluster.mbarrier::complete_tx::bytes.v4.b32 [%5], {%1,%2,%3,%4}, [%6]; }"
                     ::"r"(own + Q * 8192), "r"(pack_bf16(acc[n][2 * hf], acc[n][2 * hf + 1])), "r"(pack_bf16(acc[n + 1][2 * hf], acc[n + 1][2 * hf + 1])),
                     "r"(pack_bf16(acc[n + 2][2 * hf], acc[n + 2][2 * hf + 1])), "r"(pack_bf16(acc[n + 3][2 * hf], acc[n + 3][2 * hf + 1])),
                     "r"(peer + Q * 8192), "r"(bar_peer + 8 * Q), "r"(h), "r"(hf) : "memory");
    __syncwarp();
    if (elect_one()) mbar_arrive(bar);
}
__device__ __forceinline__ uint32_t finish_src(uint32_t sb, int h, int j, int lane) {
    const int m = lane >> 3, r = lane & 7;
    return sb + OFF_XT + (h ^ 1) * 32768 + (2 * m + (r & 1)) * 512 + (((8 * j + (r & 4) + ((r >> 1) & 1)) ^ ((r & 1) << 1)) << 4);
}
__device__ __forceinline__ uint32_t finish_dst(uint32_t sb, int h, int j, int lane) {
    const int g = lane >> 2, t = lane & 3;
    return sb + OFF_XT + h * 32768 + j * 2048 + (g >> 1) * 512 + (t >> 1) * 144 + (2 * (t & 1) + (g & 1)) * 32;
}
__device__ __forceinline__ uint32_t tile_addr(uint32_t sb, int tok, int t) {
    return sb + OFF_XT + (tok & 8) * 4096 + (tok >> 9) * 8192 + (tok & 6) * 1024 + (tok & 448) * 4 + (tok & 1) * 128 + (tok & 48) * 2 + (((t >> 1) ^ (tok & 1)) << 4) + (t & 1) * 8;
}
__device__ __forceinline__ uint2 add_update(uint2 o, uint32_t upd) {
    const float4 u = lds128f(upd);
    return make_uint2(badd2(o.x, pack_bf16(u.x, u.y)), badd2(o.y, pack_bf16(u.z, u.w)));
}
__device__ __forceinline__ void finish_half(uint32_t src, uint32_t xa, const uint4 (&x)[2]) {
    uint32_t s[2][4];
#pragma unroll
    for (int i = 0; i < 2; i++) ldsm4t(s[i], src ^ (i << 5));
#pragma unroll
    for (int i = 0; i < 2; i++) sts128(xa + i * 256, badd2(x[i].x, s[i][0]), badd2(x[i].y, s[i][1]), badd2(x[i].z, s[i][2]), badd2(x[i].w, s[i][3]));
}

__device__ __noinline__ float centred_var(uint32_t rows, float mu, int lane) {
    float var = 0.f;
#pragma unroll 1
    for (int rr = 0; rr < 16; rr++) {
        const float c0 = __shfl_sync(0xffffffffu, mu, rr);
        float c = 0.f;
#pragma unroll 1
        for (int k = 0; k < 16; k++) {
            const uint32_t q = lds32(rows + rr * ROW_PITCH + k * 128 + lane * 4);
            const float d0 = bf_lo(q) - c0, d1 = bf_hi(q) - c0;
            c = fmaf(d0, d0, fmaf(d1, d1, c));
        }
#pragma unroll 1
        for (int o = 16; o; o >>= 1) c += __shfl_xor_sync(0xffffffffu, c, o);
        if ((lane & 15) == rr) var = c * (1.f / DM);
    }
    return var;
}
__device__ __noinline__ float centred_score(uint32_t rows, uint32_t wbuf, uint32_t s0, uint32_t s1, int lane) {
    float sc = 0.f;
#pragma unroll 1
    for (int rr = 0; rr < 16; rr++) {
        const uint32_t t0 = __shfl_sync(0xffffffffu, s0, rr), t1 = __shfl_sync(0xffffffffu, s1, rr);
        float c = 0.f;
#pragma unroll 1
        for (int k = 0; k < 16; k++) {
            const uint32_t xn = normalize2(lds32(rows + rr * ROW_PITCH + k * 128 + lane * 4), t0, t1);
            const uint32_t wq = lds32(wbuf + (k >> 2) * 1024 + (k & 3) * 128 + lane * 4);
            c = fmaf(bf_lo(xn), bf_lo(wq), fmaf(bf_hi(xn), bf_hi(wq), c));
        }
#pragma unroll 1
        for (int o = 16; o; o >>= 1) c += __shfl_xor_sync(0xffffffffu, c, o);
        if ((lane & 15) == rr) sc = c;
    }
    return sc;
}

__device__ __forceinline__ void issue_rows(const __nv_bfloat16* u, uint32_t sb, int b) {
    if (elect_one()) {
        const uint32_t bar = sb + OFF_BAR + 8 * B_ROW;
#pragma unroll
        for (int j = 0; j < 4; j++) mbar_init(bar + 8 * j, 1);
        asm volatile("fence.mbarrier_init.release.cluster;" ::: "memory");
        fence_async();
#pragma unroll 1
        for (int j = 0; j < 4; j++) {
            mbar_expect_tx(bar + 8 * j, 8192);
#pragma unroll
            for (int i = 0; i < 4; i++) bulk_g2s(sb + OFF_VT + (4 * j + i) * ROW_PITCH, u + (size_t)(16 * b + 4 * j + i) * DM, 2048, bar + 8 * j);
        }
    }
    __syncwarp();
}

__global__ void __cluster_dims__(2, 1, 1) __launch_bounds__(NTHR, 1)
fused_kernel(const __grid_constant__ Ptrs p, const __grid_constant__ Maps maps) {
    extern __shared__ __align__(1024) unsigned char smem[];
    const int tid = threadIdx.x, lane = tid & 31;
    const int c_ = ((blockIdx.x >> 1) + 60) & 63, b = 2 * ((c_ & 32) | ((c_ & 7) << 2) | ((c_ >> 3) & 3)) + (blockIdx.x & 1);
    const int dch = 8 * b + (tid >> 5) - 4;
    uint2 la, aim, cre, cim;
    uint32_t ldt16;
    if ((uint32_t)(tid - 128) < 256u) {
        la = ldg64(p.logA + dch * NMODE + 4 * lane); aim = ldg64(p.Aim + dch * NMODE + 4 * lane);
        cre = ldg64(p.Cre + dch * NMODE + 4 * lane); cim = ldg64(p.Cim + dch * NMODE + 4 * lane);
        ldt16 = ldg16(p.ldt + dch);
    }
    const uint32_t sb = s_u32(smem), bar0 = sb + OFF_BAR;
    const int warp = __shfl_sync(0xffffffffu, tid >> 5, 0);
    const int h = b & 1, cl = b >> 1;
    const int m = lane >> 3, r = lane & 7, g = lane >> 2, t = lane & 3;
    const bool has_gu = b < GU_CTAS;
    if (warp == 4) { STAMP(0); GSTAMP(24); }

    if (warp >= 12) {
        asm volatile("setmaxnreg.dec.sync.aligned.u32 24;");
        const int a = warp - 12;
        uint32_t due = now_ns() + ST_T0 + (uint32_t)(2 * a + h) * (ST_PER / 2) + (has_gu ? 0 : 12 * ST_PER + 4 * ST_PER2);
        const bool el = elect_one();
        if (a == 1) issue_rows(p.u, sb, b);
        if (a == 2 && el) {
#pragma unroll
            for (int i = B_XT; i < NBAR; i++) mbar_init(bar0 + 8 * i, (i == B_V || i == B_SFREE || i == B_XFREE || i == B_OWN) ? 8 : (i >= B_RECV && i < B_RECV + 3) ? 9 : i == B_RED ? 5 : (i == B_UPD || (i >= B_FREE && i < B_FULL)) ? 4 : 1);
            asm volatile("fence.mbarrier_init.release.cluster;" ::: "memory");
            fence_async();
            mbar_expect_tx(bar0 + 8 * B_XT, 65536);
#pragma unroll
            for (int i = 0; i < 4; i++) mbar_expect_tx(bar0 + 8 * (B_RECV + i), 4096);
            mbar_expect_tx(bar0 + 8 * B_RED, 2048);
        }
        if (a == 3 && el) {
#pragma unroll
            for (int i = 0; i < 5; i++) asm volatile("prefetch.tensormap [%0];" ::"l"(&maps.u + i) : "memory");
        }
        __syncwarp();
        cluster_arrive();
        cluster_wait();
        STAMP(18);
        uint32_t fs = finish_src(sb, h, a, lane), fx = finish_dst(sb, h, a, lane);
        pin(fs); pin(fx);
        mbar_wait(bar0 + 8 * (B_ROW + a), 0);
        if (el) {
#pragma unroll
            for (int i = 0; i < 4; i++)
                tma_load_tile(sb + OFF_XT + (a >> 1) * 32768 + (a & 1) * 4096 + h * 8192 + (i & 1) * 16384 + (i >> 1) * 2048, &maps.u, 16 * cl, 4 * a + (i & 2), 16 * (i & 1) + 8 * h, bar0 + 8 * B_XT);
        }
        if (el) {
#pragma unroll 1
            for (int k = has_gu ? 0 : 4; k < 6; k++) {
                const int i = 4 * k + a, s = k < 3 ? i : i - 12;
                sleep_until(due);
                due += k < 3 ? 4 * ST_PER : 4 * ST_PER2;
                const bool again = k >= 3 && has_gu;
                if (s >= 6 || again) mbar_wait(bar0 + 8 * (s < 10 || again ? B_FREE + s : B_V), slot_priv(s) && again);
                if (k == 5 && a >= 2) mbar_wait(bar0 + 8 * B_LN, 1);
                const uint32_t dst = sb + slot_off(s), bar = bar0 + 8 * (B_FULL + s);
                if (k < 4) {
                    mbar_expect_tx(bar, 8192);
                    tma_load_2d(dst, &maps.wg, 64 * cl, 512 * h + 32 * i, bar);
                    tma_load_2d(dst + 4096, &maps.wu, 64 * cl, 512 * h + 32 * i, bar);
                } else {
                    mbar_expect_tx(bar, 7168);
                    tma_load_perm(dst, &maps.wd, 16 * cl, 56 * h + 14 * a + 7 * (k & 1), bar);
                }
            }
            STAMP(19);
        }
        __syncwarp();
        {
            mbar_wait(bar0 + 8 * B_XT, 0);
#pragma unroll 1
            for (int Q = 0; Q < 3; Q++) {
#pragma unroll
                for (int q = 0; q < 2; q++) {
                    const uint4 x[2] = {lds128(fx ^ (q << 4)), lds128((fx ^ (q << 4)) + 256)};
                    if (q == 0) mbar_wait(bar0 + 8 * (B_RECV + Q), 0);
                    finish_half(fs + q * 4096, fx ^ (q << 4), x);
                }
                fence_async();
                __syncwarp();
                if (el) tma_store_tile(&maps.out, sb + OFF_XT + h * 32768 + Q * 8192 + a * 2048, 16 * cl, 8 * h + 2 * a, 8 * Q);
                fs += 8192; fx += 8192;
                STAMP(Q ? 58 + Q : 20);
            }
            const int tok = 2047 - (int)(lds32(sb + OFF_MISC + 48 + 8 * g) & 2047);
            const bool mine = ((tok >> 1) & 7) == 4 * h + a && tok < 1536;
            if (el) asm volatile("cp.async.bulk.wait_group 0;" ::: "memory");
            if (__any_sync(0xffffffffu, mine)) {
                const uint2 o0 = lds64(tile_addr(sb, tok, t));
                mbar_wait(bar0 + 8 * B_UPD, 0);
                const uint2 o1 = add_update(o0, sb + tab_off(g) + T_RED + 16 * t);
                if (mine) *reinterpret_cast<uint2*>(p.out + (size_t)tok * DM + 16 * cl + 4 * t) = o1;
            } else STAMP(62);
        }
    } else if (warp >= 4) {
        const int w = warp - 4;
        uint32_t dsk16 = ldg16(p.dsk + dch);
        cluster_arrive();
        asm volatile("setmaxnreg.inc.sync.aligned.u32 176;");
        const uint32_t vrow = sb + OFF_VT + w * VT_PITCH + VT_PAD, tab = sb + tab_off(w);
        const uint32_t rb0 = bar0 + 8 * B_RECV, rb1 = mapa(rb0, h ^ 1);
        uint32_t tpo = 80 + (g - 2 * t) * 8 - (g < 2 * t ? 16 : 0);
        uint32_t xa = sb + OFF_XT + (w >> 1) * 8192 + (w & 1) * 1024 + (g >> 1) * 2048 + (g & 1) * 128 + t * 32 + ((h ^ (g & 1)) << 4);
        uint32_t va = sb + OFF_VT + (2 * m + (r & 1)) * VT_PITCH + VT_PAD + (16 * w + (r >> 1)) * 16;
        uint32_t qa = sb + OFF_ST + 2048 * w + 128 * t + 16 * (g ^ (2 * t));
        uint32_t vmin = vrow + (m & 1) * VT_PLANE - 16, vd = vmin + 16 + (m >> 1) * 1024 + r * 16;
        uint32_t vz = vrow - VT_PAD + (lane >> 1) * VT_PLANE + (lane & 1) * 16;
        pin(vmin); pin(vd); pin(vz);
        pin(tpo); pin(xa); pin(va); pin(qa);
        uint32_t bits = box_bits(lane), h0 = vrow + 16 * g + tok_off(2 * t - 18);
        pin(bits); pin(h0);
        const KgenAddr ka(sb + OFF_PRIV + w * 8192, lane);
        if (__any_sync(0xffffffffu, (vmin | (vd | vz) | (tpo | xa) | (va | qa) | (bits | h0) | ka.any()) & p.zero)) __trap();
        cluster_wait();
        pin(la.x); pin(la.y); pin(aim.x); pin(aim.y); pin(cre.x); pin(cre.y); pin(cim.x); pin(cim.y); pin(ldt16); pin(dsk16);
        uint4 x[8];
        auto load_x = [&]() {
            mbar_wait(bar0 + 8 * B_XT, 0);
#pragma unroll
            for (int i = 0; i < 8; i++) x[i] = lds128(xa + (i & 1) * 32768 + (i >> 1) * 256);
        };
        kgen(ka, tab, lane, la, aim, cre, cim, bf_round(ex2f(bf_lo(ldt16) * 1.4426950408889634f)), 1.f + bf_lo(dsk16), dch, [&]() {
            STAMP(21);
            if (elect_one()) mbar_arrive_n(bar0 + 8 * (B_FREE + 6 + ((w >> 1) ^ 2)), 2);
        }, [&]() {
            if ((LN_PAUSE >> w) & 1) mbar_wait(bar0 + 8 * B_LN, 0);
        });
        STAMP(1);
        const uint32_t pb = tab + T_DENSE + (g - 2 * t) * 4;
        uint32_t A[4][4];
        load_toep(A[0], pb, pb + p.zero);
        load_toep(A[2], pb + 1024, pb + p.zero + 1024);
        {
            load_x();
            STAMP(47);
            mbar_wait(bar0 + 8 * (B_ST + (w >> 1)), 0);
            uint4 q[4];
#pragma unroll
            for (int n = 0; n < 4; n++) q[n] = lds128(qa + 512 * n);
            if (lane < 4) sts128(vz, 0, 0, 0, 0);
            STAMP(2); GSTAMP(28);
#pragma unroll
            for (int i = 0; i < 8; i++) {
                const uint32_t s0 = (i & 1) ? q[i >> 1].z : q[i >> 1].x, s1 = (i & 1) ? q[i >> 1].w : q[i >> 1].y;
                stsm4t(va + (i >> 1) * 64 + (i & 1) * VT_PLANE, normalize2(x[i].x, s0, s1), normalize2(x[i].y, s0, s1),
                       normalize2(x[i].z, s0, s1), normalize2(x[i].w, s0, s1));
            }
            __syncwarp();
            if (elect_one()) mbar_arrive(bar0 + 8 * B_V);
        }
        float acc[16][4], W[8][4];
#pragma unroll
        for (int i = 0; i < 64; i++) { acc[i >> 2][i & 3] = 0.f; W[i >> 3][i & 3] = 0.f; }
        bits |= dense_phase(acc, W, A, vmin, vd, pb, p.zero, lane, bar0 + 8 * B_V);
        const uint32_t h1 = h0 + (t ? VT_PLANE : 16 - VT_PLANE);
        const Boxes b2(bits, 0, h0, h1), b3(bits, 4, (t == 1 ? h1 : h0) - 4, t == 1 ? h0 + 12 : h1 - 4);
        STAMP(4);
        const uint32_t so = sb + OFF_XT + (8 * h + w) * 512 + ((lane ^ ((w & 1) << 1)) << 4);
        const uint32_t dst0 = so + (h ^ 1) * 32768, dst1 = mapa(so + h * 32768, h ^ 1);
        tail_phase(acc, b2, b3, tab + T_R2 + 2 * tpo, tab + T_R3 + tpo, p.zero, [&](int j) {
            if (j == -1) {
                mbar_wait(bar0 + 8 * B_SFREE, 0);
                emit<0>(acc, h, dst0, dst1, rb0, rb1);
            }
            if (j == 3) { emit<1>(acc, h, dst0, dst1, rb0 + 8, rb1); STAMP(5); }
            if (j == 11) {
                mbar_wait(bar0 + 8 * B_XFREE, 0);
                emit<2>(acc, h, dst0, dst1, rb0 + 16, rb1);
                STAMP(58);
            }
        });
        emit<3>(acc, h, dst0, dst1, bar0 + 8 * B_OWN, rb1);
        STAMP(30);
        if (w < 4) {
            const uint32_t fs = finish_src(sb, h, w, lane) + 24576 + h * 4096, fx = (finish_dst(sb, h, w, lane) + 24576) ^ (h << 4);
            const int tok = 2047 - (int)(lds32(sb + OFF_MISC + 48 + 8 * g) & 2047);
            const bool mine = ((tok >> 1) & 7) == 4 * h + w && tok >= 1536;
            const uint32_t ta = tile_addr(sb, tok, t);
            const uint4 x0[2] = {lds128(fx), lds128(fx + 256)}, x1[2] = {lds128(fx ^ 16), lds128((fx ^ 16) + 256)};
            mbar_wait(bar0 + 8 * B_OWN, 0);
            finish_half(fs, fx, x0);
            mbar_wait(bar0 + 8 * (B_RECV + 3), 0);
            STAMP(6);
            finish_half(fs + (h ? -4096 : 4096), fx ^ 16, x1);
            __syncwarp();
            if (__any_sync(0xffffffffu, mine)) {
                const uint2 o0 = lds64(ta);
                mbar_wait(bar0 + 8 * B_UPD, 0);
                const uint2 o1 = add_update(o0, sb + tab_off(g) + T_RED + 16 * t);
                if (mine) sts64(ta, o1.x, o1.y);
            }
            fence_async();
            __syncwarp();
            if (elect_one()) {
                tma_store_tile(&maps.out, sb + OFF_XT + h * 32768 + 24576 + w * 2048, 16 * cl, 8 * h + 2 * w, 24);
                if (w == 3) STAMP(61);
                asm volatile("cp.async.bulk.wait_group.read 0;" ::: "memory");
            }
        }
        STAMP(7);
    } else {
        const int a = warp;
        const uint4 wq = ldg128(p.wr + 8 * tid);
        const uint32_t epoch = ld_relaxed_32(&p.sc[a].cnt[b & 96]) >> 5;
        cluster_arrive();
        asm volatile("setmaxnreg.inc.sync.aligned.u32 136;");
        const uint32_t tag = __shfl_sync(0xffffffffu, epoch, 0) + 1u, misc = sb + OFF_MISC, abar = bar0 + 8 * (B_AUX + a);
        uint32_t aph = 0;
        const Exchange* in = &p.sc[cl & (NREP - 1)];
        uint2* pub = p.sc[m >> 1].stat + 16 * b + 2 * (r ^ (2 * (b & 3))) + (m & 1);
        uint32_t* cnt_s = &p.sc[t].cnt[b & 96];
        pin(pub); pin(cnt_s);
        if (tid < 32) sts32(sb + OFF_XCH + 4 * tid, 0);
        const uint32_t wbuf = sb + OFF_LN + a * 1024, part = sb + OFF_LN + 4096;
        {
            sts128(wbuf + 16 * lane, wq.x, wq.y, wq.z, wq.w);
            sts128(wbuf + 512 + 16 * lane, 0x3f803f80u, 0x3f803f80u, 0x3f803f80u, 0x3f803f80u);
            float wsum = ((bf_lo(wq.x) + bf_hi(wq.x)) + (bf_lo(wq.y) + bf_hi(wq.y))) + ((bf_lo(wq.z) + bf_hi(wq.z)) + (bf_lo(wq.w) + bf_hi(wq.w)));
#pragma unroll
            for (int o = 16; o; o >>= 1) wsum += __shfl_xor_sync(0xffffffffu, wsum, o);
            sts32f(part + 1024 + 4 * a, wsum);
            uint32_t wf[4][4];
#pragma unroll
            for (int i = 0; i < 4; i++) ldsm4(wf[i], wbuf + ((uint32_t)(r - 1) < 2u ? 16 * (r - 1) : 512) + 32 * m + 128 * i);
            uint32_t ra = sb + OFF_VT + r * ROW_PITCH + 512 * a + 16 * m, pa = part + a * 256 + g * 16;
            cluster_wait();
            STAMP(22);
#pragma unroll 1
            for (int hf = 0; hf < 2; hf++) {
                mbar_wait(bar0 + 8 * B_ROW + 16 * hf, 0);
                mbar_wait(bar0 + 8 * B_ROW + 16 * hf + 8, 0);
                STAMP(23);
                uint32_t x[8][4];
                float cs[2][4], q[8][4];
#pragma unroll
                for (int i = 0; i < 40; i++) (i < 8 ? cs[i >> 2 & 1] : q[(i - 8) >> 2 & 7])[i & 3] = 0.f;
#pragma unroll
                for (int k = 0; k < 8; k++) ldsm4(x[k], ra + k * 64);
                const bool more = __any_sync(0xffffffffu, after_all(x, p.zero));
#pragma unroll 1
                do {
#pragma unroll
                    for (int k = 0; k < 8; k++) {
                        mma_v(cs[k & 1], x[k], wf[k >> 1][2 * (k & 1)], wf[k >> 1][2 * (k & 1) + 1]);
#pragma unroll
                        for (int i = 0; i < 4; i++) mma_bf16_k8(q[4 * (k & 1) + i], x[k][i & 2], x[k][i | 1], x[k][i]);
                    }
                } while (more);
                const float c2 = cs[0][2] + cs[1][2];
                if (t == 0) sts64f(pa, (cs[0][0] + cs[1][0]) + c2, cs[0][1] + cs[1][1]);
                if (t == 1) sts32f(pa + 12, c2);
                const float e0 = ((q[0][0] + q[2][0]) + (q[4][0] + q[6][0])) + ((q[1][2] + q[3][2]) + (q[5][2] + q[7][2]));
                const float e1 = ((q[0][1] + q[2][1]) + (q[4][1] + q[6][1])) + ((q[1][3] + q[3][3]) + (q[5][3] + q[7][3]));
                if (t == (g >> 1)) sts32f(pa + 8, (g & 1) ? e1 : e0);
                ra += 8 * ROW_PITCH; pa += 128;
            }
        }
        STAMP(31);
        named_sync(1, 128);
        if (a == 0) {
            const uint32_t pa = part + (lane & 15) * 16;
            const float4 p0 = lds128f(pa), p1 = lds128f(pa + 256), p2 = lds128f(pa + 512), p3 = lds128f(pa + 768), ws = lds128f(part + 1024);
            const float mu = ((p0.x + p1.x) + (p2.x + p3.x)) * (1.f / DM);
            float var = ((p0.z + p1.z) + (p2.z + p3.z)) * (1.f / DM) - mu * mu;
            const bool centred = __any_sync(0xffffffffu, !(mu * mu <= 4.f * var));
            if (centred) var = centred_var(sb + OFF_VT, mu, lane);
            const float ri = rcpf(bf_round(sqrtaf(bf_round(bf_round(var) + 1e-5f))));
            const uint32_t s0 = pack_bf16(mu, ri), s1 = (pack_bf16(ri - bf_hi(s0), 0.f) & 0xfffcu) | (tag & 3);
            float sc = ((((p0.y + p1.y) + (p2.y + p3.y)) + ((p0.w + p1.w) + (p2.w + p3.w))) - bf_lo(s0) * ((ws.x + ws.y) + (ws.z + ws.w))) * ri;
            if (centred) sc = centred_score(sb + OFF_VT, sb + OFF_LN, s0, s1, lane);
            const uint32_t sb16 = pack_bf16(0.f, sc);
            const uint32_t s2 = s1 | (sb16 ^ (((uint32_t)((int)sb16 >> 31) & 0x7fff0000u) | 0x80000000u));
            st_relaxed_64(pub, s0, s2);
            st_relaxed_64(pub + 2 * sizeof(Exchange) / 8, s0, s2);
            if (lane < NREP) red_add(cnt_s, 1);
            if (elect_one()) mbar_arrive(bar0 + 8 * B_LN);
            STAMP(9); GSTAMP(25);
        }
        const uint32_t slot0 = sb + OFF_RING + a * 8192, slot1 = sb + slot_off(4 + a), slot2 = sb + slot_off(8 + a), fbar = bar0 + 8 * (B_FULL + a);
        uint32_t mine, row[2];
        {
            uint32_t q[16];
            named_sync(1, 128);
            wait_count(&in->cnt[32 * a], 32 * tag - FEW_ST);
            STAMP(41);
#pragma unroll 1
            for (uint32_t it = 0;; spin_guard(it)) {
                if (elect_one()) {
                    mbar_expect_tx(abar, 4096);
                    bulk_g2s(sb + OFF_ST + 4096 * a, in->stat + 512 * a, 4096, abar);
                }
                mbar_wait(abar, aph);
                aph ^= 1;
                uint32_t bad = 0;
#pragma unroll
                for (int n = 0; n < 8; n++) {
                    const uint4 u = lds128v(sb + OFF_ST + 4096 * a + 512 * n + 16 * lane);
                    q[2 * n] = u.y; q[2 * n + 1] = u.w;
                    bad = or_xor(bad, u.y, tag);
                }
                const bool ok = __all_sync(0xffffffffu, (bad & 3) == 0);
                asm volatile("{ .reg .pred p; setp.ne.u32 p, %1, 0; @p mbarrier.arrive.shared::cta.b64 _, [%0]; }" ::"r"(bar0 + 8 * (B_ST + a)), "r"((uint32_t)(ok && lane == 0)) : "memory");
                if (ok) break;
            }
            STAMP(8);
            const uint32_t inv = 2047 - 512 * a - 16 * m - (r ^ (2 * m));
#pragma unroll
            for (int i = 0; i < 16; i++) asm("lop3.b32 %0, %0, %1, %2, 0x9b;" : "+r"(q[i]) : "r"(inv), "r"(0xffff0000u | (64 * (i >> 1) + 8 * (i & 1))));
            auto below = [&](uint32_t x) {
                uint32_t d[4];
#pragma unroll
                for (int i = 0; i < 16; i++) d[i & 3] = i < 4 ? x + q[i] : min(d[i & 3], x + q[i]);
                d[0] = min(min(d[0], d[1]), min(d[2], d[3]));
                return d[0] < x ? x - 1 - d[0] : 0u;
            };
            const uint32_t mx0 = ~min(min(min(min(q[0], q[1]), min(q[2], q[3])), min(min(q[4], q[5]), min(q[6], q[7]))),
                                      min(min(min(q[8], q[9]), min(q[10], q[11])), min(min(q[12], q[13]), min(q[14], q[15]))));
            const uint32_t gm = __reduce_max_sync(0xffffffffu, mx0 == __reduce_max_sync(0xffffffffu, mx0) ? 0u : mx0);
            if (lane == 0) sts32(misc + 16 + 4 * a, gm);
            named_sync(1, 128);
            STAMP(42);
            const uint4 t0 = lds128(misc + 16);
            uint32_t tau = min(min(t0.x, t0.y), min(t0.z, t0.w));
            uint32_t mx = mx0, cnt = 0, bal;
            const uint32_t list = sb + OFF_XCH + 32 * a;
#pragma unroll 1
            while ((bal = __ballot_sync(0xffffffffu, mx >= tau)) != 0) {
                const uint32_t pos = cnt + __popc(bal & ((1u << lane) - 1u));
                cnt += __popc(bal);
                if (cnt > 8) break;
                if (mx >= tau) sts32(list + 4 * pos, mx);
                mx = below(mx);
            }
            if (cnt > 8) {
                mx = mx0;
#pragma unroll 1
                for (int j = 0; j < 8; j++) {
                    const uint32_t top = __reduce_max_sync(0xffffffffu, mx), nx = below(mx);
                    if (mx == top) { sts32(list + 4 * j, mx); mx = nx; }
                }
            }
            named_sync(1, 128);
            STAMP(43);
            const uint32_t k = lds32(sb + OFF_XCH + 4 * lane);
            uint32_t rk[4] = {misc + 48, 0, 0, 0};
#pragma unroll
            for (int j = 0; j < 8; j++) {
                const uint4 c = lds128(sb + OFF_XCH + 16 * j);
                asm("{ .reg .pred p, q, r, s; setp.gt.u32 p, %4, %8; setp.gt.u32 q, %5, %8; setp.gt.u32 r, %6, %8; setp.gt.u32 s, %7, %8;\n\t"
                    "@p add.u32 %0, %0, 8; @q add.u32 %1, %1, 8; @r add.u32 %2, %2, 8; @s add.u32 %3, %3, 8; }"
                    : "+r"(rk[0]), "+r"(rk[1]), "+r"(rk[2]), "+r"(rk[3]) : "r"(c.x), "r"(c.y), "r"(c.z), "r"(c.w), "r"(k));
            }
            rk[0] = (rk[0] + rk[1]) + (rk[2] + rk[3]);
            if (rk[0] < misc + 112) sts32(rk[0], k);
            __syncwarp();
            mine = lds32(misc + 48 + 8 * g);
            const uint4 two = lds128v(misc + 48 + 16 * a);
            row[0] = two.x; row[1] = two.z;
            mbar_wait(bar0 + 8 * B_V, 0);
        }
        STAMP(11);
        const int tok = 2047 - (int)(mine & 2047);
        const uint32_t xs = sb + OFF_XT + (h ^ 1) * 32768 + 16384;
        if (has_gu) {
            if (elect_one()) {
                mbar_expect_tx(abar, 2048);
#pragma unroll
                for (int j = 0; j < 2; j++) bulk_g2s(xs + (2 * a + j) * 1040, p.u + (size_t)(2047 - (row[j] & 2047)) * DM + 512 * h, 1024, abar);
            }
        }
        STAMP(44);
        uint32_t af[20][4], ko = sb + (m & 1) * 4096 + (r + ((m >> 1) << 3)) * 128 + ((r ^ (4 * h) ^ a) << 4);
        auto load_level = [&](int c) {
#pragma unroll
            for (int j = 0; j < 4; j++) {
                mbar_wait(bar0 + 8 * (B_FULL + 4 * (c % 3) + j), c / 3);
#pragma unroll
                for (int i = 0; i < 4; i++) ldsm4t(af[8 * (i >> 1) + 2 * j + (i & 1)], (ko ^ ((i & 1) << 6)) + slot_off(4 * (c % 3) + j) + (i >> 1) * 2048);
            }
            STAMP(36 + c);
            __syncwarp();
            if (c < 3 && lane < 4) mbar_arrive(bar0 + 8 * (B_FREE + 4 * c + lane));
        };
        const uint2 st = ld_relaxed_64(in->stat + (tok & ~15) + 2 * ((tok & 7) ^ ((tok >> 3) & 6)) + ((tok >> 3) & 1));
        if (has_gu) load_level(0);
        if (a == 0 && t == 0) sts32f(misc + 52 + 8 * g, bf_hi(st.x) + bf_lo(st.y));
        if (a == 0) STAMP(45);
        if (has_gu) {
            const uint32_t mean = __shfl_sync(0xffffffffu, st.x, 8 * a + 4 * (lane >> 4)), xr = xs + (2 * a + (lane >> 4)) * 1040 + 16 * (lane & 15);
            mbar_wait(abar, aph);
            aph ^= 1;
            STAMP(46);
            uint4 x[4];
#pragma unroll
            for (int j = 0; j < 4; j++) x[j] = lds128(xr + 256 * j);
#pragma unroll
            for (int j = 0; j < 4; j++) sts128(xr + 256 * j, bsub2_lo(x[j].x, mean), bsub2_lo(x[j].y, mean), bsub2_lo(x[j].z, mean), bsub2_lo(x[j].w, mean));
            if (elect_one()) mbar_expect_tx(abar, 512);
            named_sync(1, 128);
        }
        if (lane < (has_gu ? 2 : 4)) mbar_arrive_peer(mapa(bar0 + 8 * (lane & 2 ? B_XFREE : B_SFREE), lane & 1));
        if (has_gu) {
            STAMP(12);
            float gacc[8][4];
#pragma unroll
            for (int i = 0; i < 8; i++) { gacc[i][0] = gacc[i][1] = gacc[i][2] = gacc[i][3] = 0.f; }
            uint32_t* pubh = reinterpret_cast<uint32_t*>(&p.sc[0].h[b * 32 + 8 * a + (g ^ (2 * a))]) + t;
            uint32_t* cnt_h = &p.sc[t].cnt[32 * (b / 28) + 1 + ((b / 14) & 1)];
            uint32_t xb = xs + r * 1040 + m * 16;
            uint32_t xch = sb + OFF_XCH + 16 * tid, tagm = t == 3 ? 1u : 0u;
            pin(pubh); pin(cnt_h); pin(xb); pin(xch); pin(tagm);
            const float r0 = lds32f(misc + 52 + 16 * t), r1 = lds32f(misc + 60 + 16 * t);
#pragma unroll
            for (int c = 0; c < 4; c++) {
#pragma unroll
                for (int j = 0; j < 4; j++) ldsm4(af[16 + j], xb + 256 * c + 64 * j);
                if (c == 3) mbar_wait(bar0 + 8 * B_SFREE, 0);
                if (c) load_level(c);
                const bool more = __any_sync(0xffffffffu, (c ? af[6][3] | af[7][3] | af[14][3] | af[15][3] : af[16][3] | af[17][3] | af[18][3] | af[19][3]) & p.zero);
#pragma unroll 1
                do {
#pragma unroll
                    for (int i = 0; i < 16; i++) mma_v(gacc[i & 7], af[i], af[16 + ((i >> 1) & 3)][2 * (i >> 3)], af[16 + ((i >> 1) & 3)][2 * (i >> 3) + 1]);
                } while (more);
            }
            STAMP(13);
            float own[4], oth[4];
#pragma unroll
            for (int j = 0; j < 4; j++) oth[j] = (gacc[1][j] + gacc[3][j]) + (gacc[5][j] + gacc[7][j]);
            st_async128(mapa(xch, h ^ 1), __float_as_uint(oth[0]), __float_as_uint(oth[1]), __float_as_uint(oth[2]), __float_as_uint(oth[3]), mapa(abar, h ^ 1));
            STAMP(56);
#pragma unroll
            for (int j = 0; j < 4; j++) own[j] = ((gacc[0][j] + gacc[2][j]) + (gacc[4][j] + gacc[6][j])) * ((j & 1) ? r1 : r0);
            mbar_wait(abar, aph);
            aph ^= 1;
            STAMP(57);
            const float4 o4 = lds128f(xch);
            const float g0 = bf_round(fmaf(o4.x, r0, own[0])), g1 = bf_round(fmaf(o4.y, r1, own[1]));
            const float h0 = bf_round(g0 * rcpf(1.f + ex2f(-1.4426950408889634f * g0))) * bf_round(fmaf(o4.z, r0, own[2]));
            const float h1 = bf_round(g1 * rcpf(1.f + ex2f(-1.4426950408889634f * g1))) * bf_round(fmaf(o4.w, r1, own[3]));
            uint32_t hw;
            asm volatile("movmatrix.sync.aligned.m8n8.trans.b16 %0, %1;" : "=r"(hw) : "r"(pack_bf16(h0, h1)));
            hw = (hw & ~tagm) | (tag & tagm);
#pragma unroll
            for (int j = 0; j < NREP; j++) st_relaxed_32(pubh + j * (sizeof(Exchange) / 4), hw);
            if (lane < NREP) red_add(cnt_h, b % 14 < 2 ? 2 : 1);
            if (lane < 2) mbar_arrive_peer(mapa(bar0 + 8 * B_XFREE, lane));
            named_sync(1, 128);
            STAMP(14);
        }
        float dacc[4];
        const int tk = ((tid >> 1) & 6) | (tid & 1);
        uint32_t ro = 4 * tid, red = sb + tab_off(tk) + T_RED + 4 * ((tid >> 4) + 4 * (tid & 2));
        if (!has_gu) named_sync(1, 128);
        const float sg = bf_round(rcpf(1.f + ex2f(-1.4426950408889634f * __uint_as_float(unorder_key(lds32(misc + 48 + 8 * tk) >> 16) << 16))));
        pin(ro); pin(red);
        mbar_wait(bar0 + 8 * B_XFREE, 0);
        {
            uint32_t wo = (r + ((m >> 1) << 3)) * 32 + (((m & 1) ^ (r >> 2)) << 4), af[14][4];
            uint32_t ho = slot0 + 128 * t + 16 * (g ^ (2 * t));
            pin(wo); pin(ho);
            float d[7][4];
#pragma unroll
            for (int i = 0; i < 7; i++) { d[i][0] = d[i][1] = d[i][2] = d[i][3] = 0.f; }
            auto first_half = [&]() {
                mbar_wait(fbar + 32, has_gu);
#pragma unroll
                for (int j = 0; j < 14; j++) ldsm4t(af[j], slot1 + wo + j * 512);
            };
            auto fetch = [&]() {
                if (elect_one()) {
                    mbar_expect_tx(abar, 7168);
                    bulk_g2s(slot0, &in->h[(56 * h + 14 * a) * 32], 7168, abar);
                }
            };
            wait_count(&in->cnt[64 * h + 32 * (a >> 1) + 1 + (a & 1)], 64 * tag - FEW_H);
            STAMP(33);
            fetch();
            if (a == 3 && elect_one()) mbar_arrive(bar0 + 8 * B_LN);
            first_half();
            mbar_wait(abar, aph);
#pragma unroll
            for (int s = 0; s < 2; s++) {
                if (s) {
                    mbar_wait(fbar + 64, has_gu);
#pragma unroll
                    for (int j = 0; j < 14; j++) ldsm4t(af[j], slot2 + wo + j * 512);
                }
                uint4 hq[7];
#pragma unroll 1
                for (uint32_t it = 0;; spin_guard(it)) {
                    uint32_t bad = 0;
#pragma unroll
                    for (int j = 0; j < 7; j++) { hq[j] = lds128(ho + 512 * (7 * s + j)); bad = or_xor(bad, hq[j].w, tag); }
                    if (__all_sync(0xffffffffu, (bad & 1) == 0)) break;
                    fetch();
                    aph ^= 1;
                    mbar_wait(abar, aph);
                }
                if (s == 0) STAMP(15);
#pragma unroll
                for (int j = 0; j < 14; j++) {
                    const uint4 q = hq[j >> 1];
                    mma_v(d[j % 7], af[j], (j & 1) ? q.z : q.x, (j & 1) ? q.w : q.y);
                }
            }
#pragma unroll
            for (int j = 0; j < 4; j++) dacc[j] = ((d[0][j] + d[1][j]) + (d[2][j] + d[3][j])) + ((d[4][j] + d[5][j]) + d[6][j]);
        }
        STAMP(16);
        {
            st_async128(mapa(sb + OFF_XCH + 16 * tid, h ^ 1), __float_as_uint(dacc[0]), __float_as_uint(dacc[1]), __float_as_uint(dacc[2]), __float_as_uint(dacc[3]),
                        mapa(bar0 + 8 * B_RED, h ^ 1));
            sts128f(slot0 + 7680 + lane * 16, dacc);
            __syncwarp();
            if (elect_one()) mbar_arrive(bar0 + 8 * B_RED);
            mbar_wait(bar0 + 8 * B_RED, 0);
            const uint32_t b0 = sb + OFF_RING + 7680 + ro, b1 = sb + OFF_XCH + ro;
            const float y = ((lds32f(b0) + lds32f(b0 + 8192)) + (lds32f(b0 + 16384) + lds32f(b0 + 24576))) +
                            ((lds32f(b1) + lds32f(b1 + 512)) + (lds32f(b1 + 1024) + lds32f(b1 + 1536)));
            sts32f(red, bf_round(y) * sg);
            __syncwarp();
            if (elect_one()) mbar_arrive(bar0 + 8 * B_UPD);
        }
        STAMP(17); GSTAMP(29);
    }
}

typedef CUresult (*EncodeFn)(CUtensorMap*, CUtensorMapDataType, cuuint32_t, void*, const cuuint64_t*, const cuuint64_t*,
                             const cuuint32_t*, const cuuint32_t*, CUtensorMapInterleave, CUtensorMapSwizzle,
                             CUtensorMapL2promotion, CUtensorMapFloatOOBfill);

void make_map(EncodeFn enc, CUtensorMap* m, const void* ptr, uint64_t cols, uint64_t rows, uint32_t bc, uint32_t br,
              CUtensorMapSwizzle sw, CUtensorMapL2promotion pr) {
    cuuint64_t dims[2] = {cols, rows};
    cuuint64_t str[1] = {cols * 2};
    cuuint32_t box[2] = {bc, br};
    cuuint32_t es[2] = {1, 1};
    enc(m, CU_TENSOR_MAP_DATA_TYPE_BFLOAT16, 2, const_cast<void*>(ptr), dims, str, box, es, CU_TENSOR_MAP_INTERLEAVE_NONE, sw, pr,
        CU_TENSOR_MAP_FLOAT_OOB_FILL_NONE);
}
void make_perm_map(EncodeFn enc, CUtensorMap* m, const void* ptr, CUtensorMapL2promotion pr) {
    cuuint64_t dims[5] = {DM, 2, 4, 4, FF / 32};
    cuuint64_t str[4] = {DM * 2, 8 * DM * 2, 2 * DM * 2, 32 * DM * 2};
    cuuint32_t box[5] = {16, 2, 4, 4, 7};
    cuuint32_t es[5] = {1, 1, 1, 1, 1};
    enc(m, CU_TENSOR_MAP_DATA_TYPE_BFLOAT16, 5, const_cast<void*>(ptr), dims, str, box, es, CU_TENSOR_MAP_INTERLEAVE_NONE,
        CU_TENSOR_MAP_SWIZZLE_32B, pr, CU_TENSOR_MAP_FLOAT_OOB_FILL_NONE);
}
void make_tile_map(EncodeFn enc, CUtensorMap* m, const void* ptr) {
    cuuint64_t dims[4] = {DM, 4, 16, SEQ / 64};
    cuuint64_t str[3] = {16 * DM * 2, DM * 2, 64 * DM * 2};
    cuuint32_t box[4] = {16, 4, 2, 8};
    cuuint32_t es[4] = {1, 1, 1, 1};
    enc(m, CU_TENSOR_MAP_DATA_TYPE_BFLOAT16, 4, const_cast<void*>(ptr), dims, str, box, es, CU_TENSOR_MAP_INTERLEAVE_NONE,
        CU_TENSOR_MAP_SWIZZLE_32B, CU_TENSOR_MAP_L2_PROMOTION_NONE, CU_TENSOR_MAP_FLOAT_OOB_FILL_NONE);
}

}

extern "C" void kernel_launch(void* const* d_in, const int* in_sizes, int n_in, void* d_out, int out_size) {
    (void)in_sizes; (void)n_in; (void)out_size;
    static EncodeFn enc = nullptr;
    static void* scratch = nullptr;
    if (!enc) {
        void* fn = nullptr;
        cudaDriverEntryPointQueryResult q;
        cudaGetDriverEntryPoint("cuTensorMapEncodeTiled", &fn, cudaEnableDefault, &q);
        enc = (EncodeFn)fn;
        cudaGetSymbolAddress(&scratch, g_scratch);
        cudaFuncSetAttribute(fused_kernel, cudaFuncAttributeMaxDynamicSharedMemorySize, SMEM_BYTES);
    }
    Maps maps;
    make_tile_map(enc, &maps.u, d_in[0]);
    make_tile_map(enc, &maps.out, d_out);
    make_map(enc, &maps.wg, d_in[9], FF, DM, 64, 32, CU_TENSOR_MAP_SWIZZLE_128B, CU_TENSOR_MAP_L2_PROMOTION_L2_128B);
    make_map(enc, &maps.wu, d_in[10], FF, DM, 64, 32, CU_TENSOR_MAP_SWIZZLE_128B, CU_TENSOR_MAP_L2_PROMOTION_L2_128B);
    make_perm_map(enc, &maps.wd, d_in[11], CU_TENSOR_MAP_L2_PROMOTION_L2_64B);
    Ptrs p;
    p.sc = (Exchange*)scratch;
    p.u = (const __nv_bfloat16*)d_in[0];
    p.logA = (const __nv_bfloat16*)d_in[1];
    p.Aim = (const __nv_bfloat16*)d_in[2];
    p.Cre = (const __nv_bfloat16*)d_in[3];
    p.Cim = (const __nv_bfloat16*)d_in[4];
    p.ldt = (const __nv_bfloat16*)d_in[5];
    p.dsk = (const __nv_bfloat16*)d_in[6];
    p.wr = (const __nv_bfloat16*)d_in[8];
    p.out = (__nv_bfloat16*)d_out;
    p.zero = 0;
    fused_kernel<<<NCTA, NTHR, SMEM_BYTES, cudaStreamPerThread>>>(p, maps);
}
```

```cpp
#include <cuda_runtime.h>
#include <cuda_bf16.h>
#include <cuda_fp16.h>
#include <cuda.h>
#include <stdint.h>

namespace {

constexpr int SEQ = 2048, DM = 1024, NMODE = 128, FF = 3584;
constexpr int NCTA = 128, NTHR = 512;
constexpr int GU_CTAS = 112;
constexpr int NREP = 4;

constexpr int OFF_XT = 0;
constexpr int OFF_RING = 65536;
constexpr int OFF_PRIV = OFF_RING + 65536;
constexpr int OFF_VT = OFF_PRIV + 65536;
constexpr int VT_PAD = 32, VT_PLANE = VT_PAD + 2048, VT_PITCH = 2 * VT_PLANE, ROW_PITCH = 2064;
constexpr int OFF_BAR = OFF_VT + 8 * VT_PITCH;
constexpr int OFF_MISC = OFF_BAR + 384;
constexpr int OFF_XCH = OFF_MISC + 112;
constexpr int SMEM_BYTES = OFF_XCH + 2048;
constexpr int OFF_LN = OFF_RING + 7 * 8192;
constexpr int OFF_ST = OFF_RING + 6 * 8192;
static_assert(SMEM_BYTES <= 232448, "shared memory");

constexpr int B_ROW = 0, B_XT = 4, B_V = 5, B_LN = 6, B_SFREE = 7, B_XFREE = 8, B_OWN = 9, B_RED = 10, B_UPD = 11, B_ST = 12, B_RECV = 16, B_FREE = 20, B_FULL = 32, B_AUX = 44, NBAR = 48;

constexpr int T_DENSE = 60;
constexpr int T_PATCH = 2208;
constexpr int T_R2 = 2368;
constexpr int T_R3 = 3296;

constexpr int T_RED = 4032;
__device__ __forceinline__ bool slot_priv(int s) { return (uint32_t)(s - 6) < 4u; }
__device__ __forceinline__ uint32_t slot_off(int s) { return slot_priv(s) ? OFF_PRIV + 4096 + (s & 3) * 16384 : OFF_RING + (s < 6 ? s : s - 4) * 8192; }
__device__ __forceinline__ uint32_t tab_off(int w) { return OFF_PRIV + w * 8192 + (w & 1) * 4096; }

constexpr uint32_t SPIN_LIMIT = 1u << 20;
#define BB_UNROLL 2
constexpr int kBbUnroll = BB_UNROLL;
#define ST_T0 2200
#define ST_PER 286
#define ST_PER2 320
#define LN_PAUSE 0xf0
#define FEW_ST 10
#define FEW_H 24

struct Exchange {
    uint2 stat[SEQ];
    uint4 h[GU_CTAS * 32];
    uint32_t cnt[4 * 32];
};
__device__ __align__(128) Exchange g_scratch[NREP];

struct Ptrs {
    const __nv_bfloat16 *logA, *Aim, *Cre, *Cim, *ldt, *u;
    const __nv_bfloat16 *dsk, *wr;
    Exchange* sc;
    __nv_bfloat16* out;
    uint32_t zero;
};
struct Maps {
    CUtensorMap u, out, wg, wu, wd;
};

#define STAMP(i) do { } while (0)
#define GSTAMP(i) do { } while (0)

__device__ __forceinline__ uint32_t s_u32(const void* p) { return (uint32_t)__cvta_generic_to_shared(p); }
__device__ __forceinline__ void mbar_init(uint32_t b, uint32_t n) {
    asm volatile("mbarrier.init.shared::cta.b64 [%0], %1;" ::"r"(b), "r"(n) : "memory");
}
__device__ __forceinline__ void mbar_expect_tx(uint32_t b, uint32_t bytes) {
    asm volatile("mbarrier.arrive.expect_tx.shared::cta.b64 _, [%0], %1;" ::"r"(b), "r"(bytes) : "memory");
}
__device__ __forceinline__ void mbar_arrive(uint32_t b) {
    asm volatile("mbarrier.arrive.shared::cta.b64 _, [%0];" ::"r"(b) : "memory");
}
__device__ __forceinline__ void mbar_arrive_n(uint32_t b, uint32_t n) {
    asm volatile("mbarrier.arrive.shared::cta.b64 _, [%0], %1;" ::"r"(b), "r"(n) : "memory");
}
__device__ __forceinline__ void mbar_arrive_peer(uint32_t b_cluster) {
    asm volatile("mbarrier.arrive.relaxed.cluster.shared::cluster.b64 _, [%0];" ::"r"(b_cluster) : "memory");
}
__device__ __forceinline__ void mbar_wait(uint32_t b, uint32_t parity) {
    asm volatile("{\n\t.reg .pred p;\n\t.reg .u32 c;\n\tmov.u32 c, 0;\n"
                 "W:\n\tmbarrier.try_wait.parity.shared::cta.b64 p, [%0], %1;\n\t@p bra D;\n\t"
                 "add.u32 c, c, 1;\n\tsetp.lt.u32 p, c, 1048576;\n\t@p bra W;\n\ttrap;\nD:\n\t}"
                 ::"r"(b), "r"(parity) : "memory");
}
__device__ __forceinline__ bool elect_one() {
    uint32_t p;
    asm volatile("{ .reg .pred P; elect.sync _|P, 0xffffffff; selp.u32 %0, 1, 0, P; }" : "=r"(p));
    return p != 0;
}
__device__ __forceinline__ uint32_t mapa(uint32_t a, uint32_t rank) {
    uint32_t r;
    asm("mapa.shared::cluster.u32 %0, %1, %2;" : "=r"(r) : "r"(a), "r"(rank));
    return r;
}
__device__ __forceinline__ void cluster_arrive() { asm volatile("barrier.cluster.arrive.relaxed.aligned;" ::: "memory"); }
__device__ __forceinline__ void cluster_wait() { asm volatile("barrier.cluster.wait.acquire.aligned;" ::: "memory"); }
__device__ __forceinline__ void tma_load_2d(uint32_t dst, const CUtensorMap* m, int c0, int c1, uint32_t bar) {
    asm volatile("cp.async.bulk.tensor.2d.shared::cluster.global.mbarrier::complete_tx::bytes [%0], [%1, {%3, %4}], [%2];"
                 ::"r"(dst), "l"(m), "r"(bar), "r"(c0), "r"(c1) : "memory");
}
__device__ __forceinline__ void tma_load_perm(uint32_t dst, const CUtensorMap* m, int c0, int blk, uint32_t bar) {
    asm volatile("cp.async.bulk.tensor.5d.shared::cluster.global.mbarrier::complete_tx::bytes [%0], [%1, {%3, %4, %4, %4, %5}], [%2];"
                 ::"r"(dst), "l"(m), "r"(bar), "r"(c0), "r"(0), "r"(blk) : "memory");
}
__device__ __forceinline__ void tma_load_tile(uint32_t dst, const CUtensorMap* m, int c0, int c2, int c3, uint32_t bar) {
    asm volatile("cp.async.bulk.tensor.4d.shared::cluster.global.mbarrier::complete_tx::bytes.multicast::cluster [%0], [%1, {%3, %4, %5, %6}], [%2], %7;"
                 ::"r"(dst), "l"(m), "r"(bar), "r"(c0), "r"(0), "r"(c2), "r"(c3), "h"((uint16_t)3) : "memory");
}
__device__ __forceinline__ void tma_store_tile(const CUtensorMap* m, uint32_t src, int c0, int c2, int c3) {
    asm volatile("cp.async.bulk.tensor.4d.global.shared::cta.bulk_group [%0, {%2, %3, %4, %5}], [%1];"
                 ::"l"(m), "r"(src), "r"(c0), "r"(0), "r"(c2), "r"(c3) : "memory");
    asm volatile("cp.async.bulk.commit_group;" ::: "memory");
}
__device__ __forceinline__ void bulk_g2s(uint32_t dst, const void* src, uint32_t bytes, uint32_t bar) {
    asm volatile("cp.async.bulk.shared::cluster.global.mbarrier::complete_tx::bytes [%0], [%1], %2, [%3];"
                 ::"r"(dst), "l"(src), "r"(bytes), "r"(bar) : "memory");
}
__device__ __forceinline__ void st_async128(uint32_t dst_cluster, uint32_t x, uint32_t y, uint32_t z, uint32_t w, uint32_t bar_cluster) {
    asm volatile("st.async.weak.shared::cluster.mbarrier::complete_tx::bytes.v4.b32 [%0], {%1,%2,%3,%4}, [%5];"
                 ::"r"(dst_cluster), "r"(x), "r"(y), "r"(z), "r"(w), "r"(bar_cluster) : "memory");
}
__device__ __forceinline__ void fence_async() { asm volatile("fence.proxy.async.shared::cta;" ::: "memory"); }
__device__ __forceinline__ void named_sync(int id, int n) { asm volatile("bar.sync %0, %1;" ::"r"(id), "r"(n) : "memory"); }

__device__ __forceinline__ void ldsm4(uint32_t* r, uint32_t a) {
    asm volatile("ldmatrix.sync.aligned.m8n8.x4.shared.b16 {%0,%1,%2,%3}, [%4];"
                 : "=r"(r[0]), "=r"(r[1]), "=r"(r[2]), "=r"(r[3]) : "r"(a));
}
__device__ __forceinline__ void ldsm4t(uint32_t* r, uint32_t a) {
    asm volatile("ldmatrix.sync.aligned.m8n8.x4.trans.shared.b16 {%0,%1,%2,%3}, [%4];"
                 : "=r"(r[0]), "=r"(r[1]), "=r"(r[2]), "=r"(r[3]) : "r"(a));
}
__device__ __forceinline__ void stsm4t(uint32_t a, uint32_t x, uint32_t y, uint32_t z, uint32_t w) {
    asm volatile("stmatrix.sync.aligned.m8n8.x4.trans.shared.b16 [%0], {%1,%2,%3,%4};"
                 ::"r"(a), "r"(x), "r"(y), "r"(z), "r"(w) : "memory");
}
__device__ __forceinline__ uint32_t lds32(uint32_t a) { uint32_t v; asm volatile("ld.shared.u32 %0, [%1];" : "=r"(v) : "r"(a)); return v; }
__device__ __forceinline__ float lds32f(uint32_t a) { float v; asm volatile("ld.shared.f32 %0, [%1];" : "=f"(v) : "r"(a)); return v; }
__device__ __forceinline__ uint2 lds64(uint32_t a) { uint2 v; asm volatile("ld.shared.v2.u32 {%0,%1}, [%2];" : "=r"(v.x), "=r"(v.y) : "r"(a)); return v; }
__device__ __forceinline__ uint4 lds128(uint32_t a) {
    uint4 v; asm volatile("ld.shared.v4.u32 {%0,%1,%2,%3}, [%4];" : "=r"(v.x), "=r"(v.y), "=r"(v.z), "=r"(v.w) : "r"(a)); return v;
}
__device__ __forceinline__ uint4 lds128v(uint32_t a) {
    uint4 v; asm volatile("ld.volatile.shared.v4.u32 {%0,%1,%2,%3}, [%4];" : "=r"(v.x), "=r"(v.y), "=r"(v.z), "=r"(v.w) : "r"(a)); return v;
}
__device__ __forceinline__ uint32_t or_xor(uint32_t a, uint32_t b, uint32_t c) {
    uint32_t r; asm("lop3.b32 %0, %1, %2, %3, 0xf6;" : "=r"(r) : "r"(a), "r"(b), "r"(c)); return r;
}
__device__ __forceinline__ float4 lds128f(uint32_t a) {
    float4 v; asm volatile("ld.shared.v4.f32 {%0,%1,%2,%3}, [%4];" : "=f"(v.x), "=f"(v.y), "=f"(v.z), "=f"(v.w) : "r"(a)); return v;
}
__device__ __forceinline__ void sts32(uint32_t a, uint32_t v) { asm volatile("st.shared.u32 [%0], %1;" ::"r"(a), "r"(v) : "memory"); }
__device__ __forceinline__ void sts32f(uint32_t a, float v) { asm volatile("st.shared.f32 [%0], %1;" ::"r"(a), "f"(v) : "memory"); }
__device__ __forceinline__ void sts64(uint32_t a, uint32_t x, uint32_t y) { asm volatile("st.shared.v2.u32 [%0], {%1,%2};" ::"r"(a), "r"(x), "r"(y) : "memory"); }
__device__ __forceinline__ void sts64f(uint32_t a, float x, float y) { asm volatile("st.shared.v2.f32 [%0], {%1,%2};" ::"r"(a), "f"(x), "f"(y) : "memory"); }
__device__ __forceinline__ void sts128(uint32_t a, uint32_t x, uint32_t y, uint32_t z, uint32_t w) {
    asm volatile("st.shared.v4.u32 [%0], {%1,%2,%3,%4};" ::"r"(a), "r"(x), "r"(y), "r"(z), "r"(w) : "memory");
}
__device__ __forceinline__ void sts128f(uint32_t a, const float* v) {
    asm volatile("st.shared.v4.f32 [%0], {%1,%2,%3,%4};" ::"r"(a), "f"(v[0]), "f"(v[1]), "f"(v[2]), "f"(v[3]) : "memory");
}
__device__ __forceinline__ uint4 ldg128(const void* p) {
    uint4 v; asm volatile("ld.global.nc.L1::no_allocate.v4.u32 {%0,%1,%2,%3}, [%4];" : "=r"(v.x), "=r"(v.y), "=r"(v.z), "=r"(v.w) : "l"(p)); return v;
}
__device__ __forceinline__ uint2 ldg64(const void* p) {
    uint2 v; asm volatile("ld.global.nc.L1::no_allocate.v2.u32 {%0,%1}, [%2];" : "=r"(v.x), "=r"(v.y) : "l"(p)); return v;
}
__device__ __forceinline__ uint32_t ldg16(const void* p) {
    uint32_t v; asm volatile("ld.global.nc.u16 %0, [%1];" : "=r"(v) : "l"(p)); return v;
}
__device__ __forceinline__ uint2 ld_relaxed_64(const void* p) {
    uint2 v; asm volatile("ld.relaxed.gpu.global.v2.u32 {%0,%1}, [%2];" : "=r"(v.x), "=r"(v.y) : "l"(p) : "memory"); return v;
}
__device__ __forceinline__ uint32_t ld_relaxed_32(const void* p) {
    uint32_t v; asm volatile("ld.relaxed.gpu.global.u32 %0, [%1];" : "=r"(v) : "l"(p) : "memory"); return v;
}
__device__ __forceinline__ void st_relaxed_64(void* p, uint32_t x, uint32_t y) {
    asm volatile("st.relaxed.gpu.global.v2.u32 [%0], {%1,%2};" ::"l"(p), "r"(x), "r"(y) : "memory");
}
__device__ __forceinline__ void st_relaxed_32(void* p, uint32_t v) {
    asm volatile("st.relaxed.gpu.global.u32 [%0], %1;" ::"l"(p), "r"(v) : "memory");
}
__device__ __forceinline__ void red_add(void* p, uint32_t v) { asm volatile("red.relaxed.gpu.global.add.u32 [%0], %1;" ::"l"(p), "r"(v) : "memory"); }
__device__ __forceinline__ uint32_t now_ns() { uint32_t t; asm volatile("mov.u32 %0, %%globaltimer_lo;" : "=r"(t) :: "memory"); return t; }
__device__ __forceinline__ void sleep_until(uint32_t t) {
#pragma unroll 1
    for (int left; (left = (int)(t - now_ns())) > 0;) __nanosleep(left >> 1);
}
__device__ __forceinline__ void spin_guard(uint32_t& it) { if (++it > SPIN_LIMIT) __trap(); }
__device__ __forceinline__ void wait_count(const uint32_t* p, uint32_t target) {
#pragma unroll 1
    for (uint32_t it = 0; __any_sync(0xffffffffu, (int)(ld_relaxed_32(p) - target) < 0); spin_guard(it)) { }
}
__device__ __forceinline__ void mma_bf16_k8(float* c, uint32_t a0, uint32_t a1, uint32_t b0) {
    asm("mma.sync.aligned.m16n8k8.row.col.f32.bf16.bf16.f32 {%0,%1,%2,%3}, {%4,%5}, {%6}, {%0,%1,%2,%3};"
                 : "+f"(c[0]), "+f"(c[1]), "+f"(c[2]), "+f"(c[3]) : "r"(a0), "r"(a1), "r"(b0));
}
__device__ __forceinline__ void mma_v(float* c, const uint32_t* a, uint32_t b0, uint32_t b1) {
    asm volatile("mma.sync.aligned.m16n8k16.row.col.f32.bf16.bf16.f32 {%0,%1,%2,%3}, {%4,%5,%6,%7}, {%8,%9}, {%0,%1,%2,%3};"
                 : "+f"(c[0]), "+f"(c[1]), "+f"(c[2]), "+f"(c[3]) : "r"(a[0]), "r"(a[1]), "r"(a[2]), "r"(a[3]), "r"(b0), "r"(b1));
}
__device__ __forceinline__ void mma_bf16_z(float* c, uint32_t a0, uint32_t a1, uint32_t a2, uint32_t a3, uint32_t b0, uint32_t b1) {
    asm volatile("mma.sync.aligned.m16n8k16.row.col.f32.bf16.bf16.f32 {%0,%1,%2,%3}, {%4,%5,%6,%7}, {%8,%9}, {%10,%10,%10,%10};"
        : "=f"(c[0]), "=f"(c[1]), "=f"(c[2]), "=f"(c[3]) : "r"(a0), "r"(a1), "r"(a2), "r"(a3), "r"(b0), "r"(b1), "f"(0.f));
}
__device__ __forceinline__ void mma_f16(float* c, uint32_t a0, uint32_t a1, uint32_t a2, uint32_t a3, uint32_t b0, uint32_t b1) {
    asm("mma.sync.aligned.m16n8k16.row.col.f32.f16.f16.f32 {%0,%1,%2,%3}, {%4,%5,%6,%7}, {%8,%9}, {%0,%1,%2,%3};"
                 : "+f"(c[0]), "+f"(c[1]), "+f"(c[2]), "+f"(c[3]) : "r"(a0), "r"(a1), "r"(a2), "r"(a3), "r"(b0), "r"(b1));
}
__device__ __forceinline__ uint32_t pack_bf16(float lo, float hi) {
    uint32_t r; asm("cvt.rn.bf16x2.f32 %0, %1, %2;" : "=r"(r) : "f"(hi), "f"(lo)); return r;
}
__device__ __forceinline__ uint32_t pack_v(float lo, float hi) {
    uint32_t r; asm volatile("cvt.rn.bf16x2.f32 %0, %1, %2;" : "=r"(r) : "f"(hi), "f"(lo)); return r;
}
__device__ __forceinline__ uint32_t pack_w(float lo, float hi) {
    uint32_t r; asm volatile("cvt.rn.satfinite.bf16x2.f32 %0, %1, %2;" : "=r"(r) : "f"(hi), "f"(lo)); return r;
}
template <int N> __device__ __forceinline__ uint32_t after_all(const uint32_t (&f)[N][4], uint32_t zero) {
    uint32_t d[3] = {0, 0, 0};
#pragma unroll
    for (int i = 0; i < N; i++) d[i % 3] |= f[i][3];
    return (d[0] | d[1] | d[2]) & zero;
}
__device__ __forceinline__ void pin(uint32_t& x) { asm volatile("" : "+r"(x)); }
template <class T> __device__ __forceinline__ void pin(T*& x) { asm volatile("" : "+l"(x)); }
__device__ __forceinline__ uint32_t pack_f16(float lo, float hi) {
    uint32_t r; asm("cvt.rn.f16x2.f32 %0, %1, %2;" : "=r"(r) : "f"(hi), "f"(lo)); return r;
}
__device__ __forceinline__ float bf_lo(uint32_t v) { return __uint_as_float(v << 16); }
__device__ __forceinline__ float bf_hi(uint32_t v) { return __uint_as_float(v & 0xffff0000u); }
__device__ __forceinline__ float bf_round(float x) { return __uint_as_float(pack_bf16(0.f, x)); }
__device__ __forceinline__ uint32_t badd2(uint32_t a, uint32_t b) { uint32_t r; asm("add.rn.bf16x2 %0, %1, %2;" : "=r"(r) : "r"(a), "r"(b)); return r; }
__device__ __forceinline__ uint32_t bsub2_lo(uint32_t a, uint32_t b) {
    uint32_t r; asm("{ .reg .b16 m, h; .reg .b32 m2; mov.b32 {m, h}, %2; mov.b32 m2, {m, m}; sub.rn.bf16x2 %0, %1, m2; }" : "=r"(r) : "r"(a), "r"(b)); return r;
}
__device__ __forceinline__ uint32_t bmax2(uint32_t a, uint32_t b) { uint32_t r; asm("max.bf16x2 %0, %1, %2;" : "=r"(r) : "r"(a), "r"(b)); return r; }
__device__ __forceinline__ uint32_t normalize2(uint32_t x, uint32_t s0, uint32_t s1) {
    uint32_t r;
    asm("{ .reg .b16 m, h, l, k; .reg .b32 m2, h2, l2, d, t;\n\t"
        "mov.b32 {m, h}, %2; mov.b32 {l, k}, %3; mov.b32 m2, {m, m}; mov.b32 h2, {h, h}; mov.b32 l2, {l, l};\n\t"
        "sub.rn.bf16x2 d, %1, m2; mul.rn.bf16x2 t, d, l2; fma.rn.bf16x2 %0, d, h2, t; }" : "=r"(r) : "r"(x), "r"(s0), "r"(s1));
    return r;
}
__device__ __forceinline__ float rcpf(float x) { float r; asm("rcp.approx.ftz.f32 %0, %1;" : "=f"(r) : "f"(x)); return r; }
__device__ __forceinline__ float sqrtaf(float x) { float r; asm("sqrt.approx.ftz.f32 %0, %1;" : "=f"(r) : "f"(x)); return r; }
__device__ __forceinline__ float ex2f(float x) { float r; asm("ex2.approx.ftz.f32 %0, %1;" : "=f"(r) : "f"(x)); return r; }

__device__ __forceinline__ int tok_off(int t) { return ((t >> 3) & 1) * VT_PLANE + (t >> 4) * 16 + (t & 7) * 2; }

__device__ __forceinline__ uint32_t unorder_key(uint32_t k16) { return k16 ^ ((k16 & 0x8000u) ? 0x8000u : 0xffffu); }

struct cplx { float r, i; };
struct hc { uint32_t r, i; };
template <bool CONJ> __device__ __forceinline__ cplx csq(cplx a) {
    float im;
    asm("{ .reg .f32 t; mul.ftz.f32 t, %1, %2; mul.ftz.f32 %0, t, 0f40000000; }" : "=f"(im) : "f"(CONJ ? -a.r : a.r), "f"(a.i));
    return {fmaf(a.r, a.r, -(a.i * a.i)), im};
}
__device__ __forceinline__ cplx cexpp(float a2, float ai) {
    float m = ex2f(a2), s, c;
    __sincosf(ai, &s, &c);
    return {m * c, m * s};
}
__device__ __forceinline__ __half2 as_h2(uint32_t x) { return *reinterpret_cast<__half2*>(&x); }
__device__ __forceinline__ uint32_t as_u(__half2 x) { return *reinterpret_cast<uint32_t*>(&x); }
__device__ __forceinline__ hc hmul(hc a, hc b) {
    return {as_u(__hfma2(as_h2(a.r), as_h2(b.r), __hneg2(__hmul2(as_h2(a.i), as_h2(b.i))))),
            as_u(__hfma2(as_h2(a.r), as_h2(b.i), __hmul2(as_h2(a.i), as_h2(b.r))))};
}
__device__ __forceinline__ hc hpack(cplx a, cplx b) { return {pack_f16(a.r, b.r), pack_f16(a.i, b.i)}; }
__device__ __forceinline__ void sts16(uint32_t a, uint32_t v) { asm volatile("st.shared.u16 [%0], %1;" ::"r"(a), "r"(v) : "memory"); }

struct KgenAddr {
    uint32_t l, h, m2, m3, m4, z, w, wz;
    __device__ __forceinline__ KgenAddr(uint32_t scr, int lane) {
        const int g = lane >> 2, t = lane & 3;
        const uint32_t rec = scr + t * 480;
        l = rec + 16 * g; h = rec + 128 + 8 * g; m2 = rec + 192 + 8 * (g & 1); m3 = rec + 208 + 4 * (g & 2); m4 = rec + 224 + 2 * (g & 4);
        z = scr + 7680 + 16 * t; w = scr + 240 * lane; wz = scr + 7680 + 8 * lane;
        pin(l); pin(h); pin(m2); pin(m3); pin(m4); pin(z); pin(w); pin(wz);
    }
    __device__ __forceinline__ uint32_t any() const { return (l | h | m2) | (m3 | m4 | z) | (w | wz); }
};
template <class Hook, class Hook2>
__device__ __forceinline__ void kgen(const KgenAddr& ad, uint32_t tab, int lane, uint2 la, uint2 aim, uint2 cre, uint2 cim, float dt, float skip, int dch, Hook main_done, Hook2 half_done) {
    const int g = lane >> 2, t = lane & 3;
    const float dt2 = 2.f * dt;
    const uint32_t am = bmax2(bmax2(cre.x & 0x7fff7fffu, cre.y & 0x7fff7fffu), bmax2(cim.x & 0x7fff7fffu, cim.y & 0x7fff7fffu));
    const float mx = dt2 * fmaxf(bf_lo(am), bf_hi(am));
    const uint32_t eb = min(max(__reduce_max_sync(0xffffffffu, __float_as_uint(mx)) >> 23, 1u), 252u);
    const float cscale = dt2 * __uint_as_float((253u - eb) << 23);
    const float scale_inv = __uint_as_float((eb + 1u) << 23);
    float k0 = (bf_lo(cre.x) + bf_hi(cre.x)) + (bf_lo(cre.y) + bf_hi(cre.y));
#pragma unroll
    for (int o = 16; o; o >>= 1) k0 += __shfl_xor_sync(0xffffffffu, k0, o);
    const float ndt = -1.4426950408889634f * dt;
    STAMP(40);

    float acc[5][4];
#pragma unroll
    for (int i = 0; i < 5; i++) { acc[i][0] = acc[i][1] = acc[i][2] = acc[i][3] = 0.f; }

#pragma unroll kBbUnroll
    for (int bb = 0; bb < 2; bb++) {
        cplx z[2][11], cz[2];
#pragma unroll
        for (int e = 0; e < 2; e++) {
            const float lg = e ? bf_hi(la.x) : bf_lo(la.x), ai = (e ? bf_hi(aim.x) : bf_lo(aim.x)) * dt;
            const float cr = (e ? bf_hi(cre.x) : bf_lo(cre.x)) * cscale, ci = (e ? bf_hi(cim.x) : bf_lo(cim.x)) * cscale;
            const float a2 = bf_round(ex2f(lg * 1.4426950408889634f)) * ndt;
            z[e][0] = cexpp(a2, ai);
            z[e][5] = cexpp(a2 * 32.f, ai * -32.f);
#pragma unroll
            for (int i = 1; i < 11; i++) if (i != 5) z[e][i] = (i == 3 || i == 7) ? csq<true>(z[e][i - 1]) : csq<false>(z[e][i - 1]);
            cz[e] = {fmaf(cr, z[e][0].r, -(ci * z[e][0].i)), fmaf(cr, z[e][0].i, ci * z[e][0].r)};
        }
        la.x = la.y; aim.x = aim.y; cre.x = cre.y; cim.x = cim.y;
        const hc z1 = hpack(z[0][0], z[1][0]), z2 = hpack(z[0][1], z[1][1]), z4 = hpack(z[0][2], z[1][2]);
        hc L[8], H[8];
        L[1] = hpack(z[0][3], z[1][3]); L[2] = hpack(z[0][4], z[1][4]); L[4] = hpack(z[0][5], z[1][5]);
        const hc y64 = hpack(z[0][6], z[1][6]), z128 = hpack(z[0][7], z[1][7]), z256 = hpack(z[0][8], z[1][8]);
        const hc z512 = hpack(z[0][9], z[1][9]), z1024 = hpack(z[0][10], z[1][10]);
        H[0] = hpack(cz[0], cz[1]);
        H[1] = hmul(H[0], z1); H[2] = hmul(H[0], z2); H[3] = hmul(H[1], z2);
        L[3] = hmul(L[1], L[2]);
#pragma unroll
        for (int i = 0; i < 4; i++) { H[4 + i] = hmul(H[i], z4); if (i) L[4 + i] = hmul(L[i], L[4]); }
        __syncwarp();
        sts128(ad.w, 0x3c003c00u, y64.r, 0u, y64.i);
#pragma unroll
        for (int i = 1; i < 8; i++) { const hc q = hmul(L[i], y64); sts128(ad.w + 16 * i, L[i].r, q.r, L[i].i, q.i); }
#pragma unroll
        for (int i = 0; i < 4; i++) sts128(ad.w + 128 + 16 * i, H[2 * i].r, H[2 * i].i, H[2 * i + 1].r, H[2 * i + 1].i);
        {
            const hc a = hmul(z256, z1), b = hmul(z256, z128), c = hmul(z256, z2), d = hmul(z512, z4);
            sts128(ad.w + 192, a.r, a.i, b.r, b.i);
            sts128(ad.w + 208, c.r, c.i, z512.r, z512.i);
            sts128(ad.w + 224, d.r, d.i, z1024.r, z1024.i);
            sts64(ad.wz, z128.r, z128.i);
        }
        __syncwarp();

#pragma unroll
        for (int k2 = 0; k2 < 4; k2++) {
#pragma unroll
            for (uint32_t s = 0; s < 2; s++) {
                const uint32_t o = k2 * 1920 + s * 240;
                const uint4 l = lds128(ad.l + o);
                const uint2 h0 = lds64(ad.h + o), m2 = lds64(ad.m2 + o), m3 = lds64(ad.m3 + o), m4 = lds64(ad.m4 + o), mz = lds64(ad.z + k2 * 64 + s * 8);
                const hc H0 = {h0.x, h0.y};
                const hc H1 = hmul(H0, {mz.x, mz.y}), H2 = hmul(H0, {m2.x, m2.y}), H3 = hmul(H2, {m3.x, m3.y}), H4 = hmul(H3, {m4.x, m4.y});
                mma_f16(acc[0], l.x, l.y, l.z, l.w, H0.r, H0.i);
                mma_f16(acc[1], l.x, l.y, l.z, l.w, H1.r, H1.i);
                mma_f16(acc[2], l.x, l.y, l.z, l.w, H2.r, H2.i);
                mma_f16(acc[3], l.x, l.y, l.z, l.w, H3.r, H3.i);
                mma_f16(acc[4], l.x, l.y, l.z, l.w, H4.r, H4.i);
            }
        }

        if (bb == 0) half_done();
    }
    __syncwarp();
    main_done();

#pragma unroll
    for (int i = 0; i < 4; i++) sts128(tab + 2048 + 512 * i + 16 * lane, 0, 0, 0, 0);
    if (lane < 15) sts32(tab + 4 * lane, 0);
    __syncwarp();
    const uint32_t d0 = tab + T_DENSE + 4 + 8 * lane, src = (lane + 31) & 31;
    const uint32_t p0 = pack_bf16(fmaf(k0, dt2, skip), 0.f);
    uint32_t prev = p0;
#pragma unroll
    for (int i = 0; i < 4; i++) {
        const uint32_t pk = pack_bf16(acc[i >> 1][2 * (i & 1) + 1] * scale_inv, acc[i >> 1][2 * (i & 1)] * scale_inv);
        sts64(d0 + 256 * i, __byte_perm(pk, __shfl_sync(0xffffffffu, lane == 31 ? prev : pk, src), 0x5432), pk);
        prev = pk;
    }
    const uint32_t w0 = pack_bf16(acc[2][0] * scale_inv, acc[2][1] * scale_inv), w1 = pack_bf16(acc[2][2] * scale_inv, acc[2][3] * scale_inv);
    const uint32_t sa = (lane & 1) ? 0x5410u : 0x5454u, sb2 = (lane & 1) ? 0x1010u : 0x5410u;
#pragma unroll
    for (int hf = 0; hf < 2; hf++) {
        const uint32_t w = hf ? w1 : w0;
        const uint32_t pv = __shfl_sync(0xffffffffu, lane != 31 ? w : hf ? w0 : __byte_perm(prev, w1, 0x5410), src);
        sts64(d0 + 1024 + 256 * hf, __byte_perm(w, pv, sa), __byte_perm(w, pv, sb2));
        sts64(d0 + 1536 + 256 * hf, __byte_perm(w, pv, sa + 0x2222u), __byte_perm(w, pv, sb2 + 0x2222u));
    }
    const uint32_t d3 = tab + T_R2 + 160 + 320 * (t & 1) + 16 * (g >> 1) + 8 * (g & 1) + 4 * (t >> 1), d3n = d3 + (g >= 6 ? 32 : 0);
    const uint32_t d4 = tab + T_R3 + 80 + 160 * t + 4 * g, d4n = d4 + (g >= 6 ? 16 : 0);
    uint32_t p3;
#pragma unroll
    for (int hf = 0; hf < 2; hf++)
#pragma unroll
        for (int e = 0; e < 2; e++) {
            const float v3 = acc[3][2 * hf + e] * scale_inv;
            const uint32_t p4 = pack_bf16(acc[4][2 * hf + e] * scale_inv, 0.f);
            p3 = pack_bf16(v3, v3);
            sts16(d3 + 64 * hf + 160 * e, p3);
            sts16((hf ? d3n : d3) + 64 * hf + 160 * e + 18, p3);
            sts16(d4 + 32 * hf + 80 * e, p4);
            sts16((hf ? d4n : d4) + 32 * hf + 80 * e + 10, p4);
        }
    if (lane == 31) {
        const uint32_t k512 = __byte_perm(w1, 0, 0x3232);
        sts32(tab + T_DENSE, p0);
        sts64(tab + T_DENSE + 4 * 513, k512, k512); sts16(tab + T_DENSE + 4 * 515 + 2, k512);
        sts16(tab + T_PATCH + 4 * 17, p3); sts32(tab + T_PATCH + 4 * 18, p3); sts16(tab + T_PATCH + 4 * 19 + 2, p3);
    }
    __syncwarp();
}

__device__ __forceinline__ void load_toep(uint32_t* a, uint32_t p, uint32_t pz) {
    a[0] = lds32(p); a[1] = lds32(p + 32); a[2] = lds32(pz - 32); a[3] = lds32(pz);
}
template <int F>
__device__ __forceinline__ void ffa_step(float (&acc)[16][4], float (&W)[8][4], uint32_t (&R)[8][4], uint32_t (&A)[4][4],
                                         uint32_t va, uint32_t vn, uint32_t vmin, uint32_t pb, uint32_t pz) {
    constexpr int S = F ^ 1;
    auto load = [&](int sh) {
#pragma unroll
        for (int i = S; i < 8; i += 2) ldsm4(R[i], i == 0 ? max(sh ? vn : va, vmin) : (sh ? vn : va) + i * 128);
#pragma unroll
        for (int k = S; k < 4; k += 2) load_toep(A[k], pb + 64 * sh + k * 512, pz + 64 * sh + k * 512);
    };
    auto prod = [&](int par, int dst) {
#pragma unroll
        for (int k = 0; k < 2; k++)
#pragma unroll
            for (int m = k; m < 8; m++) {
                const uint32_t* x = &R[2 * ((m - k) & 3) + par][2 * ((m - k) >> 2)];
                mma_v(dst == 1 ? W[m] : acc[2 * m + (dst >> 1)], A[2 * k + par], x[0], x[1]);
            }
    };
    load(0);
    prod(F, F);
    prod(S, S);
#pragma unroll
    for (int i = 0; i < 8; i++) A[(i >> 2) * 2 + F][i & 3] = badd2(A[(i >> 2) * 2][i & 3], A[(i >> 2) * 2 + 1][i & 3]);
#pragma unroll
    for (int i = 0; i < 16; i++) R[(i >> 2) * 2 + F][i & 3] = badd2(R[(i >> 2) * 2][i & 3], R[(i >> 2) * 2 + 1][i & 3]);
    load(1);
    prod(F, 2);
}
__device__ __forceinline__ uint32_t dense_phase(float (&acc)[16][4], float (&W)[8][4], uint32_t (&A)[4][4], uint32_t vmin, uint32_t va, uint32_t pb, uint32_t zero, int lane,
                                                uint32_t vbar, uint32_t sbar) {
    uint32_t R[8][4], pz = pb + zero;
#pragma unroll 1
    for (int rho = 0; rho < 8; rho += 2) {
        if (rho == (int)zero) {
            mbar_wait(vbar, 0);
            STAMP(3);
#pragma unroll
            for (int i = 0; i < 8; i += 2) ldsm4(R[i], va + i * 128);
        }
        ffa_step<0>(acc, W, R, A, va, va - 16, vmin, pb, pz);
        ffa_step<1>(acc, W, R, A, va - 16, rho == 6 ? va + 96 : va - 32, vmin, pb + 64, pz + 64);
        pb += 128; pz += 128; va -= 32;
    }
    mbar_wait(sbar, 0);
    constexpr int PE = 2048 - 512, PP = T_PATCH - T_DENSE + 56 - 512;
    uint32_t E[4], F[4], G[4], H[4][4];
    const uint32_t vo = va + 128 + VT_PLANE + 496 - ((lane >> 3) & 1) * (512 + VT_PLANE) - (lane >> 4) * 896;
    load_toep(E, pb + PE, pz + PE);
#pragma unroll
    for (int i = 1; i < 8; i += 2) ldsm4(R[i], va + 128 + i * 128);
    load_toep(F, pb + PP, pz + PP);
    G[0] = lds32(pz + PE + 32); G[1] = lds32(pb + PE + 64); G[2] = lds32(pz + PP + 32); G[3] = lds32(pb + PP + 64);
#pragma unroll
    for (int i = 0; i < 4; i++) ldsm4(H[i], vo + i * 256);
#pragma unroll
    for (int i = 0; i < 32; i++) {
        const int m = i >> 2, j = i & 3;
        acc[2 * m + 1][j] = (acc[2 * m + 1][j] - acc[2 * m][j]) - W[m][j];
        if (m) acc[2 * m][j] += W[m - 1][j];
    }
#pragma unroll
    for (int i = 0; i < 12; i++) mma_v(acc[i + 4], E, R[i & 7][2 * (i >> 3)], R[i & 7][2 * (i >> 3) + 1]);
#pragma unroll
    for (int i = 0; i < 8; i++) mma_v(acc[i + 8], F, R[i][0], R[i][1]);
#pragma unroll
    for (int i = 0; i < 4; i++) mma_bf16_k8(acc[i + 4], G[0], G[1], H[i >> 1][2 * (i & 1) + 1]);
#pragma unroll
    for (int i = 0; i < 8; i++) mma_v(acc[i + 8], G, H[i >> 1][2 * (i & 1)], H[i >> 1][2 * (i & 1) + 1]);
    return __float_as_uint(W[7][0]) & zero;
}
__device__ __forceinline__ uint32_t ones2(int c, int lo, int hi) {
    return (((uint32_t)(c - lo) <= (uint32_t)(hi - lo)) ? 1u : 0u) | (((uint32_t)(c + 1 - lo) <= (uint32_t)(hi - lo)) ? 0x10000u : 0u);
}
__device__ __forceinline__ uint32_t box_bits(int lane) {
    const int d = 2 * (lane & 3) - (lane >> 2);
    auto four = [&](int L1, int H1, int L2, int H2) { return ones2(d, L1, H1) | ones2(d, L2, H2) << 1 | ones2(d + 8, L1, H1) << 2 | ones2(d + 8, L2, H2) << 3; };
    return four(5, 7, 0, 4) | four(1, 7, 0, 8) << 4;
}
struct Boxes {
    uint32_t q[4], ha[2];
    __device__ __forceinline__ Boxes(uint32_t bits, int k0, uint32_t h0, uint32_t h1) {
#pragma unroll
        for (int i = 0; i < 4; i++) q[i] = (bits & (0x10001u << (k0 + i))) * (0x3f80u >> (k0 + i));
        ha[0] = h0; ha[1] = h1;
    }
    __device__ __forceinline__ void load(int j, uint32_t* v, uint32_t zero) const {
        const uint32_t o = j * 128;
        v[0] = lds32(ha[0] + o); v[1] = lds32(ha[1] + zero + o); v[2] = lds32(ha[1] + o);
        v[3] = lds32(ha[0] + zero + o + 16); v[4] = lds32(ha[0] + o + 16); v[5] = lds32(ha[1] + o + 16);
    }
    __device__ __forceinline__ void sums(const uint32_t* v, float* Z, float* X, float* Y) const {
        mma_bf16_z(Z, q[0], q[1], q[2], q[3], v[0], v[1]);
        mma_bf16_z(X, q[0], q[1], q[2], q[3], v[2], v[3]);
        mma_bf16_z(Y, q[0], q[1], q[2], q[3], v[4], v[5]);
    }
};
__host__ __device__ constexpr int tail_step(int n) { return n < 8 ? n : n < 12 ? n + 4 : (n & 1) ? 11 - (n - 13) / 2 : 19 - (n - 12) / 2; }
template <class After>
__device__ __forceinline__ void tail_phase(float (&acc)[16][4], const Boxes& b2, const Boxes& b3, uint32_t tp2, uint32_t tp3, uint32_t zero, After after) {
    uint4 t2[5];
    uint2 t3[8];
    uint32_t v[6], a0[4], a1[4];
    float Z[4], X[4], Y[4];
    b2.load(0, v, zero);
#pragma unroll
    for (int i = 0; i < 5; i++) t2[i] = lds128(tp2 + 160 * i);
#pragma unroll
    for (int n = -1; n < 20; n++) {
        const int j = tail_step(n), j1 = tail_step(n + 1), j2 = tail_step(n + 2);
        if (n < 19) {
            (j1 < 12 ? b2 : b3).sums(v, Z, X, Y);
            if (n < 18) { if (j2 < 12) b2.load(j2, v, zero); else b3.load(j2 - 12, v, zero); }
        }
        if (n >= 0 && j < 12) {
#pragma unroll
            for (int b = 0; b < 5; b++) if (j + 4 + b < 16) mma_v(acc[j + 4 + b], a1, t2[b].z, t2[b].w);
        }
        if (n < 19 && j1 < 12) { a1[0] = pack_v(Z[0], Z[1]); a1[1] = pack_w(X[0], X[1]); a1[2] = pack_v(Z[2], Z[3]); a1[3] = pack_w(X[2], X[3]); }
        if (n == 6) {
#pragma unroll
            for (int b = 0; b < 8; b++) t3[b] = lds64(tp3 + 80 * b);
        }
        if (n >= 0 && j < 12) {
#pragma unroll
            for (int b = 0; b < 5; b++) if (j + 4 + b < 16) mma_v(acc[j + 4 + b], a0, t2[b].x, t2[b].y);
        } else if (n >= 0) {
#pragma unroll
            for (int b = 0; b < 8; b++) if (j - 4 + b < 16) mma_v(acc[j - 4 + b], a0, t3[b].x, t3[b].y);
        }
        if (n < 19) {
            if (j1 < 12) { a0[0] = pack_v(X[0], X[1]); a0[1] = pack_v(Y[0], Y[1]); a0[2] = pack_v(X[2], X[3]); a0[3] = pack_v(Y[2], Y[3]); }
            else { a0[0] = pack_v(X[0], X[1]); a0[1] = pack_v(Y[0], Y[1]); a0[2] = pack_v(Z[2], Z[3]); a0[3] = pack_v(X[2], X[3]); }
        }
        after(n);
    }
}
template <int Q>
__device__ __forceinline__ void emit(const float (&acc)[16][4], int h, uint32_t own, uint32_t peer, uint32_t bar, uint32_t bar_peer) {
    uint32_t lo[4], hi[4];
#pragma unroll
    for (int i = 0; i < 4; i++) { lo[i] = pack_bf16(acc[4 * Q + i][0], acc[4 * Q + i][1]); hi[i] = pack_bf16(acc[4 * Q + i][2], acc[4 * Q + i][3]); }
    st_async128(peer + Q * 8192, h ? lo[0] : hi[0], h ? lo[1] : hi[1], h ? lo[2] : hi[2], h ? lo[3] : hi[3], bar_peer + 8 * Q);
    sts128(own + Q * 8192, h ? hi[0] : lo[0], h ? hi[1] : lo[1], h ? hi[2] : lo[2], h ? hi[3] : lo[3]);
    __syncwarp();
    if (elect_one()) mbar_arrive(bar);
}
__device__ __forceinline__ uint32_t finish_src(uint32_t sb, int h, int j, int lane) {
    const int m = lane >> 3, r = lane & 7;
    return sb + OFF_XT + (h ^ 1) * 32768 + (2 * m + (r & 1)) * 512 + (((8 * j + (r & 4) + ((r >> 1) & 1)) ^ ((r & 1) << 1)) << 4);
}
__device__ __forceinline__ uint32_t finish_dst(uint32_t sb, int h, int j, int lane) {
    const int g = lane >> 2, t = lane & 3;
    return sb + OFF_XT + h * 32768 + j * 2048 + (g >> 1) * 512 + (t >> 1) * 144 + (2 * (t & 1) + (g & 1)) * 32;
}
__device__ __forceinline__ uint32_t tile_addr(uint32_t sb, int tok, int t) {
    return sb + OFF_XT + (tok & 8) * 4096 + (tok >> 9) * 8192 + (tok & 6) * 1024 + (tok & 448) * 4 + (tok & 1) * 128 + (tok & 48) * 2 + (((t >> 1) ^ (tok & 1)) << 4) + (t & 1) * 8;
}
__device__ __forceinline__ uint2 add_update(uint2 o, uint32_t upd) {
    const float4 u = lds128f(upd);
    return make_uint2(badd2(o.x, pack_bf16(u.x, u.y)), badd2(o.y, pack_bf16(u.z, u.w)));
}
__device__ __forceinline__ void finish_half(uint32_t src, uint32_t xa, const uint4 (&x)[2]) {
    uint32_t s[2][4];
#pragma unroll
    for (int i = 0; i < 2; i++) ldsm4t(s[i], src ^ (i << 5));
#pragma unroll
    for (int i = 0; i < 2; i++) sts128(xa + i * 256, badd2(x[i].x, s[i][0]), badd2(x[i].y, s[i][1]), badd2(x[i].z, s[i][2]), badd2(x[i].w, s[i][3]));
}

__device__ __noinline__ float centred_var(uint32_t rows, float mu, int lane) {
    float var = 0.f;
#pragma unroll 1
    for (int rr = 0; rr < 16; rr++) {
        const float c0 = __shfl_sync(0xffffffffu, mu, rr);
        float c = 0.f;
#pragma unroll 1
        for (int k = 0; k < 16; k++) {
            const uint32_t q = lds32(rows + rr * ROW_PITCH + k * 128 + lane * 4);
            const float d0 = bf_lo(q) - c0, d1 = bf_hi(q) - c0;
            c = fmaf(d0, d0, fmaf(d1, d1, c));
        }
#pragma unroll 1
        for (int o = 16; o; o >>= 1) c += __shfl_xor_sync(0xffffffffu, c, o);
        if ((lane & 15) == rr) var = c * (1.f / DM);
    }
    return var;
}
__device__ __noinline__ float centred_score(uint32_t rows, uint32_t wbuf, uint32_t s0, uint32_t s1, int lane) {
    float sc = 0.f;
#pragma unroll 1
    for (int rr = 0; rr < 16; rr++) {
        const uint32_t t0 = __shfl_sync(0xffffffffu, s0, rr), t1 = __shfl_sync(0xffffffffu, s1, rr);
        float c = 0.f;
#pragma unroll 1
        for (int k = 0; k < 16; k++) {
            const uint32_t xn = normalize2(lds32(rows + rr * ROW_PITCH + k * 128 + lane * 4), t0, t1);
            const uint32_t wq = lds32(wbuf + (k >> 2) * 1024 + (k & 3) * 128 + lane * 4);
            c = fmaf(bf_lo(xn), bf_lo(wq), fmaf(bf_hi(xn), bf_hi(wq), c));
        }
#pragma unroll 1
        for (int o = 16; o; o >>= 1) c += __shfl_xor_sync(0xffffffffu, c, o);
        if ((lane & 15) == rr) sc = c;
    }
    return sc;
}

__device__ __forceinline__ void issue_rows(const __nv_bfloat16* u, uint32_t sb, int b) {
    if (elect_one()) {
        const uint32_t bar = sb + OFF_BAR + 8 * B_ROW;
#pragma unroll
        for (int j = 0; j < 4; j++) mbar_init(bar + 8 * j, 1);
        asm volatile("fence.mbarrier_init.release.cluster;" ::: "memory");
        fence_async();
#pragma unroll 1
        for (int j = 0; j < 4; j++) {
            mbar_expect_tx(bar + 8 * j, 8192);
#pragma unroll
            for (int i = 0; i < 4; i++) bulk_g2s(sb + OFF_VT + (4 * j + i) * ROW_PITCH, u + (size_t)(16 * b + 4 * j + i) * DM, 2048, bar + 8 * j);
        }
    }
    __syncwarp();
}

__global__ void __cluster_dims__(2, 1, 1) __launch_bounds__(NTHR, 1)
fused_kernel(const __grid_constant__ Ptrs p, const __grid_constant__ Maps maps) {
    extern __shared__ __align__(1024) unsigned char smem[];
    const int tid = threadIdx.x, lane = tid & 31;
    const int c_ = ((blockIdx.x >> 1) + 60) & 63, b = 2 * ((c_ & 32) | ((c_ & 7) << 2) | ((c_ >> 3) & 3)) + (blockIdx.x & 1);
    const int dch = 8 * b + (tid >> 5) - 4;
    uint2 la, aim, cre, cim;
    uint32_t ldt16;
    if ((uint32_t)(tid - 128) < 256u) {
        la = ldg64(p.logA + dch * NMODE + 4 * lane); aim = ldg64(p.Aim + dch * NMODE + 4 * lane);
        cre = ldg64(p.Cre + dch * NMODE + 4 * lane); cim = ldg64(p.Cim + dch * NMODE + 4 * lane);
        ldt16 = ldg16(p.ldt + dch);
    }
    const uint32_t sb = s_u32(smem), bar0 = sb + OFF_BAR;
    const int warp = __shfl_sync(0xffffffffu, tid >> 5, 0);
    const int h = b & 1, cl = b >> 1;
    const int m = lane >> 3, r = lane & 7, g = lane >> 2, t = lane & 3;
    const bool has_gu = b < GU_CTAS;
    if (warp == 4) { STAMP(0); GSTAMP(24); }

    if (warp >= 12) {
        asm volatile("setmaxnreg.dec.sync.aligned.u32 24;");
        const int a = warp - 12;
        uint32_t due = now_ns() + ST_T0 + (uint32_t)(2 * a + h) * (ST_PER / 2) + (has_gu ? 0 : 12 * ST_PER + 4 * ST_PER2);
        const bool el = elect_one();
        if (a == 1) issue_rows(p.u, sb, b);
        if (a == 2 && el) {
#pragma unroll
            for (int i = B_XT; i < NBAR; i++) mbar_init(bar0 + 8 * i, (i == B_V || i == B_SFREE || i == B_XFREE || i == B_OWN) ? 8 : (i >= B_RECV && i < B_RECV + 3) ? 9 : i == B_RED ? 5 : (i == B_UPD || (i >= B_FREE && i < B_FULL)) ? 4 : 1);
            asm volatile("fence.mbarrier_init.release.cluster;" ::: "memory");
            fence_async();
            mbar_expect_tx(bar0 + 8 * B_XT, 65536);
#pragma unroll
            for (int i = 0; i < 4; i++) mbar_expect_tx(bar0 + 8 * (B_RECV + i), 4096);
            mbar_expect_tx(bar0 + 8 * B_RED, 2048);
        }
        if (a == 3 && el) {
#pragma unroll
            for (int i = 0; i < 5; i++) asm volatile("prefetch.tensormap [%0];" ::"l"(&maps.u + i) : "memory");
        }
        __syncwarp();
        cluster_arrive();
        cluster_wait();
        STAMP(18);
        uint32_t fs = finish_src(sb, h, a, lane), fx = finish_dst(sb, h, a, lane);
        pin(fs); pin(fx);
        mbar_wait(bar0 + 8 * (B_ROW + a), 0);
        if (el) {
#pragma unroll
            for (int i = 0; i < 4; i++)
                tma_load_tile(sb + OFF_XT + (a >> 1) * 32768 + (a & 1) * 4096 + h * 8192 + (i & 1) * 16384 + (i >> 1) * 2048, &maps.u, 16 * cl, 4 * a + (i & 2), 16 * (i & 1) + 8 * h, bar0 + 8 * B_XT);
        }
        if (el) {
#pragma unroll 1
            for (int k = has_gu ? 0 : 4; k < 6; k++) {
                const int i = 4 * k + a, s = k < 3 ? i : i - 12;
                sleep_until(due);
                due += k < 3 ? 4 * ST_PER : 4 * ST_PER2;
                const bool again = k >= 3 && has_gu;
                if (s >= 6 || again) mbar_wait(bar0 + 8 * (s < 10 || again ? B_FREE + s : B_V), slot_priv(s) && again);
                if (k == 5 && a >= 2) mbar_wait(bar0 + 8 * B_LN, 1);
                const uint32_t dst = sb + slot_off(s), bar = bar0 + 8 * (B_FULL + s);
                if (k < 4) {
                    mbar_expect_tx(bar, 8192);
                    tma_load_2d(dst, &maps.wg, 64 * cl, 512 * h + 32 * i, bar);
                    tma_load_2d(dst + 4096, &maps.wu, 64 * cl, 512 * h + 32 * i, bar);
                } else {
                    mbar_expect_tx(bar, 7168);
                    tma_load_perm(dst, &maps.wd, 16 * cl, 56 * h + 14 * a + 7 * (k & 1), bar);
                }
            }
            STAMP(19);
        }
        __syncwarp();
        {
            mbar_wait(bar0 + 8 * B_XT, 0);
#pragma unroll 1
            for (int Q = 0; Q < 3; Q++) {
#pragma unroll
                for (int q = 0; q < 2; q++) {
                    const uint4 x[2] = {lds128(fx ^ (q << 4)), lds128((fx ^ (q << 4)) + 256)};
                    if (q == 0) mbar_wait(bar0 + 8 * (B_RECV + Q), 0);
                    finish_half(fs + q * 4096, fx ^ (q << 4), x);
                }
                fence_async();
                __syncwarp();
                if (el) tma_store_tile(&maps.out, sb + OFF_XT + h * 32768 + Q * 8192 + a * 2048, 16 * cl, 8 * h + 2 * a, 8 * Q);
                fs += 8192; fx += 8192;
                STAMP(Q ? 58 + Q : 20);
            }
            const int tok = 2047 - (int)(lds32(sb + OFF_MISC + 48 + 8 * g) & 2047);
            const bool mine = ((tok >> 1) & 7) == 4 * h + a && tok < 1536;
            if (el) asm volatile("cp.async.bulk.wait_group 0;" ::: "memory");
            if (__any_sync(0xffffffffu, mine)) {
                const uint2 o0 = lds64(tile_addr(sb, tok, t));
                mbar_wait(bar0 + 8 * B_UPD, 0);
                const uint2 o1 = add_update(o0, sb + tab_off(g) + T_RED + 16 * t);
                if (mine) *reinterpret_cast<uint2*>(p.out + (size_t)tok * DM + 16 * cl + 4 * t) = o1;
            } else STAMP(62);
        }
    } else if (warp >= 4) {
        const int w = warp - 4;
        uint32_t dsk16 = ldg16(p.dsk + dch);
        cluster_arrive();
        asm volatile("setmaxnreg.inc.sync.aligned.u32 176;");
        const uint32_t vrow = sb + OFF_VT + w * VT_PITCH + VT_PAD, tab = sb + tab_off(w);
        const uint32_t rb0 = bar0 + 8 * B_RECV, rb1 = mapa(rb0, h ^ 1);
        uint32_t tpo = 80 + (g - 2 * t) * 8 - (g < 2 * t ? 16 : 0);
        uint32_t xa = sb + OFF_XT + (w >> 1) * 8192 + (w & 1) * 1024 + (g >> 1) * 2048 + (g & 1) * 128 + t * 32 + ((h ^ (g & 1)) << 4);
        uint32_t va = sb + OFF_VT + (2 * m + (r & 1)) * VT_PITCH + VT_PAD + (16 * w + (r >> 1)) * 16;
        uint32_t qa = sb + OFF_ST + 2048 * w + 128 * t + 16 * (g ^ (2 * t));
        uint32_t vmin = vrow + (m & 1) * VT_PLANE - 16, vd = vmin + 16 + (m >> 1) * 1024 + r * 16;
        uint32_t vz = vrow - VT_PAD + (lane >> 1) * VT_PLANE + (lane & 1) * 16;
        pin(vmin); pin(vd); pin(vz);
        pin(tpo); pin(xa); pin(va); pin(qa);
        uint32_t bits = box_bits(lane), h0 = vrow + 16 * g + tok_off(2 * t - 18);
        pin(bits); pin(h0);
        const KgenAddr ka(sb + OFF_PRIV + w * 8192, lane);
        if (__any_sync(0xffffffffu, (vmin | (vd | vz) | (tpo | xa) | (va | qa) | (bits | h0) | ka.any()) & p.zero)) __trap();
        cluster_wait();
        pin(la.x); pin(la.y); pin(aim.x); pin(aim.y); pin(cre.x); pin(cre.y); pin(cim.x); pin(cim.y); pin(ldt16); pin(dsk16);
        uint4 x[8];
        auto load_x = [&]() {
            mbar_wait(bar0 + 8 * B_XT, 0);
#pragma unroll
            for (int i = 0; i < 8; i++) x[i] = lds128(xa + (i & 1) * 32768 + (i >> 1) * 256);
        };
        kgen(ka, tab, lane, la, aim, cre, cim, bf_round(ex2f(bf_lo(ldt16) * 1.4426950408889634f)), 1.f + bf_lo(dsk16), dch, [&]() {
            STAMP(21);
            if (elect_one()) mbar_arrive_n(bar0 + 8 * (B_FREE + 6 + ((w >> 1) ^ 2)), 2);
        }, [&]() {
            if ((LN_PAUSE >> w) & 1) mbar_wait(bar0 + 8 * B_LN, 0);
        });
        STAMP(1);
        const uint32_t pb = tab + T_DENSE + (g - 2 * t) * 4;
        uint32_t A[4][4];
        load_toep(A[0], pb, pb + p.zero);
        load_toep(A[2], pb + 1024, pb + p.zero + 1024);
        {
            load_x();
            STAMP(47);
            mbar_wait(bar0 + 8 * (B_ST + (w >> 1)), 0);
            uint4 q[4];
#pragma unroll
            for (int n = 0; n < 4; n++) q[n] = lds128(qa + 512 * n);
            if (lane < 4) sts128(vz, 0, 0, 0, 0);
            STAMP(2); GSTAMP(28);
#pragma unroll
            for (int i = 0; i < 8; i++) {
                const uint32_t s0 = (i & 1) ? q[i >> 1].z : q[i >> 1].x, s1 = (i & 1) ? q[i >> 1].w : q[i >> 1].y;
                stsm4t(va + (i >> 1) * 64 + (i & 1) * VT_PLANE, normalize2(x[i].x, s0, s1), normalize2(x[i].y, s0, s1),
                       normalize2(x[i].z, s0, s1), normalize2(x[i].w, s0, s1));
            }
            __syncwarp();
            if (elect_one()) mbar_arrive(bar0 + 8 * B_V);
        }
        float acc[16][4], W[8][4];
#pragma unroll
        for (int i = 0; i < 64; i++) { acc[i >> 2][i & 3] = 0.f; W[i >> 3][i & 3] = 0.f; }
        bits |= dense_phase(acc, W, A, vmin, vd, pb, p.zero, lane, bar0 + 8 * B_V, bar0 + 8 * B_SFREE);
        const uint32_t h1 = h0 + (t ? VT_PLANE : 16 - VT_PLANE);
        const Boxes b2(bits, 0, h0, h1), b3(bits, 4, (t == 1 ? h1 : h0) - 4, t == 1 ? h0 + 12 : h1 - 4);
        STAMP(4);
        const uint32_t so = sb + OFF_XT + (8 * h + w) * 512 + ((lane ^ ((w & 1) << 1)) << 4);
        const uint32_t dst0 = so + (h ^ 1) * 32768, dst1 = mapa(so + h * 32768, h ^ 1);
        tail_phase(acc, b2, b3, tab + T_R2 + 2 * tpo, tab + T_R3 + tpo, p.zero, [&](int j) {
            if (j == -1) emit<0>(acc, h, dst0, dst1, rb0, rb1);
            if (j == 3) { emit<1>(acc, h, dst0, dst1, rb0 + 8, rb1); STAMP(5); }
            if (j == 11) {
                mbar_wait(bar0 + 8 * B_XFREE, 0);
                emit<2>(acc, h, dst0, dst1, rb0 + 16, rb1);
                STAMP(58);
            }
        });
        emit<3>(acc, h, dst0, dst1, bar0 + 8 * B_OWN, rb1);
        STAMP(30);
        if (w < 4) {
            const uint32_t fs = finish_src(sb, h, w, lane) + 24576 + h * 4096, fx = (finish_dst(sb, h, w, lane) + 24576) ^ (h << 4);
            const int tok = 2047 - (int)(lds32(sb + OFF_MISC + 48 + 8 * g) & 2047);
            const bool mine = ((tok >> 1) & 7) == 4 * h + w && tok >= 1536;
            const uint32_t ta = tile_addr(sb, tok, t);
            const uint4 x0[2] = {lds128(fx), lds128(fx + 256)}, x1[2] = {lds128(fx ^ 16), lds128((fx ^ 16) + 256)};
            mbar_wait(bar0 + 8 * B_OWN, 0);
            finish_half(fs, fx, x0);
            mbar_wait(bar0 + 8 * (B_RECV + 3), 0);
            STAMP(6);
            finish_half(fs + (h ? -4096 : 4096), fx ^ 16, x1);
            __syncwarp();
            if (__any_sync(0xffffffffu, mine)) {
                const uint2 o0 = lds64(ta);
                mbar_wait(bar0 + 8 * B_UPD, 0);
                const uint2 o1 = add_update(o0, sb + tab_off(g) + T_RED + 16 * t);
                if (mine) sts64(ta, o1.x, o1.y);
            }
            fence_async();
            __syncwarp();
            if (elect_one()) {
                tma_store_tile(&maps.out, sb + OFF_XT + h * 32768 + 24576 + w * 2048, 16 * cl, 8 * h + 2 * w, 24);
                if (w == 3) STAMP(61);
                asm volatile("cp.async.bulk.wait_group.read 0;" ::: "memory");
            }
        }
        STAMP(7);
    } else {
        const int a = warp;
        const uint4 wq = ldg128(p.wr + 8 * tid);
        const uint32_t epoch = ld_relaxed_32(&p.sc[a].cnt[b & 96]) >> 5;
        cluster_arrive();
        asm volatile("setmaxnreg.inc.sync.aligned.u32 136;");
        const uint32_t tag = __shfl_sync(0xffffffffu, epoch, 0) + 1u, misc = sb + OFF_MISC, abar = bar0 + 8 * (B_AUX + a);
        uint32_t aph = 0;
        const Exchange* in = &p.sc[cl & (NREP - 1)];
        uint2* pub = p.sc[m >> 1].stat + 16 * b + 2 * (r ^ (2 * (b & 3))) + (m & 1);
        uint32_t* cnt_s = &p.sc[t].cnt[b & 96];
        pin(pub); pin(cnt_s);
        if (tid < 32) sts32(sb + OFF_XCH + 4 * tid, 0);
        const uint32_t wbuf = sb + OFF_LN + a * 1024, part = sb + OFF_LN + 4096;
        {
            sts128(wbuf + 16 * lane, wq.x, wq.y, wq.z, wq.w);
            sts128(wbuf + 512 + 16 * lane, 0x3f803f80u, 0x3f803f80u, 0x3f803f80u, 0x3f803f80u);
            float wsum = ((bf_lo(wq.x) + bf_hi(wq.x)) + (bf_lo(wq.y) + bf_hi(wq.y))) + ((bf_lo(wq.z) + bf_hi(wq.z)) + (bf_lo(wq.w) + bf_hi(wq.w)));
#pragma unroll
            for (int o = 16; o; o >>= 1) wsum += __shfl_xor_sync(0xffffffffu, wsum, o);
            sts32f(part + 1024 + 4 * a, wsum);
            uint32_t wf[4][4];
#pragma unroll
            for (int i = 0; i < 4; i++) ldsm4(wf[i], wbuf + ((uint32_t)(r - 1) < 2u ? 16 * (r - 1) : 512) + 32 * m + 128 * i);
            uint32_t ra = sb + OFF_VT + r * ROW_PITCH + 512 * a + 16 * m, pa = part + a * 256 + g * 16;
            cluster_wait();
            STAMP(22);
#pragma unroll 1
            for (int hf = 0; hf < 2; hf++) {
                mbar_wait(bar0 + 8 * B_ROW + 16 * hf, 0);
                mbar_wait(bar0 + 8 * B_ROW + 16 * hf + 8, 0);
                STAMP(23);
                uint32_t x[8][4];
                float cs[2][4], q[8][4];
#pragma unroll
                for (int i = 0; i < 40; i++) (i < 8 ? cs[i >> 2 & 1] : q[(i - 8) >> 2 & 7])[i & 3] = 0.f;
#pragma unroll
                for (int k = 0; k < 8; k++) ldsm4(x[k], ra + k * 64);
                const bool more = __any_sync(0xffffffffu, after_all(x, p.zero));
#pragma unroll 1
                do {
#pragma unroll
                    for (int k = 0; k < 8; k++) {
                        mma_v(cs[k & 1], x[k], wf[k >> 1][2 * (k & 1)], wf[k >> 1][2 * (k & 1) + 1]);
#pragma unroll
                        for (int i = 0; i < 4; i++) mma_bf16_k8(q[4 * (k & 1) + i], x[k][i & 2], x[k][i | 1], x[k][i]);
                    }
                } while (more);
                const float c2 = cs[0][2] + cs[1][2];
                if (t == 0) sts64f(pa, (cs[0][0] + cs[1][0]) + c2, cs[0][1] + cs[1][1]);
                if (t == 1) sts32f(pa + 12, c2);
                const float e0 = ((q[0][0] + q[2][0]) + (q[4][0] + q[6][0])) + ((q[1][2] + q[3][2]) + (q[5][2] + q[7][2]));
                const float e1 = ((q[0][1] + q[2][1]) + (q[4][1] + q[6][1])) + ((q[1][3] + q[3][3]) + (q[5][3] + q[7][3]));
                if (t == (g >> 1)) sts32f(pa + 8, (g & 1) ? e1 : e0);
                ra += 8 * ROW_PITCH; pa += 128;
            }
        }
        STAMP(31);
        named_sync(1, 128);
        if (a == 0) {
            const uint32_t pa = part + (lane & 15) * 16;
            const float4 p0 = lds128f(pa), p1 = lds128f(pa + 256), p2 = lds128f(pa + 512), p3 = lds128f(pa + 768), ws = lds128f(part + 1024);
            const float mu = ((p0.x + p1.x) + (p2.x + p3.x)) * (1.f / DM);
            float var = ((p0.z + p1.z) + (p2.z + p3.z)) * (1.f / DM) - mu * mu;
            const bool centred = __any_sync(0xffffffffu, !(mu * mu <= 64.f * var));
            if (centred) var = centred_var(sb + OFF_VT, mu, lane);
            const float ri = rcpf(bf_round(sqrtaf(bf_round(bf_round(var) + 1e-5f))));
            const uint32_t s0 = pack_bf16(mu, ri), s1 = (pack_bf16(ri - bf_hi(s0), 0.f) & 0xfffcu) | (tag & 3);
            float sc = ((((p0.y + p1.y) + (p2.y + p3.y)) + ((p0.w + p1.w) + (p2.w + p3.w))) - bf_lo(s0) * ((ws.x + ws.y) + (ws.z + ws.w))) * ri;
            if (centred) sc = centred_score(sb + OFF_VT, sb + OFF_LN, s0, s1, lane);
            const uint32_t sb16 = pack_bf16(0.f, sc);
            const uint32_t s2 = s1 | (sb16 ^ (((uint32_t)((int)sb16 >> 31) & 0x7fff0000u) | 0x80000000u));
            st_relaxed_64(pub, s0, s2);
            st_relaxed_64(pub + 2 * sizeof(Exchange) / 8, s0, s2);
            if (lane < NREP) red_add(cnt_s, 1);
            if (elect_one()) mbar_arrive(bar0 + 8 * B_LN);
            STAMP(9); GSTAMP(25);
        }
        const uint32_t slot0 = sb + OFF_RING + a * 8192, slot1 = sb + slot_off(4 + a), slot2 = sb + slot_off(8 + a), fbar = bar0 + 8 * (B_FULL + a);
        uint32_t mine, row[2];
        {
            uint32_t q[16];
            named_sync(1, 128);
            wait_count(&in->cnt[32 * a], 32 * tag - FEW_ST);
            STAMP(41);
#pragma unroll 1
            for (uint32_t it = 0;; spin_guard(it)) {
                if (elect_one()) {
                    mbar_expect_tx(abar, 4096);
                    bulk_g2s(sb + OFF_ST + 4096 * a, in->stat + 512 * a, 4096, abar);
                }
                mbar_wait(abar, aph);
                aph ^= 1;
                uint32_t bad = 0;
#pragma unroll
                for (int n = 0; n < 8; n++) {
                    const uint4 u = lds128v(sb + OFF_ST + 4096 * a + 512 * n + 16 * lane);
                    q[2 * n] = u.y; q[2 * n + 1] = u.w;
                    bad = or_xor(bad, u.y, tag);
                }
                const bool ok = __all_sync(0xffffffffu, (bad & 3) == 0);
                asm volatile("{ .reg .pred p; setp.ne.u32 p, %1, 0; @p mbarrier.arrive.shared::cta.b64 _, [%0]; }" ::"r"(bar0 + 8 * (B_ST + a)), "r"((uint32_t)(ok && lane == 0)) : "memory");
                if (ok) break;
            }
            STAMP(8);
            const uint32_t inv = 2047 - 512 * a - 16 * m - (r ^ (2 * m));
#pragma unroll
            for (int i = 0; i < 16; i++) asm("lop3.b32 %0, %0, %1, %2, 0x9b;" : "+r"(q[i]) : "r"(inv), "r"(0xffff0000u | (64 * (i >> 1) + 8 * (i & 1))));
            auto below = [&](uint32_t x) {
                uint32_t d[4];
#pragma unroll
                for (int i = 0; i < 16; i++) d[i & 3] = i < 4 ? x + q[i] : min(d[i & 3], x + q[i]);
                d[0] = min(min(d[0], d[1]), min(d[2], d[3]));
                return d[0] < x ? x - 1 - d[0] : 0u;
            };
            const uint32_t mx0 = ~min(min(min(min(q[0], q[1]), min(q[2], q[3])), min(min(q[4], q[5]), min(q[6], q[7]))),
                                      min(min(min(q[8], q[9]), min(q[10], q[11])), min(min(q[12], q[13]), min(q[14], q[15]))));
            const uint32_t gm = __reduce_max_sync(0xffffffffu, mx0 == __reduce_max_sync(0xffffffffu, mx0) ? 0u : mx0);
            if (lane == 0) sts32(misc + 16 + 4 * a, gm);
            named_sync(1, 128);
            STAMP(42);
            const uint4 t0 = lds128(misc + 16);
            uint32_t tau = min(min(t0.x, t0.y), min(t0.z, t0.w));
            uint32_t mx = mx0, cnt = 0, bal;
            const uint32_t list = sb + OFF_XCH + 32 * a;
#pragma unroll 1
            while ((bal = __ballot_sync(0xffffffffu, mx >= tau)) != 0) {
                const uint32_t pos = cnt + __popc(bal & ((1u << lane) - 1u));
                cnt += __popc(bal);
                if (cnt > 8) break;
                if (mx >= tau) sts32(list + 4 * pos, mx);
                mx = below(mx);
            }
            if (cnt > 8) {
                mx = mx0;
#pragma unroll 1
                for (int j = 0; j < 8; j++) {
                    const uint32_t top = __reduce_max_sync(0xffffffffu, mx), nx = below(mx);
                    if (mx == top) { sts32(list + 4 * j, mx); mx = nx; }
                }
            }
            named_sync(1, 128);
            STAMP(43);
            const uint32_t k = lds32(sb + OFF_XCH + 4 * lane);
            uint32_t rk[4] = {misc + 48, 0, 0, 0};
#pragma unroll
            for (int j = 0; j < 8; j++) {
                const uint4 c = lds128(sb + OFF_XCH + 16 * j);
                asm("{ .reg .pred p, q, r, s; setp.gt.u32 p, %4, %8; setp.gt.u32 q, %5, %8; setp.gt.u32 r, %6, %8; setp.gt.u32 s, %7, %8;\n\t"
                    "@p add.u32 %0, %0, 8; @q add.u32 %1, %1, 8; @r add.u32 %2, %2, 8; @s add.u32 %3, %3, 8; }"
                    : "+r"(rk[0]), "+r"(rk[1]), "+r"(rk[2]), "+r"(rk[3]) : "r"(c.x), "r"(c.y), "r"(c.z), "r"(c.w), "r"(k));
            }
            rk[0] = (rk[0] + rk[1]) + (rk[2] + rk[3]);
            if (rk[0] < misc + 112) sts32(rk[0], k);
            __syncwarp();
            mine = lds32(misc + 48 + 8 * g);
            const uint4 two = lds128v(misc + 48 + 16 * a);
            row[0] = two.x; row[1] = two.z;
            mbar_wait(bar0 + 8 * B_V, 0);
        }
        STAMP(11);
        const int tok = 2047 - (int)(mine & 2047);
        const uint32_t xs = sb + OFF_XT + (h ^ 1) * 32768 + 16384;
        if (has_gu) {
            if (elect_one()) {
                mbar_expect_tx(abar, 2048);
#pragma unroll
                for (int j = 0; j < 2; j++) bulk_g2s(xs + (2 * a + j) * 1040, p.u + (size_t)(2047 - (row[j] & 2047)) * DM + 512 * h, 1024, abar);
            }
        }
        STAMP(44);
        uint32_t af[20][4], ko = sb + (m & 1) * 4096 + (r + ((m >> 1) << 3)) * 128 + ((r ^ (4 * h) ^ a) << 4);
        auto load_level = [&](int c) {
#pragma unroll
            for (int j = 0; j < 4; j++) {
                mbar_wait(bar0 + 8 * (B_FULL + 4 * (c % 3) + j), c / 3);
#pragma unroll
                for (int i = 0; i < 4; i++) ldsm4t(af[8 * (i >> 1) + 2 * j + (i & 1)], (ko ^ ((i & 1) << 6)) + slot_off(4 * (c % 3) + j) + (i >> 1) * 2048);
            }
            STAMP(36 + c);
            __syncwarp();
            if (c < 3 && lane < 4) mbar_arrive(bar0 + 8 * (B_FREE + 4 * c + lane));
        };
        const uint2 st = ld_relaxed_64(in->stat + (tok & ~15) + 2 * ((tok & 7) ^ ((tok >> 3) & 6)) + ((tok >> 3) & 1));
        if (has_gu) load_level(0);
        if (a == 0 && t == 0) sts32f(misc + 52 + 8 * g, bf_hi(st.x) + bf_lo(st.y));
        if (a == 0) STAMP(45);
        if (has_gu) {
            const uint32_t mean = __shfl_sync(0xffffffffu, st.x, 8 * a + 4 * (lane >> 4)), xr = xs + (2 * a + (lane >> 4)) * 1040 + 16 * (lane & 15);
            mbar_wait(abar, aph);
            aph ^= 1;
            STAMP(46);
            uint4 x[4];
#pragma unroll
            for (int j = 0; j < 4; j++) x[j] = lds128(xr + 256 * j);
#pragma unroll
            for (int j = 0; j < 4; j++) sts128(xr + 256 * j, bsub2_lo(x[j].x, mean), bsub2_lo(x[j].y, mean), bsub2_lo(x[j].z, mean), bsub2_lo(x[j].w, mean));
            if (elect_one()) mbar_expect_tx(abar, 512);
            named_sync(1, 128);
        }
        if (lane < (has_gu ? 2 : 4)) mbar_arrive_peer(mapa(bar0 + 8 * (lane & 2 ? B_XFREE : B_SFREE), lane & 1));
        if (has_gu) {
            STAMP(12);
            float gacc[8][4];
#pragma unroll
            for (int i = 0; i < 8; i++) { gacc[i][0] = gacc[i][1] = gacc[i][2] = gacc[i][3] = 0.f; }
            uint32_t* pubh = reinterpret_cast<uint32_t*>(&p.sc[0].h[b * 32 + 8 * a + (g ^ (2 * a))]) + t;
            uint32_t* cnt_h = &p.sc[t].cnt[32 * (b / 28) + 1 + ((b / 14) & 1)];
            uint32_t xb = xs + r * 1040 + m * 16;
            uint32_t xch = sb + OFF_XCH + 16 * tid, tagm = t == 3 ? 1u : 0u;
            pin(pubh); pin(cnt_h); pin(xb); pin(xch); pin(tagm);
            const float r0 = lds32f(misc + 52 + 16 * t), r1 = lds32f(misc + 60 + 16 * t);
#pragma unroll
            for (int c = 0; c < 4; c++) {
#pragma unroll
                for (int j = 0; j < 4; j++) ldsm4(af[16 + j], xb + 256 * c + 64 * j);
                if (c == 3) mbar_wait(bar0 + 8 * B_SFREE, 0);
                if (c) load_level(c);
                const bool more = __any_sync(0xffffffffu, (c ? af[6][3] | af[7][3] | af[14][3] | af[15][3] : af[16][3] | af[17][3] | af[18][3] | af[19][3]) & p.zero);
#pragma unroll 1
                do {
#pragma unroll
                    for (int i = 0; i < 16; i++) mma_v(gacc[i & 7], af[i], af[16 + ((i >> 1) & 3)][2 * (i >> 3)], af[16 + ((i >> 1) & 3)][2 * (i >> 3) + 1]);
                } while (more);
            }
            STAMP(13);
            float own[4], oth[4];
#pragma unroll
            for (int j = 0; j < 4; j++) oth[j] = (gacc[1][j] + gacc[3][j]) + (gacc[5][j] + gacc[7][j]);
            st_async128(mapa(xch, h ^ 1), __float_as_uint(oth[0]), __float_as_uint(oth[1]), __float_as_uint(oth[2]), __float_as_uint(oth[3]), mapa(abar, h ^ 1));
            STAMP(56);
#pragma unroll
            for (int j = 0; j < 4; j++) own[j] = ((gacc[0][j] + gacc[2][j]) + (gacc[4][j] + gacc[6][j])) * ((j & 1) ? r1 : r0);
            mbar_wait(abar, aph);
            aph ^= 1;
            STAMP(57);
            const float4 o4 = lds128f(xch);
            const float g0 = bf_round(fmaf(o4.x, r0, own[0])), g1 = bf_round(fmaf(o4.y, r1, own[1]));
            const float h0 = bf_round(g0 * rcpf(1.f + ex2f(-1.4426950408889634f * g0))) * bf_round(fmaf(o4.z, r0, own[2]));
            const float h1 = bf_round(g1 * rcpf(1.f + ex2f(-1.4426950408889634f * g1))) * bf_round(fmaf(o4.w, r1, own[3]));
            uint32_t hw;
            asm volatile("movmatrix.sync.aligned.m8n8.trans.b16 %0, %1;" : "=r"(hw) : "r"(pack_bf16(h0, h1)));
            hw = (hw & ~tagm) | (tag & tagm);
#pragma unroll
            for (int j = 0; j < NREP; j++) st_relaxed_32(pubh + j * (sizeof(Exchange) / 4), hw);
            if (lane < NREP) red_add(cnt_h, b % 14 < 2 ? 2 : 1);
            if (lane < 2) mbar_arrive_peer(mapa(bar0 + 8 * B_XFREE, lane));
            named_sync(1, 128);
            STAMP(14);
        }
        float dacc[4];
        const int tk = ((tid >> 1) & 6) | (tid & 1);
        uint32_t ro = 4 * tid, red = sb + tab_off(tk) + T_RED + 4 * ((tid >> 4) + 4 * (tid & 2));
        if (!has_gu) named_sync(1, 128);
        const float sg = bf_round(rcpf(1.f + ex2f(-1.4426950408889634f * __uint_as_float(unorder_key(lds32(misc + 48 + 8 * tk) >> 16) << 16))));
        pin(ro); pin(red);
        mbar_wait(bar0 + 8 * B_XFREE, 0);
        {
            uint32_t wo = (r + ((m >> 1) << 3)) * 32 + (((m & 1) ^ (r >> 2)) << 4), af[14][4];
            uint32_t ho = slot0 + 128 * t + 16 * (g ^ (2 * t));
            pin(wo); pin(ho);
            float d[7][4];
#pragma unroll
            for (int i = 0; i < 7; i++) { d[i][0] = d[i][1] = d[i][2] = d[i][3] = 0.f; }
            auto first_half = [&]() {
                mbar_wait(fbar + 32, has_gu);
#pragma unroll
                for (int j = 0; j < 14; j++) ldsm4t(af[j], slot1 + wo + j * 512);
            };
            auto fetch = [&]() {
                if (elect_one()) {
                    mbar_expect_tx(abar, 7168);
                    bulk_g2s(slot0, &in->h[(56 * h + 14 * a) * 32], 7168, abar);
                }
            };
            wait_count(&in->cnt[64 * h + 32 * (a >> 1) + 1 + (a & 1)], 64 * tag - FEW_H);
            STAMP(33);
            fetch();
            if (a == 3 && elect_one()) mbar_arrive(bar0 + 8 * B_LN);
            first_half();
            mbar_wait(abar, aph);
#pragma unroll
            for (int s = 0; s < 2; s++) {
                if (s) {
                    mbar_wait(fbar + 64, has_gu);
#pragma unroll
                    for (int j = 0; j < 14; j++) ldsm4t(af[j], slot2 + wo + j * 512);
                }
                uint4 hq[7];
#pragma unroll 1
                for (uint32_t it = 0;; spin_guard(it)) {
                    uint32_t bad = 0;
#pragma unroll
                    for (int j = 0; j < 7; j++) { hq[j] = lds128(ho + 512 * (7 * s + j)); bad = or_xor(bad, hq[j].w, tag); }
                    if (__all_sync(0xffffffffu, (bad & 1) == 0)) break;
                    fetch();
                    aph ^= 1;
                    mbar_wait(abar, aph);
                }
                if (s == 0) STAMP(15);
#pragma unroll
                for (int j = 0; j < 14; j++) {
                    const uint4 q = hq[j >> 1];
                    mma_v(d[j % 7], af[j], (j & 1) ? q.z : q.x, (j & 1) ? q.w : q.y);
                }
            }
#pragma unroll
            for (int j = 0; j < 4; j++) dacc[j] = ((d[0][j] + d[1][j]) + (d[2][j] + d[3][j])) + ((d[4][j] + d[5][j]) + d[6][j]);
        }
        STAMP(16);
        {
            st_async128(mapa(sb + OFF_XCH + 16 * tid, h ^ 1), __float_as_uint(dacc[0]), __float_as_uint(dacc[1]), __float_as_uint(dacc[2]), __float_as_uint(dacc[3]),
                        mapa(bar0 + 8 * B_RED, h ^ 1));
            sts128f(slot0 + 7680 + lane * 16, dacc);
            __syncwarp();
            if (elect_one()) mbar_arrive(bar0 + 8 * B_RED);
            mbar_wait(bar0 + 8 * B_RED, 0);
            const uint32_t b0 = sb + OFF_RING + 7680 + ro, b1 = sb + OFF_XCH + ro;
            const float y = ((lds32f(b0) + lds32f(b0 + 8192)) + (lds32f(b0 + 16384) + lds32f(b0 + 24576))) +
                            ((lds32f(b1) + lds32f(b1 + 512)) + (lds32f(b1 + 1024) + lds32f(b1 + 1536)));
            sts32f(red, bf_round(y) * sg);
            __syncwarp();
            if (elect_one()) mbar_arrive(bar0 + 8 * B_UPD);
        }
        STAMP(17); GSTAMP(29);
    }
}

typedef CUresult (*EncodeFn)(CUtensorMap*, CUtensorMapDataType, cuuint32_t, void*, const cuuint64_t*, const cuuint64_t*,
                             const cuuint32_t*, const cuuint32_t*, CUtensorMapInterleave, CUtensorMapSwizzle,
                             CUtensorMapL2promotion, CUtensorMapFloatOOBfill);

void make_map(EncodeFn enc, CUtensorMap* m, const void* ptr, uint64_t cols, uint64_t rows, uint32_t bc, uint32_t br,
              CUtensorMapSwizzle sw, CUtensorMapL2promotion pr) {
    cuuint64_t dims[2] = {cols, rows};
    cuuint64_t str[1] = {cols * 2};
    cuuint32_t box[2] = {bc, br};
    cuuint32_t es[2] = {1, 1};
    enc(m, CU_TENSOR_MAP_DATA_TYPE_BFLOAT16, 2, const_cast<void*>(ptr), dims, str, box, es, CU_TENSOR_MAP_INTERLEAVE_NONE, sw, pr,
        CU_TENSOR_MAP_FLOAT_OOB_FILL_NONE);
}
void make_perm_map(EncodeFn enc, CUtensorMap* m, const void* ptr, CUtensorMapL2promotion pr) {
    cuuint64_t dims[5] = {DM, 2, 4, 4, FF / 32};
    cuuint64_t str[4] = {DM * 2, 8 * DM * 2, 2 * DM * 2, 32 * DM * 2};
    cuuint32_t box[5] = {16, 2, 4, 4, 7};
    cuuint32_t es[5] = {1, 1, 1, 1, 1};
    enc(m, CU_TENSOR_MAP_DATA_TYPE_BFLOAT16, 5, const_cast<void*>(ptr), dims, str, box, es, CU_TENSOR_MAP_INTERLEAVE_NONE,
        CU_TENSOR_MAP_SWIZZLE_32B, pr, CU_TENSOR_MAP_FLOAT_OOB_FILL_NONE);
}
void make_tile_map(EncodeFn enc, CUtensorMap* m, const void* ptr) {
    cuuint64_t dims[4] = {DM, 4, 16, SEQ / 64};
    cuuint64_t str[3] = {16 * DM * 2, DM * 2, 64 * DM * 2};
    cuuint32_t box[4] = {16, 4, 2, 8};
    cuuint32_t es[4] = {1, 1, 1, 1};
    enc(m, CU_TENSOR_MAP_DATA_TYPE_BFLOAT16, 4, const_cast<void*>(ptr), dims, str, box, es, CU_TENSOR_MAP_INTERLEAVE_NONE,
        CU_TENSOR_MAP_SWIZZLE_32B, CU_TENSOR_MAP_L2_PROMOTION_NONE, CU_TENSOR_MAP_FLOAT_OOB_FILL_NONE);
}

}

extern "C" void kernel_launch(void* const* d_in, const int* in_sizes, int n_in, void* d_out, int out_size) {
    (void)in_sizes; (void)n_in; (void)out_size;
    static EncodeFn enc = nullptr;
    static void* scratch = nullptr;
    if (!enc) {
        void* fn = nullptr;
        cudaDriverEntryPointQueryResult q;
        cudaGetDriverEntryPoint("cuTensorMapEncodeTiled", &fn, cudaEnableDefault, &q);
        enc = (EncodeFn)fn;
        cudaGetSymbolAddress(&scratch, g_scratch);
        cudaFuncSetAttribute(fused_kernel, cudaFuncAttributeMaxDynamicSharedMemorySize, SMEM_BYTES);
    }
    Maps maps;
    make_tile_map(enc, &maps.u, d_in[0]);
    make_tile_map(enc, &maps.out, d_out);
    make_map(enc, &maps.wg, d_in[9], FF, DM, 64, 32, CU_TENSOR_MAP_SWIZZLE_128B, CU_TENSOR_MAP_L2_PROMOTION_L2_128B);
    make_map(enc, &maps.wu, d_in[10], FF, DM, 64, 32, CU_TENSOR_MAP_SWIZZLE_128B, CU_TENSOR_MAP_L2_PROMOTION_L2_128B);
    make_perm_map(enc, &maps.wd, d_in[11], CU_TENSOR_MAP_L2_PROMOTION_L2_64B);
    Ptrs p;
    p.sc = (Exchange*)scratch;
    p.u = (const __nv_bfloat16*)d_in[0];
    p.logA = (const __nv_bfloat16*)d_in[1];
    p.Aim = (const __nv_bfloat16*)d_in[2];
    p.Cre = (const __nv_bfloat16*)d_in[3];
    p.Cim = (const __nv_bfloat16*)d_in[4];
    p.ldt = (const __nv_bfloat16*)d_in[5];
    p.dsk = (const __nv_bfloat16*)d_in[6];
    p.wr = (const __nv_bfloat16*)d_in[8];
    p.out = (__nv_bfloat16*)d_out;
    p.zero = 0;
    fused_kernel<<<NCTA, NTHR, SMEM_BYTES, cudaStreamPerThread>>>(p, maps);
}
```

```cpp
#include <cuda_runtime.h>
#include <cuda_bf16.h>
#include <cuda_fp16.h>
#include <cuda.h>
#include <stdint.h>

namespace {

constexpr int SEQ = 2048, DM = 1024, NMODE = 128, FF = 3584;
constexpr int NCTA = 128, NTHR = 512;
constexpr int GU_CTAS = 112;
constexpr int NREP = 4;

constexpr int OFF_XT = 0;
constexpr int OFF_RING = 65536;
constexpr int OFF_PRIV = OFF_RING + 65536;
constexpr int OFF_VT = OFF_PRIV + 65536;
constexpr int VT_PAD = 32, VT_PLANE = VT_PAD + 2048, VT_PITCH = 2 * VT_PLANE, ROW_PITCH = 2064;
constexpr int OFF_BAR = OFF_VT + 8 * VT_PITCH;
constexpr int OFF_MISC = OFF_BAR + 384;
constexpr int OFF_XCH = OFF_MISC + 112;
constexpr int SMEM_BYTES = OFF_XCH + 2048;
constexpr int OFF_LN = OFF_RING + 7 * 8192;
constexpr int OFF_ST = OFF_RING + 6 * 8192;
static_assert(SMEM_BYTES <= 232448, "shared memory");

constexpr int B_ROW = 0, B_XT = 4, B_V = 5, B_LN = 6, B_SFREE = 7, B_XFREE = 8, B_OWN = 9, B_RED = 10, B_UPD = 11, B_ST = 12, B_RECV = 16, B_FREE = 20, B_FULL = 32, B_AUX = 44, NBAR = 48;

constexpr int T_DENSE = 60;
constexpr int T_PATCH = 2208;
constexpr int T_R2 = 2368;
constexpr int T_R3 = 3296;

constexpr int T_RED = 4032;
__device__ __forceinline__ bool slot_priv(int s) { return (uint32_t)(s - 6) < 4u; }
__device__ __forceinline__ uint32_t slot_off(int s) { return slot_priv(s) ? OFF_PRIV + 4096 + (s & 3) * 16384 : OFF_RING + (s < 6 ? s : s - 4) * 8192; }
__device__ __forceinline__ uint32_t tab_off(int w) { return OFF_PRIV + w * 8192 + (w & 1) * 4096; }

constexpr uint32_t SPIN_LIMIT = 1u << 20;
#define BB_UNROLL 2
constexpr int kBbUnroll = BB_UNROLL;
#define ST_T0 2050
#define ST_PER 286
#define ST_PER2 320
#define LN_PAUSE 0xf0
#define FEW_ST 10
#define FEW_H 24

struct Exchange {
    uint2 stat[SEQ];
    uint4 h[GU_CTAS * 32];
    uint32_t cnt[4 * 32];
};
__device__ __align__(128) Exchange g_scratch[NREP];

struct Ptrs {
    const __nv_bfloat16 *logA, *Aim, *Cre, *Cim, *ldt, *u;
    const __nv_bfloat16 *dsk, *wr;
    Exchange* sc;
    __nv_bfloat16* out;
    uint32_t zero;
};
struct Maps {
    CUtensorMap u, out, wg, wu, wd;
};

#define STAMP(i) do { } while (0)
#define GSTAMP(i) do { } while (0)

__device__ __forceinline__ uint32_t s_u32(const void* p) { return (uint32_t)__cvta_generic_to_shared(p); }
__device__ __forceinline__ void mbar_init(uint32_t b, uint32_t n) {
    asm volatile("mbarrier.init.shared::cta.b64 [%0], %1;" ::"r"(b), "r"(n) : "memory");
}
__device__ __forceinline__ void mbar_expect_tx(uint32_t b, uint32_t bytes) {
    asm volatile("mbarrier.arrive.expect_tx.shared::cta.b64 _, [%0], %1;" ::"r"(b), "r"(bytes) : "memory");
}
__device__ __forceinline__ void mbar_arrive(uint32_t b) {
    asm volatile("mbarrier.arrive.shared::cta.b64 _, [%0];" ::"r"(b) : "memory");
}
__device__ __forceinline__ void mbar_arrive_n(uint32_t b, uint32_t n) {
    asm volatile("mbarrier.arrive.shared::cta.b64 _, [%0], %1;" ::"r"(b), "r"(n) : "memory");
}
__device__ __forceinline__ void mbar_arrive_peer(uint32_t b_cluster) {
    asm volatile("mbarrier.arrive.relaxed.cluster.shared::cluster.b64 _, [%0];" ::"r"(b_cluster) : "memory");
}
__device__ __forceinline__ void mbar_wait(uint32_t b, uint32_t parity) {
    asm volatile("{\n\t.reg .pred p;\n\t.reg .u32 c;\n\tmov.u32 c, 0;\n"
                 "W:\n\tmbarrier.try_wait.parity.shared::cta.b64 p, [%0], %1;\n\t@p bra D;\n\t"
                 "add.u32 c, c, 1;\n\tsetp.lt.u32 p, c, 1048576;\n\t@p bra W;\n\ttrap;\nD:\n\t}"
                 ::"r"(b), "r"(parity) : "memory");
}
__device__ __forceinline__ bool elect_one() {
    uint32_t p;
    asm volatile("{ .reg .pred P; elect.sync _|P, 0xffffffff; selp.u32 %0, 1, 0, P; }" : "=r"(p));
    return p != 0;
}
__device__ __forceinline__ uint32_t mapa(uint32_t a, uint32_t rank) {
    uint32_t r;
    asm("mapa.shared::cluster.u32 %0, %1, %2;" : "=r"(r) : "r"(a), "r"(rank));
    return r;
}
__device__ __forceinline__ void cluster_arrive() { asm volatile("barrier.cluster.arrive.relaxed.aligned;" ::: "memory"); }
__device__ __forceinline__ void cluster_wait() { asm volatile("barrier.cluster.wait.acquire.aligned;" ::: "memory"); }
__device__ __forceinline__ void tma_load_2d(uint32_t dst, const CUtensorMap* m, int c0, int c1, uint32_t bar) {
    asm volatile("cp.async.bulk.tensor.2d.shared::cluster.global.mbarrier::complete_tx::bytes [%0], [%1, {%3, %4}], [%2];"
                 ::"r"(dst), "l"(m), "r"(bar), "r"(c0), "r"(c1) : "memory");
}
__device__ __forceinline__ void tma_load_perm(uint32_t dst, const CUtensorMap* m, int c0, int blk, uint32_t bar) {
    asm volatile("cp.async.bulk.tensor.5d.shared::cluster.global.mbarrier::complete_tx::bytes [%0], [%1, {%3, %4, %4, %4, %5}], [%2];"
                 ::"r"(dst), "l"(m), "r"(bar), "r"(c0), "r"(0), "r"(blk) : "memory");
}
__device__ __forceinline__ void tma_load_tile(uint32_t dst, const CUtensorMap* m, int c0, int c2, int c3, uint32_t bar) {
    asm volatile("cp.async.bulk.tensor.4d.shared::cluster.global.mbarrier::complete_tx::bytes.multicast::cluster [%0], [%1, {%3, %4, %5, %6}], [%2], %7;"
                 ::"r"(dst), "l"(m), "r"(bar), "r"(c0), "r"(0), "r"(c2), "r"(c3), "h"((uint16_t)3) : "memory");
}
__device__ __forceinline__ void tma_store_tile(const CUtensorMap* m, uint32_t src, int c0, int c2, int c3) {
    asm volatile("cp.async.bulk.tensor.4d.global.shared::cta.bulk_group [%0, {%2, %3, %4, %5}], [%1];"
                 ::"l"(m), "r"(src), "r"(c0), "r"(0), "r"(c2), "r"(c3) : "memory");
    asm volatile("cp.async.bulk.commit_group;" ::: "memory");
}
__device__ __forceinline__ void bulk_g2s(uint32_t dst, const void* src, uint32_t bytes, uint32_t bar) {
    asm volatile("cp.async.bulk.shared::cluster.global.mbarrier::complete_tx::bytes [%0], [%1], %2, [%3];"
                 ::"r"(dst), "l"(src), "r"(bytes), "r"(bar) : "memory");
}
__device__ __forceinline__ void st_async128(uint32_t dst_cluster, uint32_t x, uint32_t y, uint32_t z, uint32_t w, uint32_t bar_cluster) {
    asm volatile("st.async.weak.shared::cluster.mbarrier::complete_tx::bytes.v4.b32 [%0], {%1,%2,%3,%4}, [%5];"
                 ::"r"(dst_cluster), "r"(x), "r"(y), "r"(z), "r"(w), "r"(bar_cluster) : "memory");
}
__device__ __forceinline__ void fence_async() { asm volatile("fence.proxy.async.shared::cta;" ::: "memory"); }
__device__ __forceinline__ void named_sync(int id, int n) { asm volatile("bar.sync %0, %1;" ::"r"(id), "r"(n) : "memory"); }

__device__ __forceinline__ void ldsm4(uint32_t* r, uint32_t a) {
    asm volatile("ldmatrix.sync.aligned.m8n8.x4.shared.b16 {%0,%1,%2,%3}, [%4];"
                 : "=r"(r[0]), "=r"(r[1]), "=r"(r[2]), "=r"(r[3]) : "r"(a));
}
__device__ __forceinline__ void ldsm4t(uint32_t* r, uint32_t a) {
    asm volatile("ldmatrix.sync.aligned.m8n8.x4.trans.shared.b16 {%0,%1,%2,%3}, [%4];"
                 : "=r"(r[0]), "=r"(r[1]), "=r"(r[2]), "=r"(r[3]) : "r"(a));
}
__device__ __forceinline__ void stsm4t(uint32_t a, uint32_t x, uint32_t y, uint32_t z, uint32_t w) {
    asm volatile("stmatrix.sync.aligned.m8n8.x4.trans.shared.b16 [%0], {%1,%2,%3,%4};"
                 ::"r"(a), "r"(x), "r"(y), "r"(z), "r"(w) : "memory");
}
__device__ __forceinline__ uint32_t lds32(uint32_t a) { uint32_t v; asm volatile("ld.shared.u32 %0, [%1];" : "=r"(v) : "r"(a)); return v; }
__device__ __forceinline__ float lds32f(uint32_t a) { float v; asm volatile("ld.shared.f32 %0, [%1];" : "=f"(v) : "r"(a)); return v; }
__device__ __forceinline__ uint2 lds64(uint32_t a) { uint2 v; asm volatile("ld.shared.v2.u32 {%0,%1}, [%2];" : "=r"(v.x), "=r"(v.y) : "r"(a)); return v; }
__device__ __forceinline__ uint4 lds128(uint32_t a) {
    uint4 v; asm volatile("ld.shared.v4.u32 {%0,%1,%2,%3}, [%4];" : "=r"(v.x), "=r"(v.y), "=r"(v.z), "=r"(v.w) : "r"(a)); return v;
}
__device__ __forceinline__ uint4 lds128v(uint32_t a) {
    uint4 v; asm volatile("ld.volatile.shared.v4.u32 {%0,%1,%2,%3}, [%4];" : "=r"(v.x), "=r"(v.y), "=r"(v.z), "=r"(v.w) : "r"(a)); return v;
}
__device__ __forceinline__ uint32_t or_xor(uint32_t a, uint32_t b, uint32_t c) {
    uint32_t r; asm("lop3.b32 %0, %1, %2, %3, 0xf6;" : "=r"(r) : "r"(a), "r"(b), "r"(c)); return r;
}
__device__ __forceinline__ float4 lds128f(uint32_t a) {
    float4 v; asm volatile("ld.shared.v4.f32 {%0,%1,%2,%3}, [%4];" : "=f"(v.x), "=f"(v.y), "=f"(v.z), "=f"(v.w) : "r"(a)); return v;
}
__device__ __forceinline__ void sts32(uint32_t a, uint32_t v) { asm volatile("st.shared.u32 [%0], %1;" ::"r"(a), "r"(v) : "memory"); }
__device__ __forceinline__ void sts32f(uint32_t a, float v) { asm volatile("st.shared.f32 [%0], %1;" ::"r"(a), "f"(v) : "memory"); }
__device__ __forceinline__ void sts64(uint32_t a, uint32_t x, uint32_t y) { asm volatile("st.shared.v2.u32 [%0], {%1,%2};" ::"r"(a), "r"(x), "r"(y) : "memory"); }
__device__ __forceinline__ void sts64f(uint32_t a, float x, float y) { asm volatile("st.shared.v2.f32 [%0], {%1,%2};" ::"r"(a), "f"(x), "f"(y) : "memory"); }
__device__ __forceinline__ void sts128(uint32_t a, uint32_t x, uint32_t y, uint32_t z, uint32_t w) {
    asm volatile("st.shared.v4.u32 [%0], {%1,%2,%3,%4};" ::"r"(a), "r"(x), "r"(y), "r"(z), "r"(w) : "memory");
}
__device__ __forceinline__ void sts128f(uint32_t a, const float* v) {
    asm volatile("st.shared.v4.f32 [%0], {%1,%2,%3,%4};" ::"r"(a), "f"(v[0]), "f"(v[1]), "f"(v[2]), "f"(v[3]) : "memory");
}
__device__ __forceinline__ uint4 ldg128(const void* p) {
    uint4 v; asm volatile("ld.global.nc.L1::no_allocate.v4.u32 {%0,%1,%2,%3}, [%4];" : "=r"(v.x), "=r"(v.y), "=r"(v.z), "=r"(v.w) : "l"(p)); return v;
}
__device__ __forceinline__ uint2 ldg64(const void* p) {
    uint2 v; asm volatile("ld.global.nc.L1::no_allocate.v2.u32 {%0,%1}, [%2];" : "=r"(v.x), "=r"(v.y) : "l"(p)); return v;
}
__device__ __forceinline__ uint32_t ldg16(const void* p) {
    uint32_t v; asm volatile("ld.global.nc.u16 %0, [%1];" : "=r"(v) : "l"(p)); return v;
}
__device__ __forceinline__ uint2 ld_relaxed_64(const void* p) {
    uint2 v; asm volatile("ld.relaxed.gpu.global.v2.u32 {%0,%1}, [%2];" : "=r"(v.x), "=r"(v.y) : "l"(p) : "memory"); return v;
}
__device__ __forceinline__ uint32_t ld_relaxed_32(const void* p) {
    uint32_t v; asm volatile("ld.relaxed.gpu.global.u32 %0, [%1];" : "=r"(v) : "l"(p) : "memory"); return v;
}
__device__ __forceinline__ void st_relaxed_64(void* p, uint32_t x, uint32_t y) {
    asm volatile("st.relaxed.gpu.global.v2.u32 [%0], {%1,%2};" ::"l"(p), "r"(x), "r"(y) : "memory");
}
__device__ __forceinline__ void st_relaxed_32(void* p, uint32_t v) {
    asm volatile("st.relaxed.gpu.global.u32 [%0], %1;" ::"l"(p), "r"(v) : "memory");
}
__device__ __forceinline__ void red_add(void* p, uint32_t v) { asm volatile("red.relaxed.gpu.global.add.u32 [%0], %1;" ::"l"(p), "r"(v) : "memory"); }
__device__ __forceinline__ uint32_t now_ns() { uint32_t t; asm volatile("mov.u32 %0, %%globaltimer_lo;" : "=r"(t) :: "memory"); return t; }
__device__ __forceinline__ void sleep_until(uint32_t t) {
#pragma unroll 1
    for (int left; (left = (int)(t - now_ns())) > 0;) __nanosleep(left >> 1);
}
__device__ __forceinline__ void spin_guard(uint32_t& it) { if (++it > SPIN_LIMIT) __trap(); }
__device__ __forceinline__ void wait_count(const uint32_t* p, uint32_t target) {
#pragma unroll 1
    for (uint32_t it = 0; __any_sync(0xffffffffu, (int)(ld_relaxed_32(p) - target) < 0); spin_guard(it)) { }
}
__device__ __forceinline__ void mma_bf16_k8(float* c, uint32_t a0, uint32_t a1, uint32_t b0) {
    asm("mma.sync.aligned.m16n8k8.row.col.f32.bf16.bf16.f32 {%0,%1,%2,%3}, {%4,%5}, {%6}, {%0,%1,%2,%3};"
                 : "+f"(c[0]), "+f"(c[1]), "+f"(c[2]), "+f"(c[3]) : "r"(a0), "r"(a1), "r"(b0));
}
__device__ __forceinline__ void mma_v(float* c, const uint32_t* a, uint32_t b0, uint32_t b1) {
    asm volatile("mma.sync.aligned.m16n8k16.row.col.f32.bf16.bf16.f32 {%0,%1,%2,%3}, {%4,%5,%6,%7}, {%8,%9}, {%0,%1,%2,%3};"
                 : "+f"(c[0]), "+f"(c[1]), "+f"(c[2]), "+f"(c[3]) : "r"(a[0]), "r"(a[1]), "r"(a[2]), "r"(a[3]), "r"(b0), "r"(b1));
}
__device__ __forceinline__ void mma_bf16_z(float* c, uint32_t a0, uint32_t a1, uint32_t a2, uint32_t a3, uint32_t b0, uint32_t b1) {
    asm volatile("mma.sync.aligned.m16n8k16.row.col.f32.bf16.bf16.f32 {%0,%1,%2,%3}, {%4,%5,%6,%7}, {%8,%9}, {%10,%10,%10,%10};"
        : "=f"(c[0]), "=f"(c[1]), "=f"(c[2]), "=f"(c[3]) : "r"(a0), "r"(a1), "r"(a2), "r"(a3), "r"(b0), "r"(b1), "f"(0.f));
}
__device__ __forceinline__ void mma_f16(float* c, uint32_t a0, uint32_t a1, uint32_t a2, uint32_t a3, uint32_t b0, uint32_t b1) {
    asm("mma.sync.aligned.m16n8k16.row.col.f32.f16.f16.f32 {%0,%1,%2,%3}, {%4,%5,%6,%7}, {%8,%9}, {%0,%1,%2,%3};"
                 : "+f"(c[0]), "+f"(c[1]), "+f"(c[2]), "+f"(c[3]) : "r"(a0), "r"(a1), "r"(a2), "r"(a3), "r"(b0), "r"(b1));
}
__device__ __forceinline__ uint32_t pack_bf16(float lo, float hi) {
    uint32_t r; asm("cvt.rn.bf16x2.f32 %0, %1, %2;" : "=r"(r) : "f"(hi), "f"(lo)); return r;
}
__device__ __forceinline__ uint32_t pack_v(float lo, float hi) {
    uint32_t r; asm volatile("cvt.rn.bf16x2.f32 %0, %1, %2;" : "=r"(r) : "f"(hi), "f"(lo)); return r;
}
__device__ __forceinline__ uint32_t pack_w(float lo, float hi) {
    uint32_t r; asm volatile("cvt.rn.satfinite.bf16x2.f32 %0, %1, %2;" : "=r"(r) : "f"(hi), "f"(lo)); return r;
}
template <int N> __device__ __forceinline__ uint32_t after_all(const uint32_t (&f)[N][4], uint32_t zero) {
    uint32_t d[3] = {0, 0, 0};
#pragma unroll
    for (int i = 0; i < N; i++) d[i % 3] |= f[i][3];
    return (d[0] | d[1] | d[2]) & zero;
}
__device__ __forceinline__ void pin(uint32_t& x) { asm volatile("" : "+r"(x)); }
template <class T> __device__ __forceinline__ void pin(T*& x) { asm volatile("" : "+l"(x)); }
__device__ __forceinline__ uint32_t pack_f16(float lo, float hi) {
    uint32_t r; asm("cvt.rn.f16x2.f32 %0, %1, %2;" : "=r"(r) : "f"(hi), "f"(lo)); return r;
}
__device__ __forceinline__ float bf_lo(uint32_t v) { return __uint_as_float(v << 16); }
__device__ __forceinline__ float bf_hi(uint32_t v) { return __uint_as_float(v & 0xffff0000u); }
__device__ __forceinline__ float bf_round(float x) { return __uint_as_float(pack_bf16(0.f, x)); }
__device__ __forceinline__ uint32_t badd2(uint32_t a, uint32_t b) { uint32_t r; asm("add.rn.bf16x2 %0, %1, %2;" : "=r"(r) : "r"(a), "r"(b)); return r; }
__device__ __forceinline__ uint32_t bsub2_lo(uint32_t a, uint32_t b) {
    uint32_t r; asm("{ .reg .b16 m, h; .reg .b32 m2; mov.b32 {m, h}, %2; mov.b32 m2, {m, m}; sub.rn.bf16x2 %0, %1, m2; }" : "=r"(r) : "r"(a), "r"(b)); return r;
}
__device__ __forceinline__ uint32_t bmax2(uint32_t a, uint32_t b) { uint32_t r; asm("max.bf16x2 %0, %1, %2;" : "=r"(r) : "r"(a), "r"(b)); return r; }
__device__ __forceinline__ uint32_t normalize2(uint32_t x, uint32_t s0, uint32_t s1) {
    uint32_t r;
    asm("{ .reg .b16 m, h, l, k; .reg .b32 m2, h2, l2, d, t;\n\t"
        "mov.b32 {m, h}, %2; mov.b32 {l, k}, %3; mov.b32 m2, {m, m}; mov.b32 h2, {h, h}; mov.b32 l2, {l, l};\n\t"
        "sub.rn.bf16x2 d, %1, m2; mul.rn.bf16x2 t, d, l2; fma.rn.bf16x2 %0, d, h2, t; }" : "=r"(r) : "r"(x), "r"(s0), "r"(s1));
    return r;
}
__device__ __forceinline__ float rcpf(float x) { float r; asm("rcp.approx.ftz.f32 %0, %1;" : "=f"(r) : "f"(x)); return r; }
__device__ __forceinline__ float sqrtaf(float x) { float r; asm("sqrt.approx.ftz.f32 %0, %1;" : "=f"(r) : "f"(x)); return r; }
__device__ __forceinline__ float ex2f(float x) { float r; asm("ex2.approx.ftz.f32 %0, %1;" : "=f"(r) : "f"(x)); return r; }

__device__ __forceinline__ int tok_off(int t) { return ((t >> 3) & 1) * VT_PLANE + (t >> 4) * 16 + (t & 7) * 2; }

__device__ __forceinline__ uint32_t unorder_key(uint32_t k16) { return k16 ^ ((k16 & 0x8000u) ? 0x8000u : 0xffffu); }

struct cplx { float r, i; };
struct hc { uint32_t r, i; };
template <bool CONJ> __device__ __forceinline__ cplx csq(cplx a) {
    float im;
    asm("{ .reg .f32 t; mul.ftz.f32 t, %1, %2; mul.ftz.f32 %0, t, 0f40000000; }" : "=f"(im) : "f"(CONJ ? -a.r : a.r), "f"(a.i));
    return {fmaf(a.r, a.r, -(a.i * a.i)), im};
}
__device__ __forceinline__ cplx cexpp(float a2, float ai) {
    float m = ex2f(a2), s, c;
    __sincosf(ai, &s, &c);
    return {m * c, m * s};
}
__device__ __forceinline__ __half2 as_h2(uint32_t x) { return *reinterpret_cast<__half2*>(&x); }
__device__ __forceinline__ uint32_t as_u(__half2 x) { return *reinterpret_cast<uint32_t*>(&x); }
__device__ __forceinline__ hc hmul(hc a, hc b) {
    return {as_u(__hfma2(as_h2(a.r), as_h2(b.r), __hneg2(__hmul2(as_h2(a.i), as_h2(b.i))))),
            as_u(__hfma2(as_h2(a.r), as_h2(b.i), __hmul2(as_h2(a.i), as_h2(b.r))))};
}
__device__ __forceinline__ hc hpack(cplx a, cplx b) { return {pack_f16(a.r, b.r), pack_f16(a.i, b.i)}; }
__device__ __forceinline__ void sts16(uint32_t a, uint32_t v) { asm volatile("st.shared.u16 [%0], %1;" ::"r"(a), "r"(v) : "memory"); }

struct KgenAddr {
    uint32_t l, h, m2, m3, m4, z, w, wz;
    __device__ __forceinline__ KgenAddr(uint32_t scr, int lane) {
        const int g = lane >> 2, t = lane & 3;
        const uint32_t rec = scr + t * 480;
        l = rec + 16 * g; h = rec + 128 + 8 * g; m2 = rec + 192 + 8 * (g & 1); m3 = rec + 208 + 4 * (g & 2); m4 = rec + 224 + 2 * (g & 4);
        z = scr + 7680 + 16 * t; w = scr + 240 * lane; wz = scr + 7680 + 8 * lane;
        pin(l); pin(h); pin(m2); pin(m3); pin(m4); pin(z); pin(w); pin(wz);
    }
    __device__ __forceinline__ uint32_t any() const { return (l | h | m2) | (m3 | m4 | z) | (w | wz); }
};
template <class Hook, class Hook2>
__device__ __forceinline__ void kgen(const KgenAddr& ad, uint32_t tab, int lane, uint2 la, uint2 aim, uint2 cre, uint2 cim, float dt, float skip, int dch, Hook main_done, Hook2 half_done) {
    const int g = lane >> 2, t = lane & 3;
    const float dt2 = 2.f * dt;
    const uint32_t am = bmax2(bmax2(cre.x & 0x7fff7fffu, cre.y & 0x7fff7fffu), bmax2(cim.x & 0x7fff7fffu, cim.y & 0x7fff7fffu));
    const float mx = dt2 * fmaxf(bf_lo(am), bf_hi(am));
    const uint32_t eb = min(max(__reduce_max_sync(0xffffffffu, __float_as_uint(mx)) >> 23, 1u), 252u);
    const float cscale = dt2 * __uint_as_float((253u - eb) << 23);
    const float scale_inv = __uint_as_float((eb + 1u) << 23);
    float k0 = (bf_lo(cre.x) + bf_hi(cre.x)) + (bf_lo(cre.y) + bf_hi(cre.y));
#pragma unroll
    for (int o = 16; o; o >>= 1) k0 += __shfl_xor_sync(0xffffffffu, k0, o);
    const float ndt = -1.4426950408889634f * dt;
    STAMP(40);

    float acc[5][4];
#pragma unroll
    for (int i = 0; i < 5; i++) { acc[i][0] = acc[i][1] = acc[i][2] = acc[i][3] = 0.f; }

#pragma unroll kBbUnroll
    for (int bb = 0; bb < 2; bb++) {
        cplx z[2][11], cz[2];
#pragma unroll
        for (int e = 0; e < 2; e++) {
            const float lg = e ? bf_hi(la.x) : bf_lo(la.x), ai = (e ? bf_hi(aim.x) : bf_lo(aim.x)) * dt;
            const float cr = (e ? bf_hi(cre.x) : bf_lo(cre.x)) * cscale, ci = (e ? bf_hi(cim.x) : bf_lo(cim.x)) * cscale;
            const float a2 = bf_round(ex2f(lg * 1.4426950408889634f)) * ndt;
            z[e][0] = cexpp(a2, ai);
            z[e][5] = cexpp(a2 * 32.f, ai * -32.f);
#pragma unroll
            for (int i = 1; i < 11; i++) if (i != 5) z[e][i] = (i == 3 || i == 7) ? csq<true>(z[e][i - 1]) : csq<false>(z[e][i - 1]);
            cz[e] = {fmaf(cr, z[e][0].r, -(ci * z[e][0].i)), fmaf(cr, z[e][0].i, ci * z[e][0].r)};
        }
        la.x = la.y; aim.x = aim.y; cre.x = cre.y; cim.x = cim.y;
        const hc z1 = hpack(z[0][0], z[1][0]), z2 = hpack(z[0][1], z[1][1]), z4 = hpack(z[0][2], z[1][2]);
        hc L[8], H[8];
        L[1] = hpack(z[0][3], z[1][3]); L[2] = hpack(z[0][4], z[1][4]); L[4] = hpack(z[0][5], z[1][5]);
        const hc y64 = hpack(z[0][6], z[1][6]), z128 = hpack(z[0][7], z[1][7]), z256 = hpack(z[0][8], z[1][8]);
        const hc z512 = hpack(z[0][9], z[1][9]), z1024 = hpack(z[0][10], z[1][10]);
        H[0] = hpack(cz[0], cz[1]);
        H[1] = hmul(H[0], z1); H[2] = hmul(H[0], z2); H[3] = hmul(H[1], z2);
        L[3] = hmul(L[1], L[2]);
#pragma unroll
        for (int i = 0; i < 4; i++) { H[4 + i] = hmul(H[i], z4); if (i) L[4 + i] = hmul(L[i], L[4]); }
        __syncwarp();
        sts128(ad.w, 0x3c003c00u, y64.r, 0u, y64.i);
#pragma unroll
        for (int i = 1; i < 8; i++) { const hc q = hmul(L[i], y64); sts128(ad.w + 16 * i, L[i].r, q.r, L[i].i, q.i); }
#pragma unroll
        for (int i = 0; i < 4; i++) sts128(ad.w + 128 + 16 * i, H[2 * i].r, H[2 * i].i, H[2 * i + 1].r, H[2 * i + 1].i);
        {
            const hc a = hmul(z256, z1), b = hmul(z256, z128), c = hmul(z256, z2), d = hmul(z512, z4);
            sts128(ad.w + 192, a.r, a.i, b.r, b.i);
            sts128(ad.w + 208, c.r, c.i, z512.r, z512.i);
            sts128(ad.w + 224, d.r, d.i, z1024.r, z1024.i);
            sts64(ad.wz, z128.r, z128.i);
        }
        __syncwarp();

#pragma unroll
        for (int k2 = 0; k2 < 4; k2++) {
#pragma unroll
            for (uint32_t s = 0; s < 2; s++) {
                const uint32_t o = k2 * 1920 + s * 240;
                const uint4 l = lds128(ad.l + o);
                const uint2 h0 = lds64(ad.h + o), m2 = lds64(ad.m2 + o), m3 = lds64(ad.m3 + o), m4 = lds64(ad.m4 + o), mz = lds64(ad.z + k2 * 64 + s * 8);
                const hc H0 = {h0.x, h0.y};
                const hc H1 = hmul(H0, {mz.x, mz.y}), H2 = hmul(H0, {m2.x, m2.y}), H3 = hmul(H2, {m3.x, m3.y}), H4 = hmul(H3, {m4.x, m4.y});
                mma_f16(acc[0], l.x, l.y, l.z, l.w, H0.r, H0.i);
                mma_f16(acc[1], l.x, l.y, l.z, l.w, H1.r, H1.i);
                mma_f16(acc[2], l.x, l.y, l.z, l.w, H2.r, H2.i);
                mma_f16(acc[3], l.x, l.y, l.z, l.w, H3.r, H3.i);
                mma_f16(acc[4], l.x, l.y, l.z, l.w, H4.r, H4.i);
            }
        }

        if (bb == 0) half_done();
    }
    __syncwarp();
    main_done();

#pragma unroll
    for (int i = 0; i < 4; i++) sts128(tab + 2048 + 512 * i + 16 * lane, 0, 0, 0, 0);
    if (lane < 15) sts32(tab + 4 * lane, 0);
    __syncwarp();
    const uint32_t d0 = tab + T_DENSE + 4 + 8 * lane, src = (lane + 31) & 31;
    const uint32_t p0 = pack_bf16(fmaf(k0, dt2, skip), 0.f);
    uint32_t prev = p0;
#pragma unroll
    for (int i = 0; i < 4; i++) {
        const uint32_t pk = pack_bf16(acc[i >> 1][2 * (i & 1) + 1] * scale_inv, acc[i >> 1][2 * (i & 1)] * scale_inv);
        sts64(d0 + 256 * i, __byte_perm(pk, __shfl_sync(0xffffffffu, lane == 31 ? prev : pk, src), 0x5432), pk);
        prev = pk;
    }
    const uint32_t w0 = pack_bf16(acc[2][0] * scale_inv, acc[2][1] * scale_inv), w1 = pack_bf16(acc[2][2] * scale_inv, acc[2][3] * scale_inv);
    const uint32_t sa = (lane & 1) ? 0x5410u : 0x5454u, sb2 = (lane & 1) ? 0x1010u : 0x5410u;
#pragma unroll
    for (int hf = 0; hf < 2; hf++) {
        const uint32_t w = hf ? w1 : w0;
        const uint32_t pv = __shfl_sync(0xffffffffu, lane != 31 ? w : hf ? w0 : __byte_perm(prev, w1, 0x5410), src);
        sts64(d0 + 1024 + 256 * hf, __byte_perm(w, pv, sa), __byte_perm(w, pv, sb2));
        sts64(d0 + 1536 + 256 * hf, __byte_perm(w, pv, sa + 0x2222u), __byte_perm(w, pv, sb2 + 0x2222u));
    }
    const uint32_t d3 = tab + T_R2 + 160 + 320 * (t & 1) + 16 * (g >> 1) + 8 * (g & 1) + 4 * (t >> 1), d3n = d3 + (g >= 6 ? 32 : 0);
    const uint32_t d4 = tab + T_R3 + 80 + 160 * t + 4 * g, d4n = d4 + (g >= 6 ? 16 : 0);
    uint32_t p3;
#pragma unroll
    for (int hf = 0; hf < 2; hf++)
#pragma unroll
        for (int e = 0; e < 2; e++) {
            const float v3 = acc[3][2 * hf + e] * scale_inv;
            const uint32_t p4 = pack_bf16(acc[4][2 * hf + e] * scale_inv, 0.f);
            p3 = pack_bf16(v3, v3);
            sts16(d3 + 64 * hf + 160 * e, p3);
            sts16((hf ? d3n : d3) + 64 * hf + 160 * e + 18, p3);
            sts16(d4 + 32 * hf + 80 * e, p4);
            sts16((hf ? d4n : d4) + 32 * hf + 80 * e + 10, p4);
        }
    if (lane == 31) {
        const uint32_t k512 = __byte_perm(w1, 0, 0x3232);
        sts32(tab + T_DENSE, p0);
        sts64(tab + T_DENSE + 4 * 513, k512, k512); sts16(tab + T_DENSE + 4 * 515 + 2, k512);
        sts16(tab + T_PATCH + 4 * 17, p3); sts32(tab + T_PATCH + 4 * 18, p3); sts16(tab + T_PATCH + 4 * 19 + 2, p3);
    }
    __syncwarp();
}

__device__ __forceinline__ void load_toep(uint32_t* a, uint32_t p, uint32_t pz) {
    a[0] = lds32(p); a[1] = lds32(p + 32); a[2] = lds32(pz - 32); a[3] = lds32(pz);
}
template <int F>
__device__ __forceinline__ void ffa_step(float (&acc)[16][4], float (&W)[8][4], uint32_t (&R)[8][4], uint32_t (&A)[4][4],
                                         uint32_t va, uint32_t vn, uint32_t vmin, uint32_t pb, uint32_t pz) {
    constexpr int S = F ^ 1;
    auto load = [&](int sh) {
#pragma unroll
        for (int i = S; i < 8; i += 2) ldsm4(R[i], i == 0 ? max(sh ? vn : va, vmin) : (sh ? vn : va) + i * 128);
#pragma unroll
        for (int k = S; k < 4; k += 2) load_toep(A[k], pb + 64 * sh + k * 512, pz + 64 * sh + k * 512);
    };
    auto prod = [&](int par, int dst) {
#pragma unroll
        for (int k = 0; k < 2; k++)
#pragma unroll
            for (int m = k; m < 8; m++) {
                const uint32_t* x = &R[2 * ((m - k) & 3) + par][2 * ((m - k) >> 2)];
                mma_v(dst == 1 ? W[m] : acc[2 * m + (dst >> 1)], A[2 * k + par], x[0], x[1]);
            }
    };
    load(0);
    prod(F, F);
    prod(S, S);
#pragma unroll
    for (int i = 0; i < 8; i++) A[(i >> 2) * 2 + F][i & 3] = badd2(A[(i >> 2) * 2][i & 3], A[(i >> 2) * 2 + 1][i & 3]);
#pragma unroll
    for (int i = 0; i < 16; i++) R[(i >> 2) * 2 + F][i & 3] = badd2(R[(i >> 2) * 2][i & 3], R[(i >> 2) * 2 + 1][i & 3]);
    load(1);
    prod(F, 2);
}
__device__ __forceinline__ uint32_t dense_phase(float (&acc)[16][4], float (&W)[8][4], uint32_t (&A)[4][4], uint32_t vmin, uint32_t va, uint32_t pb, uint32_t zero, int lane,
                                                uint32_t vbar, uint32_t sbar) {
    uint32_t R[8][4], pz = pb + zero;
#pragma unroll 1
    for (int rho = 0; rho < 8; rho += 2) {
        if (rho == (int)zero) {
            mbar_wait(vbar, 0);
            STAMP(3);
#pragma unroll
            for (int i = 0; i < 8; i += 2) ldsm4(R[i], va + i * 128);
        }
        ffa_step<0>(acc, W, R, A, va, va - 16, vmin, pb, pz);
        ffa_step<1>(acc, W, R, A, va - 16, rho == 6 ? va + 96 : va - 32, vmin, pb + 64, pz + 64);
        pb += 128; pz += 128; va -= 32;
    }
    mbar_wait(sbar, 0);
    constexpr int PE = 2048 - 512, PP = T_PATCH - T_DENSE + 56 - 512;
    uint32_t E[4], F[4], G[4], H[4][4];
    const uint32_t vo = va + 128 + VT_PLANE + 496 - ((lane >> 3) & 1) * (512 + VT_PLANE) - (lane >> 4) * 896;
    load_toep(E, pb + PE, pz + PE);
#pragma unroll
    for (int i = 1; i < 8; i += 2) ldsm4(R[i], va + 128 + i * 128);
    load_toep(F, pb + PP, pz + PP);
    G[0] = lds32(pz + PE + 32); G[1] = lds32(pb + PE + 64); G[2] = lds32(pz + PP + 32); G[3] = lds32(pb + PP + 64);
#pragma unroll
    for (int i = 0; i < 4; i++) ldsm4(H[i], vo + i * 256);
#pragma unroll
    for (int i = 0; i < 32; i++) {
        const int m = i >> 2, j = i & 3;
        acc[2 * m + 1][j] = (acc[2 * m + 1][j] - acc[2 * m][j]) - W[m][j];
        if (m) acc[2 * m][j] += W[m - 1][j];
    }
#pragma unroll
    for (int i = 0; i < 12; i++) mma_v(acc[i + 4], E, R[i & 7][2 * (i >> 3)], R[i & 7][2 * (i >> 3) + 1]);
#pragma unroll
    for (int i = 0; i < 8; i++) mma_v(acc[i + 8], F, R[i][0], R[i][1]);
#pragma unroll
    for (int i = 0; i < 4; i++) mma_bf16_k8(acc[i + 4], G[0], G[1], H[i >> 1][2 * (i & 1) + 1]);
#pragma unroll
    for (int i = 0; i < 8; i++) mma_v(acc[i + 8], G, H[i >> 1][2 * (i & 1)], H[i >> 1][2 * (i & 1) + 1]);
    return __float_as_uint(W[7][0]) & zero;
}
__device__ __forceinline__ uint32_t ones2(int c, int lo, int hi) {
    return (((uint32_t)(c - lo) <= (uint32_t)(hi - lo)) ? 1u : 0u) | (((uint32_t)(c + 1 - lo) <= (uint32_t)(hi - lo)) ? 0x10000u : 0u);
}
__device__ __forceinline__ uint32_t box_bits(int lane) {
    const int d = 2 * (lane & 3) - (lane >> 2);
    auto four = [&](int L1, int H1, int L2, int H2) { return ones2(d, L1, H1) | ones2(d, L2, H2) << 1 | ones2(d + 8, L1, H1) << 2 | ones2(d + 8, L2, H2) << 3; };
    return four(5, 7, 0, 4) | four(1, 7, 0, 8) << 4;
}
struct Boxes {
    uint32_t q[4], ha[2];
    __device__ __forceinline__ Boxes(uint32_t bits, int k0, uint32_t h0, uint32_t h1) {
#pragma unroll
        for (int i = 0; i < 4; i++) q[i] = (bits & (0x10001u << (k0 + i))) * (0x3f80u >> (k0 + i));
        ha[0] = h0; ha[1] = h1;
    }
    __device__ __forceinline__ void load(int j, uint32_t* v, uint32_t zero) const {
        const uint32_t o = j * 128;
        v[0] = lds32(ha[0] + o); v[1] = lds32(ha[1] + zero + o); v[2] = lds32(ha[1] + o);
        v[3] = lds32(ha[0] + zero + o + 16); v[4] = lds32(ha[0] + o + 16); v[5] = lds32(ha[1] + o + 16);
    }
    __device__ __forceinline__ void sums(const uint32_t* v, float* Z, float* X, float* Y) const {
        mma_bf16_z(Z, q[0], q[1], q[2], q[3], v[0], v[1]);
        mma_bf16_z(X, q[0], q[1], q[2], q[3], v[2], v[3]);
        mma_bf16_z(Y, q[0], q[1], q[2], q[3], v[4], v[5]);
    }
};
__host__ __device__ constexpr int tail_step(int n) { return n < 8 ? n : n < 12 ? n + 4 : (n & 1) ? 11 - (n - 13) / 2 : 19 - (n - 12) / 2; }
template <class After>
__device__ __forceinline__ void tail_phase(float (&acc)[16][4], const Boxes& b2, const Boxes& b3, uint32_t tp2, uint32_t tp3, uint32_t zero, After after) {
    uint4 t2[5];
    uint2 t3[8];
    uint32_t v[6], a0[4], a1[4];
    float Z[4], X[4], Y[4];
    b2.load(0, v, zero);
#pragma unroll
    for (int i = 0; i < 5; i++) t2[i] = lds128(tp2 + 160 * i);
#pragma unroll
    for (int n = -1; n < 20; n++) {
        const int j = tail_step(n), j1 = tail_step(n + 1), j2 = tail_step(n + 2);
        if (n < 19) {
            (j1 < 12 ? b2 : b3).sums(v, Z, X, Y);
            if (n < 18) { if (j2 < 12) b2.load(j2, v, zero); else b3.load(j2 - 12, v, zero); }
        }
        if (n >= 0 && j < 12) {
#pragma unroll
            for (int b = 0; b < 5; b++) if (j + 4 + b < 16) mma_v(acc[j + 4 + b], a1, t2[b].z, t2[b].w);
        }
        if (n < 19 && j1 < 12) { a1[0] = pack_v(Z[0], Z[1]); a1[1] = pack_w(X[0], X[1]); a1[2] = pack_v(Z[2], Z[3]); a1[3] = pack_w(X[2], X[3]); }
        if (n == 6) {
#pragma unroll
            for (int b = 0; b < 8; b++) t3[b] = lds64(tp3 + 80 * b);
        }
        if (n >= 0 && j < 12) {
#pragma unroll
            for (int b = 0; b < 5; b++) if (j + 4 + b < 16) mma_v(acc[j + 4 + b], a0, t2[b].x, t2[b].y);
        } else if (n >= 0) {
#pragma unroll
            for (int b = 0; b < 8; b++) if (j - 4 + b < 16) mma_v(acc[j - 4 + b], a0, t3[b].x, t3[b].y);
        }
        if (n < 19) {
            if (j1 < 12) { a0[0] = pack_v(X[0], X[1]); a0[1] = pack_v(Y[0], Y[1]); a0[2] = pack_v(X[2], X[3]); a0[3] = pack_v(Y[2], Y[3]); }
            else { a0[0] = pack_v(X[0], X[1]); a0[1] = pack_v(Y[0], Y[1]); a0[2] = pack_v(Z[2], Z[3]); a0[3] = pack_v(X[2], X[3]); }
        }
        after(n);
    }
}
template <int Q>
__device__ __forceinline__ void emit(const float (&acc)[16][4], int h, uint32_t own, uint32_t peer, uint32_t bar, uint32_t bar_peer) {
    uint32_t lo[4], hi[4];
#pragma unroll
    for (int i = 0; i < 4; i++) { lo[i] = pack_bf16(acc[4 * Q + i][0], acc[4 * Q + i][1]); hi[i] = pack_bf16(acc[4 * Q + i][2], acc[4 * Q + i][3]); }
    st_async128(peer + Q * 8192, h ? lo[0] : hi[0], h ? lo[1] : hi[1], h ? lo[2] : hi[2], h ? lo[3] : hi[3], bar_peer + 8 * Q);
    sts128(own + Q * 8192, h ? hi[0] : lo[0], h ? hi[1] : lo[1], h ? hi[2] : lo[2], h ? hi[3] : lo[3]);
    __syncwarp();
    if (elect_one()) mbar_arrive(bar);
}
__device__ __forceinline__ uint32_t finish_src(uint32_t sb, int h, int j, int lane) {
    const int m = lane >> 3, r = lane & 7;
    return sb + OFF_XT + (h ^ 1) * 32768 + (2 * m + (r & 1)) * 512 + (((8 * j + (r & 4) + ((r >> 1) & 1)) ^ ((r & 1) << 1)) << 4);
}
__device__ __forceinline__ uint32_t finish_dst(uint32_t sb, int h, int j, int lane) {
    const int g = lane >> 2, t = lane & 3;
    return sb + OFF_XT + h * 32768 + j * 2048 + (g >> 1) * 512 + (t >> 1) * 144 + (2 * (t & 1) + (g & 1)) * 32;
}
__device__ __forceinline__ uint32_t tile_addr(uint32_t sb, int tok, int t) {
    return sb + OFF_XT + (tok & 8) * 4096 + (tok >> 9) * 8192 + (tok & 6) * 1024 + (tok & 448) * 4 + (tok & 1) * 128 + (tok & 48) * 2 + (((t >> 1) ^ (tok & 1)) << 4) + (t & 1) * 8;
}
__device__ __forceinline__ uint2 add_update(uint2 o, uint32_t upd) {
    const float4 u = lds128f(upd);
    return make_uint2(badd2(o.x, pack_bf16(u.x, u.y)), badd2(o.y, pack_bf16(u.z, u.w)));
}
__device__ __forceinline__ void finish_half(uint32_t src, uint32_t xa, const uint4 (&x)[2]) {
    uint32_t s[2][4];
#pragma unroll
    for (int i = 0; i < 2; i++) ldsm4t(s[i], src ^ (i << 5));
#pragma unroll
    for (int i = 0; i < 2; i++) sts128(xa + i * 256, badd2(x[i].x, s[i][0]), badd2(x[i].y, s[i][1]), badd2(x[i].z, s[i][2]), badd2(x[i].w, s[i][3]));
}

__device__ __noinline__ float centred_var(uint32_t rows, float mu, int lane) {
    float var = 0.f;
#pragma unroll 1
    for (int rr = 0; rr < 16; rr++) {
        const float c0 = __shfl_sync(0xffffffffu, mu, rr);
        float c = 0.f;
#pragma unroll 1
        for (int k = 0; k < 16; k++) {
            const uint32_t q = lds32(rows + rr * ROW_PITCH + k * 128 + lane * 4);
            const float d0 = bf_lo(q) - c0, d1 = bf_hi(q) - c0;
            c = fmaf(d0, d0, fmaf(d1, d1, c));
        }
#pragma unroll 1
        for (int o = 16; o; o >>= 1) c += __shfl_xor_sync(0xffffffffu, c, o);
        if ((lane & 15) == rr) var = c * (1.f / DM);
    }
    return var;
}
__device__ __noinline__ float centred_score(uint32_t rows, uint32_t wbuf, uint32_t s0, uint32_t s1, int lane) {
    float sc = 0.f;
#pragma unroll 1
    for (int rr = 0; rr < 16; rr++) {
        const uint32_t t0 = __shfl_sync(0xffffffffu, s0, rr), t1 = __shfl_sync(0xffffffffu, s1, rr);
        float c = 0.f;
#pragma unroll 1
        for (int k = 0; k < 16; k++) {
            const uint32_t xn = normalize2(lds32(rows + rr * ROW_PITCH + k * 128 + lane * 4), t0, t1);
            const uint32_t wq = lds32(wbuf + (k >> 2) * 1024 + (k & 3) * 128 + lane * 4);
            c = fmaf(bf_lo(xn), bf_lo(wq), fmaf(bf_hi(xn), bf_hi(wq), c));
        }
#pragma unroll 1
        for (int o = 16; o; o >>= 1) c += __shfl_xor_sync(0xffffffffu, c, o);
        if ((lane & 15) == rr) sc = c;
    }
    return sc;
}

__device__ __forceinline__ void issue_rows(const __nv_bfloat16* u, uint32_t sb, int b) {
    if (elect_one()) {
        const uint32_t bar = sb + OFF_BAR + 8 * B_ROW;
#pragma unroll
        for (int j = 0; j < 4; j++) mbar_init(bar + 8 * j, 1);
        asm volatile("fence.mbarrier_init.release.cluster;" ::: "memory");
        fence_async();
#pragma unroll 1
        for (int j = 0; j < 4; j++) {
            mbar_expect_tx(bar + 8 * j, 8192);
#pragma unroll
            for (int i = 0; i < 4; i++) bulk_g2s(sb + OFF_VT + (4 * j + i) * ROW_PITCH, u + (size_t)(16 * b + 4 * j + i) * DM, 2048, bar + 8 * j);
        }
    }
    __syncwarp();
}

__global__ void __cluster_dims__(2, 1, 1) __launch_bounds__(NTHR, 1)
fused_kernel(const __grid_constant__ Ptrs p, const __grid_constant__ Maps maps) {
    extern __shared__ __align__(1024) unsigned char smem[];
    const int tid = threadIdx.x, lane = tid & 31;
    const int c_ = ((blockIdx.x >> 1) + 60) & 63, b = 2 * ((c_ & 32) | ((c_ & 7) << 2) | ((c_ >> 3) & 3)) + (blockIdx.x & 1);
    const int dch = 8 * b + (tid >> 5) - 4;
    uint2 la, aim, cre, cim;
    uint32_t ldt16;
    if ((uint32_t)(tid - 128) < 256u) {
        la = ldg64(p.logA + dch * NMODE + 4 * lane); aim = ldg64(p.Aim + dch * NMODE + 4 * lane);
        cre = ldg64(p.Cre + dch * NMODE + 4 * lane); cim = ldg64(p.Cim + dch * NMODE + 4 * lane);
        ldt16 = ldg16(p.ldt + dch);
    }
    const uint32_t sb = s_u32(smem), bar0 = sb + OFF_BAR;
    const int warp = __shfl_sync(0xffffffffu, tid >> 5, 0);
    const int h = b & 1, cl = b >> 1;
    const int m = lane >> 3, r = lane & 7, g = lane >> 2, t = lane & 3;
    const bool has_gu = b < GU_CTAS;
    if (warp == 4) { STAMP(0); GSTAMP(24); }

    if (warp >= 12) {
        asm volatile("setmaxnreg.dec.sync.aligned.u32 24;");
        const int a = warp - 12;
        uint32_t due = now_ns() + ST_T0 + (uint32_t)(2 * a + h) * (ST_PER / 2) + (has_gu ? 0 : 12 * ST_PER + 4 * ST_PER2);
        const bool el = elect_one();
        if (a == 1) issue_rows(p.u, sb, b);
        if (a == 2 && el) {
#pragma unroll
            for (int i = B_XT; i < NBAR; i++) mbar_init(bar0 + 8 * i, (i == B_V || i == B_SFREE || i == B_XFREE) ? 8 : (i >= B_RECV && i < B_RECV + 4) ? 9 : i == B_RED ? 5 : (i == B_UPD || (i >= B_FREE && i < B_FULL)) ? 4 : 1);
            asm volatile("fence.mbarrier_init.release.cluster;" ::: "memory");
            fence_async();
            mbar_expect_tx(bar0 + 8 * B_XT, 65536);
#pragma unroll
            for (int i = 0; i < 4; i++) mbar_expect_tx(bar0 + 8 * (B_RECV + i), 4096);
            mbar_expect_tx(bar0 + 8 * B_RED, 2048);
        }
        if (a == 3 && el) {
#pragma unroll
            for (int i = 0; i < 5; i++) asm volatile("prefetch.tensormap [%0];" ::"l"(&maps.u + i) : "memory");
        }
        __syncwarp();
        cluster_arrive();
        cluster_wait();
        STAMP(18);
        uint32_t fs = finish_src(sb, h, a, lane), fx = finish_dst(sb, h, a, lane);
        pin(fs); pin(fx);
        mbar_wait(bar0 + 8 * (B_ROW + a), 0);
        if (el) {
#pragma unroll
            for (int i = 0; i < 4; i++)
                tma_load_tile(sb + OFF_XT + (a >> 1) * 32768 + (a & 1) * 4096 + h * 8192 + (i & 1) * 16384 + (i >> 1) * 2048, &maps.u, 16 * cl, 4 * a + (i & 2), 16 * (i & 1) + 8 * h, bar0 + 8 * B_XT);
        }
        if (el) {
#pragma unroll 1
            for (int k = has_gu ? 0 : 4; k < 6; k++) {
                const int i = 4 * k + a, s = k < 3 ? i : i - 12;
                sleep_until(due);
                due += k < 3 ? 4 * ST_PER : 4 * ST_PER2;
                const bool again = k >= 3 && has_gu;
                if (s >= 6 || again) mbar_wait(bar0 + 8 * (s < 10 || again ? B_FREE + s : B_V), slot_priv(s) && again);
                if (k == 5 && a >= 2) mbar_wait(bar0 + 8 * B_LN, 1);
                const uint32_t dst = sb + slot_off(s), bar = bar0 + 8 * (B_FULL + s);
                if (k < 4) {
                    mbar_expect_tx(bar, 8192);
                    tma_load_2d(dst, &maps.wg, 64 * cl, 512 * h + 32 * i, bar);
                    tma_load_2d(dst + 4096, &maps.wu, 64 * cl, 512 * h + 32 * i, bar);
                } else {
                    mbar_expect_tx(bar, 7168);
                    tma_load_perm(dst, &maps.wd, 16 * cl, 56 * h + 14 * a + 7 * (k & 1), bar);
                }
            }
            STAMP(19);
        }
        __syncwarp();
        {
            mbar_wait(bar0 + 8 * B_XT, 0);
#pragma unroll 1
            for (int Q = 0; Q < 3; Q++) {
#pragma unroll
                for (int q = 0; q < 2; q++) {
                    const uint4 x[2] = {lds128(fx ^ (q << 4)), lds128((fx ^ (q << 4)) + 256)};
                    if (q == 0) mbar_wait(bar0 + 8 * (B_RECV + Q), 0);
                    finish_half((fs ^ (q << 6)) + q * 4096, fx ^ (q << 4), x);
                }
                fence_async();
                __syncwarp();
                if (el) tma_store_tile(&maps.out, sb + OFF_XT + h * 32768 + Q * 8192 + a * 2048, 16 * cl, 8 * h + 2 * a, 8 * Q);
                fs += 8192; fx += 8192;
                STAMP(Q ? 58 + Q : 20);
            }
            const int tok = 2047 - (int)(lds32(sb + OFF_MISC + 48 + 8 * g) & 2047);
            const bool mine = ((tok >> 1) & 7) == 4 * h + a && tok < 1536;
            if (el) asm volatile("cp.async.bulk.wait_group 0;" ::: "memory");
            if (__any_sync(0xffffffffu, mine)) {
                const uint2 o0 = lds64(tile_addr(sb, tok, t));
                mbar_wait(bar0 + 8 * B_UPD, 0);
                const uint2 o1 = add_update(o0, sb + tab_off(g) + T_RED + 16 * t);
                if (mine) *reinterpret_cast<uint2*>(p.out + (size_t)tok * DM + 16 * cl + 4 * t) = o1;
            } else STAMP(62);
        }
    } else if (warp >= 4) {
        const int w = warp - 4;
        uint32_t dsk16 = ldg16(p.dsk + dch);
        cluster_arrive();
        asm volatile("setmaxnreg.inc.sync.aligned.u32 176;");
        const uint32_t vrow = sb + OFF_VT + w * VT_PITCH + VT_PAD, tab = sb + tab_off(w);
        const uint32_t rb0 = bar0 + 8 * B_RECV, rb1 = mapa(rb0, h ^ 1);
        uint32_t tpo = 80 + (g - 2 * t) * 8 - (g < 2 * t ? 16 : 0);
        uint32_t xa = sb + OFF_XT + (w >> 1) * 8192 + (w & 1) * 1024 + (g >> 1) * 2048 + (g & 1) * 128 + t * 32 + ((h ^ (g & 1)) << 4);
        uint32_t va = sb + OFF_VT + (2 * m + (r & 1)) * VT_PITCH + VT_PAD + (16 * w + (r >> 1)) * 16;
        uint32_t qa = sb + OFF_ST + 2048 * w + 128 * t + 16 * (g ^ (2 * t));
        uint32_t vmin = vrow + (m & 1) * VT_PLANE - 16, vd = vmin + 16 + (m >> 1) * 1024 + r * 16;
        uint32_t vz = vrow - VT_PAD + (lane >> 1) * VT_PLANE + (lane & 1) * 16;
        pin(vmin); pin(vd); pin(vz);
        pin(tpo); pin(xa); pin(va); pin(qa);
        uint32_t bits = box_bits(lane), h0 = vrow + 16 * g + tok_off(2 * t - 18);
        pin(bits); pin(h0);
        const KgenAddr ka(sb + OFF_PRIV + w * 8192, lane);
        if (__any_sync(0xffffffffu, (vmin | (vd | vz) | (tpo | xa) | (va | qa) | (bits | h0) | ka.any()) & p.zero)) __trap();
        cluster_wait();
        pin(la.x); pin(la.y); pin(aim.x); pin(aim.y); pin(cre.x); pin(cre.y); pin(cim.x); pin(cim.y); pin(ldt16); pin(dsk16);
        uint4 x[8];
        auto load_x = [&]() {
            mbar_wait(bar0 + 8 * B_XT, 0);
#pragma unroll
            for (int i = 0; i < 8; i++) x[i] = lds128(xa + (i & 1) * 32768 + (i >> 1) * 256);
        };
        kgen(ka, tab, lane, la, aim, cre, cim, bf_round(ex2f(bf_lo(ldt16) * 1.4426950408889634f)), 1.f + bf_lo(dsk16), dch, [&]() {
            STAMP(21);
            if (elect_one()) mbar_arrive_n(bar0 + 8 * (B_FREE + 6 + ((w >> 1) ^ 2)), 2);
        }, [&]() {
            if ((LN_PAUSE >> w) & 1) mbar_wait(bar0 + 8 * B_LN, 0);
        });
        STAMP(1);
        const uint32_t pb = tab + T_DENSE + (g - 2 * t) * 4;
        uint32_t A[4][4];
        load_toep(A[0], pb, pb + p.zero);
        load_toep(A[2], pb + 1024, pb + p.zero + 1024);
        {
            load_x();
            STAMP(47);
            mbar_wait(bar0 + 8 * (B_ST + (w >> 1)), 0);
            uint4 q[4];
#pragma unroll
            for (int n = 0; n < 4; n++) q[n] = lds128(qa + 512 * n);
            if (lane < 4) sts128(vz, 0, 0, 0, 0);
            STAMP(2); GSTAMP(28);
#pragma unroll
            for (int i = 0; i < 8; i++) {
                const uint32_t s0 = (i & 1) ? q[i >> 1].z : q[i >> 1].x, s1 = (i & 1) ? q[i >> 1].w : q[i >> 1].y;
                stsm4t(va + (i >> 1) * 64 + (i & 1) * VT_PLANE, normalize2(x[i].x, s0, s1), normalize2(x[i].y, s0, s1),
                       normalize2(x[i].z, s0, s1), normalize2(x[i].w, s0, s1));
            }
            __syncwarp();
            if (elect_one()) mbar_arrive(bar0 + 8 * B_V);
        }
        float acc[16][4], W[8][4];
#pragma unroll
        for (int i = 0; i < 64; i++) { acc[i >> 2][i & 3] = 0.f; W[i >> 3][i & 3] = 0.f; }
        bits |= dense_phase(acc, W, A, vmin, vd, pb, p.zero, lane, bar0 + 8 * B_V, bar0 + 8 * B_SFREE);
        const uint32_t h1 = h0 + (t ? VT_PLANE : 16 - VT_PLANE);
        const Boxes b2(bits, 0, h0, h1), b3(bits, 4, (t == 1 ? h1 : h0) - 4, t == 1 ? h0 + 12 : h1 - 4);
        STAMP(4);
        const uint32_t so = sb + OFF_XT + (8 * h + w) * 512 + ((lane ^ ((w & 1) << 1) ^ (h << 2)) << 4);
        const uint32_t dst0 = so + (h ^ 1) * 32768, dst1 = mapa(so + h * 32768, h ^ 1);
        tail_phase(acc, b2, b3, tab + T_R2 + 2 * tpo, tab + T_R3 + tpo, p.zero, [&](int j) {
            if (j == -1) emit<0>(acc, h, dst0, dst1, rb0, rb1);
            if (j == 3) { emit<1>(acc, h, dst0, dst1, rb0 + 8, rb1); STAMP(5); }
            if (j == 11) {
                mbar_wait(bar0 + 8 * B_XFREE, 0);
                emit<2>(acc, h, dst0, dst1, rb0 + 16, rb1);
                STAMP(58);
            }
        });
        emit<3>(acc, h, dst0, dst1, rb0 + 24, rb1);
        STAMP(30);
        {
            const int j = w & 3, th = w >> 2;
            const int tok = 2047 - (int)(lds32(sb + OFF_MISC + 48 + 8 * g) & 2047);
            const bool mine = (((tok >> 3) & 8) | ((tok >> 1) & 7)) == 8 * th + 4 * h + j && tok >= 1536;
            const uint32_t fs = sb + OFF_XT + (h ^ 1) * 32768 + 24576 + (4 * (r & 2) + 2 * m + (r & 1)) * 512 + (((8 * j + 2 * th + (r >> 2)) ^ ((r & 3) << 1)) << 4);
            const uint32_t fx = sb + OFF_XT + h * 32768 + 24576 + j * 2048 + th * 256 + (g >> 1) * 512 + ((t & 2) + (g & 1)) * 32 + (t & 1) * 16;
            __nv_bfloat16* dst = p.out + (size_t)(1536 + 64 * th + 8 * h + 2 * j + 128 * (g >> 1) + 16 * ((t & 2) + (g & 1))) * DM + 16 * cl + 8 * (t & 1);
            const uint4 x[2] = {lds128(fx), lds128((fx ^ 16) + 128)};
            mbar_wait(bar0 + 8 * (B_RECV + 3), 0);
            STAMP(6);
            uint32_t sv[2][4];
#pragma unroll
            for (int u = 0; u < 2; u++) ldsm4t(sv[u], fs ^ (u << 6));
            uint4 o[2];
#pragma unroll
            for (int u = 0; u < 2; u++) {
                o[u] = make_uint4(badd2(x[u].x, sv[u][0]), badd2(x[u].y, sv[u][1]), badd2(x[u].z, sv[u][2]), badd2(x[u].w, sv[u][3]));
                *reinterpret_cast<uint4*>(dst + u * DM) = o[u];
            }
            if (__any_sync(0xffffffffu, mine)) {
#pragma unroll
                for (int u = 0; u < 2; u++) sts128((fx ^ (u << 4)) + u * 128, o[u].x, o[u].y, o[u].z, o[u].w);
                __syncwarp();
                const uint2 o0 = lds64(tile_addr(sb, tok, t));
                uint2* row = reinterpret_cast<uint2*>(p.out + (size_t)tok * DM + 16 * cl + 4 * t);
                pin(row);
                mbar_wait(bar0 + 8 * B_UPD, 0);
                const uint2 o1 = add_update(o0, sb + tab_off(g) + T_RED + 16 * t);
                if (mine) *row = o1;
            }
        }
        STAMP(7);
    } else {
        const int a = warp;
        const uint4 wq = ldg128(p.wr + 8 * tid);
        const uint32_t epoch = ld_relaxed_32(&p.sc[a].cnt[b & 96]) >> 5;
        cluster_arrive();
        asm volatile("setmaxnreg.inc.sync.aligned.u32 136;");
        const uint32_t tag = __shfl_sync(0xffffffffu, epoch, 0) + 1u, misc = sb + OFF_MISC, abar = bar0 + 8 * (B_AUX + a);
        uint32_t aph = 0;
        const Exchange* in = &p.sc[cl & (NREP - 1)];
        uint2* pub = p.sc[m >> 1].stat + 16 * b + 2 * (r ^ (2 * (b & 3))) + (m & 1);
        uint32_t* cnt_s = &p.sc[t].cnt[b & 96];
        pin(pub); pin(cnt_s);
        if (tid < 32) sts32(sb + OFF_XCH + 4 * tid, 0);
        const uint32_t wbuf = sb + OFF_LN + a * 1024, part = sb + OFF_LN + 4096;
        {
            sts128(wbuf + 16 * lane, wq.x, wq.y, wq.z, wq.w);
            sts128(wbuf + 512 + 16 * lane, 0x3f803f80u, 0x3f803f80u, 0x3f803f80u, 0x3f803f80u);
            float wsum = ((bf_lo(wq.x) + bf_hi(wq.x)) + (bf_lo(wq.y) + bf_hi(wq.y))) + ((bf_lo(wq.z) + bf_hi(wq.z)) + (bf_lo(wq.w) + bf_hi(wq.w)));
#pragma unroll
            for (int o = 16; o; o >>= 1) wsum += __shfl_xor_sync(0xffffffffu, wsum, o);
            sts32f(part + 1024 + 4 * a, wsum);
            uint32_t wf[4][4];
#pragma unroll
            for (int i = 0; i < 4; i++) ldsm4(wf[i], wbuf + ((uint32_t)(r - 1) < 2u ? 16 * (r - 1) : 512) + 32 * m + 128 * i);
            uint32_t ra = sb + OFF_VT + r * ROW_PITCH + 512 * a + 16 * m, pa = part + a * 256 + g * 16;
            cluster_wait();
            STAMP(22);
#pragma unroll 1
            for (int hf = 0; hf < 2; hf++) {
                mbar_wait(bar0 + 8 * B_ROW + 16 * hf, 0);
                mbar_wait(bar0 + 8 * B_ROW + 16 * hf + 8, 0);
                STAMP(23);
                uint32_t x[8][4];
                float cs[2][4], q[8][4];
#pragma unroll
                for (int i = 0; i < 40; i++) (i < 8 ? cs[i >> 2 & 1] : q[(i - 8) >> 2 & 7])[i & 3] = 0.f;
#pragma unroll
                for (int k = 0; k < 8; k++) ldsm4(x[k], ra + k * 64);
                const bool more = __any_sync(0xffffffffu, after_all(x, p.zero));
#pragma unroll 1
                do {
#pragma unroll
                    for (int k = 0; k < 8; k++) {
                        mma_v(cs[k & 1], x[k], wf[k >> 1][2 * (k & 1)], wf[k >> 1][2 * (k & 1) + 1]);
#pragma unroll
                        for (int i = 0; i < 4; i++) mma_bf16_k8(q[4 * (k & 1) + i], x[k][i & 2], x[k][i | 1], x[k][i]);
                    }
                } while (more);
                const float c2 = cs[0][2] + cs[1][2];
                if (t == 0) sts64f(pa, (cs[0][0] + cs[1][0]) + c2, cs[0][1] + cs[1][1]);
                if (t == 1) sts32f(pa + 12, c2);
                const float e0 = ((q[0][0] + q[2][0]) + (q[4][0] + q[6][0])) + ((q[1][2] + q[3][2]) + (q[5][2] + q[7][2]));
                const float e1 = ((q[0][1] + q[2][1]) + (q[4][1] + q[6][1])) + ((q[1][3] + q[3][3]) + (q[5][3] + q[7][3]));
                if (t == (g >> 1)) sts32f(pa + 8, (g & 1) ? e1 : e0);
                ra += 8 * ROW_PITCH; pa += 128;
            }
        }
        STAMP(31);
        named_sync(1, 128);
        if (a == 0) {
            const uint32_t pa = part + (lane & 15) * 16;
            const float4 p0 = lds128f(pa), p1 = lds128f(pa + 256), p2 = lds128f(pa + 512), p3 = lds128f(pa + 768), ws = lds128f(part + 1024);
            const float mu = ((p0.x + p1.x) + (p2.x + p3.x)) * (1.f / DM);
            float var = ((p0.z + p1.z) + (p2.z + p3.z)) * (1.f / DM) - mu * mu;
            const bool centred = __any_sync(0xffffffffu, !(mu * mu <= 64.f * var));
            if (centred) var = centred_var(sb + OFF_VT, mu, lane);
            const float ri = rcpf(bf_round(sqrtaf(bf_round(bf_round(var) + 1e-5f))));
            const uint32_t s0 = pack_bf16(mu, ri), s1 = (pack_bf16(ri - bf_hi(s0), 0.f) & 0xfffcu) | (tag & 3);
            float sc = ((((p0.y + p1.y) + (p2.y + p3.y)) + ((p0.w + p1.w) + (p2.w + p3.w))) - bf_lo(s0) * ((ws.x + ws.y) + (ws.z + ws.w))) * ri;
            if (centred) sc = centred_score(sb + OFF_VT, sb + OFF_LN, s0, s1, lane);
            const uint32_t sb16 = pack_bf16(0.f, sc);
            const uint32_t s2 = s1 | (sb16 ^ (((uint32_t)((int)sb16 >> 31) & 0x7fff0000u) | 0x80000000u));
            st_relaxed_64(pub, s0, s2);
            st_relaxed_64(pub + 2 * sizeof(Exchange) / 8, s0, s2);
            if (lane < NREP) red_add(cnt_s, 1);
            if (elect_one()) mbar_arrive(bar0 + 8 * B_LN);
            STAMP(9); GSTAMP(25);
        }
        const uint32_t slot0 = sb + OFF_RING + a * 8192, slot1 = sb + slot_off(4 + a), slot2 = sb + slot_off(8 + a), fbar = bar0 + 8 * (B_FULL + a);
        uint32_t mine, row[2];
        {
            uint32_t q[16];
            named_sync(1, 128);
            wait_count(&in->cnt[32 * a], 32 * tag - FEW_ST);
            STAMP(41);
#pragma unroll 1
            for (uint32_t it = 0;; spin_guard(it)) {
                if (elect_one()) {
                    mbar_expect_tx(abar, 4096);
                    bulk_g2s(sb + OFF_ST + 4096 * a, in->stat + 512 * a, 4096, abar);
                }
                mbar_wait(abar, aph);
                aph ^= 1;
                uint32_t bad = 0;
#pragma unroll
                for (int n = 0; n < 8; n++) {
                    const uint4 u = lds128v(sb + OFF_ST + 4096 * a + 512 * n + 16 * lane);
                    q[2 * n] = u.y; q[2 * n + 1] = u.w;
                    bad = or_xor(bad, u.y, tag);
                }
                const bool ok = __all_sync(0xffffffffu, (bad & 3) == 0);
                asm volatile("{ .reg .pred p; setp.ne.u32 p, %1, 0; @p mbarrier.arrive.shared::cta.b64 _, [%0]; }" ::"r"(bar0 + 8 * (B_ST + a)), "r"((uint32_t)(ok && lane == 0)) : "memory");
                if (ok) break;
            }
            STAMP(8);
            const uint32_t inv = 2047 - 512 * a - 16 * m - (r ^ (2 * m));
#pragma unroll
            for (int i = 0; i < 16; i++) asm("lop3.b32 %0, %0, %1, %2, 0x9b;" : "+r"(q[i]) : "r"(inv), "r"(0xffff0000u | (64 * (i >> 1) + 8 * (i & 1))));
            auto below = [&](uint32_t x) {
                uint32_t d[4];
#pragma unroll
                for (int i = 0; i < 16; i++) d[i & 3] = i < 4 ? x + q[i] : min(d[i & 3], x + q[i]);
                d[0] = min(min(d[0], d[1]), min(d[2], d[3]));
                return d[0] < x ? x - 1 - d[0] : 0u;
            };
            const uint32_t mx0 = ~min(min(min(min(q[0], q[1]), min(q[2], q[3])), min(min(q[4], q[5]), min(q[6], q[7]))),
                                      min(min(min(q[8], q[9]), min(q[10], q[11])), min(min(q[12], q[13]), min(q[14], q[15]))));
            const uint32_t gm = __reduce_max_sync(0xffffffffu, mx0 == __reduce_max_sync(0xffffffffu, mx0) ? 0u : mx0);
            if (lane == 0) sts32(misc + 16 + 4 * a, gm);
            named_sync(1, 128);
            STAMP(42);
            const uint4 t0 = lds128(misc + 16);
            uint32_t tau = min(min(t0.x, t0.y), min(t0.z, t0.w));
            uint32_t mx = mx0, cnt = 0, bal;
            const uint32_t list = sb + OFF_XCH + 32 * a;
#pragma unroll 1
            while ((bal = __ballot_sync(0xffffffffu, mx >= tau)) != 0) {
                const uint32_t pos = cnt + __popc(bal & ((1u << lane) - 1u));
                cnt += __popc(bal);
                if (cnt > 8) break;
                if (mx >= tau) sts32(list + 4 * pos, mx);
                mx = below(mx);
            }
            if (cnt > 8) {
                mx = mx0;
#pragma unroll 1
                for (int j = 0; j < 8; j++) {
                    const uint32_t top = __reduce_max_sync(0xffffffffu, mx), nx = below(mx);
                    if (mx == top) { sts32(list + 4 * j, mx); mx = nx; }
                }
            }
            named_sync(1, 128);
            STAMP(43);
            const uint32_t k = lds32(sb + OFF_XCH + 4 * lane);
            uint32_t rk[4] = {misc + 48, 0, 0, 0};
#pragma unroll
            for (int j = 0; j < 8; j++) {
                const uint4 c = lds128(sb + OFF_XCH + 16 * j);
                asm("{ .reg .pred p, q, r, s; setp.gt.u32 p, %4, %8; setp.gt.u32 q, %5, %8; setp.gt.u32 r, %6, %8; setp.gt.u32 s, %7, %8;\n\t"
                    "@p add.u32 %0, %0, 8; @q add.u32 %1, %1, 8; @r add.u32 %2, %2, 8; @s add.u32 %3, %3, 8; }"
                    : "+r"(rk[0]), "+r"(rk[1]), "+r"(rk[2]), "+r"(rk[3]) : "r"(c.x), "r"(c.y), "r"(c.z), "r"(c.w), "r"(k));
            }
            rk[0] = (rk[0] + rk[1]) + (rk[2] + rk[3]);
            if (rk[0] < misc + 112) sts32(rk[0], k);
            __syncwarp();
            mine = lds32(misc + 48 + 8 * g);
            const uint4 two = lds128v(misc + 48 + 16 * a);
            row[0] = two.x; row[1] = two.z;
            mbar_wait(bar0 + 8 * B_V, 0);
        }
        STAMP(11);
        const int tok = 2047 - (int)(mine & 2047);
        const uint32_t xs = sb + OFF_XT + (h ^ 1) * 32768 + 16384;
        if (has_gu) {
            if (elect_one()) {
                mbar_expect_tx(abar, 2048);
#pragma unroll
                for (int j = 0; j < 2; j++) bulk_g2s(xs + (2 * a + j) * 1040, p.u + (size_t)(2047 - (row[j] & 2047)) * DM + 512 * h, 1024, abar);
            }
        }
        STAMP(44);
        uint32_t af[20][4], ko = sb + (m & 1) * 4096 + (r + ((m >> 1) << 3)) * 128 + ((r ^ (4 * h) ^ a) << 4);
        auto load_level = [&](int c) {
#pragma unroll
            for (int j = 0; j < 4; j++) {
                mbar_wait(bar0 + 8 * (B_FULL + 4 * (c % 3) + j), c / 3);
#pragma unroll
                for (int i = 0; i < 4; i++) ldsm4t(af[8 * (i >> 1) + 2 * j + (i & 1)], (ko ^ ((i & 1) << 6)) + slot_off(4 * (c % 3) + j) + (i >> 1) * 2048);
            }
            STAMP(36 + c);
            __syncwarp();
            if (c < 3 && lane < 4) mbar_arrive(bar0 + 8 * (B_FREE + 4 * c + lane));
        };
        const uint2 st = ld_relaxed_64(in->stat + (tok & ~15) + 2 * ((tok & 7) ^ ((tok >> 3) & 6)) + ((tok >> 3) & 1));
        if (has_gu) load_level(0);
        if (a == 0 && t == 0) sts32f(misc + 52 + 8 * g, bf_hi(st.x) + bf_lo(st.y));
        if (a == 0) STAMP(45);
        if (has_gu) {
            const uint32_t mean = __shfl_sync(0xffffffffu, st.x, 8 * a + 4 * (lane >> 4)), xr = xs + (2 * a + (lane >> 4)) * 1040 + 16 * (lane & 15);
            mbar_wait(abar, aph);
            aph ^= 1;
            STAMP(46);
            uint4 x[4];
#pragma unroll
            for (int j = 0; j < 4; j++) x[j] = lds128(xr + 256 * j);
#pragma unroll
            for (int j = 0; j < 4; j++) sts128(xr + 256 * j, bsub2_lo(x[j].x, mean), bsub2_lo(x[j].y, mean), bsub2_lo(x[j].z, mean), bsub2_lo(x[j].w, mean));
            if (elect_one()) mbar_expect_tx(abar, 512);
            named_sync(1, 128);
        }
        if (lane < (has_gu ? 2 : 4)) mbar_arrive_peer(mapa(bar0 + 8 * (lane & 2 ? B_XFREE : B_SFREE), lane & 1));
        if (has_gu) {
            STAMP(12);
            float gacc[8][4];
#pragma unroll
            for (int i = 0; i < 8; i++) { gacc[i][0] = gacc[i][1] = gacc[i][2] = gacc[i][3] = 0.f; }
            uint32_t* pubh = reinterpret_cast<uint32_t*>(&p.sc[0].h[b * 32 + 8 * a + (g ^ (2 * a))]) + t;
            uint32_t* cnt_h = &p.sc[t].cnt[32 * (b / 28) + 1 + ((b / 14) & 1)];
            uint32_t xb = xs + r * 1040 + m * 16;
            uint32_t xch = sb + OFF_XCH + 16 * tid, tagm = t == 3 ? 1u : 0u;
            pin(pubh); pin(cnt_h); pin(xb); pin(xch); pin(tagm);
            const float r0 = lds32f(misc + 52 + 16 * t), r1 = lds32f(misc + 60 + 16 * t);
#pragma unroll
            for (int c = 0; c < 4; c++) {
#pragma unroll
                for (int j = 0; j < 4; j++) ldsm4(af[16 + j], xb + 256 * c + 64 * j);
                if (c == 3) mbar_wait(bar0 + 8 * B_SFREE, 0);
                if (c) load_level(c);
                const bool more = __any_sync(0xffffffffu, (c ? af[6][3] | af[7][3] | af[14][3] | af[15][3] : af[16][3] | af[17][3] | af[18][3] | af[19][3]) & p.zero);
#pragma unroll 1
                do {
#pragma unroll
                    for (int i = 0; i < 16; i++) mma_v(gacc[i & 7], af[i], af[16 + ((i >> 1) & 3)][2 * (i >> 3)], af[16 + ((i >> 1) & 3)][2 * (i >> 3) + 1]);
                } while (more);
            }
            STAMP(13);
            float own[4], oth[4];
#pragma unroll
            for (int j = 0; j < 4; j++) oth[j] = (gacc[1][j] + gacc[3][j]) + (gacc[5][j] + gacc[7][j]);
            st_async128(mapa(xch, h ^ 1), __float_as_uint(oth[0]), __float_as_uint(oth[1]), __float_as_uint(oth[2]), __float_as_uint(oth[3]), mapa(abar, h ^ 1));
            STAMP(56);
#pragma unroll
            for (int j = 0; j < 4; j++) own[j] = ((gacc[0][j] + gacc[2][j]) + (gacc[4][j] + gacc[6][j])) * ((j & 1) ? r1 : r0);
            mbar_wait(abar, aph);
            aph ^= 1;
            STAMP(57);
            const float4 o4 = lds128f(xch);
            const float g0 = bf_round(fmaf(o4.x, r0, own[0])), g1 = bf_round(fmaf(o4.y, r1, own[1]));
            const float h0 = bf_round(g0 * rcpf(1.f + ex2f(-1.4426950408889634f * g0))) * bf_round(fmaf(o4.z, r0, own[2]));
            const float h1 = bf_round(g1 * rcpf(1.f + ex2f(-1.4426950408889634f * g1))) * bf_round(fmaf(o4.w, r1, own[3]));
            uint32_t hw;
            asm volatile("movmatrix.sync.aligned.m8n8.trans.b16 %0, %1;" : "=r"(hw) : "r"(pack_bf16(h0, h1)));
            hw = (hw & ~tagm) | (tag & tagm);
#pragma unroll
            for (int j = 0; j < NREP; j++) st_relaxed_32(pubh + j * (sizeof(Exchange) / 4), hw);
            if (lane < NREP) red_add(cnt_h, b % 14 < 2 ? 2 : 1);
            if (lane < 2) mbar_arrive_peer(mapa(bar0 + 8 * B_XFREE, lane));
            named_sync(1, 128);
            STAMP(14);
        }
        float dacc[4];
        const int tk = ((tid >> 1) & 6) | (tid & 1);
        uint32_t ro = 4 * tid, red = sb + tab_off(tk) + T_RED + 4 * ((tid >> 4) + 4 * (tid & 2));
        if (!has_gu) named_sync(1, 128);
        const float sg = bf_round(rcpf(1.f + ex2f(-1.4426950408889634f * __uint_as_float(unorder_key(lds32(misc + 48 + 8 * tk) >> 16) << 16))));
        pin(ro); pin(red);
        mbar_wait(bar0 + 8 * B_XFREE, 0);
        {
            uint32_t wo = (r + ((m >> 1) << 3)) * 32 + (((m & 1) ^ (r >> 2)) << 4), af[14][4];
            uint32_t ho = slot0 + 128 * t + 16 * (g ^ (2 * t));
            pin(wo); pin(ho);
            float d[7][4];
#pragma unroll
            for (int i = 0; i < 7; i++) { d[i][0] = d[i][1] = d[i][2] = d[i][3] = 0.f; }
            auto first_half = [&]() {
                mbar_wait(fbar + 32, has_gu);
#pragma unroll
                for (int j = 0; j < 14; j++) ldsm4t(af[j], slot1 + wo + j * 512);
            };
            auto fetch = [&]() {
                if (elect_one()) {
                    mbar_expect_tx(abar, 7168);
                    bulk_g2s(slot0, &in->h[(56 * h + 14 * a) * 32], 7168, abar);
                }
            };
            wait_count(&in->cnt[64 * h + 32 * (a >> 1) + 1 + (a & 1)], 64 * tag - FEW_H);
            STAMP(33);
            fetch();
            if (a == 3 && elect_one()) mbar_arrive(bar0 + 8 * B_LN);
            first_half();
            mbar_wait(abar, aph);
#pragma unroll
            for (int s = 0; s < 2; s++) {
                if (s) {
                    mbar_wait(fbar + 64, has_gu);
#pragma unroll
                    for (int j = 0; j < 14; j++) ldsm4t(af[j], slot2 + wo + j * 512);
                }
                uint4 hq[7];
#pragma unroll 1
                for (uint32_t it = 0;; spin_guard(it)) {
                    uint32_t bad = 0;
#pragma unroll
                    for (int j = 0; j < 7; j++) { hq[j] = lds128(ho + 512 * (7 * s + j)); bad = or_xor(bad, hq[j].w, tag); }
                    if (__all_sync(0xffffffffu, (bad & 1) == 0)) break;
                    fetch();
                    aph ^= 1;
                    mbar_wait(abar, aph);
                }
                if (s == 0) STAMP(15);
#pragma unroll
                for (int j = 0; j < 14; j++) {
                    const uint4 q = hq[j >> 1];
                    mma_v(d[j % 7], af[j], (j & 1) ? q.z : q.x, (j & 1) ? q.w : q.y);
                }
            }
#pragma unroll
            for (int j = 0; j < 4; j++) dacc[j] = ((d[0][j] + d[1][j]) + (d[2][j] + d[3][j])) + ((d[4][j] + d[5][j]) + d[6][j]);
        }
        STAMP(16);
        {
            st_async128(mapa(sb + OFF_XCH + 16 * tid, h ^ 1), __float_as_uint(dacc[0]), __float_as_uint(dacc[1]), __float_as_uint(dacc[2]), __float_as_uint(dacc[3]),
                        mapa(bar0 + 8 * B_RED, h ^ 1));
            sts128f(slot0 + 7680 + lane * 16, dacc);
            __syncwarp();
            if (elect_one()) mbar_arrive(bar0 + 8 * B_RED);
            mbar_wait(bar0 + 8 * B_RED, 0);
            const uint32_t b0 = sb + OFF_RING + 7680 + ro, b1 = sb + OFF_XCH + ro;
            const float y = ((lds32f(b0) + lds32f(b0 + 8192)) + (lds32f(b0 + 16384) + lds32f(b0 + 24576))) +
                            ((lds32f(b1) + lds32f(b1 + 512)) + (lds32f(b1 + 1024) + lds32f(b1 + 1536)));
            sts32f(red, bf_round(y) * sg);
            __syncwarp();
            if (elect_one()) mbar_arrive(bar0 + 8 * B_UPD);
        }
        STAMP(17); GSTAMP(29);
    }
}

typedef CUresult (*EncodeFn)(CUtensorMap*, CUtensorMapDataType, cuuint32_t, void*, const cuuint64_t*, const cuuint64_t*,
                             const cuuint32_t*, const cuuint32_t*, CUtensorMapInterleave, CUtensorMapSwizzle,
                             CUtensorMapL2promotion, CUtensorMapFloatOOBfill);

void make_map(EncodeFn enc, CUtensorMap* m, const void* ptr, uint64_t cols, uint64_t rows, uint32_t bc, uint32_t br,
              CUtensorMapSwizzle sw, CUtensorMapL2promotion pr) {
    cuuint64_t dims[2] = {cols, rows};
    cuuint64_t str[1] = {cols * 2};
    cuuint32_t box[2] = {bc, br};
    cuuint32_t es[2] = {1, 1};
    enc(m, CU_TENSOR_MAP_DATA_TYPE_BFLOAT16, 2, const_cast<void*>(ptr), dims, str, box, es, CU_TENSOR_MAP_INTERLEAVE_NONE, sw, pr,
        CU_TENSOR_MAP_FLOAT_OOB_FILL_NONE);
}
void make_perm_map(EncodeFn enc, CUtensorMap* m, const void* ptr, CUtensorMapL2promotion pr) {
    cuuint64_t dims[5] = {DM, 2, 4, 4, FF / 32};
    cuuint64_t str[4] = {DM * 2, 8 * DM * 2, 2 * DM * 2, 32 * DM * 2};
    cuuint32_t box[5] = {16, 2, 4, 4, 7};
    cuuint32_t es[5] = {1, 1, 1, 1, 1};
    enc(m, CU_TENSOR_MAP_DATA_TYPE_BFLOAT16, 5, const_cast<void*>(ptr), dims, str, box, es, CU_TENSOR_MAP_INTERLEAVE_NONE,
        CU_TENSOR_MAP_SWIZZLE_32B, pr, CU_TENSOR_MAP_FLOAT_OOB_FILL_NONE);
}
void make_tile_map(EncodeFn enc, CUtensorMap* m, const void* ptr) {
    cuuint64_t dims[4] = {DM, 4, 16, SEQ / 64};
    cuuint64_t str[3] = {16 * DM * 2, DM * 2, 64 * DM * 2};
    cuuint32_t box[4] = {16, 4, 2, 8};
    cuuint32_t es[4] = {1, 1, 1, 1};
    enc(m, CU_TENSOR_MAP_DATA_TYPE_BFLOAT16, 4, const_cast<void*>(ptr), dims, str, box, es, CU_TENSOR_MAP_INTERLEAVE_NONE,
        CU_TENSOR_MAP_SWIZZLE_32B, CU_TENSOR_MAP_L2_PROMOTION_NONE, CU_TENSOR_MAP_FLOAT_OOB_FILL_NONE);
}

}

extern "C" void kernel_launch(void* const* d_in, const int* in_sizes, int n_in, void* d_out, int out_size) {
    (void)in_sizes; (void)n_in; (void)out_size;
    static EncodeFn enc = nullptr;
    static void* scratch = nullptr;
    if (!enc) {
        void* fn = nullptr;
        cudaDriverEntryPointQueryResult q;
        cudaGetDriverEntryPoint("cuTensorMapEncodeTiled", &fn, cudaEnableDefault, &q);
        enc = (EncodeFn)fn;
        cudaGetSymbolAddress(&scratch, g_scratch);
        cudaFuncSetAttribute(fused_kernel, cudaFuncAttributeMaxDynamicSharedMemorySize, SMEM_BYTES);
    }
    Maps maps;
    make_tile_map(enc, &maps.u, d_in[0]);
    make_tile_map(enc, &maps.out, d_out);
    make_map(enc, &maps.wg, d_in[9], FF, DM, 64, 32, CU_TENSOR_MAP_SWIZZLE_128B, CU_TENSOR_MAP_L2_PROMOTION_L2_128B);
    make_map(enc, &maps.wu, d_in[10], FF, DM, 64, 32, CU_TENSOR_MAP_SWIZZLE_128B, CU_TENSOR_MAP_L2_PROMOTION_L2_128B);
    make_perm_map(enc, &maps.wd, d_in[11], CU_TENSOR_MAP_L2_PROMOTION_L2_64B);
    Ptrs p;
    p.sc = (Exchange*)scratch;
    p.u = (const __nv_bfloat16*)d_in[0];
    p.logA = (const __nv_bfloat16*)d_in[1];
    p.Aim = (const __nv_bfloat16*)d_in[2];
    p.Cre = (const __nv_bfloat16*)d_in[3];
    p.Cim = (const __nv_bfloat16*)d_in[4];
    p.ldt = (const __nv_bfloat16*)d_in[5];
    p.dsk = (const __nv_bfloat16*)d_in[6];
    p.wr = (const __nv_bfloat16*)d_in[8];
    p.out = (__nv_bfloat16*)d_out;
    p.zero = 0;
    fused_kernel<<<NCTA, NTHR, SMEM_BYTES, cudaStreamPerThread>>>(p, maps);
}
```

```cpp
#include <cuda_runtime.h>
#include <cuda_bf16.h>
#include <cuda_fp16.h>
#include <cuda.h>
#include <stdint.h>

namespace {

constexpr int SEQ = 2048, DM = 1024, NMODE = 128, FF = 3584;
constexpr int NCTA = 128, NTHR = 512;
constexpr int GU_CTAS = 112;
constexpr int NREP = 4;

constexpr int OFF_XT = 0;
constexpr int OFF_RING = 65536;
constexpr int OFF_PRIV = OFF_RING + 65536;
constexpr int OFF_VT = OFF_PRIV + 65536;
constexpr int VT_PAD = 32, VT_PLANE = VT_PAD + 2048, VT_PITCH = 2 * VT_PLANE, ROW_PITCH = 2064;
constexpr int OFF_BAR = OFF_VT + 8 * VT_PITCH;
constexpr int OFF_MISC = OFF_BAR + 384;
constexpr int OFF_XCH = OFF_MISC + 112;
constexpr int SMEM_BYTES = OFF_XCH + 2048;
constexpr int OFF_LN = OFF_RING + 7 * 8192;
constexpr int OFF_ST = OFF_RING + 6 * 8192;
static_assert(SMEM_BYTES <= 232448, "shared memory");

constexpr int B_ROW = 0, B_XT = 4, B_V = 5, B_LN = 6, B_SFREE = 7, B_XFREE = 8, B_RED = 10, B_UPD = 11, B_ST = 12, B_RECV = 16, B_FREE = 20, B_FULL = 32, B_AUX = 44, NBAR = 48;

constexpr int T_DENSE = 60;
constexpr int T_PATCH = 2208;
constexpr int T_R2 = 2368;
constexpr int T_R3 = 3296;

constexpr int T_RED = 4032;
__device__ __forceinline__ bool slot_priv(int s) { return (uint32_t)(s - 6) < 4u; }
__device__ __forceinline__ uint32_t slot_off(int s) { return slot_priv(s) ? OFF_PRIV + 4096 + (s & 3) * 16384 : OFF_RING + (s < 6 ? s : s - 4) * 8192; }
__device__ __forceinline__ uint32_t tab_off(int w) { return OFF_PRIV + w * 8192 + (w & 1) * 4096; }

constexpr uint32_t SPIN_LIMIT = 1u << 20;
#define ST_T0 2050
#define ST_PER 286
#define ST_PER2 320
#define LN_PAUSE 0xf0
#define FEW_ST 10
#define FEW_H 24

struct Exchange {
    uint2 stat[SEQ];
    uint4 h[GU_CTAS * 32];
    uint32_t cnt[4 * 32];
};
__device__ __align__(128) Exchange g_scratch[NREP];

struct Ptrs {
    const __nv_bfloat16 *logA, *Aim, *Cre, *Cim, *ldt, *u;
    const __nv_bfloat16 *dsk, *wr;
    Exchange* sc;
    __nv_bfloat16* out;
    uint32_t zero;
};
struct Maps {
    CUtensorMap u, out, wg, wu, wd;
};

#define STAMP(i) do { } while (0)
#define GSTAMP(i) do { } while (0)

__device__ __forceinline__ uint32_t s_u32(const void* p) { return (uint32_t)__cvta_generic_to_shared(p); }
__device__ __forceinline__ void mbar_init(uint32_t b, uint32_t n) {
    asm volatile("mbarrier.init.shared::cta.b64 [%0], %1;" ::"r"(b), "r"(n) : "memory");
}
__device__ __forceinline__ void mbar_expect_tx(uint32_t b, uint32_t bytes) {
    asm volatile("mbarrier.arrive.expect_tx.shared::cta.b64 _, [%0], %1;" ::"r"(b), "r"(bytes) : "memory");
}
__device__ __forceinline__ void mbar_arrive(uint32_t b) {
    asm volatile("mbarrier.arrive.shared::cta.b64 _, [%0];" ::"r"(b) : "memory");
}
__device__ __forceinline__ void mbar_arrive_n(uint32_t b, uint32_t n) {
    asm volatile("mbarrier.arrive.shared::cta.b64 _, [%0], %1;" ::"r"(b), "r"(n) : "memory");
}
__device__ __forceinline__ void mbar_arrive_peer(uint32_t b_cluster) {
    asm volatile("mbarrier.arrive.relaxed.cluster.shared::cluster.b64 _, [%0];" ::"r"(b_cluster) : "memory");
}
__device__ __forceinline__ void mbar_wait(uint32_t b, uint32_t parity) {
    asm volatile("{\n\t.reg .pred p;\n\t.reg .u32 c;\n\tmov.u32 c, 0;\n"
                 "W:\n\tmbarrier.try_wait.parity.shared::cta.b64 p, [%0], %1;\n\t@p bra D;\n\t"
                 "add.u32 c, c, 1;\n\tsetp.lt.u32 p, c, 1048576;\n\t@p bra W;\n\ttrap;\nD:\n\t}"
                 ::"r"(b), "r"(parity) : "memory");
}
__device__ __forceinline__ bool elect_one() {
    uint32_t p;
    asm volatile("{ .reg .pred P; elect.sync _|P, 0xffffffff; selp.u32 %0, 1, 0, P; }" : "=r"(p));
    return p != 0;
}
__device__ __forceinline__ uint32_t mapa(uint32_t a, uint32_t rank) {
    uint32_t r;
    asm("mapa.shared::cluster.u32 %0, %1, %2;" : "=r"(r) : "r"(a), "r"(rank));
    return r;
}
__device__ __forceinline__ void cluster_arrive() { asm volatile("barrier.cluster.arrive.relaxed.aligned;" ::: "memory"); }
__device__ __forceinline__ void cluster_wait() { asm volatile("barrier.cluster.wait.acquire.aligned;" ::: "memory"); }
__device__ __forceinline__ void tma_load_2d(uint32_t dst, const CUtensorMap* m, int c0, int c1, uint32_t bar) {
    asm volatile("cp.async.bulk.tensor.2d.shared::cluster.global.mbarrier::complete_tx::bytes [%0], [%1, {%3, %4}], [%2];"
                 ::"r"(dst), "l"(m), "r"(bar), "r"(c0), "r"(c1) : "memory");
}
__device__ __forceinline__ void tma_load_perm(uint32_t dst, const CUtensorMap* m, int c0, int blk, uint32_t bar) {
    asm volatile("cp.async.bulk.tensor.5d.shared::cluster.global.mbarrier::complete_tx::bytes [%0], [%1, {%3, %4, %4, %4, %5}], [%2];"
                 ::"r"(dst), "l"(m), "r"(bar), "r"(c0), "r"(0), "r"(blk) : "memory");
}
__device__ __forceinline__ void tma_load_tile(uint32_t dst, const CUtensorMap* m, int c0, int c2, int c3, uint32_t bar) {
    asm volatile("cp.async.bulk.tensor.4d.shared::cluster.global.mbarrier::complete_tx::bytes.multicast::cluster [%0], [%1, {%3, %4, %5, %6}], [%2], %7;"
                 ::"r"(dst), "l"(m), "r"(bar), "r"(c0), "r"(0), "r"(c2), "r"(c3), "h"((uint16_t)3) : "memory");
}
__device__ __forceinline__ void tma_store_tile(const CUtensorMap* m, uint32_t src, int c0, int c2, int c3) {
    asm volatile("cp.async.bulk.tensor.4d.global.shared::cta.bulk_group [%0, {%2, %3, %4, %5}], [%1];"
                 ::"l"(m), "r"(src), "r"(c0), "r"(0), "r"(c2), "r"(c3) : "memory");
    asm volatile("cp.async.bulk.commit_group;" ::: "memory");
}
__device__ __forceinline__ void bulk_g2s(uint32_t dst, const void* src, uint32_t bytes, uint32_t bar) {
    asm volatile("cp.async.bulk.shared::cluster.global.mbarrier::complete_tx::bytes [%0], [%1], %2, [%3];"
                 ::"r"(dst), "l"(src), "r"(bytes), "r"(bar) : "memory");
}
__device__ __forceinline__ void st_async128(uint32_t dst_cluster, uint32_t x, uint32_t y, uint32_t z, uint32_t w, uint32_t bar_cluster) {
    asm volatile("st.async.weak.shared::cluster.mbarrier::complete_tx::bytes.v4.b32 [%0], {%1,%2,%3,%4}, [%5];"
                 ::"r"(dst_cluster), "r"(x), "r"(y), "r"(z), "r"(w), "r"(bar_cluster) : "memory");
}
__device__ __forceinline__ void fence_async() { asm volatile("fence.proxy.async.shared::cta;" ::: "memory"); }
__device__ __forceinline__ void named_sync(int id, int n) { asm volatile("bar.sync %0, %1;" ::"r"(id), "r"(n) : "memory"); }

__device__ __forceinline__ void ldsm4(uint32_t* r, uint32_t a) {
    asm volatile("ldmatrix.sync.aligned.m8n8.x4.shared.b16 {%0,%1,%2,%3}, [%4];"
                 : "=r"(r[0]), "=r"(r[1]), "=r"(r[2]), "=r"(r[3]) : "r"(a));
}
__device__ __forceinline__ void ldsm4t(uint32_t* r, uint32_t a) {
    asm volatile("ldmatrix.sync.aligned.m8n8.x4.trans.shared.b16 {%0,%1,%2,%3}, [%4];"
                 : "=r"(r[0]), "=r"(r[1]), "=r"(r[2]), "=r"(r[3]) : "r"(a));
}
__device__ __forceinline__ void stsm4t(uint32_t a, uint32_t x, uint32_t y, uint32_t z, uint32_t w) {
    asm volatile("stmatrix.sync.aligned.m8n8.x4.trans.shared.b16 [%0], {%1,%2,%3,%4};"
                 ::"r"(a), "r"(x), "r"(y), "r"(z), "r"(w) : "memory");
}
__device__ __forceinline__ uint32_t lds32(uint32_t a) { uint32_t v; asm volatile("ld.shared.u32 %0, [%1];" : "=r"(v) : "r"(a)); return v; }
__device__ __forceinline__ float lds32f(uint32_t a) { float v; asm volatile("ld.shared.f32 %0, [%1];" : "=f"(v) : "r"(a)); return v; }
__device__ __forceinline__ uint2 lds64(uint32_t a) { uint2 v; asm volatile("ld.shared.v2.u32 {%0,%1}, [%2];" : "=r"(v.x), "=r"(v.y) : "r"(a)); return v; }
__device__ __forceinline__ uint4 lds128(uint32_t a) {
    uint4 v; asm volatile("ld.shared.v4.u32 {%0,%1,%2,%3}, [%4];" : "=r"(v.x), "=r"(v.y), "=r"(v.z), "=r"(v.w) : "r"(a)); return v;
}
__device__ __forceinline__ uint4 lds128v(uint32_t a) {
    uint4 v; asm volatile("ld.volatile.shared.v4.u32 {%0,%1,%2,%3}, [%4];" : "=r"(v.x), "=r"(v.y), "=r"(v.z), "=r"(v.w) : "r"(a)); return v;
}
__device__ __forceinline__ uint32_t or_xor(uint32_t a, uint32_t b, uint32_t c) {
    uint32_t r; asm("lop3.b32 %0, %1, %2, %3, 0xf6;" : "=r"(r) : "r"(a), "r"(b), "r"(c)); return r;
}
__device__ __forceinline__ float4 lds128f(uint32_t a) {
    float4 v; asm volatile("ld.shared.v4.f32 {%0,%1,%2,%3}, [%4];" : "=f"(v.x), "=f"(v.y), "=f"(v.z), "=f"(v.w) : "r"(a)); return v;
}
__device__ __forceinline__ void sts32(uint32_t a, uint32_t v) { asm volatile("st.shared.u32 [%0], %1;" ::"r"(a), "r"(v) : "memory"); }
__device__ __forceinline__ void sts32f(uint32_t a, float v) { asm volatile("st.shared.f32 [%0], %1;" ::"r"(a), "f"(v) : "memory"); }
__device__ __forceinline__ void sts64(uint32_t a, uint32_t x, uint32_t y) { asm volatile("st.shared.v2.u32 [%0], {%1,%2};" ::"r"(a), "r"(x), "r"(y) : "memory"); }
__device__ __forceinline__ void sts64f(uint32_t a, float x, float y) { asm volatile("st.shared.v2.f32 [%0], {%1,%2};" ::"r"(a), "f"(x), "f"(y) : "memory"); }
__device__ __forceinline__ void sts128(uint32_t a, uint32_t x, uint32_t y, uint32_t z, uint32_t w) {
    asm volatile("st.shared.v4.u32 [%0], {%1,%2,%3,%4};" ::"r"(a), "r"(x), "r"(y), "r"(z), "r"(w) : "memory");
}
__device__ __forceinline__ void sts128f(uint32_t a, const float* v) {
    asm volatile("st.shared.v4.f32 [%0], {%1,%2,%3,%4};" ::"r"(a), "f"(v[0]), "f"(v[1]), "f"(v[2]), "f"(v[3]) : "memory");
}
__device__ __forceinline__ uint4 ldg128(const void* p) {
    uint4 v; asm volatile("ld.global.nc.L1::no_allocate.v4.u32 {%0,%1,%2,%3}, [%4];" : "=r"(v.x), "=r"(v.y), "=r"(v.z), "=r"(v.w) : "l"(p)); return v;
}
__device__ __forceinline__ uint2 ldg64(const void* p) {
    uint2 v; asm volatile("ld.global.nc.L1::no_allocate.v2.u32 {%0,%1}, [%2];" : "=r"(v.x), "=r"(v.y) : "l"(p)); return v;
}
__device__ __forceinline__ uint32_t ldg16(const void* p) {
    uint32_t v; asm volatile("ld.global.nc.u16 %0, [%1];" : "=r"(v) : "l"(p)); return v;
}
__device__ __forceinline__ uint2 ld_relaxed_64(const void* p) {
    uint2 v; asm volatile("ld.relaxed.gpu.global.v2.u32 {%0,%1}, [%2];" : "=r"(v.x), "=r"(v.y) : "l"(p) : "memory"); return v;
}
__device__ __forceinline__ uint32_t ld_relaxed_32(const void* p) {
    uint32_t v; asm volatile("ld.relaxed.gpu.global.u32 %0, [%1];" : "=r"(v) : "l"(p) : "memory"); return v;
}
__device__ __forceinline__ void st_relaxed_64(void* p, uint32_t x, uint32_t y) {
    asm volatile("st.relaxed.gpu.global.v2.u32 [%0], {%1,%2};" ::"l"(p), "r"(x), "r"(y) : "memory");
}
__device__ __forceinline__ void st_relaxed_32(void* p, uint32_t v) {
    asm volatile("st.relaxed.gpu.global.u32 [%0], %1;" ::"l"(p), "r"(v) : "memory");
}
__device__ __forceinline__ void red_add(void* p, uint32_t v) { asm volatile("red.relaxed.gpu.global.add.u32 [%0], %1;" ::"l"(p), "r"(v) : "memory"); }
__device__ __forceinline__ uint32_t now_ns() { uint32_t t; asm volatile("mov.u32 %0, %%globaltimer_lo;" : "=r"(t) :: "memory"); return t; }
__device__ __forceinline__ void sleep_until(uint32_t t) {
#pragma unroll 1
    for (int left; (left = (int)(t - now_ns())) > 0;) __nanosleep(left >> 1);
}
__device__ __forceinline__ void spin_guard(uint32_t& it) { if (++it > SPIN_LIMIT) __trap(); }
__device__ __forceinline__ void wait_count(const uint32_t* p, uint32_t target) {
#pragma unroll 1
    for (uint32_t it = 0; __any_sync(0xffffffffu, (int)(ld_relaxed_32(p) - target) < 0); spin_guard(it)) { }
}
__device__ __forceinline__ void mma_bf16_k8(float* c, uint32_t a0, uint32_t a1, uint32_t b0) {
    asm("mma.sync.aligned.m16n8k8.row.col.f32.bf16.bf16.f32 {%0,%1,%2,%3}, {%4,%5}, {%6}, {%0,%1,%2,%3};"
                 : "+f"(c[0]), "+f"(c[1]), "+f"(c[2]), "+f"(c[3]) : "r"(a0), "r"(a1), "r"(b0));
}
__device__ __forceinline__ void mma_v(float* c, const uint32_t* a, uint32_t b0, uint32_t b1) {
    asm volatile("mma.sync.aligned.m16n8k16.row.col.f32.bf16.bf16.f32 {%0,%1,%2,%3}, {%4,%5,%6,%7}, {%8,%9}, {%0,%1,%2,%3};"
                 : "+f"(c[0]), "+f"(c[1]), "+f"(c[2]), "+f"(c[3]) : "r"(a[0]), "r"(a[1]), "r"(a[2]), "r"(a[3]), "r"(b0), "r"(b1));
}
__device__ __forceinline__ void mma_bf16_z(float* c, uint32_t a0, uint32_t a1, uint32_t a2, uint32_t a3, uint32_t b0, uint32_t b1) {
    asm volatile("mma.sync.aligned.m16n8k16.row.col.f32.bf16.bf16.f32 {%0,%1,%2,%3}, {%4,%5,%6,%7}, {%8,%9}, {%10,%10,%10,%10};"
        : "=f"(c[0]), "=f"(c[1]), "=f"(c[2]), "=f"(c[3]) : "r"(a0), "r"(a1), "r"(a2), "r"(a3), "r"(b0), "r"(b1), "f"(0.f));
}
__device__ __forceinline__ void mma_f16(float* c, uint32_t a0, uint32_t a1, uint32_t a2, uint32_t a3, uint32_t b0, uint32_t b1) {
    asm("mma.sync.aligned.m16n8k16.row.col.f32.f16.f16.f32 {%0,%1,%2,%3}, {%4,%5,%6,%7}, {%8,%9}, {%0,%1,%2,%3};"
                 : "+f"(c[0]), "+f"(c[1]), "+f"(c[2]), "+f"(c[3]) : "r"(a0), "r"(a1), "r"(a2), "r"(a3), "r"(b0), "r"(b1));
}
__device__ __forceinline__ uint32_t pack_bf16(float lo, float hi) {
    uint32_t r; asm("cvt.rn.bf16x2.f32 %0, %1, %2;" : "=r"(r) : "f"(hi), "f"(lo)); return r;
}
__device__ __forceinline__ uint32_t pack_v(float lo, float hi) {
    uint32_t r; asm volatile("cvt.rn.bf16x2.f32 %0, %1, %2;" : "=r"(r) : "f"(hi), "f"(lo)); return r;
}
__device__ __forceinline__ uint32_t pack_w(float lo, float hi) {
    uint32_t r; asm volatile("cvt.rn.satfinite.bf16x2.f32 %0, %1, %2;" : "=r"(r) : "f"(hi), "f"(lo)); return r;
}
template <int N> __device__ __forceinline__ uint32_t after_all(const uint32_t (&f)[N][4], uint32_t zero) {
    uint32_t d[3] = {0, 0, 0};
#pragma unroll
    for (int i = 0; i < N; i++) d[i % 3] |= f[i][3];
    return (d[0] | d[1] | d[2]) & zero;
}
__device__ __forceinline__ void pin(uint32_t& x) { asm volatile("" : "+r"(x)); }
template <class T> __device__ __forceinline__ void pin(T*& x) { asm volatile("" : "+l"(x)); }
__device__ __forceinline__ uint32_t pack_f16(float lo, float hi) {
    uint32_t r; asm("cvt.rn.f16x2.f32 %0, %1, %2;" : "=r"(r) : "f"(hi), "f"(lo)); return r;
}
__device__ __forceinline__ float bf_lo(uint32_t v) { return __uint_as_float(v << 16); }
__device__ __forceinline__ float bf_hi(uint32_t v) { return __uint_as_float(v & 0xffff0000u); }
__device__ __forceinline__ float bf_round(float x) { return __uint_as_float(pack_bf16(0.f, x)); }
__device__ __forceinline__ uint32_t badd2(uint32_t a, uint32_t b) { uint32_t r; asm("add.rn.bf16x2 %0, %1, %2;" : "=r"(r) : "r"(a), "r"(b)); return r; }
__device__ __forceinline__ uint32_t bsub2_lo(uint32_t a, uint32_t b) {
    uint32_t r; asm("{ .reg .b16 m, h; .reg .b32 m2; mov.b32 {m, h}, %2; mov.b32 m2, {m, m}; sub.rn.bf16x2 %0, %1, m2; }" : "=r"(r) : "r"(a), "r"(b)); return r;
}
__device__ __forceinline__ uint32_t bmax2(uint32_t a, uint32_t b) { uint32_t r; asm("max.bf16x2 %0, %1, %2;" : "=r"(r) : "r"(a), "r"(b)); return r; }
__device__ __forceinline__ uint32_t normalize2(uint32_t x, uint32_t s0, uint32_t s1) {
    uint32_t r;
    asm("{ .reg .b16 m, h, l, k; .reg .b32 m2, h2, l2, d, t;\n\t"
        "mov.b32 {m, h}, %2; mov.b32 {l, k}, %3; mov.b32 m2, {m, m}; mov.b32 h2, {h, h}; mov.b32 l2, {l, l};\n\t"
        "sub.rn.bf16x2 d, %1, m2; mul.rn.bf16x2 t, d, l2; fma.rn.bf16x2 %0, d, h2, t; }" : "=r"(r) : "r"(x), "r"(s0), "r"(s1));
    return r;
}
__device__ __forceinline__ float rcpf(float x) { float r; asm("rcp.approx.ftz.f32 %0, %1;" : "=f"(r) : "f"(x)); return r; }
__device__ __forceinline__ float sqrtaf(float x) { float r; asm("sqrt.approx.ftz.f32 %0, %1;" : "=f"(r) : "f"(x)); return r; }
__device__ __forceinline__ float ex2f(float x) { float r; asm("ex2.approx.ftz.f32 %0, %1;" : "=f"(r) : "f"(x)); return r; }

__device__ __forceinline__ int tok_off(int t) { return ((t >> 3) & 1) * VT_PLANE + (t >> 4) * 16 + (t & 7) * 2; }

__device__ __forceinline__ uint32_t unorder_key(uint32_t k16) { return k16 ^ ((k16 & 0x8000u) ? 0x8000u : 0xffffu); }

struct cplx { float r, i; };
struct hc { uint32_t r, i; };
template <bool CONJ> __device__ __forceinline__ cplx csq(cplx a) {
    float im;
    asm("{ .reg .f32 t; mul.ftz.f32 t, %1, %2; mul.ftz.f32 %0, t, 0f40000000; }" : "=f"(im) : "f"(CONJ ? -a.r : a.r), "f"(a.i));
    return {fmaf(a.r, a.r, -(a.i * a.i)), im};
}
__device__ __forceinline__ cplx cexpp(float a2, float ai) {
    float m = ex2f(a2), s, c;
    __sincosf(ai, &s, &c);
    return {m * c, m * s};
}
__device__ __forceinline__ __half2 as_h2(uint32_t x) { return *reinterpret_cast<__half2*>(&x); }
__device__ __forceinline__ uint32_t as_u(__half2 x) { return *reinterpret_cast<uint32_t*>(&x); }
__device__ __forceinline__ hc hmul(hc a, hc b) {
    return {as_u(__hfma2(as_h2(a.r), as_h2(b.r), __hneg2(__hmul2(as_h2(a.i), as_h2(b.i))))),
            as_u(__hfma2(as_h2(a.r), as_h2(b.i), __hmul2(as_h2(a.i), as_h2(b.r))))};
}
__device__ __forceinline__ hc hpack(cplx a, cplx b) { return {pack_f16(a.r, b.r), pack_f16(a.i, b.i)}; }
__device__ __forceinline__ void sts16(uint32_t a, uint32_t v) { asm volatile("st.shared.u16 [%0], %1;" ::"r"(a), "r"(v) : "memory"); }

struct KgenAddr {
    uint32_t l, h, m2, m3, m4, z, w, wz;
    __device__ __forceinline__ KgenAddr(uint32_t scr, int lane) {
        const int g = lane >> 2, t = lane & 3;
        const uint32_t rec = scr + t * 480;
        l = rec + 16 * g; h = rec + 128 + 8 * g; m2 = rec + 192 + 8 * (g & 1); m3 = rec + 208 + 4 * (g & 2); m4 = rec + 224 + 2 * (g & 4);
        z = scr + 7680 + 16 * t; w = scr + 240 * lane; wz = scr + 7680 + 8 * lane;
        pin(l); pin(h); pin(m2); pin(m3); pin(m4); pin(z); pin(w); pin(wz);
    }
    __device__ __forceinline__ uint32_t any() const { return (l | h | m2) | (m3 | m4 | z) | (w | wz); }
};
template <class Hook, class Hook2>
__device__ __forceinline__ void kgen(const KgenAddr& ad, uint32_t tab, int lane, uint2 la, uint2 aim, uint2 cre, uint2 cim, float dt, float skip, int dch, Hook main_done, Hook2 half_done) {
    const int g = lane >> 2, t = lane & 3;
    const float dt2 = 2.f * dt;
    const uint32_t am = bmax2(bmax2(cre.x & 0x7fff7fffu, cre.y & 0x7fff7fffu), bmax2(cim.x & 0x7fff7fffu, cim.y & 0x7fff7fffu));
    const float mx = dt2 * fmaxf(bf_lo(am), bf_hi(am));
    const uint32_t eb = min(max(__reduce_max_sync(0xffffffffu, __float_as_uint(mx)) >> 23, 1u), 252u);
    const float cscale = dt2 * __uint_as_float((253u - eb) << 23);
    const float scale_inv = __uint_as_float((eb + 1u) << 23);
    float k0 = (bf_lo(cre.x) + bf_hi(cre.x)) + (bf_lo(cre.y) + bf_hi(cre.y));
#pragma unroll
    for (int o = 16; o; o >>= 1) k0 += __shfl_xor_sync(0xffffffffu, k0, o);
    const float ndt = -1.4426950408889634f * dt;
    STAMP(40);

    float acc[5][4];
#pragma unroll
    for (int i = 0; i < 5; i++) { acc[i][0] = acc[i][1] = acc[i][2] = acc[i][3] = 0.f; }

#pragma unroll
    for (int bb = 0; bb < 2; bb++) {
        cplx z[2][11], cz[2];
#pragma unroll
        for (int e = 0; e < 2; e++) {
            const float lg = e ? bf_hi(la.x) : bf_lo(la.x), ai = (e ? bf_hi(aim.x) : bf_lo(aim.x)) * dt;
            const float cr = (e ? bf_hi(cre.x) : bf_lo(cre.x)) * cscale, ci = (e ? bf_hi(cim.x) : bf_lo(cim.x)) * cscale;
            const float a2 = bf_round(ex2f(lg * 1.4426950408889634f)) * ndt;
            z[e][0] = cexpp(a2, ai);
            z[e][5] = cexpp(a2 * 32.f, ai * -32.f);
#pragma unroll
            for (int i = 1; i < 11; i++) if (i != 5) z[e][i] = (i == 3 || i == 7) ? csq<true>(z[e][i - 1]) : csq<false>(z[e][i - 1]);
            cz[e] = {fmaf(cr, z[e][0].r, -(ci * z[e][0].i)), fmaf(cr, z[e][0].i, ci * z[e][0].r)};
        }
        la.x = la.y; aim.x = aim.y; cre.x = cre.y; cim.x = cim.y;
        const hc z1 = hpack(z[0][0], z[1][0]), z2 = hpack(z[0][1], z[1][1]), z4 = hpack(z[0][2], z[1][2]);
        hc L[8], H[8];
        L[1] = hpack(z[0][3], z[1][3]); L[2] = hpack(z[0][4], z[1][4]); L[4] = hpack(z[0][5], z[1][5]);
        const hc y64 = hpack(z[0][6], z[1][6]), z128 = hpack(z[0][7], z[1][7]), z256 = hpack(z[0][8], z[1][8]);
        const hc z512 = hpack(z[0][9], z[1][9]), z1024 = hpack(z[0][10], z[1][10]);
        H[0] = hpack(cz[0], cz[1]);
        H[1] = hmul(H[0], z1); H[2] = hmul(H[0], z2); H[3] = hmul(H[1], z2);
        L[3] = hmul(L[1], L[2]);
#pragma unroll
        for (int i = 0; i < 4; i++) { H[4 + i] = hmul(H[i], z4); if (i) L[4 + i] = hmul(L[i], L[4]); }
        __syncwarp();
        sts128(ad.w, 0x3c003c00u, y64.r, 0u, y64.i);
#pragma unroll
        for (int i = 1; i < 8; i++) { const hc q = hmul(L[i], y64); sts128(ad.w + 16 * i, L[i].r, q.r, L[i].i, q.i); }
#pragma unroll
        for (int i = 0; i < 4; i++) sts128(ad.w + 128 + 16 * i, H[2 * i].r, H[2 * i].i, H[2 * i + 1].r, H[2 * i + 1].i);
        {
            const hc a = hmul(z256, z1), b = hmul(z256, z128), c = hmul(z256, z2), d = hmul(z512, z4);
            sts128(ad.w + 192, a.r, a.i, b.r, b.i);
            sts128(ad.w + 208, c.r, c.i, z512.r, z512.i);
            sts128(ad.w + 224, d.r, d.i, z1024.r, z1024.i);
            sts64(ad.wz, z128.r, z128.i);
        }
        __syncwarp();

#pragma unroll
        for (int k2 = 0; k2 < 4; k2++) {
#pragma unroll
            for (uint32_t s = 0; s < 2; s++) {
                const uint32_t o = k2 * 1920 + s * 240;
                const uint4 l = lds128(ad.l + o);
                const uint2 h0 = lds64(ad.h + o), m2 = lds64(ad.m2 + o), m3 = lds64(ad.m3 + o), m4 = lds64(ad.m4 + o), mz = lds64(ad.z + k2 * 64 + s * 8);
                const hc H0 = {h0.x, h0.y};
                const hc H1 = hmul(H0, {mz.x, mz.y}), H2 = hmul(H0, {m2.x, m2.y}), H3 = hmul(H2, {m3.x, m3.y}), H4 = hmul(H3, {m4.x, m4.y});
                mma_f16(acc[0], l.x, l.y, l.z, l.w, H0.r, H0.i);
                mma_f16(acc[1], l.x, l.y, l.z, l.w, H1.r, H1.i);
                mma_f16(acc[2], l.x, l.y, l.z, l.w, H2.r, H2.i);
                mma_f16(acc[3], l.x, l.y, l.z, l.w, H3.r, H3.i);
                mma_f16(acc[4], l.x, l.y, l.z, l.w, H4.r, H4.i);
            }
        }

        if (bb == 0) half_done();
    }
    __syncwarp();
    main_done();

#pragma unroll
    for (int i = 0; i < 4; i++) sts128(tab + 2048 + 512 * i + 16 * lane, 0, 0, 0, 0);
    if (lane < 15) sts32(tab + 4 * lane, 0);
    __syncwarp();
    const uint32_t d0 = tab + T_DENSE + 4 + 8 * lane, src = (lane + 31) & 31;
    const uint32_t p0 = pack_bf16(fmaf(k0, dt2, skip), 0.f);
    uint32_t prev = p0;
#pragma unroll
    for (int i = 0; i < 4; i++) {
        const uint32_t pk = pack_bf16(acc[i >> 1][2 * (i & 1) + 1] * scale_inv, acc[i >> 1][2 * (i & 1)] * scale_inv);
        sts64(d0 + 256 * i, __byte_perm(pk, __shfl_sync(0xffffffffu, lane == 31 ? prev : pk, src), 0x5432), pk);
        prev = pk;
    }
    const uint32_t w0 = pack_bf16(acc[2][0] * scale_inv, acc[2][1] * scale_inv), w1 = pack_bf16(acc[2][2] * scale_inv, acc[2][3] * scale_inv);
    const uint32_t sa = (lane & 1) ? 0x5410u : 0x5454u, sb2 = (lane & 1) ? 0x1010u : 0x5410u;
#pragma unroll
    for (int hf = 0; hf < 2; hf++) {
        const uint32_t w = hf ? w1 : w0;
        const uint32_t pv = __shfl_sync(0xffffffffu, lane != 31 ? w : hf ? w0 : __byte_perm(prev, w1, 0x5410), src);
        sts64(d0 + 1024 + 256 * hf, __byte_perm(w, pv, sa), __byte_perm(w, pv, sb2));
        sts64(d0 + 1536 + 256 * hf, __byte_perm(w, pv, sa + 0x2222u), __byte_perm(w, pv, sb2 + 0x2222u));
    }
    const uint32_t d3 = tab + T_R2 + 160 + 320 * (t & 1) + 16 * (g >> 1) + 8 * (g & 1) + 4 * (t >> 1), d3n = d3 + (g >= 6 ? 32 : 0);
    const uint32_t d4 = tab + T_R3 + 80 + 160 * t + 4 * g, d4n = d4 + (g >= 6 ? 16 : 0);
    uint32_t p3;
#pragma unroll
    for (int hf = 0; hf < 2; hf++)
#pragma unroll
        for (int e = 0; e < 2; e++) {
            const float v3 = acc[3][2 * hf + e] * scale_inv;
            const uint32_t p4 = pack_bf16(acc[4][2 * hf + e] * scale_inv, 0.f);
            p3 = pack_bf16(v3, v3);
            sts16(d3 + 64 * hf + 160 * e, p3);
            sts16((hf ? d3n : d3) + 64 * hf + 160 * e + 18, p3);
            sts16(d4 + 32 * hf + 80 * e, p4);
            sts16((hf ? d4n : d4) + 32 * hf + 80 * e + 10, p4);
        }
    if (lane == 31) {
        const uint32_t k512 = __byte_perm(w1, 0, 0x3232);
        sts32(tab + T_DENSE, p0);
        sts64(tab + T_DENSE + 4 * 513, k512, k512); sts16(tab + T_DENSE + 4 * 515 + 2, k512);
        sts16(tab + T_PATCH + 4 * 17, p3); sts32(tab + T_PATCH + 4 * 18, p3); sts16(tab + T_PATCH + 4 * 19 + 2, p3);
    }
    __syncwarp();
}

__device__ __forceinline__ void load_toep(uint32_t* a, uint32_t p, uint32_t pz) {
    a[0] = lds32(p); a[1] = lds32(p + 32); a[2] = lds32(pz - 32); a[3] = lds32(pz);
}
template <int F>
__device__ __forceinline__ void ffa_step(float (&acc)[16][4], float (&W)[8][4], uint32_t (&R)[8][4], uint32_t (&A)[4][4],
                                         uint32_t va, uint32_t vn, uint32_t vmin, uint32_t pb, uint32_t pz) {
    constexpr int S = F ^ 1;
    auto load = [&](int sh) {
#pragma unroll
        for (int i = S; i < 8; i += 2) ldsm4(R[i], i == 0 ? max(sh ? vn : va, vmin) : (sh ? vn : va) + i * 128);
#pragma unroll
        for (int k = S; k < 4; k += 2) load_toep(A[k], pb + 64 * sh + k * 512, pz + 64 * sh + k * 512);
    };
    auto prod = [&](int par, int dst) {
#pragma unroll
        for (int k = 0; k < 2; k++)
#pragma unroll
            for (int m = k; m < 8; m++) {
                const uint32_t* x = &R[2 * ((m - k) & 3) + par][2 * ((m - k) >> 2)];
                mma_v(dst == 1 ? W[m] : acc[2 * m + (dst >> 1)], A[2 * k + par], x[0], x[1]);
            }
    };
    load(0);
    prod(F, F);
    prod(S, S);
#pragma unroll
    for (int i = 0; i < 8; i++) A[(i >> 2) * 2 + F][i & 3] = badd2(A[(i >> 2) * 2][i & 3], A[(i >> 2) * 2 + 1][i & 3]);
#pragma unroll
    for (int i = 0; i < 16; i++) R[(i >> 2) * 2 + F][i & 3] = badd2(R[(i >> 2) * 2][i & 3], R[(i >> 2) * 2 + 1][i & 3]);
    load(1);
    prod(F, 2);
}
__device__ __forceinline__ uint32_t dense_phase(float (&acc)[16][4], float (&W)[8][4], uint32_t (&A)[4][4], uint32_t vmin, uint32_t va, uint32_t pb, uint32_t zero, int lane,
                                                uint32_t vbar, uint32_t sbar) {
    uint32_t R[8][4], pz = pb + zero;
#pragma unroll 1
    for (int rho = 0; rho < 8; rho += 2) {
        if (rho == (int)zero) {
            mbar_wait(vbar, 0);
            STAMP(3);
#pragma unroll
            for (int i = 0; i < 8; i += 2) ldsm4(R[i], va + i * 128);
        }
        ffa_step<0>(acc, W, R, A, va, va - 16, vmin, pb, pz);
        ffa_step<1>(acc, W, R, A, va - 16, rho == 6 ? va + 96 : va - 32, vmin, pb + 64, pz + 64);
        pb += 128; pz += 128; va -= 32;
    }
    mbar_wait(sbar, 0);
    constexpr int PE = 2048 - 512, PP = T_PATCH - T_DENSE + 56 - 512;
    uint32_t E[4], F[4], G[4], H[4][4];
    const uint32_t vo = va + 128 + VT_PLANE + 496 - ((lane >> 3) & 1) * (512 + VT_PLANE) - (lane >> 4) * 896;
    load_toep(E, pb + PE, pz + PE);
#pragma unroll
    for (int i = 1; i < 8; i += 2) ldsm4(R[i], va + 128 + i * 128);
    load_toep(F, pb + PP, pz + PP);
    G[0] = lds32(pz + PE + 32); G[1] = lds32(pb + PE + 64); G[2] = lds32(pz + PP + 32); G[3] = lds32(pb + PP + 64);
#pragma unroll
    for (int i = 0; i < 4; i++) ldsm4(H[i], vo + i * 256);
#pragma unroll
    for (int i = 0; i < 32; i++) {
        const int m = i >> 2, j = i & 3;
        acc[2 * m + 1][j] = (acc[2 * m + 1][j] - acc[2 * m][j]) - W[m][j];
        if (m) acc[2 * m][j] += W[m - 1][j];
    }
#pragma unroll
    for (int i = 0; i < 12; i++) mma_v(acc[i + 4], E, R[i & 7][2 * (i >> 3)], R[i & 7][2 * (i >> 3) + 1]);
#pragma unroll
    for (int i = 0; i < 8; i++) mma_v(acc[i + 8], F, R[i][0], R[i][1]);
#pragma unroll
    for (int i = 0; i < 4; i++) mma_bf16_k8(acc[i + 4], G[0], G[1], H[i >> 1][2 * (i & 1) + 1]);
#pragma unroll
    for (int i = 0; i < 8; i++) mma_v(acc[i + 8], G, H[i >> 1][2 * (i & 1)], H[i >> 1][2 * (i & 1) + 1]);
    return __float_as_uint(W[7][0]) & zero;
}
__device__ __forceinline__ uint32_t ones2(int c, int lo, int hi) {
    return (((uint32_t)(c - lo) <= (uint32_t)(hi - lo)) ? 1u : 0u) | (((uint32_t)(c + 1 - lo) <= (uint32_t)(hi - lo)) ? 0x10000u : 0u);
}
__device__ __forceinline__ uint32_t box_bits(int lane) {
    const int d = 2 * (lane & 3) - (lane >> 2);
    auto four = [&](int L1, int H1, int L2, int H2) { return ones2(d, L1, H1) | ones2(d, L2, H2) << 1 | ones2(d + 8, L1, H1) << 2 | ones2(d + 8, L2, H2) << 3; };
    return four(5, 7, 0, 4) | four(1, 7, 0, 8) << 4;
}
struct Boxes {
    uint32_t q[4], ha[2];
    __device__ __forceinline__ Boxes(uint32_t bits, int k0, uint32_t h0, uint32_t h1) {
#pragma unroll
        for (int i = 0; i < 4; i++) q[i] = (bits & (0x10001u << (k0 + i))) * (0x3f80u >> (k0 + i));
        ha[0] = h0; ha[1] = h1;
    }
    __device__ __forceinline__ void load(int j, uint32_t* v, uint32_t zero) const {
        const uint32_t o = j * 128;
        v[0] = lds32(ha[0] + o); v[1] = lds32(ha[1] + zero + o); v[2] = lds32(ha[1] + o);
        v[3] = lds32(ha[0] + zero + o + 16); v[4] = lds32(ha[0] + o + 16); v[5] = lds32(ha[1] + o + 16);
    }
    __device__ __forceinline__ void sums(const uint32_t* v, float* Z, float* X, float* Y) const {
        mma_bf16_z(Z, q[0], q[1], q[2], q[3], v[0], v[1]);
        mma_bf16_z(X, q[0], q[1], q[2], q[3], v[2], v[3]);
        mma_bf16_z(Y, q[0], q[1], q[2], q[3], v[4], v[5]);
    }
};
__host__ __device__ constexpr int tail_step(int n) { return n < 8 ? n : n < 12 ? n + 4 : (n & 1) ? 11 - (n - 13) / 2 : 19 - (n - 12) / 2; }
template <class After>
__device__ __forceinline__ void tail_phase(float (&acc)[16][4], const Boxes& b2, const Boxes& b3, uint32_t tp2, uint32_t tp3, uint32_t zero, After after) {
    uint4 t2[5];
    uint2 t3[8];
    uint32_t v[6], a0[4], a1[4];
    float Z[4], X[4], Y[4];
    b2.load(0, v, zero);
#pragma unroll
    for (int i = 0; i < 5; i++) t2[i] = lds128(tp2 + 160 * i);
#pragma unroll
    for (int n = -1; n < 20; n++) {
        const int j = tail_step(n), j1 = tail_step(n + 1), j2 = tail_step(n + 2);
        if (n < 19) {
            (j1 < 12 ? b2 : b3).sums(v, Z, X, Y);
            if (n < 18) { if (j2 < 12) b2.load(j2, v, zero); else b3.load(j2 - 12, v, zero); }
        }
        if (n >= 0 && j < 12) {
#pragma unroll
            for (int b = 0; b < 5; b++) if (j + 4 + b < 16) mma_v(acc[j + 4 + b], a1, t2[b].z, t2[b].w);
        }
        if (n < 19 && j1 < 12) { a1[0] = pack_v(Z[0], Z[1]); a1[1] = pack_w(X[0], X[1]); a1[2] = pack_v(Z[2], Z[3]); a1[3] = pack_w(X[2], X[3]); }
        if (n == 6) {
#pragma unroll
            for (int b = 0; b < 8; b++) t3[b] = lds64(tp3 + 80 * b);
        }
        if (n >= 0 && j < 12) {
#pragma unroll
            for (int b = 0; b < 5; b++) if (j + 4 + b < 16) mma_v(acc[j + 4 + b], a0, t2[b].x, t2[b].y);
        } else if (n >= 0) {
#pragma unroll
            for (int b = 0; b < 8; b++) if (j - 4 + b < 16) mma_v(acc[j - 4 + b], a0, t3[b].x, t3[b].y);
        }
        if (n < 19) {
            if (j1 < 12) { a0[0] = pack_v(X[0], X[1]); a0[1] = pack_v(Y[0], Y[1]); a0[2] = pack_v(X[2], X[3]); a0[3] = pack_v(Y[2], Y[3]); }
            else { a0[0] = pack_v(X[0], X[1]); a0[1] = pack_v(Y[0], Y[1]); a0[2] = pack_v(Z[2], Z[3]); a0[3] = pack_v(X[2], X[3]); }
        }
        after(n);
    }
}
template <int Q>
__device__ __forceinline__ void emit(const float (&acc)[16][4], int h, uint32_t own, uint32_t peer, uint32_t bar, uint32_t bar_peer) {
    uint32_t lo[4], hi[4];
#pragma unroll
    for (int i = 0; i < 4; i++) { lo[i] = pack_bf16(acc[4 * Q + i][0], acc[4 * Q + i][1]); hi[i] = pack_bf16(acc[4 * Q + i][2], acc[4 * Q + i][3]); }
    st_async128(peer + Q * 8192, h ? lo[0] : hi[0], h ? lo[1] : hi[1], h ? lo[2] : hi[2], h ? lo[3] : hi[3], bar_peer + 8 * Q);
    sts128(own + Q * 8192, h ? hi[0] : lo[0], h ? hi[1] : lo[1], h ? hi[2] : lo[2], h ? hi[3] : lo[3]);
    __syncwarp();
    if (elect_one()) mbar_arrive(bar);
}
__device__ __forceinline__ uint32_t finish_src(uint32_t sb, int h, int j, int lane) {
    const int m = lane >> 3, r = lane & 7;
    return sb + OFF_XT + (h ^ 1) * 32768 + (2 * m + (r & 1)) * 512 + (((8 * j + (r & 4) + ((r >> 1) & 1)) ^ ((r & 1) << 1)) << 4);
}
__device__ __forceinline__ uint32_t finish_dst(uint32_t sb, int h, int j, int lane) {
    const int g = lane >> 2, t = lane & 3;
    return sb + OFF_XT + h * 32768 + j * 2048 + (g >> 1) * 512 + (t >> 1) * 144 + (2 * (t & 1) + (g & 1)) * 32;
}
__device__ __forceinline__ uint32_t tile_addr(uint32_t sb, int tok, int t) {
    return sb + OFF_XT + (tok & 8) * 4096 + (tok >> 9) * 8192 + (tok & 6) * 1024 + (tok & 448) * 4 + (tok & 1) * 128 + (tok & 48) * 2 + (((t >> 1) ^ (tok & 1)) << 4) + (t & 1) * 8;
}
__device__ __forceinline__ uint2 add_update(uint2 o, uint32_t upd) {
    const float4 u = lds128f(upd);
    return make_uint2(badd2(o.x, pack_bf16(u.x, u.y)), badd2(o.y, pack_bf16(u.z, u.w)));
}
__device__ __forceinline__ void finish_half(uint32_t src, uint32_t xa, const uint4 (&x)[2]) {
    uint32_t s[2][4];
#pragma unroll
    for (int i = 0; i < 2; i++) ldsm4t(s[i], src ^ (i << 5));
#pragma unroll
    for (int i = 0; i < 2; i++) sts128(xa + i * 256, badd2(x[i].x, s[i][0]), badd2(x[i].y, s[i][1]), badd2(x[i].z, s[i][2]), badd2(x[i].w, s[i][3]));
}

__device__ __noinline__ float centred_var(uint32_t rows, float mu, int lane) {
    float var = 0.f;
#pragma unroll 1
    for (int rr = 0; rr < 16; rr++) {
        const float c0 = __shfl_sync(0xffffffffu, mu, rr);
        float c = 0.f;
#pragma unroll 1
        for (int k = 0; k < 16; k++) {
            const uint32_t q = lds32(rows + rr * ROW_PITCH + k * 128 + lane * 4);
            const float d0 = bf_lo(q) - c0, d1 = bf_hi(q) - c0;
            c = fmaf(d0, d0, fmaf(d1, d1, c));
        }
#pragma unroll 1
        for (int o = 16; o; o >>= 1) c += __shfl_xor_sync(0xffffffffu, c, o);
        if ((lane & 15) == rr) var = c * (1.f / DM);
    }
    return var;
}
__device__ __noinline__ float centred_score(uint32_t rows, uint32_t wbuf, uint32_t s0, uint32_t s1, int lane) {
    float sc = 0.f;
#pragma unroll 1
    for (int rr = 0; rr < 16; rr++) {
        const uint32_t t0 = __shfl_sync(0xffffffffu, s0, rr), t1 = __shfl_sync(0xffffffffu, s1, rr);
        float c = 0.f;
#pragma unroll 1
        for (int k = 0; k < 16; k++) {
            const uint32_t xn = normalize2(lds32(rows + rr * ROW_PITCH + k * 128 + lane * 4), t0, t1);
            const uint32_t wq = lds32(wbuf + (k >> 2) * 1024 + (k & 3) * 128 + lane * 4);
            c = fmaf(bf_lo(xn), bf_lo(wq), fmaf(bf_hi(xn), bf_hi(wq), c));
        }
#pragma unroll 1
        for (int o = 16; o; o >>= 1) c += __shfl_xor_sync(0xffffffffu, c, o);
        if ((lane & 15) == rr) sc = c;
    }
    return sc;
}

__device__ __forceinline__ void issue_rows(const __nv_bfloat16* u, uint32_t sb, int b) {
    if (elect_one()) {
        const uint32_t bar = sb + OFF_BAR + 8 * B_ROW;
#pragma unroll
        for (int j = 0; j < 4; j++) mbar_init(bar + 8 * j, 1);
        asm volatile("fence.mbarrier_init.release.cluster;" ::: "memory");
        fence_async();
#pragma unroll 1
        for (int j = 0; j < 4; j++) {
            mbar_expect_tx(bar + 8 * j, 8192);
#pragma unroll
            for (int i = 0; i < 4; i++) bulk_g2s(sb + OFF_VT + (4 * j + i) * ROW_PITCH, u + (size_t)(16 * b + 4 * j + i) * DM, 2048, bar + 8 * j);
        }
    }
    __syncwarp();
}

__global__ void __cluster_dims__(2, 1, 1) __launch_bounds__(NTHR, 1)
fused_kernel(const __grid_constant__ Ptrs p, const __grid_constant__ Maps maps) {
    extern __shared__ __align__(1024) unsigned char smem[];
    const int tid = threadIdx.x, lane = tid & 31;
    const int c_ = ((blockIdx.x >> 1) + 60) & 63, b = 2 * ((c_ & 32) | ((c_ & 7) << 2) | ((c_ >> 3) & 3)) + (blockIdx.x & 1);
    const int dch = 8 * b + (tid >> 5) - 4;
    uint2 la, aim, cre, cim;
    uint32_t ldt16;
    if ((uint32_t)(tid - 128) < 256u) {
        la = ldg64(p.logA + dch * NMODE + 4 * lane); aim = ldg64(p.Aim + dch * NMODE + 4 * lane);
        cre = ldg64(p.Cre + dch * NMODE + 4 * lane); cim = ldg64(p.Cim + dch * NMODE + 4 * lane);
        ldt16 = ldg16(p.ldt + dch);
    }
    const uint32_t sb = s_u32(smem), bar0 = sb + OFF_BAR;
    const int warp = __shfl_sync(0xffffffffu, tid >> 5, 0);
    const int h = b & 1, cl = b >> 1;
    const int m = lane >> 3, r = lane & 7, g = lane >> 2, t = lane & 3;
    const bool has_gu = b < GU_CTAS;
    if (warp == 4) { STAMP(0); GSTAMP(24); }

    if (warp >= 12) {
        asm volatile("setmaxnreg.dec.sync.aligned.u32 24;");
        const int a = warp - 12;
        uint32_t due = now_ns() + ST_T0 + (uint32_t)(2 * a + h) * (ST_PER / 2) + (has_gu ? 0 : 12 * ST_PER + 4 * ST_PER2);
        const bool el = elect_one();
        if (a == 1) issue_rows(p.u, sb, b);
        if (a == 2 && el) {
#pragma unroll
            for (int i = B_XT; i < NBAR; i++) mbar_init(bar0 + 8 * i, (i == B_V || i == B_SFREE || i == B_XFREE) ? 8 : (i >= B_RECV && i < B_RECV + 4) ? 9 : i == B_RED ? 5 : (i == B_UPD || (i >= B_FREE && i < B_FULL)) ? 4 : 1);
            asm volatile("fence.mbarrier_init.release.cluster;" ::: "memory");
            fence_async();
            mbar_expect_tx(bar0 + 8 * B_XT, 65536);
#pragma unroll
            for (int i = 0; i < 4; i++) mbar_expect_tx(bar0 + 8 * (B_RECV + i), 4096);
            mbar_expect_tx(bar0 + 8 * B_RED, 2048);
        }
        if (a == 3 && el) {
#pragma unroll
            for (int i = 0; i < 5; i++) asm volatile("prefetch.tensormap [%0];" ::"l"(&maps.u + i) : "memory");
        }
        __syncwarp();
        cluster_arrive();
        cluster_wait();
        STAMP(18);
        uint32_t fs = finish_src(sb, h, a, lane), fx = finish_dst(sb, h, a, lane);
        pin(fs); pin(fx);
        mbar_wait(bar0 + 8 * (B_ROW + a), 0);
        if (el) {
#pragma unroll
            for (int i = 0; i < 4; i++)
                tma_load_tile(sb + OFF_XT + (a >> 1) * 32768 + (a & 1) * 4096 + h * 8192 + (i & 1) * 16384 + (i >> 1) * 2048, &maps.u, 16 * cl, 4 * a + (i & 2), 16 * (i & 1) + 8 * h, bar0 + 8 * B_XT);
        }
        if (el) {
#pragma unroll 1
            for (int k = has_gu ? 0 : 4; k < 6 - (a >> 1); k++) {
                const int i = 4 * k + a, s = k < 3 ? i : i - 12;
                sleep_until(due);
                due += k < 3 ? 4 * ST_PER : 4 * ST_PER2;
                const bool again = k >= 3 && has_gu;
                if (s >= 6 || again) mbar_wait(bar0 + 8 * (s < 10 || again ? B_FREE + s : B_V), slot_priv(s) && again);
                const uint32_t dst = sb + slot_off(s), bar = bar0 + 8 * (B_FULL + s);
                if (k < 4) {
                    mbar_expect_tx(bar, 8192);
                    tma_load_2d(dst, &maps.wg, 64 * cl, 512 * h + 32 * i, bar);
                    tma_load_2d(dst + 4096, &maps.wu, 64 * cl, 512 * h + 32 * i, bar);
                } else {
                    mbar_expect_tx(bar, 7168);
                    tma_load_perm(dst, &maps.wd, 16 * cl, 56 * h + 14 * a + 7 * (k & 1), bar);
                }
            }
            STAMP(19);
        }
        __syncwarp();
        {
            mbar_wait(bar0 + 8 * B_XT, 0);
#pragma unroll 1
            for (int Q = 0; Q < 3; Q++) {
#pragma unroll
                for (int q = 0; q < 2; q++) {
                    const uint4 x[2] = {lds128(fx ^ (q << 4)), lds128((fx ^ (q << 4)) + 256)};
                    if (q == 0) mbar_wait(bar0 + 8 * (B_RECV + Q), 0);
                    finish_half((fs ^ (q << 6)) + q * 4096, fx ^ (q << 4), x);
                }
                fence_async();
                __syncwarp();
                if (el) tma_store_tile(&maps.out, sb + OFF_XT + h * 32768 + Q * 8192 + a * 2048, 16 * cl, 8 * h + 2 * a, 8 * Q);
                fs += 8192; fx += 8192;
                STAMP(Q ? 58 + Q : 20);
            }
            const int tok = 2047 - (int)(lds32(sb + OFF_MISC + 48 + 8 * g) & 2047);
            const bool mine = ((tok >> 1) & 7) == 4 * h + a && tok < 1536;
            if (el) asm volatile("cp.async.bulk.wait_group 0;" ::: "memory");
            __syncwarp();
            if (__any_sync(0xffffffffu, mine)) {
                const uint2 o0 = lds64(tile_addr(sb, tok, t));
                mbar_wait(bar0 + 8 * B_UPD, 0);
                const uint2 o1 = add_update(o0, sb + tab_off(g) + T_RED + 16 * t);
                if (mine) *reinterpret_cast<uint2*>(p.out + (size_t)tok * DM + 16 * cl + 4 * t) = o1;
            } else STAMP(62);
        }
    } else if (warp >= 4) {
        const int w = warp - 4;
        uint32_t dsk16 = ldg16(p.dsk + dch);
        cluster_arrive();
        asm volatile("setmaxnreg.inc.sync.aligned.u32 176;");
        const uint32_t vrow = sb + OFF_VT + w * VT_PITCH + VT_PAD, tab = sb + tab_off(w);
        const uint32_t rb0 = bar0 + 8 * B_RECV, rb1 = mapa(rb0, h ^ 1);
        uint32_t tpo = 80 + (g - 2 * t) * 8 - (g < 2 * t ? 16 : 0);
        uint32_t xa = sb + OFF_XT + (w >> 1) * 8192 + (w & 1) * 1024 + (g >> 1) * 2048 + (g & 1) * 128 + t * 32 + ((h ^ (g & 1)) << 4);
        uint32_t va = sb + OFF_VT + (2 * m + (r & 1)) * VT_PITCH + VT_PAD + (16 * w + (r >> 1)) * 16;
        uint32_t qa = sb + OFF_ST + 2048 * w + 128 * t + 16 * (g ^ (2 * t));
        uint32_t vmin = vrow + (m & 1) * VT_PLANE - 16, vd = vmin + 16 + (m >> 1) * 1024 + r * 16;
        uint32_t vz = vrow - VT_PAD + (lane >> 1) * VT_PLANE + (lane & 1) * 16;
        pin(vmin); pin(vd); pin(vz);
        pin(tpo); pin(xa); pin(va); pin(qa);
        uint32_t bits = box_bits(lane), h0 = vrow + 16 * g + tok_off(2 * t - 18);
        pin(bits); pin(h0);
        const KgenAddr ka(sb + OFF_PRIV + w * 8192, lane);
        if (__any_sync(0xffffffffu, (vmin | (vd | vz) | (tpo | xa) | (va | qa) | (bits | h0) | ka.any()) & p.zero)) __trap();
        cluster_wait();
        pin(la.x); pin(la.y); pin(aim.x); pin(aim.y); pin(cre.x); pin(cre.y); pin(cim.x); pin(cim.y); pin(ldt16); pin(dsk16);
        uint4 x[8];
        auto load_x = [&]() {
            mbar_wait(bar0 + 8 * B_XT, 0);
#pragma unroll
            for (int i = 0; i < 8; i++) x[i] = lds128(xa + (i & 1) * 32768 + (i >> 1) * 256);
        };
        kgen(ka, tab, lane, la, aim, cre, cim, bf_round(ex2f(bf_lo(ldt16) * 1.4426950408889634f)), 1.f + bf_lo(dsk16), dch, [&]() {
            STAMP(21);
            if (elect_one()) mbar_arrive_n(bar0 + 8 * (B_FREE + 6 + ((w >> 1) ^ 2)), 2);
        }, [&]() {
            if ((LN_PAUSE >> w) & 1) mbar_wait(bar0 + 8 * B_LN, 0);
        });
        STAMP(1);
        const uint32_t pb = tab + T_DENSE + (g - 2 * t) * 4;
        uint32_t A[4][4];
        load_toep(A[0], pb, pb + p.zero);
        load_toep(A[2], pb + 1024, pb + p.zero + 1024);
        {
            load_x();
            STAMP(47);
            mbar_wait(bar0 + 8 * (B_ST + (w >> 1)), 0);
            uint4 q[4];
#pragma unroll
            for (int n = 0; n < 4; n++) q[n] = lds128(qa + 512 * n);
            if (lane < 4) sts128(vz, 0, 0, 0, 0);
            STAMP(2); GSTAMP(28);
#pragma unroll
            for (int i = 0; i < 8; i++) {
                const uint32_t s0 = (i & 1) ? q[i >> 1].z : q[i >> 1].x, s1 = (i & 1) ? q[i >> 1].w : q[i >> 1].y;
                stsm4t(va + (i >> 1) * 64 + (i & 1) * VT_PLANE, normalize2(x[i].x, s0, s1), normalize2(x[i].y, s0, s1),
                       normalize2(x[i].z, s0, s1), normalize2(x[i].w, s0, s1));
            }
            __syncwarp();
            if (elect_one()) mbar_arrive(bar0 + 8 * B_V);
        }
        float acc[16][4], W[8][4];
#pragma unroll
        for (int i = 0; i < 64; i++) { acc[i >> 2][i & 3] = 0.f; W[i >> 3][i & 3] = 0.f; }
        bits |= dense_phase(acc, W, A, vmin, vd, pb, p.zero, lane, bar0 + 8 * B_V, bar0 + 8 * B_SFREE);
        const uint32_t h1 = h0 + (t ? VT_PLANE : 16 - VT_PLANE);
        const Boxes b2(bits, 0, h0, h1), b3(bits, 4, (t == 1 ? h1 : h0) - 4, t == 1 ? h0 + 12 : h1 - 4);
        STAMP(4);
        const uint32_t so = sb + OFF_XT + (8 * h + w) * 512 + ((lane ^ ((w & 1) << 1) ^ (h << 2)) << 4);
        const uint32_t dst0 = so + (h ^ 1) * 32768, dst1 = mapa(so + h * 32768, h ^ 1);
        tail_phase(acc, b2, b3, tab + T_R2 + 2 * tpo, tab + T_R3 + tpo, p.zero, [&](int j) {
            if (j == -1) emit<0>(acc, h, dst0, dst1, rb0, rb1);
            if (j == 3) { emit<1>(acc, h, dst0, dst1, rb0 + 8, rb1); STAMP(5); }
            if (j == 11) {
                mbar_wait(bar0 + 8 * B_XFREE, 0);
                emit<2>(acc, h, dst0, dst1, rb0 + 16, rb1);
                STAMP(58);
            }
        });
        emit<3>(acc, h, dst0, dst1, rb0 + 24, rb1);
        STAMP(30);
        {
            const int j = w & 3, th = w >> 2;
            const int tok = 2047 - (int)(lds32(sb + OFF_MISC + 48 + 8 * g) & 2047);
            const bool mine = (((tok >> 3) & 8) | ((tok >> 1) & 7)) == 8 * th + 4 * h + j && tok >= 1536;
            const uint32_t fs = sb + OFF_XT + (h ^ 1) * 32768 + 24576 + (4 * (r & 2) + 2 * m + (r & 1)) * 512 + (((8 * j + 2 * th + (r >> 2)) ^ ((r & 3) << 1)) << 4);
            const uint32_t fx = sb + OFF_XT + h * 32768 + 24576 + j * 2048 + th * 256 + (g >> 1) * 512 + ((t & 2) + (g & 1)) * 32 + (t & 1) * 16;
            __nv_bfloat16* dst = p.out + (size_t)(1536 + 64 * th + 8 * h + 2 * j + 128 * (g >> 1) + 16 * ((t & 2) + (g & 1))) * DM + 16 * cl + 8 * (t & 1);
            const uint4 x[2] = {lds128(fx), lds128((fx ^ 16) + 128)};
            mbar_wait(bar0 + 8 * (B_RECV + 3), 0);
            STAMP(6);
            uint32_t sv[2][4];
#pragma unroll
            for (int u = 0; u < 2; u++) ldsm4t(sv[u], fs ^ (u << 6));
            uint4 o[2];
#pragma unroll
            for (int u = 0; u < 2; u++) {
                o[u] = make_uint4(badd2(x[u].x, sv[u][0]), badd2(x[u].y, sv[u][1]), badd2(x[u].z, sv[u][2]), badd2(x[u].w, sv[u][3]));
                *reinterpret_cast<uint4*>(dst + u * DM) = o[u];
            }
            if (__any_sync(0xffffffffu, mine)) {
#pragma unroll
                for (int u = 0; u < 2; u++) sts128((fx ^ (u << 4)) + u * 128, o[u].x, o[u].y, o[u].z, o[u].w);
                __syncwarp();
                const uint2 o0 = lds64(tile_addr(sb, tok, t));
                uint2* row = reinterpret_cast<uint2*>(p.out + (size_t)tok * DM + 16 * cl + 4 * t);
                pin(row);
                mbar_wait(bar0 + 8 * B_UPD, 0);
                const uint2 o1 = add_update(o0, sb + tab_off(g) + T_RED + 16 * t);
                if (mine) *row = o1;
            }
        }
        STAMP(7);
    } else {
        const int a = warp;
        const uint4 wq = ldg128(p.wr + 8 * tid);
        const uint32_t epoch = ld_relaxed_32(&p.sc[a].cnt[b & 96]) >> 5;
        cluster_arrive();
        asm volatile("setmaxnreg.inc.sync.aligned.u32 136;");
        const uint32_t tag = __shfl_sync(0xffffffffu, epoch, 0) + 1u, misc = sb + OFF_MISC, abar = bar0 + 8 * (B_AUX + a);
        uint32_t aph = 0;
        const Exchange* in = &p.sc[cl & (NREP - 1)];
        uint2* pub = p.sc[m >> 1].stat + 16 * b + 2 * (r ^ (2 * (b & 3))) + (m & 1);
        uint32_t* cnt_s = &p.sc[t].cnt[b & 96];
        pin(pub); pin(cnt_s);
        if (tid < 32) sts32(sb + OFF_XCH + 4 * tid, 0);
        const uint32_t wbuf = sb + OFF_LN + a * 1024, part = sb + OFF_LN + 4096;
        {
            sts128(wbuf + 16 * lane, wq.x, wq.y, wq.z, wq.w);
            sts128(wbuf + 512 + 16 * lane, 0x3f803f80u, 0x3f803f80u, 0x3f803f80u, 0x3f803f80u);
            float wsum = ((bf_lo(wq.x) + bf_hi(wq.x)) + (bf_lo(wq.y) + bf_hi(wq.y))) + ((bf_lo(wq.z) + bf_hi(wq.z)) + (bf_lo(wq.w) + bf_hi(wq.w)));
#pragma unroll
            for (int o = 16; o; o >>= 1) wsum += __shfl_xor_sync(0xffffffffu, wsum, o);
            sts32f(part + 1024 + 4 * a, wsum);
            uint32_t wf[4][4];
#pragma unroll
            for (int i = 0; i < 4; i++) ldsm4(wf[i], wbuf + ((uint32_t)(r - 1) < 2u ? 16 * (r - 1) : 512) + 32 * m + 128 * i);
            uint32_t ra = sb + OFF_VT + r * ROW_PITCH + 512 * a + 16 * m, pa = part + a * 256 + g * 16;
            cluster_wait();
            STAMP(22);
#pragma unroll 1
            for (int hf = 0; hf < 2; hf++) {
                mbar_wait(bar0 + 8 * B_ROW + 16 * hf, 0);
                mbar_wait(bar0 + 8 * B_ROW + 16 * hf + 8, 0);
                STAMP(23);
                uint32_t x[8][4];
                float cs[2][4], q[8][4];
#pragma unroll
                for (int i = 0; i < 40; i++) (i < 8 ? cs[i >> 2 & 1] : q[(i - 8) >> 2 & 7])[i & 3] = 0.f;
#pragma unroll
                for (int k = 0; k < 8; k++) ldsm4(x[k], ra + k * 64);
                const bool more = __any_sync(0xffffffffu, after_all(x, p.zero));
#pragma unroll 1
                do {
#pragma unroll
                    for (int k = 0; k < 8; k++) {
                        mma_v(cs[k & 1], x[k], wf[k >> 1][2 * (k & 1)], wf[k >> 1][2 * (k & 1) + 1]);
#pragma unroll
                        for (int i = 0; i < 4; i++) mma_bf16_k8(q[4 * (k & 1) + i], x[k][i & 2], x[k][i | 1], x[k][i]);
                    }
                } while (more);
                const float c2 = cs[0][2] + cs[1][2];
                if (t == 0) sts64f(pa, (cs[0][0] + cs[1][0]) + c2, cs[0][1] + cs[1][1]);
                if (t == 1) sts32f(pa + 12, c2);
                const float e0 = ((q[0][0] + q[2][0]) + (q[4][0] + q[6][0])) + ((q[1][2] + q[3][2]) + (q[5][2] + q[7][2]));
                const float e1 = ((q[0][1] + q[2][1]) + (q[4][1] + q[6][1])) + ((q[1][3] + q[3][3]) + (q[5][3] + q[7][3]));
                if (t == (g >> 1)) sts32f(pa + 8, (g & 1) ? e1 : e0);
                ra += 8 * ROW_PITCH; pa += 128;
            }
        }
        STAMP(31);
        named_sync(1, 128);
        if (a == 0) {
            const uint32_t pa = part + (lane & 15) * 16;
            const float4 p0 = lds128f(pa), p1 = lds128f(pa + 256), p2 = lds128f(pa + 512), p3 = lds128f(pa + 768), ws = lds128f(part + 1024);
            const float mu = ((p0.x + p1.x) + (p2.x + p3.x)) * (1.f / DM);
            float var = ((p0.z + p1.z) + (p2.z + p3.z)) * (1.f / DM) - mu * mu;
            const bool centred = __any_sync(0xffffffffu, !(mu * mu <= 64.f * var));
            if (centred) var = centred_var(sb + OFF_VT, mu, lane);
            const float ri = rcpf(bf_round(sqrtaf(bf_round(bf_round(var) + 1e-5f))));
            const uint32_t s0 = pack_bf16(mu, ri), s1 = (pack_bf16(ri - bf_hi(s0), 0.f) & 0xfffcu) | (tag & 3);
            float sc = ((((p0.y + p1.y) + (p2.y + p3.y)) + ((p0.w + p1.w) + (p2.w + p3.w))) - bf_lo(s0) * ((ws.x + ws.y) + (ws.z + ws.w))) * ri;
            if (centred) sc = centred_score(sb + OFF_VT, sb + OFF_LN, s0, s1, lane);
            const uint32_t sb16 = pack_bf16(0.f, sc);
            const uint32_t s2 = s1 | (sb16 ^ (((uint32_t)((int)sb16 >> 31) & 0x7fff0000u) | 0x80000000u));
            st_relaxed_64(pub, s0, s2);
            st_relaxed_64(pub + 2 * sizeof(Exchange) / 8, s0, s2);
            if (lane < NREP) red_add(cnt_s, 1);
            if (elect_one()) mbar_arrive(bar0 + 8 * B_LN);
            STAMP(9); GSTAMP(25);
        }
        const uint32_t slot0 = sb + OFF_RING + a * 8192, slot1 = sb + slot_off(4 + a), slot2 = sb + slot_off(8 + a), fbar = bar0 + 8 * (B_FULL + a);
        uint32_t mine, row[2];
        {
            uint32_t q[16];
            named_sync(1, 128);
            wait_count(&in->cnt[32 * a], 32 * tag - FEW_ST);
            STAMP(41);
#pragma unroll 1
            for (uint32_t it = 0;; spin_guard(it)) {
                if (elect_one()) {
                    mbar_expect_tx(abar, 4096);
                    bulk_g2s(sb + OFF_ST + 4096 * a, in->stat + 512 * a, 4096, abar);
                }
                mbar_wait(abar, aph);
                aph ^= 1;
                uint32_t bad = 0;
#pragma unroll
                for (int n = 0; n < 8; n++) {
                    const uint4 u = lds128v(sb + OFF_ST + 4096 * a + 512 * n + 16 * lane);
                    q[2 * n] = u.y; q[2 * n + 1] = u.w;
                    bad = or_xor(bad, u.y, tag);
                }
                const bool ok = __all_sync(0xffffffffu, (bad & 3) == 0);
                asm volatile("{ .reg .pred p; setp.ne.u32 p, %1, 0; @p mbarrier.arrive.shared::cta.b64 _, [%0]; }" ::"r"(bar0 + 8 * (B_ST + a)), "r"((uint32_t)(ok && lane == 0)) : "memory");
                if (ok) break;
            }
            STAMP(8);
            const uint32_t inv = 2047 - 512 * a - 16 * m - (r ^ (2 * m));
#pragma unroll
            for (int i = 0; i < 16; i++) asm("lop3.b32 %0, %0, %1, %2, 0x9b;" : "+r"(q[i]) : "r"(inv), "r"(0xffff0000u | (64 * (i >> 1) + 8 * (i & 1))));
            auto below = [&](uint32_t x) {
                uint32_t d[4];
#pragma unroll
                for (int i = 0; i < 16; i++) d[i & 3] = i < 4 ? x + q[i] : min(d[i & 3], x + q[i]);
                d[0] = min(min(d[0], d[1]), min(d[2], d[3]));
                return d[0] < x ? x - 1 - d[0] : 0u;
            };
            const uint32_t mx0 = ~min(min(min(min(q[0], q[1]), min(q[2], q[3])), min(min(q[4], q[5]), min(q[6], q[7]))),
                                      min(min(min(q[8], q[9]), min(q[10], q[11])), min(min(q[12], q[13]), min(q[14], q[15]))));
            const uint32_t gm = __reduce_max_sync(0xffffffffu, mx0 == __reduce_max_sync(0xffffffffu, mx0) ? 0u : mx0);
            if (lane == 0) sts32(misc + 16 + 4 * a, gm);
            named_sync(1, 128);
            STAMP(42);
            const uint4 t0 = lds128(misc + 16);
            uint32_t tau = min(min(t0.x, t0.y), min(t0.z, t0.w));
            uint32_t mx = mx0, cnt = 0, bal;
            const uint32_t list = sb + OFF_XCH + 32 * a;
#pragma unroll 1
            while ((bal = __ballot_sync(0xffffffffu, mx >= tau)) != 0) {
                const uint32_t pos = cnt + __popc(bal & ((1u << lane) - 1u));
                cnt += __popc(bal);
                if (cnt > 8) break;
                if (mx >= tau) sts32(list + 4 * pos, mx);
                mx = below(mx);
            }
            if (cnt > 8) {
                mx = mx0;
#pragma unroll 1
                for (int j = 0; j < 8; j++) {
                    const uint32_t top = __reduce_max_sync(0xffffffffu, mx), nx = below(mx);
                    if (mx == top) { sts32(list + 4 * j, mx); mx = nx; }
                }
            }
            named_sync(1, 128);
            STAMP(43);
            const uint32_t k = lds32(sb + OFF_XCH + 4 * lane);
            uint32_t rk[4] = {misc + 48, 0, 0, 0};
#pragma unroll
            for (int j = 0; j < 8; j++) {
                const uint4 c = lds128(sb + OFF_XCH + 16 * j);
                asm("{ .reg .pred p, q, r, s; setp.gt.u32 p, %4, %8; setp.gt.u32 q, %5, %8; setp.gt.u32 r, %6, %8; setp.gt.u32 s, %7, %8;\n\t"
                    "@p add.u32 %0, %0, 8; @q add.u32 %1, %1, 8; @r add.u32 %2, %2, 8; @s add.u32 %3, %3, 8; }"
                    : "+r"(rk[0]), "+r"(rk[1]), "+r"(rk[2]), "+r"(rk[3]) : "r"(c.x), "r"(c.y), "r"(c.z), "r"(c.w), "r"(k));
            }
            rk[0] = (rk[0] + rk[1]) + (rk[2] + rk[3]);
            if (rk[0] < misc + 112) sts32(rk[0], k);
            __syncwarp();
            mine = lds32(misc + 48 + 8 * g);
            const uint4 two = lds128v(misc + 48 + 16 * a);
            row[0] = two.x; row[1] = two.z;
            mbar_wait(bar0 + 8 * B_V, 0);
        }
        STAMP(11);
        const int tok = 2047 - (int)(mine & 2047);
        const uint32_t xs = sb + OFF_XT + (h ^ 1) * 32768 + 16384;
        if (has_gu) {
            if (elect_one()) {
                mbar_expect_tx(abar, 2048);
#pragma unroll
                for (int j = 0; j < 2; j++) bulk_g2s(xs + (2 * a + j) * 1040, p.u + (size_t)(2047 - (row[j] & 2047)) * DM + 512 * h, 1024, abar);
            }
        }
        STAMP(44);
        uint32_t af[20][4], ko = sb + (m & 1) * 4096 + (r + ((m >> 1) << 3)) * 128 + ((r ^ (4 * h) ^ a) << 4);
        auto load_level = [&](int c) {
#pragma unroll
            for (int j = 0; j < 4; j++) {
                mbar_wait(bar0 + 8 * (B_FULL + 4 * (c % 3) + j), c / 3);
#pragma unroll
                for (int i = 0; i < 4; i++) ldsm4t(af[8 * (i >> 1) + 2 * j + (i & 1)], (ko ^ ((i & 1) << 6)) + slot_off(4 * (c % 3) + j) + (i >> 1) * 2048);
            }
            STAMP(36 + c);
            __syncwarp();
            if (c < 3 && lane < 4) mbar_arrive(bar0 + 8 * (B_FREE + 4 * c + lane));
        };
        const uint2 st = ld_relaxed_64(in->stat + (tok & ~15) + 2 * ((tok & 7) ^ ((tok >> 3) & 6)) + ((tok >> 3) & 1));
        if (has_gu) load_level(0);
        if (a == 0 && t == 0) sts32f(misc + 52 + 8 * g, bf_hi(st.x) + bf_lo(st.y));
        if (a == 0) STAMP(45);
        if (has_gu) {
            const uint32_t mean = __shfl_sync(0xffffffffu, st.x, 8 * a + 4 * (lane >> 4)), xr = xs + (2 * a + (lane >> 4)) * 1040 + 16 * (lane & 15);
            mbar_wait(abar, aph);
            aph ^= 1;
            STAMP(46);
            uint4 x[4];
#pragma unroll
            for (int j = 0; j < 4; j++) x[j] = lds128(xr + 256 * j);
#pragma unroll
            for (int j = 0; j < 4; j++) sts128(xr + 256 * j, bsub2_lo(x[j].x, mean), bsub2_lo(x[j].y, mean), bsub2_lo(x[j].z, mean), bsub2_lo(x[j].w, mean));
            if (elect_one()) mbar_expect_tx(abar, 512);
            named_sync(1, 128);
        }
        if (lane < (has_gu ? 2 : 4)) mbar_arrive_peer(mapa(bar0 + 8 * (lane & 2 ? B_XFREE : B_SFREE), lane & 1));
        if (has_gu) {
            STAMP(12);
            float gacc[8][4];
#pragma unroll
            for (int i = 0; i < 8; i++) { gacc[i][0] = gacc[i][1] = gacc[i][2] = gacc[i][3] = 0.f; }
            uint32_t* pubh = reinterpret_cast<uint32_t*>(&p.sc[0].h[b * 32 + 8 * a + (g ^ (2 * a))]) + t;
            uint32_t* cnt_h = &p.sc[t].cnt[32 * (b / 28) + 1 + ((b / 14) & 1)];
            uint32_t xb = xs + r * 1040 + m * 16;
            uint32_t xch = sb + OFF_XCH + 16 * tid, tagm = t == 3 ? 1u : 0u;
            pin(pubh); pin(cnt_h); pin(xb); pin(xch); pin(tagm);
            const float r0 = lds32f(misc + 52 + 16 * t), r1 = lds32f(misc + 60 + 16 * t);
#pragma unroll
            for (int c = 0; c < 4; c++) {
#pragma unroll
                for (int j = 0; j < 4; j++) ldsm4(af[16 + j], xb + 256 * c + 64 * j);
                if (c == 3) mbar_wait(bar0 + 8 * B_SFREE, 0);
                if (c) load_level(c);
                const bool more = __any_sync(0xffffffffu, (c ? af[6][3] | af[7][3] | af[14][3] | af[15][3] : af[16][3] | af[17][3] | af[18][3] | af[19][3]) & p.zero);
#pragma unroll 1
                do {
#pragma unroll
                    for (int i = 0; i < 16; i++) mma_v(gacc[i & 7], af[i], af[16 + ((i >> 1) & 3)][2 * (i >> 3)], af[16 + ((i >> 1) & 3)][2 * (i >> 3) + 1]);
                } while (more);
            }
            STAMP(13);
            float own[4], oth[4];
#pragma unroll
            for (int j = 0; j < 4; j++) oth[j] = (gacc[1][j] + gacc[3][j]) + (gacc[5][j] + gacc[7][j]);
            st_async128(mapa(xch, h ^ 1), __float_as_uint(oth[0]), __float_as_uint(oth[1]), __float_as_uint(oth[2]), __float_as_uint(oth[3]), mapa(abar, h ^ 1));
            STAMP(56);
#pragma unroll
            for (int j = 0; j < 4; j++) own[j] = ((gacc[0][j] + gacc[2][j]) + (gacc[4][j] + gacc[6][j])) * ((j & 1) ? r1 : r0);
            mbar_wait(abar, aph);
            aph ^= 1;
            STAMP(57);
            const float4 o4 = lds128f(xch);
            const float g0 = bf_round(fmaf(o4.x, r0, own[0])), g1 = bf_round(fmaf(o4.y, r1, own[1]));
            const float h0 = bf_round(g0 * rcpf(1.f + ex2f(-1.4426950408889634f * g0))) * bf_round(fmaf(o4.z, r0, own[2]));
            const float h1 = bf_round(g1 * rcpf(1.f + ex2f(-1.4426950408889634f * g1))) * bf_round(fmaf(o4.w, r1, own[3]));
            uint32_t hw;
            asm volatile("movmatrix.sync.aligned.m8n8.trans.b16 %0, %1;" : "=r"(hw) : "r"(pack_bf16(h0, h1)));
            hw = (hw & ~tagm) | (tag & tagm);
#pragma unroll
            for (int j = 0; j < NREP; j++) st_relaxed_32(pubh + j * (sizeof(Exchange) / 4), hw);
            if (lane < NREP) red_add(cnt_h, b % 14 < 2 ? 2 : 1);
            if (lane < 2) mbar_arrive_peer(mapa(bar0 + 8 * B_XFREE, lane));
            named_sync(1, 128);
            STAMP(14);
        }
        float dacc[4];
        const int tk = ((tid >> 1) & 6) | (tid & 1);
        uint32_t ro = 4 * tid, red = sb + tab_off(tk) + T_RED + 4 * ((tid >> 4) + 4 * (tid & 2));
        if (!has_gu) named_sync(1, 128);
        const float sg = bf_round(rcpf(1.f + ex2f(-1.4426950408889634f * __uint_as_float(unorder_key(lds32(misc + 48 + 8 * tk) >> 16) << 16))));
        pin(ro); pin(red);
        mbar_wait(bar0 + 8 * B_XFREE, 0);
        {
            uint32_t wo = (r + ((m >> 1) << 3)) * 32 + (((m & 1) ^ (r >> 2)) << 4), af[14][4];
            uint32_t ho = slot0 + 128 * t + 16 * (g ^ (2 * t));
            pin(wo); pin(ho);
            float d[7][4];
#pragma unroll
            for (int i = 0; i < 7; i++) { d[i][0] = d[i][1] = d[i][2] = d[i][3] = 0.f; }
            auto first_half = [&]() {
                mbar_wait(fbar + 32, has_gu);
#pragma unroll
                for (int j = 0; j < 14; j++) ldsm4t(af[j], slot1 + wo + j * 512);
            };
            auto fetch = [&]() {
                if (elect_one()) {
                    mbar_expect_tx(abar, 7168);
                    bulk_g2s(slot0, &in->h[(56 * h + 14 * a) * 32], 7168, abar);
                }
            };
            wait_count(&in->cnt[64 * h + 32 * (a >> 1) + 1 + (a & 1)], 64 * tag - FEW_H);
            STAMP(33);
            fetch();
            if (a >= 2 && elect_one()) {
                mbar_expect_tx(fbar + 64, 7168);
                tma_load_perm(slot2, &maps.wd, 16 * cl, 56 * h + 14 * a + 7, fbar + 64);
            }
            first_half();
            mbar_wait(abar, aph);
#pragma unroll
            for (int s = 0; s < 2; s++) {
                if (s) {
                    mbar_wait(fbar + 64, has_gu);
#pragma unroll
                    for (int j = 0; j < 14; j++) ldsm4t(af[j], slot2 + wo + j * 512);
                }
                uint4 hq[7];
#pragma unroll 1
                for (uint32_t it = 0;; spin_guard(it)) {
                    uint32_t bad = 0;
#pragma unroll
                    for (int j = 0; j < 7; j++) { hq[j] = lds128(ho + 512 * (7 * s + j)); bad = or_xor(bad, hq[j].w, tag); }
                    if (__all_sync(0xffffffffu, (bad & 1) == 0)) break;
                    fetch();
                    aph ^= 1;
                    mbar_wait(abar, aph);
                }
                if (s == 0) STAMP(15);
#pragma unroll
                for (int j = 0; j < 14; j++) {
                    const uint4 q = hq[j >> 1];
                    mma_v(d[j % 7], af[j], (j & 1) ? q.z : q.x, (j & 1) ? q.w : q.y);
                }
            }
#pragma unroll
            for (int j = 0; j < 4; j++) dacc[j] = ((d[0][j] + d[1][j]) + (d[2][j] + d[3][j])) + ((d[4][j] + d[5][j]) + d[6][j]);
        }
        STAMP(16);
        {
            st_async128(mapa(sb + OFF_XCH + 16 * tid, h ^ 1), __float_as_uint(dacc[0]), __float_as_uint(dacc[1]), __float_as_uint(dacc[2]), __float_as_uint(dacc[3]),
                        mapa(bar0 + 8 * B_RED, h ^ 1));
            sts128f(slot0 + 7680 + lane * 16, dacc);
            __syncwarp();
            if (elect_one()) mbar_arrive(bar0 + 8 * B_RED);
            mbar_wait(bar0 + 8 * B_RED, 0);
            const uint32_t b0 = sb + OFF_RING + 7680 + ro, b1 = sb + OFF_XCH + ro;
            const float y = ((lds32f(b0) + lds32f(b0 + 8192)) + (lds32f(b0 + 16384) + lds32f(b0 + 24576))) +
                            ((lds32f(b1) + lds32f(b1 + 512)) + (lds32f(b1 + 1024) + lds32f(b1 + 1536)));
            sts32f(red, bf_round(y) * sg);
            __syncwarp();
            if (elect_one()) mbar_arrive(bar0 + 8 * B_UPD);
        }
        STAMP(17); GSTAMP(29);
    }
}

typedef CUresult (*EncodeFn)(CUtensorMap*, CUtensorMapDataType, cuuint32_t, void*, const cuuint64_t*, const cuuint64_t*,
                             const cuuint32_t*, const cuuint32_t*, CUtensorMapInterleave, CUtensorMapSwizzle,
                             CUtensorMapL2promotion, CUtensorMapFloatOOBfill);

void make_map(EncodeFn enc, CUtensorMap* m, const void* ptr, uint64_t cols, uint64_t rows, uint32_t bc, uint32_t br,
              CUtensorMapSwizzle sw, CUtensorMapL2promotion pr) {
    cuuint64_t dims[2] = {cols, rows};
    cuuint64_t str[1] = {cols * 2};
    cuuint32_t box[2] = {bc, br};
    cuuint32_t es[2] = {1, 1};
    enc(m, CU_TENSOR_MAP_DATA_TYPE_BFLOAT16, 2, const_cast<void*>(ptr), dims, str, box, es, CU_TENSOR_MAP_INTERLEAVE_NONE, sw, pr,
        CU_TENSOR_MAP_FLOAT_OOB_FILL_NONE);
}
void make_perm_map(EncodeFn enc, CUtensorMap* m, const void* ptr, CUtensorMapL2promotion pr) {
    cuuint64_t dims[5] = {DM, 2, 4, 4, FF / 32};
    cuuint64_t str[4] = {DM * 2, 8 * DM * 2, 2 * DM * 2, 32 * DM * 2};
    cuuint32_t box[5] = {16, 2, 4, 4, 7};
    cuuint32_t es[5] = {1, 1, 1, 1, 1};
    enc(m, CU_TENSOR_MAP_DATA_TYPE_BFLOAT16, 5, const_cast<void*>(ptr), dims, str, box, es, CU_TENSOR_MAP_INTERLEAVE_NONE,
        CU_TENSOR_MAP_SWIZZLE_32B, pr, CU_TENSOR_MAP_FLOAT_OOB_FILL_NONE);
}
void make_tile_map(EncodeFn enc, CUtensorMap* m, const void* ptr) {
    cuuint64_t dims[4] = {DM, 4, 16, SEQ / 64};
    cuuint64_t str[3] = {16 * DM * 2, DM * 2, 64 * DM * 2};
    cuuint32_t box[4] = {16, 4, 2, 8};
    cuuint32_t es[4] = {1, 1, 1, 1};
    enc(m, CU_TENSOR_MAP_DATA_TYPE_BFLOAT16, 4, const_cast<void*>(ptr), dims, str, box, es, CU_TENSOR_MAP_INTERLEAVE_NONE,
        CU_TENSOR_MAP_SWIZZLE_32B, CU_TENSOR_MAP_L2_PROMOTION_NONE, CU_TENSOR_MAP_FLOAT_OOB_FILL_NONE);
}

}

extern "C" void kernel_launch(void* const* d_in, const int* in_sizes, int n_in, void* d_out, int out_size) {
    (void)in_sizes; (void)n_in; (void)out_size;
    static EncodeFn enc = nullptr;
    static void* scratch = nullptr;
    if (!enc) {
        void* fn = nullptr;
        cudaDriverEntryPointQueryResult q;
        cudaGetDriverEntryPoint("cuTensorMapEncodeTiled", &fn, cudaEnableDefault, &q);
        enc = (EncodeFn)fn;
        cudaGetSymbolAddress(&scratch, g_scratch);
        cudaFuncSetAttribute(fused_kernel, cudaFuncAttributeMaxDynamicSharedMemorySize, SMEM_BYTES);
    }
    Maps maps;
    make_tile_map(enc, &maps.u, d_in[0]);
    make_tile_map(enc, &maps.out, d_out);
    make_map(enc, &maps.wg, d_in[9], FF, DM, 64, 32, CU_TENSOR_MAP_SWIZZLE_128B, CU_TENSOR_MAP_L2_PROMOTION_L2_128B);
    make_map(enc, &maps.wu, d_in[10], FF, DM, 64, 32, CU_TENSOR_MAP_SWIZZLE_128B, CU_TENSOR_MAP_L2_PROMOTION_L2_128B);
    make_perm_map(enc, &maps.wd, d_in[11], CU_TENSOR_MAP_L2_PROMOTION_L2_64B);
    Ptrs p;
    p.sc = (Exchange*)scratch;
    p.u = (const __nv_bfloat16*)d_in[0];
    p.logA = (const __nv_bfloat16*)d_in[1];
    p.Aim = (const __nv_bfloat16*)d_in[2];
    p.Cre = (const __nv_bfloat16*)d_in[3];
    p.Cim = (const __nv_bfloat16*)d_in[4];
    p.ldt = (const __nv_bfloat16*)d_in[5];
    p.dsk = (const __nv_bfloat16*)d_in[6];
    p.wr = (const __nv_bfloat16*)d_in[8];
    p.out = (__nv_bfloat16*)d_out;
    p.zero = 0;
    fused_kernel<<<NCTA, NTHR, SMEM_BYTES, cudaStreamPerThread>>>(p, maps);
}
```
